```python
import torch

def _softmax(x, axis=-1):
    return torch.softmax(x, dim=axis)
def _gelu(x):
    return torch.nn.functional.gelu(x, approximate="tanh")
def _silu(x):
    return torch.nn.functional.silu(x)
def _sigmoid(x):
    return torch.sigmoid(x)
def _layernorm(x, axis=-1, eps=1e-5):
    m = x.mean(dim=axis, keepdim=True)
    v = x.var(dim=axis, keepdim=True, unbiased=False)
    return (x - m) / torch.sqrt(v + eps)
def _scatter_add(tgt, idx, src, axis=0):
    return tgt.clone().index_add_(axis, idx, src)
def _segment_sum(src, seg, n):
    out = torch.zeros((n,) + src.shape[1:], dtype=src.dtype)
    return out.index_add_(0, seg, src)
def _pad(x, pw):
    flat = tuple(v for pair in reversed(pw) for v in pair)
    return torch.nn.functional.pad(x, flat)

kernel_name = 'recurrent_scan__sliding_local_dilated__glu_gated_geglu__prompt'

def setup_inputs():

    _w = (lambda a: (lambda t: t.to(torch.bfloat16) if t.is_floating_point() else t)(torch.as_tensor(a)))
    def _A_setup():
        B, S, D = 1, 2048, 1024
        return {
            "x": _w((lambda *s: torch.randn(*s, dtype=torch.bfloat16) * 0.05)(B, S, D)),
            "wqkv": _w((lambda *s: torch.randn(*s, dtype=torch.bfloat16) * 0.2)(D, 3 * D)),
            "wo": _w((lambda *s: torch.randn(*s, dtype=torch.bfloat16) * 0.2)(D, D)),
        }
    _A_in = _A_setup()

    def _B_setup():
        B, S, Dm, Df = 1, 2048, 1024, 3584
        return {
            "x": _w((lambda *s: torch.randn(*s, dtype=torch.bfloat16) * 0.05)(B, S, Dm)),
            "w_gate": _w((lambda *s: torch.randn(*s, dtype=torch.bfloat16) * 0.1)(Dm, Df) * (Dm ** -0.5)),
            "w_up": _w((lambda *s: torch.randn(*s, dtype=torch.bfloat16) * 0.1)(Dm, Df) * (Dm ** -0.5)),
            "w_down": _w((lambda *s: torch.randn(*s, dtype=torch.bfloat16) * 0.1)(Df, Dm) * (Df ** -0.5)),
        }
    _B_in = _B_setup()

    return {
        "A_x": _A_in["x"],
        "A_wqkv": _A_in["wqkv"],
        "A_wo": _A_in["wo"],
        "B_x": _B_in["x"],
        "B_w_gate": _B_in["w_gate"],
        "B_w_up": _B_in["w_up"],
        "B_w_down": _B_in["w_down"],
    }

def reference(A_x, A_wqkv, A_wo, B_x, B_w_gate, B_w_up, B_w_down):
    def _A_ref(x, wqkv, wo):
        B, S, D = x.shape
        H = 32; Dh = D // H
        W, dil = 8, 2
        qkv = (lambda x, *d: x.permute(*d))((x @ wqkv).reshape(B, S, 3, H, Dh), 2, 0, 3, 1, 4)
        q, k, v = qkv[0], qkv[1], qkv[2]
        scale = Dh ** -0.5
        pos = torch.arange(S)
        off = torch.arange(W) * dil
        idx = pos[:, None] - off[None, :]
        mask = idx >= 0
        idx_c = torch.where(mask, idx, 0).reshape(-1)
        kg = k[:, :, idx_c, :].reshape(B, H, S, W, Dh)
        vg = v[:, :, idx_c, :].reshape(B, H, S, W, Dh)
        logits = torch.einsum("bhsd,bhswd->bhsw", q, kg) * scale
        logits = torch.where(mask[None, None, :, :], logits, -1e9)
        attn = _softmax(logits, axis=-1)
        o = torch.einsum("bhsw,bhswd->bhsd", attn, vg)
        return (lambda x, *d: x.permute(*d))(o, 0, 2, 1, 3).reshape(B, S, D) @ wo

    def _B_ref(x, w_gate, w_up, w_down):
        g = torch.einsum("bsd,df->bsf", x, w_gate)
        u = torch.einsum("bsd,df->bsf", x, w_up)
        h = _gelu(g) * u
        return torch.einsum("bsf,fd->bsd", h, w_down)

    x = A_x
    xn = _layernorm(x, axis=-1)
    s = _A_ref(xn, A_wqkv, A_wo)
    g = _silu(_B_ref(xn, B_w_gate, B_w_up, B_w_down))
    return x + s * g
```

```cpp
#include <cuda_runtime.h>
#include <cuda_bf16.h>
#include <cuda.h>
#include <stdint.h>

#define P1_MULTICAST 1
#define P2_MULTICAST 1

namespace {

constexpr int SEQ = 2048, DM = 1024, DFF = 3584;
constexpr int NGEMM = 128, NCTA = 132;

constexpr uint32_t SM_BASE = 0x400;
constexpr uint32_t P1_STAGE = 49152, P2_STAGE = 32768;
constexpr uint32_t OFF_X = 196608;
constexpr uint32_t OFF_CS = 229376;
constexpr uint32_t OFF_STATS = OFF_CS + 1088;
constexpr uint32_t OFF_BAR = OFF_STATS + 1024;
constexpr uint32_t B_F1 = OFF_BAR, B_E1 = B_F1 + 32, B_F2 = B_E1 + 32, B_E2 = B_F2 + 48;
constexpr uint32_t B_DEP = B_E2 + 48;
constexpr uint32_t B_AUX = B_DEP + 48, B_CS = B_AUX + 8, B_XT = B_CS + 8;
constexpr uint32_t SMEM_BYTES = 232448;
constexpr int ATT_SLOTS = 6;
constexpr uint32_t OFF_ATT_BAR = 12 * ATT_SLOTS * 3072;

__device__ uint4 g_xn[SEQ * DM / 8];
__device__ float2 g_stats[SEQ];
__device__ float4 g_cspart[8 * 16 * 64];
__device__ uint4 g_qkv[32 * 2 * 64 * 3 * 2 * 32];
__device__ uint4 g_o[16 * 16 * 1024];
__device__ uint4 g_h[16 * 56 * 1024];
constexpr int FL_XN = 0, FL_H = 16, FL_CS = 80, FL_QKV = 88, FL_O = 89, FL_N = 90;
__device__ unsigned g_flags[FL_N * 32];
__device__ unsigned g_epoch[NCTA * 12];
#define TS(i) do {} while (0)

struct Maps { CUtensorMap x, xn, out, wqkv, wg, wu, wd, wo; };

__device__ __forceinline__ void mbar_init(uint32_t bar, uint32_t cnt) { asm volatile("mbarrier.init.shared::cta.b64 [%0], %1;" ::"r"(bar), "r"(cnt)); }
__device__ __forceinline__ void mbar_expect_tx(uint32_t bar, uint32_t bytes) { asm volatile("mbarrier.arrive.expect_tx.shared::cta.b64 _, [%0], %1;" ::"r"(bar), "r"(bytes) : "memory"); }
__device__ __forceinline__ void mbar_arrive(uint32_t bar) { asm volatile("mbarrier.arrive.shared::cta.b64 _, [%0];" ::"r"(bar) : "memory"); }
__device__ __forceinline__ void mbar_arrive_cl(uint32_t bar) { asm volatile("mbarrier.arrive.shared::cluster.b64 _, [%0];" ::"r"(bar) : "memory"); }
__device__ __forceinline__ uint32_t mapa(uint32_t a, uint32_t cta) { uint32_t r; asm("mapa.shared::cluster.u32 %0, %1, %2;" : "=r"(r) : "r"(a), "r"(cta)); return r; }
__device__ __forceinline__ void mbar_wait(uint32_t bar, uint32_t parity) {
  asm volatile("{\n.reg .pred p;\n.reg .u32 n;\nmov.u32 n, 0;\nLAB_WAIT:\nmbarrier.try_wait.parity.shared::cta.b64 p, [%0], %1;\n@p bra LAB_DONE;\n"
               "add.u32 n, n, 1;\nsetp.gt.u32 p, n, 4000000;\n@p trap;\nbra LAB_WAIT;\nLAB_DONE:\n}" ::"r"(bar), "r"(parity) : "memory");
}
__device__ __forceinline__ void flag_wait(const unsigned* f, unsigned target) {
  asm volatile("{\n.reg .pred p;\n.reg .u32 n, v;\nmov.u32 n, 0;\nLAB_WAIT:\nld.acquire.gpu.global.u32 v, [%0];\nsub.u32 v, v, %1;\nsetp.ge.s32 p, v, 0;\n@p bra LAB_DONE;\n"
               "nanosleep.u32 200;\nadd.u32 n, n, 1;\nsetp.gt.u32 p, n, 4000000;\n@p trap;\nbra LAB_WAIT;\nLAB_DONE:\n}" ::"l"(f), "r"(target) : "memory");
}
__device__ __forceinline__ void flag_add(unsigned* f) { asm volatile("red.release.gpu.global.add.u32 [%0], 1;" ::"l"(f) : "memory"); }
__device__ __forceinline__ void fence_async() { asm volatile("fence.proxy.async;" ::: "memory"); }
__device__ __forceinline__ void bar_sync(int id, int n) { asm volatile("bar.sync %0, %1;" ::"r"(id), "r"(n) : "memory"); }
__device__ __forceinline__ void bar_arrive(int id, int n) { asm volatile("bar.arrive %0, %1;" ::"r"(id), "r"(n) : "memory"); }

__device__ __forceinline__ void tma2d(uint32_t dst, const CUtensorMap* tm, uint32_t bar, int c0, int c1) {
  asm volatile("cp.async.bulk.tensor.2d.shared::cluster.global.mbarrier::complete_tx::bytes [%0], [%1, {%3, %4}], [%2];" ::"r"(dst), "l"(tm), "r"(bar), "r"(c0), "r"(c1) : "memory");
}
__device__ __forceinline__ void tma2d_mc(uint32_t dst, const CUtensorMap* tm, uint32_t bar, int c0, int c1) {
  asm volatile("cp.async.bulk.tensor.2d.shared::cluster.global.mbarrier::complete_tx::bytes.multicast::cluster [%0], [%1, {%3, %4}], [%2], %5;" ::"r"(dst), "l"(tm), "r"(bar), "r"(c0), "r"(c1), "h"((uint16_t)3) : "memory");
}
__device__ __forceinline__ void tma3d(uint32_t dst, const CUtensorMap* tm, uint32_t bar, int c0, int c1, int c2) {
  asm volatile("cp.async.bulk.tensor.3d.shared::cluster.global.mbarrier::complete_tx::bytes [%0], [%1, {%3, %4, %5}], [%2];" ::"r"(dst), "l"(tm), "r"(bar), "r"(c0), "r"(c1), "r"(c2) : "memory");
}
__device__ __forceinline__ void tma5d(uint32_t dst, const CUtensorMap* tm, uint32_t bar, int c0, int c4) {
  asm volatile("cp.async.bulk.tensor.5d.shared::cluster.global.mbarrier::complete_tx::bytes [%0], [%1, {%3, %5, %5, %5, %4}], [%2];" ::"r"(dst), "l"(tm), "r"(bar), "r"(c0), "r"(c4), "r"(0) : "memory");
}
__device__ __forceinline__ void tma5d_mc(uint32_t dst, const CUtensorMap* tm, uint32_t bar, int c0, int c4) {
  asm volatile("cp.async.bulk.tensor.5d.shared::cluster.global.mbarrier::complete_tx::bytes.multicast::cluster [%0], [%1, {%3, %5, %5, %5, %4}], [%2], %6;" ::"r"(dst), "l"(tm), "r"(bar), "r"(c0), "r"(c4), "r"(0), "h"((uint16_t)3) : "memory");
}
__device__ __forceinline__ void tma3d_store(const CUtensorMap* tm, uint32_t src, int c0, int c1, int c2) {
  asm volatile("cp.async.bulk.tensor.3d.global.shared::cta.bulk_group [%0, {%2, %3, %4}], [%1];" ::"l"(tm), "r"(src), "r"(c0), "r"(c1), "r"(c2) : "memory");
}
__device__ __forceinline__ void bulk_load(uint32_t dst, const void* src, uint32_t bytes, uint32_t bar) {
  asm volatile("cp.async.bulk.shared::cluster.global.mbarrier::complete_tx::bytes [%0], [%1], %2, [%3];" ::"r"(dst), "l"(src), "r"(bytes), "r"(bar) : "memory");
}
__device__ __forceinline__ uint4 lds128(uint32_t a) { uint4 v; asm volatile("ld.shared.v4.b32 {%0,%1,%2,%3}, [%4];" : "=r"(v.x), "=r"(v.y), "=r"(v.z), "=r"(v.w) : "r"(a) : "memory"); return v; }
__device__ __forceinline__ uint2 lds64(uint32_t a) { uint2 v; asm volatile("ld.shared.v2.b32 {%0,%1}, [%2];" : "=r"(v.x), "=r"(v.y) : "r"(a) : "memory"); return v; }
__device__ __forceinline__ void sts64(uint32_t a, uint32_t x, uint32_t y) { asm volatile("st.shared.v2.b32 [%0], {%1,%2};" ::"r"(a), "r"(x), "r"(y) : "memory"); }
__device__ __forceinline__ void sts128(uint32_t a, uint4 v) { asm volatile("st.shared.v4.b32 [%0], {%1,%2,%3,%4};" ::"r"(a), "r"(v.x), "r"(v.y), "r"(v.z), "r"(v.w) : "memory"); }
__device__ __forceinline__ void stg128(void* p, uint32_t a, uint32_t b, uint32_t c, uint32_t d) { asm volatile("st.global.v4.b32 [%0], {%1,%2,%3,%4};" ::"l"(p), "r"(a), "r"(b), "r"(c), "r"(d) : "memory"); }

__device__ __forceinline__ uint32_t pack2(float lo, float hi) { uint32_t r; asm("cvt.rn.bf16x2.f32 %0, %1, %2;" : "=r"(r) : "f"(hi), "f"(lo)); return r; }
__device__ __forceinline__ float lo_f(uint32_t v) { return __uint_as_float(v << 16); }
__device__ __forceinline__ float hi_f(uint32_t v) { return __uint_as_float(v & 0xffff0000u); }
__device__ __forceinline__ float bf16r(float v) { return lo_f(pack2(v, 0.f)); }
__device__ __forceinline__ uint32_t mul2(uint32_t a, uint32_t b) { uint32_t r; asm("mul.rn.bf16x2 %0, %1, %2;" : "=r"(r) : "r"(a), "r"(b)); return r; }
__device__ __forceinline__ uint32_t sub2(uint32_t a, uint32_t b) { uint32_t r; asm("sub.rn.bf16x2 %0, %1, %2;" : "=r"(r) : "r"(a), "r"(b)); return r; }
__device__ __forceinline__ uint32_t fma2(uint32_t a, uint32_t b, uint32_t c) { uint32_t r; asm("fma.rn.bf16x2 %0, %1, %2, %3;" : "=r"(r) : "r"(a), "r"(b), "r"(c)); return r; }
__device__ __forceinline__ uint32_t max2(uint32_t a, uint32_t b) { uint32_t r; asm("max.bf16x2 %0, %1, %2;" : "=r"(r) : "r"(a), "r"(b)); return r; }
__device__ __forceinline__ float ex2f(float x) { float y; asm("ex2.approx.ftz.f32 %0, %1;" : "=f"(y) : "f"(x)); return y; }
__device__ __forceinline__ float rcpf(float x) { float y; asm("rcp.approx.ftz.f32 %0, %1;" : "=f"(y) : "f"(x)); return y; }
__device__ __forceinline__ float gelu2(float g) {
  float z = g * fmaf(g * g, 0.035677408136300125f, 0.7978845608028654f), t;
  asm("tanh.approx.f32 %0, %1;" : "=f"(t) : "f"(z));
  return fmaf(g, t, g);
}

__device__ __forceinline__ void wg_fence() { asm volatile("wgmma.fence.sync.aligned;" ::: "memory"); }
__device__ __forceinline__ void wg_commit() { asm volatile("wgmma.commit_group.sync.aligned;" ::: "memory"); }
template <int N> __device__ __forceinline__ void wg_wait() { asm volatile("wgmma.wait_group.sync.aligned %0;" ::"n"(N) : "memory"); }
#define A8(o) "+f"(d[(o)]), "+f"(d[(o) + 1]), "+f"(d[(o) + 2]), "+f"(d[(o) + 3]), "+f"(d[(o) + 4]), "+f"(d[(o) + 5]), "+f"(d[(o) + 6]), "+f"(d[(o) + 7])
#define A64(o) A8(o), A8((o) + 8), A8((o) + 16), A8((o) + 24), A8((o) + 32), A8((o) + 40), A8((o) + 48), A8((o) + 56)
#define REGS0_63 "%0,%1,%2,%3,%4,%5,%6,%7,%8,%9,%10,%11,%12,%13,%14,%15,%16,%17,%18,%19,%20,%21,%22,%23,%24,%25,%26,%27,%28,%29,%30,%31," \
                 "%32,%33,%34,%35,%36,%37,%38,%39,%40,%41,%42,%43,%44,%45,%46,%47,%48,%49,%50,%51,%52,%53,%54,%55,%56,%57,%58,%59,%60,%61,%62,%63"
#define REGS64_127 "%64,%65,%66,%67,%68,%69,%70,%71,%72,%73,%74,%75,%76,%77,%78,%79,%80,%81,%82,%83,%84,%85,%86,%87,%88,%89,%90,%91,%92,%93,%94,%95," \
                   "%96,%97,%98,%99,%100,%101,%102,%103,%104,%105,%106,%107,%108,%109,%110,%111,%112,%113,%114,%115,%116,%117,%118,%119,%120,%121,%122,%123,%124,%125,%126,%127"
template <int ACCUM> __device__ __forceinline__ void wgmma256(float (&d)[128], uint32_t a_lo, uint32_t b_lo) {
  asm volatile("{\n.reg .pred p;\n.reg .b64 da, db;\nsetp.ne.b32 p, %130, 0;\nmov.b64 da, {%128, 0x40000040};\nmov.b64 db, {%129, 0x40000040};\n"
               "wgmma.mma_async.sync.aligned.m64n256k16.f32.bf16.bf16 {" REGS0_63 "," REGS64_127 "}, da, db, p, 1, 1, 0, 1;\n}"
               : A64(0), A64(64) : "r"(a_lo), "r"(b_lo), "n"(ACCUM));
}
template <int ACCUM> __device__ __forceinline__ void wgmma128(float (&d)[64], uint32_t a_lo, uint32_t b_lo) {
  asm volatile("{\n.reg .pred p;\n.reg .b64 da, db;\nsetp.ne.b32 p, %66, 0;\nmov.b64 da, {%64, 0x00000040};\nmov.b64 db, {%65, 0x40000040};\n"
               "wgmma.mma_async.sync.aligned.m64n128k16.f32.bf16.bf16 {" REGS0_63 "}, da, db, p, 1, 1, 0, 1;\n}"
               : A64(0) : "r"(a_lo), "r"(b_lo), "n"(ACCUM));
}
__device__ __forceinline__ void hmma16(float (&c)[4], uint32_t a0, uint32_t a1, uint32_t a2, uint32_t a3, uint32_t b0, uint32_t b1) {
  asm("mma.sync.aligned.m16n8k16.row.col.f32.bf16.bf16.f32 {%0,%1,%2,%3}, {%4,%5,%6,%7}, {%8,%9}, {%0,%1,%2,%3};"
      : "+f"(c[0]), "+f"(c[1]), "+f"(c[2]), "+f"(c[3]) : "r"(a0), "r"(a1), "r"(a2), "r"(a3), "r"(b0), "r"(b1));
}
__device__ __forceinline__ void hmma8(float (&c)[4], uint32_t a0, uint32_t a1, uint32_t b0) {
  asm("mma.sync.aligned.m16n8k8.row.col.f32.bf16.bf16.f32 {%0,%1,%2,%3}, {%4,%5}, {%6}, {%0,%1,%2,%3};"
      : "+f"(c[0]), "+f"(c[1]), "+f"(c[2]), "+f"(c[3]) : "r"(a0), "r"(a1), "r"(b0));
}
__device__ __forceinline__ uint32_t movm(uint32_t a) { uint32_t d; asm("movmatrix.sync.aligned.m8n8.trans.b16 %0, %1;" : "=r"(d) : "r"(a)); return d; }

constexpr int BAR_LAG = 1, BAR_EV = 2;

struct Cons {
  uint32_t sb;
  uint32_t a1, a2;
  uint32_t rel;
  bool rel1, rel2;
  int wg;
};
constexpr uint32_t DB_LO = ((SM_BASE + 16384) >> 4) | ((8192 >> 4) << 16);

template <int KB> __device__ __forceinline__ void p1_step(float (&acc)[128], const Cons& c) {
  constexpr int st = KB & 3;
  if (KB == 14) { if (c.wg == 1) bar_sync(BAR_LAG, 256); }
  mbar_wait(c.sb + B_F1 + 8 * st, (KB >> 2) & 1);
  wg_fence();
  constexpr uint32_t so = st * (P1_STAGE >> 4);
  wgmma256<KB != 0>(acc, c.a1 + so, DB_LO + so);
  wgmma256<1>(acc, c.a1 + so + 2, DB_LO + so + 128);
  wgmma256<1>(acc, c.a1 + so + 4, DB_LO + so + 256);
  wgmma256<1>(acc, c.a1 + so + 6, DB_LO + so + 384);
  wg_commit();
  if (KB == 15) { if (c.wg == 0) bar_arrive(BAR_LAG, 256); }
  if (KB > 0) { wg_wait<1>(); if (c.rel1) mbar_arrive_cl(c.rel + B_E1 + 8 * ((KB - 1) & 3)); }
  if (KB == 15) { wg_wait<0>(); if (c.rel1) mbar_arrive_cl(c.rel + B_E1 + 8 * 3); }
}
template <int ST, int ACCUM, bool WAITPREV, bool RELEASE> __device__ __forceinline__ void p2_step(float (&acc)[64], const Cons& c, uint32_t parity) {
  mbar_wait(c.sb + B_F2 + 8 * ST, parity);
  wg_fence();
  constexpr uint32_t so = ST * (P2_STAGE >> 4);
  wgmma128<ACCUM>(acc, c.a2 + so, DB_LO + so);
  wgmma128<1>(acc, c.a2 + so + 16, DB_LO + so + 128);
  wgmma128<1>(acc, c.a2 + so + 32, DB_LO + so + 256);
  wgmma128<1>(acc, c.a2 + so + 48, DB_LO + so + 384);
  wg_commit();
  if (WAITPREV) wg_wait<1>();
  if (RELEASE) { if (c.rel2) mbar_arrive_cl((P2_MULTICAST ? c.rel : c.sb) + B_E2 + 8 * ((ST + 5) % 6)); }
}

template <int P> __device__ __forceinline__ void geglu_piece(const uint32_t (&pk)[64], uint8_t* dst) {
  constexpr int cg = P >> 1, r = P & 1;
  uint32_t v[4];
#pragma unroll
  for (int i = 0; i < 4; i++) {
    const uint32_t g = pk[2 * (4 * cg + i) + r];
    v[i] = mul2(pack2(gelu2(lo_f(g)), gelu2(hi_f(g))), pk[32 + 2 * (4 * cg + i) + r]);
  }
  stg128(dst + (cg >> 1) * 16384 + (cg & 1) * 512 + r * 1024, v[0], v[1], v[2], v[3]);
}
template <int H> __device__ __forceinline__ void qkv_piece(const uint32_t (&pk)[64], uint8_t* dst) {
#pragma unroll
  for (int r = 0; r < 2; r++) stg128(dst + H * 393216 + r * 512, pk[8 * H + r], pk[8 * H + 2 + r], pk[8 * H + 4 + r], pk[8 * H + 6 + r]);
}

template <int KB> struct P1Tile {
  static __device__ __forceinline__ void run(float (&acc)[128], const uint32_t (&pk)[64], const Cons& c, bool is_qkv, uint8_t* dst, int ev) {
    p1_step<KB>(acc, c);
    if (is_qkv) {
      if (KB >= 1 && KB <= 4) { qkv_piece<(2 * KB - 2) & 7>(pk, dst); qkv_piece<(2 * KB - 1) & 7>(pk, dst); }
      if (KB == 4) bar_arrive(ev, 288);
    } else {
      if (KB >= 1 && KB <= 8) geglu_piece<(KB - 1) & 7>(pk, dst);
      if (KB == 8) bar_arrive(ev, 288);
    }
    P1Tile<KB + 1>::run(acc, pk, c, is_qkv, dst, ev);
  }
};
template <> struct P1Tile<16> { static __device__ __forceinline__ void run(float (&)[128], const uint32_t (&)[64], const Cons&, bool, uint8_t*, int) {} };

__device__ __forceinline__ void ln_stats(const uint32_t* raw, float& mb, float& rinv) {
  float f[32], s = 0.f, s2 = 0.f;
#pragma unroll
  for (int i = 0; i < 16; i++) { f[2 * i] = lo_f(raw[i]); f[2 * i + 1] = hi_f(raw[i]); s += f[2 * i]; s2 += f[2 * i + 1]; }
  s += s2;
#pragma unroll
  for (int o = 16; o; o >>= 1) s += __shfl_xor_sync(~0u, s, o);
  const float mean = s * (1.0f / DM);
  float v = 0.f, v2 = 0.f;
#pragma unroll
  for (int i = 0; i < 16; i++) { const float a = f[2 * i] - mean, b = f[2 * i + 1] - mean; v = fmaf(a, a, v); v2 = fmaf(b, b, v2); }
  v += v2;
#pragma unroll
  for (int o = 16; o; o >>= 1) v += __shfl_xor_sync(~0u, v, o);
  mb = bf16r(mean);
  float sd;
  asm("sqrt.approx.ftz.f32 %0, %1;" : "=f"(sd) : "f"(bf16r(bf16r(v * (1.0f / DM)) + 1e-5f)));
  rinv = rcpf(bf16r(sd));
}
__device__ __forceinline__ void ln_store(const uint32_t* raw, float mb, float rinv, uint4* dst) {
  const uint32_t m2 = pack2(mb, mb);
#pragma unroll
  for (int c = 0; c < 4; c++) {
    uint32_t v[4];
#pragma unroll
    for (int i = 0; i < 4; i++) { const uint32_t t = sub2(raw[4 * c + i], m2); v[i] = pack2(lo_f(t) * rinv, hi_f(t) * rinv); }
    stg128(dst + 32 * c, v[0], v[1], v[2], v[3]);
  }
}

__device__ __forceinline__ void attention(uint32_t sb, int gw  , unsigned t_start) {
  const int lane = threadIdx.x & 31, warp = threadIdx.x >> 5;
  const uint32_t ring = sb + warp * (ATT_SLOTS * 3072), bars = sb + OFF_ATT_BAR + warp * (ATT_SLOTS * 8);
  const int u_end = ((gw + 1) * 4096) / 48;
  const int u_beg = (gw * 4096) / 48;
  const int u0 = (u_beg & 63) ? u_beg - 1 : u_beg;
  const uint8_t* src = (const uint8_t*)g_qkv;
  if (lane == 0) {
    for (int s = 0; s < ATT_SLOTS; s++) mbar_init(bars + 8 * s, 1);
    unsigned* ep = &g_epoch[blockIdx.x * 12 + warp];
    const unsigned e = *ep + 1;
    *ep = e;
    flag_wait(&g_flags[FL_QKV * 32], e * 192u);
    fence_async();
    if (warp == 0) TS(0);
    for (int s = 0; s < ATT_SLOTS; s++) { mbar_expect_tx(bars + 8 * s, 3072); bulk_load(ring + s * 3072, src + (size_t)(u0 + s) * 3072, 3072, bars + 8 * s); }
  }
  __syncwarp();
  const int rho = lane >> 2, q = lane & 3;
  const bool le0 = 2 * q <= rho, le1 = 2 * q + 1 <= rho;
  const uint32_t LE = (le0 ? 0xffffu : 0u) | (le1 ? 0xffff0000u : 0u);
  uint4 kh = make_uint4(0, 0, 0, 0), vh = kh;
  int slot = 0; uint32_t par = 0;
  for (int u = u0; u < u_end; u++) {
    mbar_wait(bars + 8 * slot, par);
    const uint32_t a = ring + slot * 3072 + lane * 16;
    const uint4 q0 = lds128(a), q1 = lds128(a + 512), k0 = lds128(a + 1024), k1 = lds128(a + 1536), v0 = lds128(a + 2048), v1 = lds128(a + 2560);
    const bool first = (u & 63) == 0;
    if (first) { kh = make_uint4(0, 0, 0, 0); vh = kh; }
    float s0[4] = {0, 0, 0, 0}, s1[4] = {0, 0, 0, 0}, s2[4] = {0, 0, 0, 0};
    hmma16(s0, q0.x, q1.x, q0.y, q1.y, kh.x, kh.y); hmma16(s1, q0.x, q1.x, q0.y, q1.y, k0.x, k0.y); hmma16(s2, q0.x, q1.x, q0.y, q1.y, k1.x, k1.y);
    hmma16(s0, q0.z, q1.z, q0.w, q1.w, kh.z, kh.w); hmma16(s1, q0.z, q1.z, q0.w, q1.w, k0.z, k0.w); hmma16(s2, q0.z, q1.z, q0.w, q1.w, k1.z, k1.w);
    const uint4 t0 = make_uint4(movm(v0.x), movm(v0.y), movm(v0.z), movm(v0.w)), t1 = make_uint4(movm(v1.x), movm(v1.y), movm(v1.z), movm(v1.w));
    uint32_t la = pack2(le0 ? s1[0] : s0[0], le0 ? s2[2] : s1[2]), lb = pack2(le1 ? s1[1] : s0[1], le1 ? s2[3] : s1[3]);
    __syncwarp();
    if (lane == 0 && u + ATT_SLOTS < u_end) {
      mbar_expect_tx(bars + 8 * slot, 3072);
      bulk_load(ring + slot * 3072, src + (size_t)(u + ATT_SLOTS) * 3072, 3072, bars + 8 * slot);
    }
    if (++slot == ATT_SLOTS) { slot = 0; par ^= 1; }
    if (u >= u_beg) {
      const float sc = 0.17677669529663687f;
      la = pack2((first && !le0) ? -1e9f : lo_f(la) * sc, hi_f(la) * sc);
      lb = pack2((first && !le1) ? -1e9f : lo_f(lb) * sc, hi_f(lb) * sc);
      uint32_t mx = max2(la, lb);
      mx = max2(mx, __shfl_xor_sync(~0u, mx, 1));
      mx = max2(mx, __shfl_xor_sync(~0u, mx, 2));
      const float L2E = 1.4426950408889634f;
      const float p00 = ex2f((lo_f(la) - lo_f(mx)) * L2E), p01 = ex2f((lo_f(lb) - lo_f(mx)) * L2E);
      const float p10 = ex2f((hi_f(la) - hi_f(mx)) * L2E), p11 = ex2f((hi_f(lb) - hi_f(mx)) * L2E);
      float z0 = p00 + p01, z1 = p10 + p11;
      z0 += __shfl_xor_sync(~0u, z0, 1); z1 += __shfl_xor_sync(~0u, z1, 1);
      z0 += __shfl_xor_sync(~0u, z0, 2); z1 += __shfl_xor_sync(~0u, z1, 2);
      z0 = rcpf(z0); z1 = rcpf(z1);
      const uint32_t P0 = pack2(p00 * z0, p01 * z0), P1 = pack2(p10 * z1, p11 * z1);
      const uint32_t a0 = P0 & ~LE, a2 = P0 & LE, a3 = P1 & ~LE, b1 = P1 & LE;
      float o0[4] = {0, 0, 0, 0}, o1[4] = {0, 0, 0, 0}, o2[4] = {0, 0, 0, 0}, o3[4] = {0, 0, 0, 0};
      hmma16(o0, a0, 0, a2, a3, vh.x, t0.x); hmma16(o1, a0, 0, a2, a3, vh.y, t0.y); hmma16(o2, a0, 0, a2, a3, vh.z, t0.z); hmma16(o3, a0, 0, a2, a3, vh.w, t0.w);
      hmma8(o0, 0, b1, t1.x); hmma8(o1, 0, b1, t1.y); hmma8(o2, 0, b1, t1.z); hmma8(o3, 0, b1, t1.w);
      const int slab = u & 63, par_s = (u >> 6) & 1, head = u >> 7;
      uint8_t* dst = (uint8_t*)g_o + (size_t)((slab >> 2) * 16 + (head >> 1)) * 16384 + (par_s * 8 + (slab & 3) * 2) * 1024 + (head & 1) * 512 + q * 128 + rho * 16;
      stg128(dst, pack2(o0[0], o0[1]), pack2(o1[0], o1[1]), pack2(o2[0], o2[1]), pack2(o3[0], o3[1]));
      stg128(dst + 1024, pack2(o0[2], o0[3]), pack2(o1[2], o1[3]), pack2(o2[2], o2[3]), pack2(o3[2], o3[3]));
    }
    kh = k1; vh = t1;
  }
  __syncwarp();
  if (lane == 0) { flag_add(&g_flags[FL_O * 32]); if (warp == 0) TS(1); }
}

__global__ void __cluster_dims__(2, 1, 1) __launch_bounds__(384, 1)
fused_kernel(const __grid_constant__ Maps mp, const uint4* __restrict__ x) {
  extern __shared__ __align__(1024) uint8_t smem_raw[];
  const uint32_t sb = (uint32_t)__cvta_generic_to_shared(smem_raw);
  const unsigned t_start = 0;
  if (blockIdx.x >= NGEMM) { attention(sb, (blockIdx.x - NGEMM) * 12 + (threadIdx.x >> 5), t_start); return; }

  const int warp = __shfl_sync(~0u, threadIdx.x >> 5, 0), lane = threadIdx.x & 31;
  const int m = blockIdx.x & 15, j = blockIdx.x >> 4, rank = blockIdx.x & 1;
  if (threadIdx.x == 256) {
    if ((sb & 0xffffff) != SM_BASE) asm volatile("trap;");
    asm volatile("prefetch.tensormap [%0];" ::"l"(&mp.x) : "memory");
    asm volatile("prefetch.tensormap [%0];" ::"l"(j < 4 ? &mp.wqkv : (rank ? &mp.wu : &mp.wg)) : "memory");
    for (int s = 0; s < 4; s++) { mbar_init(sb + B_F1 + 8 * s, 1); mbar_init(sb + B_E1 + 8 * s, P1_MULTICAST ? 4 : 2); }
    for (int s = 0; s < 6; s++) { mbar_init(sb + B_F2 + 8 * s, 1); mbar_init(sb + B_E2 + 8 * s, P2_MULTICAST ? 4 : 2); mbar_init(sb + B_DEP + 8 * s, 1); }
    mbar_init(sb + B_AUX, 2); mbar_init(sb + B_CS, 1); mbar_init(sb + B_XT, 1);
    asm volatile("fence.mbarrier_init.release.cluster;" ::: "memory");
  }
  __syncwarp();
  asm volatile("barrier.cluster.arrive.relaxed.aligned;\nbarrier.cluster.wait.aligned;" ::: "memory");

  if (warp >= 8) {
    asm volatile("setmaxnreg.dec.sync.aligned.u32 40;");
    if (warp == 8) {
      if (lane == 0) {
        TS(0);
        uint32_t par = 1;
        for (int R = 0; R < 5; R++) {
          const bool qkv = R == 1 || (R == 0 && j < 4);
          const int n0 = R == 0 ? (j < 4 ? 2048 + 256 * j : 3072 + 128 * (j - 4)) : (R == 1 ? 256 * j : 128 * (8 * (R - 2) + j));
          const CUtensorMap* mb0 = qkv ? &mp.wqkv : &mp.wg;
          const CUtensorMap* mb1 = qkv ? &mp.wqkv : &mp.wu;
          const int n1 = qkv ? n0 + 128 : n0;
          if (R == 1) { mbar_wait(sb + B_DEP, 0); TS(1); }
#pragma unroll 1
          for (int kb = 0; kb < 16; kb++) {
            const int st = kb & 3;
            const uint32_t sa = sb + st * P1_STAGE, fb = sb + B_F1 + 8 * st;
            mbar_wait(sb + B_E1 + 8 * st, par);
            mbar_expect_tx(fb, P1_STAGE);
            if (R == 0) tma3d(sa, &mp.x, fb, kb * 64, m * 64, 0); else tma2d(sa, &mp.xn, fb, kb * 64, m * 128);
            if (P1_MULTICAST) {
              const uint32_t d = sa + 16384 + rank * 16384;
              tma2d_mc(d, rank ? mb1 : mb0, fb, rank ? n1 : n0, kb * 64);
              tma2d_mc(d + 8192, rank ? mb1 : mb0, fb, (rank ? n1 : n0) + 64, kb * 64);
            } else {
              tma2d(sa + 16384, mb0, fb, n0, kb * 64); tma2d(sa + 24576, mb0, fb, n0 + 64, kb * 64);
              tma2d(sa + 32768, mb1, fb, n1, kb * 64); tma2d(sa + 40960, mb1, fb, n1 + 64, kb * 64);
            }
            if (R == 0 && kb == 5) {
              const uint32_t cb = sb + B_CS, d = sb + OFF_X;
              mbar_expect_tx(cb, 32768);
              tma2d(d, mb0, cb, n0, m * 64); tma2d(d + 8192, mb0, cb, n0 + 64, m * 64);
              tma2d(d + 16384, mb1, cb, n1, m * 64); tma2d(d + 24576, mb1, cb, n1 + 64, m * 64);
            }
            if (st == 3) par ^= 1;
          }
        }
        int st = 0; uint32_t par2 = 1;
#pragma unroll 1
        for (int i = 0; i < 72; i++) {
          if (i == 0 || i == 8 || i == 24 || i == 40 || i == 56) { mbar_wait(sb + B_DEP + 8 * (1 + ((i + 8) >> 4)), 0); TS(2 + ((i + 8) >> 4)); }
          const uint32_t sa = sb + st * P2_STAGE, fb = sb + B_F2 + 8 * st;
          if (i < 6) mbar_wait(sb + B_E1 + 8 * ((2 * i + 1) / 3), par); else mbar_wait(sb + B_E2 + 8 * st, par2);
          mbar_expect_tx(fb, P2_STAGE);
          const bool isd = i < 56;
          const int kb = isd ? (i < 8 ? 48 + i : i - 8) : i - 56;
          bulk_load(sa, isd ? g_h + (m * 56 + kb) * 1024 : g_o + (m * 16 + kb) * 1024, 16384, fb);
          const CUtensorMap* mw = isd ? &mp.wd : &mp.wo;
          if (P2_MULTICAST) tma5d_mc(sa + 16384 + rank * 8192, mw, fb, j * 128 + rank * 64, kb * 2);
          else { tma5d(sa + 16384, mw, fb, j * 128, kb * 2); tma5d(sa + 24576, mw, fb, j * 128 + 64, kb * 2); }
          if (i == 20) {
            mbar_expect_tx(sb + B_XT, 32768);
            tma3d(sb + OFF_X, &mp.x, sb + B_XT, j * 128, m * 64, 0); tma3d(sb + OFF_X + 16384, &mp.x, sb + B_XT, j * 128 + 64, m * 64, 0);
          }
          if (++st == 6) { st = 0; par2 ^= 1; }
        }
      }
    } else if (warp == 9) {
#pragma unroll 1
      for (int e = 0; e < 6; e++) {
        bar_sync(BAR_EV + e, 288);
        if (lane == 0) {
          const int f = e == 0 ? FL_XN + m : ((e == 2 || (e == 1 && j < 4)) ? FL_QKV : FL_H + m * 4 + (e == 1 ? 0 : e - 2));
          TS(10 + 2 * e);
          flag_add(&g_flags[f * 32]);
          TS(11 + 2 * e);
        }
        __syncwarp();
      }
    } else if (warp == 10) {
      unsigned e = 0;
      if (lane == 0) {
        unsigned* ep = &g_epoch[blockIdx.x * 12];
        e = *ep + 1; *ep = e;
        flag_wait(&g_flags[(FL_XN + m) * 32], e * 8u);
        fence_async();
        mbar_arrive(sb + B_DEP);
        TS(8);
      }
      __syncwarp();
      const uint4* sp = (const uint4*)(g_stats + m * 128);
      const uint4 s0 = __ldcg(sp + lane), s1 = __ldcg(sp + 32 + lane);
      sts128(sb + OFF_STATS + lane * 16, s0); sts128(sb + OFF_STATS + 512 + lane * 16, s1);
      __syncwarp();
      if (lane == 0) {
        mbar_arrive(sb + B_AUX);
#pragma unroll 1
        for (int g = 0; g < 5; g++) {
          flag_wait(&g_flags[(g < 4 ? FL_H + m * 4 + g : FL_O) * 32], e * (g == 0 ? 4u : (g < 4 ? 8u : 48u)));
          fence_async();
          mbar_arrive(sb + B_DEP + 8 * (1 + g));
        }
      }
    } else {
      unsigned e = 0;
      if (lane == 0) { unsigned* ep = &g_epoch[blockIdx.x * 12 + 1]; e = *ep + 1; *ep = e; }
      float cs[8] = {0, 0, 0, 0, 0, 0, 0, 0};
      mbar_wait(sb + B_CS, 0);
      const uint32_t base = sb + OFF_X + (lane >> 3) * 8192;
#pragma unroll 1
      for (int k0 = 0; k0 < 64; k0 += 8) {
#pragma unroll
        for (int k = 0; k < 8; k++) {
          const uint4 v = lds128(base + (k0 + k) * 128 + (((lane & 7) ^ k) << 4));
          cs[0] += lo_f(v.x); cs[1] += hi_f(v.x); cs[2] += lo_f(v.y); cs[3] += hi_f(v.y);
          cs[4] += lo_f(v.z); cs[5] += hi_f(v.z); cs[6] += lo_f(v.w); cs[7] += hi_f(v.w);
        }
      }
      float4* part = g_cspart + (j * 16 + m) * 64;
      part[lane] = make_float4(cs[0], cs[1], cs[2], cs[3]);
      part[32 + lane] = make_float4(cs[4], cs[5], cs[6], cs[7]);
      __syncwarp();
      if (lane == 0) {
        flag_add(&g_flags[(FL_CS + j) * 32]);
        flag_wait(&g_flags[(FL_CS + j) * 32], e * 16u);
        fence_async();
        mbar_expect_tx(sb + B_CS, 16384);
        bulk_load(sb + OFF_X, g_cspart + j * 1024, 16384, sb + B_CS);
      }
      __syncwarp();
      mbar_wait(sb + B_CS, 1);
#pragma unroll
      for (int i = 0; i < 8; i++) cs[i] = 0.f;
#pragma unroll 4
      for (int r = 0; r < 16; r++) {
        const uint4 a = lds128(sb + OFF_X + r * 1024 + lane * 16), b = lds128(sb + OFF_X + r * 1024 + 512 + lane * 16);
        cs[0] += __uint_as_float(a.x); cs[1] += __uint_as_float(a.y); cs[2] += __uint_as_float(a.z); cs[3] += __uint_as_float(a.w);
        cs[4] += __uint_as_float(b.x); cs[5] += __uint_as_float(b.y); cs[6] += __uint_as_float(b.z); cs[7] += __uint_as_float(b.w);
      }
#pragma unroll
      for (int q = 0; q < 4; q++) sts64(sb + OFF_CS + q * 272 + lane * 8, __float_as_uint(cs[2 * q]), __float_as_uint(cs[2 * q + 1]));
      asm volatile("fence.proxy.async.shared::cta;" ::: "memory");
      __syncwarp();
      if (lane == 0) { mbar_arrive(sb + B_AUX); TS(9); }
    }
  } else {
    asm volatile("setmaxnreg.inc.sync.aligned.u32 232;");
    const int wg = warp >> 2, w = warp & 3;
    Cons c;
    c.sb = sb; c.wg = wg;
    c.a1 = ((SM_BASE + wg * 8192) >> 4) | (1u << 16);
    c.a2 = ((SM_BASE + wg * 8192) >> 4) | (8u << 16);
    c.rel = (P1_MULTICAST || P2_MULTICAST) ? mapa(sb, threadIdx.x & 1) : sb;
    c.rel1 = P1_MULTICAST ? (threadIdx.x & 127) < 2 : (threadIdx.x & 127) == (P2_MULTICAST ? rank : 0);
    c.rel2 = (threadIdx.x & 127) < (P2_MULTICAST ? 2 : 1);
    const bool t0 = (threadIdx.x & 127) == 0;
    (void)t0;
    float acc[128];
    uint32_t pk[64];
    const int rho = lane >> 2, q = lane & 3;

    {
      const int prow = 16 * j + 2 * warp;
      const uint4* xr = x + (size_t)(128 * m + 2 * (prow & 63) + (prow >> 6)) * 128 + lane;
      uint4* xo = g_xn + (size_t)(128 * m + prow) * 128 + lane;
      float mb, rinv;
      p1_step<0>(acc, c);
      if (t0) TS(24 + wg * 16);
#pragma unroll
      for (int i = 0; i < 8; i++) {
        asm volatile("ld.global.nc.v4.b32 {%0,%1,%2,%3}, [%4];" : "=r"(pk[4 * i]), "=r"(pk[4 * i + 1]), "=r"(pk[4 * i + 2]), "=r"(pk[4 * i + 3]) : "l"(xr + (i >> 2) * 256 + (i & 3) * 32));
      }
      p1_step<1>(acc, c); p1_step<2>(acc, c); p1_step<3>(acc, c);
      p1_step<4>(acc, c);
      ln_stats(pk, mb, rinv);
      if (lane == 0) g_stats[128 * m + prow] = make_float2(mb, rinv);
      p1_step<5>(acc, c);
      ln_store(pk, mb, rinv, xo);
      p1_step<6>(acc, c);
      ln_stats(pk + 16, mb, rinv);
      if (lane == 0) g_stats[128 * m + prow + 1] = make_float2(mb, rinv);
      p1_step<7>(acc, c);
      ln_store(pk + 16, mb, rinv, xo + 128);
      bar_arrive(BAR_EV, 288);
      p1_step<8>(acc, c); p1_step<9>(acc, c); p1_step<10>(acc, c); p1_step<11>(acc, c); p1_step<12>(acc, c); p1_step<13>(acc, c);
      p1_step<14>(acc, c);
      mbar_wait(sb + B_AUX, 0);
#pragma unroll
      for (int i = 0; i < 16; i++) { const uint4 v = lds128(sb + OFF_CS + q * 272 + i * 16); pk[4 * i] = v.x; pk[4 * i + 1] = v.y; pk[4 * i + 2] = v.z; pk[4 * i + 3] = v.w; }
      const uint2 sa = lds64(sb + OFF_STATS + (warp * 16 + rho) * 8), sc = lds64(sb + OFF_STATS + (warp * 16 + 8 + rho) * 8);
      p1_step<15>(acc, c);
      const float m0 = -__uint_as_float(sa.x), r0 = __uint_as_float(sa.y), m1 = -__uint_as_float(sc.x), r1 = __uint_as_float(sc.y);
#pragma unroll
      for (int n = 0; n < 32; n++) {
        const float c0 = __uint_as_float(pk[2 * n]), c1 = __uint_as_float(pk[2 * n + 1]);
        pk[2 * n] = pack2(fmaf(m0, c0, acc[4 * n]) * r0, fmaf(m0, c1, acc[4 * n + 1]) * r0);
        pk[2 * n + 1] = pack2(fmaf(m1, c0, acc[4 * n + 2]) * r1, fmaf(m1, c1, acc[4 * n + 3]) * r1);
      }
      if (t0) TS(25 + wg * 16);
    }
    uint8_t* const hb = (uint8_t*)g_h + (size_t)m * 56 * 16384 + warp * 2048 + q * 128 + rho * 16;
#pragma unroll 1
    for (int R = 1; R < 5; R++) {
      const bool is_qkv = R == 2 || (R == 1 && j < 4);
      uint8_t* dst;
      if (is_qkv) dst = (uint8_t*)g_qkv + ((size_t)((((j & 3) * 16 + wg) * 64 + 4 * m + w) * 3 + (R == 1 ? 2 : j >> 2)) * 64 + lane) * 16;
      else dst = hb + (size_t)(R == 1 ? 48 + 2 * (j - 4) : 2 * (8 * (R - 3) + j)) * 16384;
      P1Tile<0>::run(acc, pk, c, is_qkv, dst, BAR_EV + R);
#pragma unroll
      for (int i = 0; i < 64; i++) pk[i] = pack2(acc[2 * i], acc[2 * i + 1]);
      if (t0) TS(25 + R + wg * 16);
    }
    float accd[64], accs[64];
    {
      uint8_t* dst = hb + (size_t)(2 * (16 + j)) * 16384;
      p2_step<0, 0, false, false>(accd, c, 0);
      p2_step<1, 1, true, true>(accd, c, 0);
      p2_step<2, 1, true, true>(accd, c, 0); geglu_piece<0>(pk, dst);
      p2_step<3, 1, true, true>(accd, c, 0);
      p2_step<4, 1, true, true>(accd, c, 0); geglu_piece<1>(pk, dst);
      p2_step<5, 1, true, true>(accd, c, 0);
      p2_step<0, 1, true, true>(accd, c, 1); geglu_piece<2>(pk, dst);
      p2_step<1, 1, true, true>(accd, c, 1);
      p2_step<2, 1, true, true>(accd, c, 1); geglu_piece<3>(pk, dst);
      p2_step<3, 1, true, true>(accd, c, 1);
      p2_step<4, 1, true, true>(accd, c, 1); geglu_piece<4>(pk, dst);
      p2_step<5, 1, true, true>(accd, c, 1);
      p2_step<0, 1, true, true>(accd, c, 0); geglu_piece<5>(pk, dst);
      p2_step<1, 1, true, true>(accd, c, 0);
      p2_step<2, 1, true, true>(accd, c, 0); geglu_piece<6>(pk, dst);
      p2_step<3, 1, true, true>(accd, c, 0);
      p2_step<4, 1, true, true>(accd, c, 0); geglu_piece<7>(pk, dst);
      bar_arrive(BAR_EV + 5, 288);
      p2_step<5, 1, true, true>(accd, c, 0);
      if (t0) TS(30 + wg * 16);
#pragma unroll 1
      for (int it = 3; it < 9; it++) {
        const uint32_t par = it & 1;
        p2_step<0, 1, true, true>(accd, c, par); p2_step<1, 1, true, true>(accd, c, par); p2_step<2, 1, true, true>(accd, c, par);
        p2_step<3, 1, true, true>(accd, c, par); p2_step<4, 1, true, true>(accd, c, par); p2_step<5, 1, true, true>(accd, c, par);
      }
      p2_step<0, 1, true, true>(accd, c, 1);
      p2_step<1, 1, true, true>(accd, c, 1);
      if (t0) TS(31 + wg * 16);
    }
    {
      auto silu_piece = [&](int p) {
#pragma unroll
        for (int i = 4 * p; i < 4 * p + 4; i++) {
          const float a = accd[2 * i], b = accd[2 * i + 1];
          const float ga = 0.5f * a * rcpf(1.0f + ex2f(a * -0.7213475204444817f)), gb = 0.5f * b * rcpf(1.0f + ex2f(b * -0.7213475204444817f));
          pk[i] = pack2(ga, gb);
        }
      };
      const uint32_t xa = sb + OFF_X + (warp * 16 + (lane & 15)) * 128 + (((lane >> 4) ^ (lane & 7)) << 4);
      p2_step<2, 0, true, true>(accs, c, 1); silu_piece(0);
      p2_step<3, 1, true, true>(accs, c, 1); silu_piece(1);
      p2_step<4, 1, true, true>(accs, c, 1); silu_piece(2);
      p2_step<5, 1, true, true>(accs, c, 1); silu_piece(3);
      p2_step<0, 1, true, true>(accs, c, 0); silu_piece(4);
      p2_step<1, 1, true, true>(accs, c, 0); silu_piece(5);
      p2_step<2, 1, true, true>(accs, c, 0); silu_piece(6);
      p2_step<3, 1, true, true>(accs, c, 0); silu_piece(7);
      p2_step<4, 1, true, true>(accs, c, 0);
      mbar_wait(sb + B_XT, 0);
#pragma unroll
      for (int i = 0; i < 8; i++)
        asm volatile("ldmatrix.sync.aligned.m8n8.x4.shared.b16 {%0,%1,%2,%3}, [%4];"
                     : "=r"(pk[32 + 4 * i]), "=r"(pk[33 + 4 * i]), "=r"(pk[34 + 4 * i]), "=r"(pk[35 + 4 * i]) : "r"((xa ^ ((i & 3) << 5)) + (i >> 2) * 16384) : "memory");
      p2_step<5, 1, true, true>(accs, c, 0);
      p2_step<0, 1, true, true>(accs, c, 1);
      p2_step<1, 1, false, false>(accs, c, 1);
      if (wg == 1) bar_sync(BAR_LAG, 256);
      p2_step<2, 1, false, false>(accs, c, 1);
      p2_step<3, 1, false, false>(accs, c, 1);
      p2_step<4, 1, false, false>(accs, c, 1);
      p2_step<5, 1, false, false>(accs, c, 1);
      if (wg == 0) bar_arrive(BAR_LAG, 256);
      wg_wait<0>();
      if (t0) TS(32 + wg * 16);
#pragma unroll
      for (int i = 0; i < 8; i++) {
        uint32_t v[4];
#pragma unroll
        for (int k = 0; k < 4; k++) v[k] = fma2(pack2(accs[8 * i + 2 * k], accs[1 + 8 * i + 2 * k]), pk[4 * i + k], pk[32 + 4 * i + k]);
        asm volatile("stmatrix.sync.aligned.m8n8.x4.shared.b16 [%0], {%1,%2,%3,%4};" ::"r"((xa ^ ((i & 3) << 5)) + (i >> 2) * 16384), "r"(v[0]), "r"(v[1]), "r"(v[2]), "r"(v[3]) : "memory");
        if (i == 3 || i == 7) {
          asm volatile("fence.proxy.async.shared::cta;" ::: "memory");
          __syncwarp();
          if (lane == 0) tma3d_store(&mp.out, sb + OFF_X + (i >> 2) * 16384 + warp * 2048, j * 128 + (i >> 2) * 64, m * 64 + w * 16, wg);
        }
      }
      if (lane == 0) { asm volatile("cp.async.bulk.commit_group;\ncp.async.bulk.wait_group.read 0;" ::: "memory"); }
      if (t0) TS(33 + wg * 16);
    }
  }
}

typedef CUresult (*EncodeFn)(CUtensorMap*, CUtensorMapDataType, cuuint32_t, void*, const cuuint64_t*, const cuuint64_t*, const cuuint32_t*, const cuuint32_t*,
                             CUtensorMapInterleave, CUtensorMapSwizzle, CUtensorMapL2promotion, CUtensorMapFloatOOBfill);

void encode(EncodeFn fn, CUtensorMap* tm, const void* p, int rank, const cuuint64_t* dims, const cuuint64_t* strides, const cuuint32_t* box) {
  const cuuint32_t es[5] = {1, 1, 1, 1, 1};
  fn(tm, CU_TENSOR_MAP_DATA_TYPE_BFLOAT16, rank, const_cast<void*>(p), dims, strides, box, es, CU_TENSOR_MAP_INTERLEAVE_NONE, CU_TENSOR_MAP_SWIZZLE_128B,
     CU_TENSOR_MAP_L2_PROMOTION_L2_128B, CU_TENSOR_MAP_FLOAT_OOB_FILL_NONE);
}

}

extern "C" void kernel_launch(void* const* d_in, const int* in_sizes, int n_in, void* d_out, int out_size) {
  (void)in_sizes; (void)n_in; (void)out_size;
  static EncodeFn fn = nullptr;
  static void* xn_ptr = nullptr;
  if (!fn) {
    void* p = nullptr;
    cudaDriverEntryPointQueryResult qr;
    cudaGetDriverEntryPoint("cuTensorMapEncodeTiled", &p, cudaEnableDefault, &qr);
    fn = (EncodeFn)p;
    cudaGetSymbolAddress(&xn_ptr, g_xn);
    cudaFuncSetAttribute(fused_kernel, cudaFuncAttributeMaxDynamicSharedMemorySize, SMEM_BYTES);
  }
  const void *x = d_in[0], *wqkv = d_in[1], *wo = d_in[2], *wg = d_in[4], *wu = d_in[5], *wd = d_in[6];
  Maps mp;
  {
    const cuuint64_t dims[3] = {DM, SEQ / 2, 2}, st[2] = {DM * 4, DM * 2};
    const cuuint32_t box_in[3] = {64, 64, 2}, box_out[3] = {64, 16, 1};
    encode(fn, &mp.x, x, 3, dims, st, box_in);
    encode(fn, &mp.out, d_out, 3, dims, st, box_out);
  }
  {
    const cuuint64_t dims[2] = {DM, SEQ}, st[1] = {DM * 2};
    const cuuint32_t box[2] = {64, 128};
    encode(fn, &mp.xn, xn_ptr, 2, dims, st, box);
  }
  {
    const cuuint32_t box[2] = {64, 64};
    const cuuint64_t dq[2] = {3 * DM, DM}, sq[1] = {3 * DM * 2}, df[2] = {DFF, DM}, sf[1] = {DFF * 2};
    encode(fn, &mp.wqkv, wqkv, 2, dq, sq, box);
    encode(fn, &mp.wg, wg, 2, df, sf, box);
    encode(fn, &mp.wu, wu, 2, df, sf, box);
  }
  {
    const cuuint32_t box[5] = {64, 2, 4, 4, 2};
    const cuuint64_t st[4] = {DM * 2, 8 * DM * 2, 2 * DM * 2, 32 * DM * 2};
    const cuuint64_t dd[5] = {DM, 2, 4, 4, DFF / 32}, dw[5] = {DM, 2, 4, 4, DM / 32};
    encode(fn, &mp.wd, wd, 5, dd, st, box);
    encode(fn, &mp.wo, wo, 5, dw, st, box);
  }
  fused_kernel<<<NCTA, 384, SMEM_BYTES>>>(mp, (const uint4*)x);
}
```

```cpp
#include <cuda_runtime.h>
#include <cuda_bf16.h>
#include <cuda.h>
#include <stdint.h>

#define P1_MULTICAST 1
#define P2_MULTICAST 1

namespace {

constexpr int SEQ = 2048, DM = 1024, DFF = 3584;
constexpr int NGEMM = 128, NCTA = 132;

constexpr uint32_t SM_BASE = 0x400;
constexpr uint32_t P1_STAGE = 49152, P2_STAGE = 32768;
constexpr uint32_t OFF_X = 196608;
constexpr uint32_t OFF_CS = 229376;
constexpr uint32_t OFF_STATS = OFF_CS + 1088;
constexpr uint32_t OFF_BAR = OFF_STATS + 1024;
constexpr uint32_t B_F1 = OFF_BAR, B_E1 = B_F1 + 32, B_F2 = B_E1 + 32, B_E2 = B_F2 + 48;
constexpr uint32_t B_DEP = B_E2 + 48;
constexpr uint32_t B_AUX = B_DEP + 48, B_CS = B_AUX + 8, B_XT = B_CS + 8;
constexpr uint32_t SMEM_BYTES = 232448;
constexpr uint32_t OFF_ATT_BAR = 12 * 16384;

__device__ uint4 g_xn[SEQ * DM / 8];
__device__ float2 g_stats[SEQ];
__device__ float4 g_cspart[8 * 16 * 64];
__device__ uint4 g_qkv[32 * 2 * 64 * 3 * 2 * 32];
__device__ uint4 g_o[16 * 16 * 1024];
__device__ uint4 g_h[16 * 56 * 1024];
constexpr int FL_XN = 0, FL_H = 16, FL_CS = 80, FL_QKV = 88, FL_O = 89, FL_N = 90;
__device__ unsigned g_flags[FL_N * 32];
__device__ unsigned g_epoch[NCTA * 12];
#define TS(i) do {} while (0)

struct Maps { CUtensorMap x, xn, out, wqkv, wg, wu, wd, wo; };

__device__ __forceinline__ void mbar_init(uint32_t bar, uint32_t cnt) { asm volatile("mbarrier.init.shared::cta.b64 [%0], %1;" ::"r"(bar), "r"(cnt)); }
__device__ __forceinline__ void mbar_expect_tx(uint32_t bar, uint32_t bytes) { asm volatile("mbarrier.arrive.expect_tx.shared::cta.b64 _, [%0], %1;" ::"r"(bar), "r"(bytes) : "memory"); }
__device__ __forceinline__ void mbar_arrive(uint32_t bar) { asm volatile("mbarrier.arrive.shared::cta.b64 _, [%0];" ::"r"(bar) : "memory"); }
__device__ __forceinline__ void mbar_arrive_cl(uint32_t bar) { asm volatile("mbarrier.arrive.shared::cluster.b64 _, [%0];" ::"r"(bar) : "memory"); }
__device__ __forceinline__ uint32_t mapa(uint32_t a, uint32_t cta) { uint32_t r; asm("mapa.shared::cluster.u32 %0, %1, %2;" : "=r"(r) : "r"(a), "r"(cta)); return r; }
__device__ __forceinline__ void mbar_wait(uint32_t bar, uint32_t parity) {
  asm volatile("{\n.reg .pred p;\n.reg .u32 n;\nmov.u32 n, 0;\nLAB_WAIT:\nmbarrier.try_wait.parity.shared::cta.b64 p, [%0], %1;\n@p bra LAB_DONE;\n"
               "add.u32 n, n, 1;\nsetp.gt.u32 p, n, 4000000;\n@p trap;\nbra LAB_WAIT;\nLAB_DONE:\n}" ::"r"(bar), "r"(parity) : "memory");
}
__device__ __forceinline__ void flag_wait(const unsigned* f, unsigned target) {
  asm volatile("{\n.reg .pred p;\n.reg .u32 n, v;\nmov.u32 n, 0;\nLAB_WAIT:\nld.relaxed.gpu.global.u32 v, [%0];\nsub.u32 v, v, %1;\nsetp.ge.s32 p, v, 0;\n@p bra LAB_DONE;\n"
               "nanosleep.u32 100;\nadd.u32 n, n, 1;\nsetp.gt.u32 p, n, 4000000;\n@p trap;\nbra LAB_WAIT;\nLAB_DONE:\nfence.acquire.gpu;\n}" ::"l"(f), "r"(target) : "memory");
}
__device__ __forceinline__ void flag_add(unsigned* f) { asm volatile("red.release.gpu.global.add.u32 [%0], 1;" ::"l"(f) : "memory"); }
__device__ __forceinline__ void fence_async() { asm volatile("fence.proxy.async.global;" ::: "memory"); }
__device__ __forceinline__ void bar_sync(int id, int n) { asm volatile("bar.sync %0, %1;" ::"r"(id), "r"(n) : "memory"); }
__device__ __forceinline__ void bar_arrive(int id, int n) { asm volatile("bar.arrive %0, %1;" ::"r"(id), "r"(n) : "memory"); }

__device__ __forceinline__ void tma2d(uint32_t dst, const CUtensorMap* tm, uint32_t bar, int c0, int c1) {
  asm volatile("cp.async.bulk.tensor.2d.shared::cluster.global.mbarrier::complete_tx::bytes [%0], [%1, {%3, %4}], [%2];" ::"r"(dst), "l"(tm), "r"(bar), "r"(c0), "r"(c1) : "memory");
}
__device__ __forceinline__ void tma2d_mc(uint32_t dst, const CUtensorMap* tm, uint32_t bar, int c0, int c1) {
  asm volatile("cp.async.bulk.tensor.2d.shared::cluster.global.mbarrier::complete_tx::bytes.multicast::cluster [%0], [%1, {%3, %4}], [%2], %5;" ::"r"(dst), "l"(tm), "r"(bar), "r"(c0), "r"(c1), "h"((uint16_t)3) : "memory");
}
__device__ __forceinline__ void tma3d(uint32_t dst, const CUtensorMap* tm, uint32_t bar, int c0, int c1, int c2) {
  asm volatile("cp.async.bulk.tensor.3d.shared::cluster.global.mbarrier::complete_tx::bytes [%0], [%1, {%3, %4, %5}], [%2];" ::"r"(dst), "l"(tm), "r"(bar), "r"(c0), "r"(c1), "r"(c2) : "memory");
}
__device__ __forceinline__ void tma5d(uint32_t dst, const CUtensorMap* tm, uint32_t bar, int c0, int c4) {
  asm volatile("cp.async.bulk.tensor.5d.shared::cluster.global.mbarrier::complete_tx::bytes [%0], [%1, {%3, %5, %5, %5, %4}], [%2];" ::"r"(dst), "l"(tm), "r"(bar), "r"(c0), "r"(c4), "r"(0) : "memory");
}
__device__ __forceinline__ void tma5d_mc(uint32_t dst, const CUtensorMap* tm, uint32_t bar, int c0, int c4) {
  asm volatile("cp.async.bulk.tensor.5d.shared::cluster.global.mbarrier::complete_tx::bytes.multicast::cluster [%0], [%1, {%3, %5, %5, %5, %4}], [%2], %6;" ::"r"(dst), "l"(tm), "r"(bar), "r"(c0), "r"(c4), "r"(0), "h"((uint16_t)3) : "memory");
}
__device__ __forceinline__ void tma3d_store(const CUtensorMap* tm, uint32_t src, int c0, int c1, int c2) {
  asm volatile("cp.async.bulk.tensor.3d.global.shared::cta.bulk_group [%0, {%2, %3, %4}], [%1];" ::"l"(tm), "r"(src), "r"(c0), "r"(c1), "r"(c2) : "memory");
}
__device__ __forceinline__ void bulk_load(uint32_t dst, const void* src, uint32_t bytes, uint32_t bar) {
  asm volatile("cp.async.bulk.shared::cluster.global.mbarrier::complete_tx::bytes [%0], [%1], %2, [%3];" ::"r"(dst), "l"(src), "r"(bytes), "r"(bar) : "memory");
}
__device__ __forceinline__ uint4 lds128(uint32_t a) { uint4 v; asm volatile("ld.shared.v4.b32 {%0,%1,%2,%3}, [%4];" : "=r"(v.x), "=r"(v.y), "=r"(v.z), "=r"(v.w) : "r"(a) : "memory"); return v; }
__device__ __forceinline__ uint2 lds64(uint32_t a) { uint2 v; asm volatile("ld.shared.v2.b32 {%0,%1}, [%2];" : "=r"(v.x), "=r"(v.y) : "r"(a) : "memory"); return v; }
__device__ __forceinline__ void sts64(uint32_t a, uint32_t x, uint32_t y) { asm volatile("st.shared.v2.b32 [%0], {%1,%2};" ::"r"(a), "r"(x), "r"(y) : "memory"); }
__device__ __forceinline__ void sts128(uint32_t a, uint4 v) { asm volatile("st.shared.v4.b32 [%0], {%1,%2,%3,%4};" ::"r"(a), "r"(v.x), "r"(v.y), "r"(v.z), "r"(v.w) : "memory"); }
__device__ __forceinline__ void stg128(void* p, uint32_t a, uint32_t b, uint32_t c, uint32_t d) { asm volatile("st.global.v4.b32 [%0], {%1,%2,%3,%4};" ::"l"(p), "r"(a), "r"(b), "r"(c), "r"(d) : "memory"); }

__device__ __forceinline__ uint32_t pack2(float lo, float hi) { uint32_t r; asm("cvt.rn.bf16x2.f32 %0, %1, %2;" : "=r"(r) : "f"(hi), "f"(lo)); return r; }
__device__ __forceinline__ float lo_f(uint32_t v) { return __uint_as_float(v << 16); }
__device__ __forceinline__ float hi_f(uint32_t v) { return __uint_as_float(v & 0xffff0000u); }
__device__ __forceinline__ float bf16r(float v) { return lo_f(pack2(v, 0.f)); }
__device__ __forceinline__ uint32_t mul2(uint32_t a, uint32_t b) { uint32_t r; asm("mul.rn.bf16x2 %0, %1, %2;" : "=r"(r) : "r"(a), "r"(b)); return r; }
__device__ __forceinline__ uint32_t sub2(uint32_t a, uint32_t b) { uint32_t r; asm("sub.rn.bf16x2 %0, %1, %2;" : "=r"(r) : "r"(a), "r"(b)); return r; }
__device__ __forceinline__ uint32_t fma2(uint32_t a, uint32_t b, uint32_t c) { uint32_t r; asm("fma.rn.bf16x2 %0, %1, %2, %3;" : "=r"(r) : "r"(a), "r"(b), "r"(c)); return r; }
__device__ __forceinline__ uint32_t max2(uint32_t a, uint32_t b) { uint32_t r; asm("max.bf16x2 %0, %1, %2;" : "=r"(r) : "r"(a), "r"(b)); return r; }
__device__ __forceinline__ float ex2f(float x) { float y; asm("ex2.approx.ftz.f32 %0, %1;" : "=f"(y) : "f"(x)); return y; }
__device__ __forceinline__ float rcpf(float x) { float y; asm("rcp.approx.ftz.f32 %0, %1;" : "=f"(y) : "f"(x)); return y; }
__device__ __forceinline__ float gelu2(float g) {
  float z = g * fmaf(g * g, 0.035677408136300125f, 0.7978845608028654f), t;
  asm("tanh.approx.f32 %0, %1;" : "=f"(t) : "f"(z));
  return fmaf(g, t, g);
}

__device__ __forceinline__ void wg_fence() { asm volatile("wgmma.fence.sync.aligned;" ::: "memory"); }
__device__ __forceinline__ void wg_commit() { asm volatile("wgmma.commit_group.sync.aligned;" ::: "memory"); }
template <int N> __device__ __forceinline__ void wg_wait() { asm volatile("wgmma.wait_group.sync.aligned %0;" ::"n"(N) : "memory"); }
#define A8(o) "+f"(d[(o)]), "+f"(d[(o) + 1]), "+f"(d[(o) + 2]), "+f"(d[(o) + 3]), "+f"(d[(o) + 4]), "+f"(d[(o) + 5]), "+f"(d[(o) + 6]), "+f"(d[(o) + 7])
#define A64(o) A8(o), A8((o) + 8), A8((o) + 16), A8((o) + 24), A8((o) + 32), A8((o) + 40), A8((o) + 48), A8((o) + 56)
#define REGS0_63 "%0,%1,%2,%3,%4,%5,%6,%7,%8,%9,%10,%11,%12,%13,%14,%15,%16,%17,%18,%19,%20,%21,%22,%23,%24,%25,%26,%27,%28,%29,%30,%31," \
                 "%32,%33,%34,%35,%36,%37,%38,%39,%40,%41,%42,%43,%44,%45,%46,%47,%48,%49,%50,%51,%52,%53,%54,%55,%56,%57,%58,%59,%60,%61,%62,%63"
#define REGS64_127 "%64,%65,%66,%67,%68,%69,%70,%71,%72,%73,%74,%75,%76,%77,%78,%79,%80,%81,%82,%83,%84,%85,%86,%87,%88,%89,%90,%91,%92,%93,%94,%95," \
                   "%96,%97,%98,%99,%100,%101,%102,%103,%104,%105,%106,%107,%108,%109,%110,%111,%112,%113,%114,%115,%116,%117,%118,%119,%120,%121,%122,%123,%124,%125,%126,%127"
template <int ACCUM> __device__ __forceinline__ void wgmma256(float (&d)[128], uint32_t a_lo, uint32_t b_lo) {
  asm volatile("{\n.reg .pred p;\n.reg .b64 da, db;\nsetp.ne.b32 p, %130, 0;\nmov.b64 da, {%128, 0x40000040};\nmov.b64 db, {%129, 0x40000040};\n"
               "wgmma.mma_async.sync.aligned.m64n256k16.f32.bf16.bf16 {" REGS0_63 "," REGS64_127 "}, da, db, p, 1, 1, 0, 1;\n}"
               : A64(0), A64(64) : "r"(a_lo), "r"(b_lo), "n"(ACCUM));
}
template <int ACCUM> __device__ __forceinline__ void wgmma128(float (&d)[64], uint32_t a_lo, uint32_t b_lo) {
  asm volatile("{\n.reg .pred p;\n.reg .b64 da, db;\nsetp.ne.b32 p, %66, 0;\nmov.b64 da, {%64, 0x80000020};\nmov.b64 db, {%65, 0x40000040};\n"
               "wgmma.mma_async.sync.aligned.m64n128k16.f32.bf16.bf16 {" REGS0_63 "}, da, db, p, 1, 1, 0, 1;\n}"
               : A64(0) : "r"(a_lo), "r"(b_lo), "n"(ACCUM));
}
__device__ __forceinline__ void hmma16(float (&c)[4], uint32_t a0, uint32_t a1, uint32_t a2, uint32_t a3, uint32_t b0, uint32_t b1) {
  asm("mma.sync.aligned.m16n8k16.row.col.f32.bf16.bf16.f32 {%0,%1,%2,%3}, {%4,%5,%6,%7}, {%8,%9}, {%0,%1,%2,%3};"
      : "+f"(c[0]), "+f"(c[1]), "+f"(c[2]), "+f"(c[3]) : "r"(a0), "r"(a1), "r"(a2), "r"(a3), "r"(b0), "r"(b1));
}
__device__ __forceinline__ void hmma8(float (&c)[4], uint32_t a0, uint32_t a1, uint32_t b0) {
  asm("mma.sync.aligned.m16n8k8.row.col.f32.bf16.bf16.f32 {%0,%1,%2,%3}, {%4,%5}, {%6}, {%0,%1,%2,%3};"
      : "+f"(c[0]), "+f"(c[1]), "+f"(c[2]), "+f"(c[3]) : "r"(a0), "r"(a1), "r"(b0));
}
__device__ __forceinline__ uint4 ldsm(uint32_t a) { uint4 v; asm volatile("ldmatrix.sync.aligned.m8n8.x4.shared.b16 {%0,%1,%2,%3}, [%4];" : "=r"(v.x), "=r"(v.y), "=r"(v.z), "=r"(v.w) : "r"(a) : "memory"); return v; }
__device__ __forceinline__ uint4 ldsm_t(uint32_t a) { uint4 v; asm volatile("ldmatrix.sync.aligned.m8n8.x4.trans.shared.b16 {%0,%1,%2,%3}, [%4];" : "=r"(v.x), "=r"(v.y), "=r"(v.z), "=r"(v.w) : "r"(a) : "memory"); return v; }

constexpr int BAR_LAG = 1, BAR_EV = 2;

struct Cons {
  uint32_t sb;
  uint32_t a1, a2;
  uint32_t rel;
  bool rel1, rel2;
  int wg;
};
constexpr uint32_t DB_LO = ((SM_BASE + 16384) >> 4) | ((8192 >> 4) << 16);

template <int KB> __device__ __forceinline__ void p1_step(float (&acc)[128], const Cons& c) {
  constexpr int st = KB & 3;
  if (KB == 14) { if (c.wg == 1) bar_sync(BAR_LAG, 256); }
  mbar_wait(c.sb + B_F1 + 8 * st, (KB >> 2) & 1);
  wg_fence();
  constexpr uint32_t so = st * (P1_STAGE >> 4);
  wgmma256<KB != 0>(acc, c.a1 + so, DB_LO + so);
  wgmma256<1>(acc, c.a1 + so + 2, DB_LO + so + 128);
  wgmma256<1>(acc, c.a1 + so + 4, DB_LO + so + 256);
  wgmma256<1>(acc, c.a1 + so + 6, DB_LO + so + 384);
  wg_commit();
  if (KB == 15) { if (c.wg == 0) bar_arrive(BAR_LAG, 256); }
  if (KB > 0) { wg_wait<1>(); if (c.rel1) mbar_arrive_cl(c.rel + B_E1 + 8 * ((KB - 1) & 3)); }
  if (KB == 15) { wg_wait<0>(); if (c.rel1) mbar_arrive_cl(c.rel + B_E1 + 8 * 3); }
}
template <int ST, int ACCUM, bool WAITPREV, bool RELEASE> __device__ __forceinline__ void p2_step(float (&acc)[64], const Cons& c, uint32_t parity) {
  mbar_wait(c.sb + B_F2 + 8 * ST, parity);
  wg_fence();
  constexpr uint32_t so = ST * (P2_STAGE >> 4);
  wgmma128<ACCUM>(acc, c.a2 + so, DB_LO + so);
  wgmma128<1>(acc, c.a2 + so + 2, DB_LO + so + 128);
  wgmma128<1>(acc, c.a2 + so + 512, DB_LO + so + 256);
  wgmma128<1>(acc, c.a2 + so + 514, DB_LO + so + 384);
  wg_commit();
  if (WAITPREV) wg_wait<1>();
  if (RELEASE) { if (c.rel2) mbar_arrive_cl((P2_MULTICAST ? c.rel : c.sb) + B_E2 + 8 * ((ST + 5) % 6)); }
}

template <int P> __device__ __forceinline__ void geglu_piece(const uint32_t (&pk)[64], uint8_t* dst) {
  constexpr int cg = P >> 1, r = P & 1;
  uint32_t v[4];
#pragma unroll
  for (int i = 0; i < 4; i++) {
    const uint32_t g = pk[2 * (4 * cg + i) + r];
    v[i] = mul2(pack2(gelu2(lo_f(g)), gelu2(hi_f(g))), pk[32 + 2 * (4 * cg + i) + r]);
  }
  stg128(dst + cg * 8192 + r * 512, v[0], v[1], v[2], v[3]);
}
template <int H> __device__ __forceinline__ void qkv_piece(const uint32_t (&pk)[64], uint8_t* dst) {
#pragma unroll
  for (int r = 0; r < 2; r++) stg128(dst + H * 393216 + r * 512, pk[8 * H + r], pk[8 * H + 2 + r], pk[8 * H + 4 + r], pk[8 * H + 6 + r]);
}

template <int KB> struct P1Tile {
  static __device__ __forceinline__ void run(float (&acc)[128], const uint32_t (&pk)[64], const Cons& c, bool is_qkv, uint8_t* dst, int ev) {
    p1_step<KB>(acc, c);
    if (is_qkv) {
      if (KB >= 1 && KB <= 4) { qkv_piece<(2 * KB - 2) & 7>(pk, dst); qkv_piece<(2 * KB - 1) & 7>(pk, dst); }
      if (KB == 4) bar_arrive(ev, 288);
    } else {
      if (KB >= 1 && KB <= 8) geglu_piece<(KB - 1) & 7>(pk, dst);
      if (KB == 8) bar_arrive(ev, 288);
    }
    P1Tile<KB + 1>::run(acc, pk, c, is_qkv, dst, ev);
  }
};
template <> struct P1Tile<16> { static __device__ __forceinline__ void run(float (&)[128], const uint32_t (&)[64], const Cons&, bool, uint8_t*, int) {} };

__device__ __forceinline__ void ln_stats(const uint32_t* raw, float& mb, float& rinv) {
  float f[32], s = 0.f, s2 = 0.f;
#pragma unroll
  for (int i = 0; i < 16; i++) { f[2 * i] = lo_f(raw[i]); f[2 * i + 1] = hi_f(raw[i]); s += f[2 * i]; s2 += f[2 * i + 1]; }
  s += s2;
#pragma unroll
  for (int o = 16; o; o >>= 1) s += __shfl_xor_sync(~0u, s, o);
  const float mean = s * (1.0f / DM);
  float v = 0.f, v2 = 0.f;
#pragma unroll
  for (int i = 0; i < 16; i++) { const float a = f[2 * i] - mean, b = f[2 * i + 1] - mean; v = fmaf(a, a, v); v2 = fmaf(b, b, v2); }
  v += v2;
#pragma unroll
  for (int o = 16; o; o >>= 1) v += __shfl_xor_sync(~0u, v, o);
  mb = bf16r(mean);
  float sd;
  asm("sqrt.approx.ftz.f32 %0, %1;" : "=f"(sd) : "f"(bf16r(bf16r(v * (1.0f / DM)) + 1e-5f)));
  rinv = rcpf(bf16r(sd));
}
__device__ __forceinline__ void ln_store(const uint32_t* raw, float mb, float rinv, uint4* dst) {
  const uint32_t m2 = pack2(mb, mb);
#pragma unroll
  for (int c = 0; c < 4; c++) {
    uint32_t v[4];
#pragma unroll
    for (int i = 0; i < 4; i++) { const uint32_t t = sub2(raw[4 * c + i], m2); v[i] = pack2(lo_f(t) * rinv, hi_f(t) * rinv); }
    stg128(dst + 32 * c, v[0], v[1], v[2], v[3]);
  }
}

struct AttItem {
  uint32_t la[2], lb[2];
  uint4 va[2], vb[2];
  uint4 k;
};
struct AttConst { bool le0, le1; uint32_t LE, offA, offB, zr[4]; };
__device__ __forceinline__ void att_logits(AttItem& n, const AttItem& p, const AttConst& c, uint32_t a, bool first) {
  const uint32_t aA = a + c.offA, aB = a + c.offB;
  uint4 qa[2], qb[2], k[5];
  k[0] = p.k;
#pragma unroll
  for (int i = 0; i < 2; i++) { qa[i] = ldsm(aA + i * 3072); k[1 + 2 * i] = ldsm(aB + 1024 + i * 3072); k[2 + 2 * i] = ldsm(aB + 1536 + i * 3072); qb[i] = ldsm((aA ^ 32) + i * 3072); }
#pragma unroll
  for (int i = 0; i < 2; i++) { n.va[i] = ldsm_t(aA + 2048 + i * 3072); n.vb[i] = ldsm_t((aA ^ 32) + 2048 + i * 3072); }
  n.k = k[4];
  float s[2][3][4];
#pragma unroll
  for (int i = 0; i < 6; i++) {
    float (&d)[4] = s[i / 3][i % 3];
    d[0] = d[1] = d[2] = d[3] = 0.f;
    const uint4 &q = qa[i / 3], &kk = k[2 * (i / 3) + i % 3];
    hmma16(d, q.x, q.y, q.z, q.w, kk.x, kk.y);
  }
#pragma unroll
  for (int i = 0; i < 6; i++) { const uint4 &q = qb[i / 3], &kk = k[2 * (i / 3) + i % 3]; hmma16(s[i / 3][i % 3], q.x, q.y, q.z, q.w, kk.z, kk.w); }
#pragma unroll
  for (int i = 0; i < 2; i++) {
    const uint32_t la = pack2(c.le0 ? s[i][1][0] : s[i][0][0], c.le0 ? s[i][2][2] : s[i][1][2]);
    const uint32_t lb = pack2(c.le1 ? s[i][1][1] : s[i][0][1], c.le1 ? s[i][2][3] : s[i][1][3]);
    n.la[i] = fma2(la, 0x3e353e35u, mul2(la, 0x379e379eu)); n.lb[i] = fma2(lb, 0x3e353e35u, mul2(lb, 0x379e379eu));
  }
  if (first && !c.le0) n.la[0] = (n.la[0] & 0xffff0000u) | 0xce6eu;
  if (first && !c.le1) n.lb[0] = (n.lb[0] & 0xffff0000u) | 0xce6eu;
}
__device__ __forceinline__ void att_out(const AttItem& u, const uint4& vh, const AttConst& c, uint32_t dst) {
  uint32_t mx[2] = {max2(u.la[0], u.lb[0]), max2(u.la[1], u.lb[1])};
#pragma unroll
  for (int o = 1; o <= 2; o++) { mx[0] = max2(mx[0], __shfl_xor_sync(~0u, mx[0], o)); mx[1] = max2(mx[1], __shfl_xor_sync(~0u, mx[1], o)); }
  const float L2E = 1.4426950408889634f;
  float pr[2][4], z[2][2];
#pragma unroll
  for (int i = 0; i < 2; i++) {
    pr[i][0] = ex2f((lo_f(u.la[i]) - lo_f(mx[i])) * L2E); pr[i][1] = ex2f((lo_f(u.lb[i]) - lo_f(mx[i])) * L2E);
    pr[i][2] = ex2f((hi_f(u.la[i]) - hi_f(mx[i])) * L2E); pr[i][3] = ex2f((hi_f(u.lb[i]) - hi_f(mx[i])) * L2E);
    z[i][0] = pr[i][0] + pr[i][1]; z[i][1] = pr[i][2] + pr[i][3];
  }
#pragma unroll
  for (int o = 1; o <= 2; o++) {
#pragma unroll
    for (int i = 0; i < 4; i++) z[i >> 1][i & 1] += __shfl_xor_sync(~0u, z[i >> 1][i & 1], o);
  }
  float o[2][4][4];
  uint32_t h0[2];
#pragma unroll
  for (int i = 0; i < 2; i++) {
    const float r0 = rcpf(z[i][0]), r1 = rcpf(z[i][1]);
    const uint32_t P0 = pack2(pr[i][0] * r0, pr[i][1] * r0), P1 = pack2(pr[i][2] * r1, pr[i][3] * r1);
    const uint32_t a0 = P0 & c.LE, a1 = P1 & ~c.LE, a3 = P1 & c.LE;
    h0[i] = P0 & ~c.LE;
#pragma unroll
    for (int n = 0; n < 4; n++) o[i][n][0] = o[i][n][1] = o[i][n][2] = o[i][n][3] = 0.f;
    hmma16(o[i][0], a0, a1, c.zr[i], a3, u.va[i].x, u.va[i].y); hmma16(o[i][1], a0, a1, c.zr[i], a3, u.va[i].z, u.va[i].w);
    hmma16(o[i][2], a0, a1, c.zr[i], a3, u.vb[i].x, u.vb[i].y); hmma16(o[i][3], a0, a1, c.zr[i], a3, u.vb[i].z, u.vb[i].w);
  }
  hmma8(o[0][0], h0[0], c.zr[2], vh.x); hmma8(o[0][1], h0[0], c.zr[2], vh.y); hmma8(o[0][2], h0[0], c.zr[2], vh.z); hmma8(o[0][3], h0[0], c.zr[2], vh.w);
  hmma8(o[1][0], h0[1], c.zr[3], u.va[0].y); hmma8(o[1][1], h0[1], c.zr[3], u.va[0].w); hmma8(o[1][2], h0[1], c.zr[3], u.vb[0].y); hmma8(o[1][3], h0[1], c.zr[3], u.vb[0].w);
#pragma unroll
  for (int i = 0; i < 2; i++) {
#pragma unroll
    for (int r = 0; r < 2; r++)
      sts128(dst + i * 1024 + r * 512, make_uint4(pack2(o[i][0][2 * r], o[i][0][2 * r + 1]), pack2(o[i][1][2 * r], o[i][1][2 * r + 1]), pack2(o[i][2][2 * r], o[i][2][2 * r + 1]), pack2(o[i][3][2 * r], o[i][3][2 * r + 1])));
  }
}
__device__ __forceinline__ void attention(uint32_t sb, int warp, unsigned t_start) {
  const int lane = threadIdx.x & 31, gw = (blockIdx.x - NGEMM) * 12 + warp;
  const uint32_t ring = sb + warp * 16384, bars = sb + OFF_ATT_BAR + warp * 16;
  const int u_beg = (gw * 2048) / 48, u_end = ((gw + 1) * 2048) / 48;
  const int u0 = gw ? u_beg - 1 : 0;
  const uint8_t* src = (const uint8_t*)g_qkv + (size_t)u0 * 6144;
  if (lane == 0) {
    mbar_init(bars, 1); mbar_init(bars + 8, 1);
    asm volatile("fence.proxy.async.shared::cta;" ::: "memory");
    unsigned* ep = &g_epoch[blockIdx.x * 12 + warp];
    const unsigned e = *ep + 1;
    *ep = e;
    flag_wait(&g_flags[FL_QKV * 32], e * 192u);
    fence_async();
    if (warp == 0) TS(0);
    for (int s = 0; s < 2; s++) { mbar_expect_tx(bars + 8 * s, 6144); bulk_load(ring + s * 6144, src + s * 6144, 6144, bars + 8 * s); }
  }
  __syncwarp();
  const int rho = lane >> 2, q = lane & 3;
  AttConst c;
  c.le0 = 2 * q <= rho; c.le1 = 2 * q + 1 <= rho;
  c.LE = (c.le0 ? 0xffffu : 0u) | (c.le1 ? 0xffff0000u : 0u);
  c.offA = ((lane >> 3) & 1) * 512 + (lane & 7) * 64 + (((lane >> 4) ^ ((lane & 7) >> 1)) << 4);
  c.offB = (lane & 7) * 64 + (((lane >> 3) ^ ((lane & 7) >> 1)) << 4);
#pragma unroll
  for (int i = 0; i < 4; i++) c.zr[i] = __shfl_sync(~0u, lane, 0, 2 << i) >> 5;
  const uint32_t ost = ring + 12288 + ((lane ^ (lane >> 3)) << 4);
  AttItem I[2];
#pragma unroll
  for (int i = 0; i < 2; i++) {
    I[i].k = I[i].va[0] = I[i].va[1] = I[i].vb[0] = I[i].vb[1] = make_uint4(0, 0, 0, 0);
    I[i].la[0] = I[i].la[1] = I[i].lb[0] = I[i].lb[1] = 0;
  }
#pragma unroll 1
  for (int ub = u0, it = 0; ub <= u_end; ub += 2, it++) {
#pragma unroll
    for (int s = 0; s < 2; s++) {
      const int u = ub + s;
      if (u < u_end) mbar_wait(bars + 8 * s, it & 1);
      const uint4 vh = make_uint4(I[s].va[1].y, I[s].va[1].w, I[s].vb[1].y, I[s].vb[1].w);
      att_logits(I[s], I[s ^ 1], c, ring + s * 6144, (u & 31) == 0);
      att_out(I[s ^ 1], vh, c, ost + s * 2048);
      asm volatile("fence.proxy.async.shared::cta;" ::: "memory");
      __syncwarp();
      if (lane == 0) {
        const int v = u - 1;
        if (u + 2 < u_end) { mbar_expect_tx(bars + 8 * s, 6144); bulk_load(ring + s * 6144, (const uint8_t*)g_qkv + (size_t)(u + 2) * 6144, 6144, bars + 8 * s); }
        if (v >= u_beg && v < u_end) {
          const uint8_t* dst = (const uint8_t*)g_o + (((v >> 1) & 15) * 16 + (v >> 7)) * 16384 + ((v >> 6) & 1) * 8192 + (((v >> 5) & 1) * 2 + (v & 1)) * 2048;
          asm volatile("cp.async.bulk.global.shared::cta.bulk_group [%0], [%1], 2048;" ::"l"(dst), "r"(ring + 12288 + s * 2048) : "memory");
        }
        asm volatile("cp.async.bulk.commit_group;\ncp.async.bulk.wait_group.read 1;" ::: "memory");
      }
      __syncwarp();
    }
  }
  if (lane == 0) {
    asm volatile("cp.async.bulk.wait_group 0;" ::: "memory");
    fence_async();
    flag_add(&g_flags[FL_O * 32]);
    if (warp == 0) TS(1);
  }
}

__global__ void __cluster_dims__(2, 1, 1) __launch_bounds__(384, 1)
fused_kernel(const __grid_constant__ Maps mp, const uint4* __restrict__ x) {
  extern __shared__ __align__(1024) uint8_t smem_raw[];
  const uint32_t sb = (uint32_t)__cvta_generic_to_shared(smem_raw);
  const unsigned t_start = 0;
  const int warp = __shfl_sync(~0u, threadIdx.x >> 5, 0), lane = threadIdx.x & 31;
  if (blockIdx.x >= NGEMM) { attention(sb, warp, t_start); return; }

  const int m = blockIdx.x & 15, j = blockIdx.x >> 4, rank = blockIdx.x & 1;
  if (threadIdx.x == 256) {
    if ((sb & 0xffffff) != SM_BASE) asm volatile("trap;");
    asm volatile("prefetch.tensormap [%0];" ::"l"(&mp.x) : "memory");
    asm volatile("prefetch.tensormap [%0];" ::"l"(j < 4 ? &mp.wqkv : (rank ? &mp.wu : &mp.wg)) : "memory");
    for (int s = 0; s < 4; s++) { mbar_init(sb + B_F1 + 8 * s, 1); mbar_init(sb + B_E1 + 8 * s, P1_MULTICAST ? 4 : 2); }
    for (int s = 0; s < 6; s++) { mbar_init(sb + B_F2 + 8 * s, 1); mbar_init(sb + B_E2 + 8 * s, P2_MULTICAST ? 4 : 2); mbar_init(sb + B_DEP + 8 * s, 1); }
    mbar_init(sb + B_AUX, 2); mbar_init(sb + B_CS, 1); mbar_init(sb + B_XT, 1);
    asm volatile("fence.mbarrier_init.release.cluster;" ::: "memory");
  }
  __syncwarp();
  asm volatile("barrier.cluster.arrive.relaxed.aligned;\nbarrier.cluster.wait.aligned;" ::: "memory");

  if (warp >= 8) {
    asm volatile("setmaxnreg.dec.sync.aligned.u32 40;");
    if (warp == 8) {
      if (lane == 0) {
        TS(0);
        uint32_t par = 1;
        for (int R = 0; R < 5; R++) {
          const bool qkv = R == 1 || (R == 0 && j < 4);
          const int n0 = R == 0 ? (j < 4 ? 2048 + 256 * j : 3072 + 128 * (j - 4)) : (R == 1 ? 256 * j : 128 * (8 * (R - 2) + j));
          const CUtensorMap* mb0 = qkv ? &mp.wqkv : &mp.wg;
          const CUtensorMap* mb1 = qkv ? &mp.wqkv : &mp.wu;
          const int n1 = qkv ? n0 + 128 : n0;
          if (R == 1) { mbar_wait(sb + B_DEP, 0); TS(1); }
#pragma unroll 1
          for (int kb = 0; kb < 16; kb++) {
            const int st = kb & 3;
            const uint32_t sa = sb + st * P1_STAGE, fb = sb + B_F1 + 8 * st;
            mbar_wait(sb + B_E1 + 8 * st, par);
            mbar_expect_tx(fb, P1_STAGE);
            if (R == 0) tma3d(sa, &mp.x, fb, kb * 64, m * 64, 0); else tma2d(sa, &mp.xn, fb, kb * 64, m * 128);
            if (P1_MULTICAST) {
              const uint32_t d = sa + 16384 + rank * 16384;
              tma2d_mc(d, rank ? mb1 : mb0, fb, rank ? n1 : n0, kb * 64);
              tma2d_mc(d + 8192, rank ? mb1 : mb0, fb, (rank ? n1 : n0) + 64, kb * 64);
            } else {
              tma2d(sa + 16384, mb0, fb, n0, kb * 64); tma2d(sa + 24576, mb0, fb, n0 + 64, kb * 64);
              tma2d(sa + 32768, mb1, fb, n1, kb * 64); tma2d(sa + 40960, mb1, fb, n1 + 64, kb * 64);
            }
            if (R == 0 && kb == 5) {
              const uint32_t cb = sb + B_CS, d = sb + OFF_X;
              mbar_expect_tx(cb, 32768);
              tma2d(d, mb0, cb, n0, m * 64); tma2d(d + 8192, mb0, cb, n0 + 64, m * 64);
              tma2d(d + 16384, mb1, cb, n1, m * 64); tma2d(d + 24576, mb1, cb, n1 + 64, m * 64);
            }
            if (st == 3) par ^= 1;
          }
        }
        int st = 0; uint32_t par2 = 1;
#pragma unroll 1
        for (int i = 0; i < 72; i++) {
          if (i == 0 || i == 8 || i == 24 || i == 40 || i == 56) { mbar_wait(sb + B_DEP + 8 * (1 + ((i + 8) >> 4)), 0); TS(2 + ((i + 8) >> 4)); }
          const uint32_t sa = sb + st * P2_STAGE, fb = sb + B_F2 + 8 * st;
          if (i < 6) mbar_wait(sb + B_E1 + 8 * ((2 * i + 1) / 3), par); else mbar_wait(sb + B_E2 + 8 * st, par2);
          mbar_expect_tx(fb, P2_STAGE);
          const bool isd = i < 56;
          const int kb = isd ? (i < 8 ? 48 + i : i - 8) : i - 56;
          bulk_load(sa, isd ? g_h + (m * 56 + kb) * 1024 : g_o + (m * 16 + kb) * 1024, 16384, fb);
          const CUtensorMap* mw = isd ? &mp.wd : &mp.wo;
          if (P2_MULTICAST) tma5d_mc(sa + 16384 + rank * 8192, mw, fb, j * 128 + rank * 64, kb * 2);
          else { tma5d(sa + 16384, mw, fb, j * 128, kb * 2); tma5d(sa + 24576, mw, fb, j * 128 + 64, kb * 2); }
          if (i == 20) {
            mbar_expect_tx(sb + B_XT, 32768);
            tma3d(sb + OFF_X, &mp.x, sb + B_XT, j * 128, m * 64, 0); tma3d(sb + OFF_X + 16384, &mp.x, sb + B_XT, j * 128 + 64, m * 64, 0);
          }
          if (++st == 6) { st = 0; par2 ^= 1; }
        }
      }
    } else if (warp == 9) {
#pragma unroll 1
      for (int e = 0; e < 6; e++) {
        bar_sync(BAR_EV + e, 288);
        if (lane == 0) {
          const int f = e == 0 ? FL_XN + m : ((e == 2 || (e == 1 && j < 4)) ? FL_QKV : FL_H + m * 4 + (e == 1 ? 0 : e - 2));
          TS(10 + 2 * e);
          flag_add(&g_flags[f * 32]);
          TS(11 + 2 * e);
        }
        __syncwarp();
      }
    } else if (warp == 10) {
      unsigned e = 0;
      if (lane == 0) {
        unsigned* ep = &g_epoch[blockIdx.x * 12];
        e = *ep + 1; *ep = e;
        flag_wait(&g_flags[(FL_XN + m) * 32], e * 8u);
        fence_async();
        mbar_arrive(sb + B_DEP);
        TS(8);
      }
      __syncwarp();
      const uint4* sp = (const uint4*)(g_stats + m * 128);
      const uint4 s0 = __ldcg(sp + lane), s1 = __ldcg(sp + 32 + lane);
      sts128(sb + OFF_STATS + lane * 16, s0); sts128(sb + OFF_STATS + 512 + lane * 16, s1);
      __syncwarp();
      if (lane == 0) {
        mbar_arrive(sb + B_AUX);
#pragma unroll 1
        for (int g = 0; g < 5; g++) {
          flag_wait(&g_flags[(g < 4 ? FL_H + m * 4 + g : FL_O) * 32], e * (g == 0 ? 4u : (g < 4 ? 8u : 48u)));
          fence_async();
          mbar_arrive(sb + B_DEP + 8 * (1 + g));
        }
      }
    } else {
      unsigned e = 0;
      if (lane == 0) { unsigned* ep = &g_epoch[blockIdx.x * 12 + 1]; e = *ep + 1; *ep = e; }
      float cs[8] = {0, 0, 0, 0, 0, 0, 0, 0};
      mbar_wait(sb + B_CS, 0);
      const uint32_t base = sb + OFF_X + (lane >> 3) * 8192;
#pragma unroll 1
      for (int k0 = 0; k0 < 64; k0 += 8) {
#pragma unroll
        for (int k = 0; k < 8; k++) {
          const uint4 v = lds128(base + (k0 + k) * 128 + (((lane & 7) ^ k) << 4));
          cs[0] += lo_f(v.x); cs[1] += hi_f(v.x); cs[2] += lo_f(v.y); cs[3] += hi_f(v.y);
          cs[4] += lo_f(v.z); cs[5] += hi_f(v.z); cs[6] += lo_f(v.w); cs[7] += hi_f(v.w);
        }
      }
      float4* part = g_cspart + (j * 16 + m) * 64;
      part[lane] = make_float4(cs[0], cs[1], cs[2], cs[3]);
      part[32 + lane] = make_float4(cs[4], cs[5], cs[6], cs[7]);
      __syncwarp();
      if (lane == 0) {
        flag_add(&g_flags[(FL_CS + j) * 32]);
        flag_wait(&g_flags[(FL_CS + j) * 32], e * 16u);
        fence_async();
        mbar_expect_tx(sb + B_CS, 16384);
        bulk_load(sb + OFF_X, g_cspart + j * 1024, 16384, sb + B_CS);
      }
      __syncwarp();
      mbar_wait(sb + B_CS, 1);
#pragma unroll
      for (int i = 0; i < 8; i++) cs[i] = 0.f;
#pragma unroll 4
      for (int r = 0; r < 16; r++) {
        const uint4 a = lds128(sb + OFF_X + r * 1024 + lane * 16), b = lds128(sb + OFF_X + r * 1024 + 512 + lane * 16);
        cs[0] += __uint_as_float(a.x); cs[1] += __uint_as_float(a.y); cs[2] += __uint_as_float(a.z); cs[3] += __uint_as_float(a.w);
        cs[4] += __uint_as_float(b.x); cs[5] += __uint_as_float(b.y); cs[6] += __uint_as_float(b.z); cs[7] += __uint_as_float(b.w);
      }
#pragma unroll
      for (int q = 0; q < 4; q++) sts64(sb + OFF_CS + q * 272 + lane * 8, __float_as_uint(cs[2 * q]), __float_as_uint(cs[2 * q + 1]));
      asm volatile("fence.proxy.async.shared::cta;" ::: "memory");
      __syncwarp();
      if (lane == 0) { mbar_arrive(sb + B_AUX); TS(9); }
    }
  } else {
    asm volatile("setmaxnreg.inc.sync.aligned.u32 232;");
    const int wg = warp >> 2, w = warp & 3;
    Cons c;
    c.sb = sb; c.wg = wg;
    c.a1 = ((SM_BASE + wg * 8192) >> 4) | (1u << 16);
    c.a2 = ((SM_BASE + wg * 4096) >> 4) | (1u << 16);
    c.rel = (P1_MULTICAST || P2_MULTICAST) ? mapa(sb, threadIdx.x & 1) : sb;
    c.rel1 = P1_MULTICAST ? (threadIdx.x & 127) < 2 : (threadIdx.x & 127) == (P2_MULTICAST ? rank : 0);
    c.rel2 = (threadIdx.x & 127) < (P2_MULTICAST ? 2 : 1);
    const bool t0 = (threadIdx.x & 127) == 0;
    (void)t0;
    float acc[128];
    uint32_t pk[64];
    const int rho = lane >> 2, q = lane & 3;

    {
      const int prow = 16 * j + 2 * warp;
      const uint4* xr = x + (size_t)(128 * m + 2 * (prow & 63) + (prow >> 6)) * 128 + lane;
      uint4* xo = g_xn + (size_t)(128 * m + prow) * 128 + lane;
      float mb, rinv;
      p1_step<0>(acc, c);
      if (t0) TS(24 + wg * 16);
#pragma unroll
      for (int i = 0; i < 8; i++) {
        asm volatile("ld.global.nc.v4.b32 {%0,%1,%2,%3}, [%4];" : "=r"(pk[4 * i]), "=r"(pk[4 * i + 1]), "=r"(pk[4 * i + 2]), "=r"(pk[4 * i + 3]) : "l"(xr + (i >> 2) * 256 + (i & 3) * 32));
      }
      p1_step<1>(acc, c); p1_step<2>(acc, c); p1_step<3>(acc, c);
      p1_step<4>(acc, c);
      ln_stats(pk, mb, rinv);
      if (lane == 0) g_stats[128 * m + prow] = make_float2(mb, rinv);
      p1_step<5>(acc, c);
      ln_store(pk, mb, rinv, xo);
      p1_step<6>(acc, c);
      ln_stats(pk + 16, mb, rinv);
      if (lane == 0) g_stats[128 * m + prow + 1] = make_float2(mb, rinv);
      p1_step<7>(acc, c);
      ln_store(pk + 16, mb, rinv, xo + 128);
      bar_arrive(BAR_EV, 288);
      p1_step<8>(acc, c); p1_step<9>(acc, c); p1_step<10>(acc, c); p1_step<11>(acc, c); p1_step<12>(acc, c); p1_step<13>(acc, c);
      p1_step<14>(acc, c);
      mbar_wait(sb + B_AUX, 0);
#pragma unroll
      for (int i = 0; i < 16; i++) { const uint4 v = lds128(sb + OFF_CS + q * 272 + i * 16); pk[4 * i] = v.x; pk[4 * i + 1] = v.y; pk[4 * i + 2] = v.z; pk[4 * i + 3] = v.w; }
      const uint2 sa = lds64(sb + OFF_STATS + (warp * 16 + rho) * 8), sc = lds64(sb + OFF_STATS + (warp * 16 + 8 + rho) * 8);
      p1_step<15>(acc, c);
      const float m0 = -__uint_as_float(sa.x), r0 = __uint_as_float(sa.y), m1 = -__uint_as_float(sc.x), r1 = __uint_as_float(sc.y);
#pragma unroll
      for (int n = 0; n < 32; n++) {
        const float c0 = __uint_as_float(pk[2 * n]), c1 = __uint_as_float(pk[2 * n + 1]);
        pk[2 * n] = pack2(fmaf(m0, c0, acc[4 * n]) * r0, fmaf(m0, c1, acc[4 * n + 1]) * r0);
        pk[2 * n + 1] = pack2(fmaf(m1, c0, acc[4 * n + 2]) * r1, fmaf(m1, c1, acc[4 * n + 3]) * r1);
      }
      if (t0) TS(25 + wg * 16);
    }
    uint8_t* const hb = (uint8_t*)g_h + (size_t)m * 56 * 16384 + warp * 1024 + ((lane ^ (lane >> 3)) << 4);
#pragma unroll 1
    for (int R = 1; R < 5; R++) {
      const bool is_qkv = R == 2 || (R == 1 && j < 4);
      uint8_t* dst;
      if (is_qkv) dst = (uint8_t*)g_qkv + ((size_t)((((j & 3) * 16 + wg) * 64 + 4 * m + w) * 3 + (R == 1 ? 2 : j >> 2)) * 64 + (lane ^ (lane >> 3))) * 16;
      else dst = hb + (size_t)(R == 1 ? 48 + 2 * (j - 4) : 2 * (8 * (R - 3) + j)) * 16384;
      P1Tile<0>::run(acc, pk, c, is_qkv, dst, BAR_EV + R);
#pragma unroll
      for (int i = 0; i < 64; i++) pk[i] = pack2(acc[2 * i], acc[2 * i + 1]);
      if (t0) TS(25 + R + wg * 16);
    }
    float accd[64], accs[64];
    {
      uint8_t* dst = hb + (size_t)(2 * (16 + j)) * 16384;
      p2_step<0, 0, false, false>(accd, c, 0);
      p2_step<1, 1, true, true>(accd, c, 0);
      p2_step<2, 1, true, true>(accd, c, 0); geglu_piece<0>(pk, dst);
      p2_step<3, 1, true, true>(accd, c, 0);
      p2_step<4, 1, true, true>(accd, c, 0); geglu_piece<1>(pk, dst);
      p2_step<5, 1, true, true>(accd, c, 0);
      p2_step<0, 1, true, true>(accd, c, 1); geglu_piece<2>(pk, dst);
      p2_step<1, 1, true, true>(accd, c, 1);
      p2_step<2, 1, true, true>(accd, c, 1); geglu_piece<3>(pk, dst);
      p2_step<3, 1, true, true>(accd, c, 1);
      p2_step<4, 1, true, true>(accd, c, 1); geglu_piece<4>(pk, dst);
      p2_step<5, 1, true, true>(accd, c, 1);
      p2_step<0, 1, true, true>(accd, c, 0); geglu_piece<5>(pk, dst);
      p2_step<1, 1, true, true>(accd, c, 0);
      p2_step<2, 1, true, true>(accd, c, 0); geglu_piece<6>(pk, dst);
      p2_step<3, 1, true, true>(accd, c, 0);
      p2_step<4, 1, true, true>(accd, c, 0); geglu_piece<7>(pk, dst);
      bar_arrive(BAR_EV + 5, 288);
      p2_step<5, 1, true, true>(accd, c, 0);
      if (t0) TS(30 + wg * 16);
#pragma unroll 1
      for (int it = 3; it < 9; it++) {
        const uint32_t par = it & 1;
        p2_step<0, 1, true, true>(accd, c, par); p2_step<1, 1, true, true>(accd, c, par); p2_step<2, 1, true, true>(accd, c, par);
        p2_step<3, 1, true, true>(accd, c, par); p2_step<4, 1, true, true>(accd, c, par); p2_step<5, 1, true, true>(accd, c, par);
      }
      p2_step<0, 1, true, true>(accd, c, 1);
      p2_step<1, 1, true, true>(accd, c, 1);
      if (t0) TS(31 + wg * 16);
    }
    {
      auto silu_piece = [&](int p) {
#pragma unroll
        for (int i = 4 * p; i < 4 * p + 4; i++) {
          const float a = accd[2 * i], b = accd[2 * i + 1];
          const float ga = 0.5f * a * rcpf(1.0f + ex2f(a * -0.7213475204444817f)), gb = 0.5f * b * rcpf(1.0f + ex2f(b * -0.7213475204444817f));
          pk[i] = pack2(ga, gb);
        }
      };
      const uint32_t xa = sb + OFF_X + (warp * 16 + (lane & 15)) * 128 + (((lane >> 4) ^ (lane & 7)) << 4);
      p2_step<2, 0, true, true>(accs, c, 1); silu_piece(0);
      p2_step<3, 1, true, true>(accs, c, 1); silu_piece(1);
      p2_step<4, 1, true, true>(accs, c, 1); silu_piece(2);
      p2_step<5, 1, true, true>(accs, c, 1); silu_piece(3);
      p2_step<0, 1, true, true>(accs, c, 0); silu_piece(4);
      p2_step<1, 1, true, true>(accs, c, 0); silu_piece(5);
      p2_step<2, 1, true, true>(accs, c, 0); silu_piece(6);
      p2_step<3, 1, true, true>(accs, c, 0); silu_piece(7);
      p2_step<4, 1, true, true>(accs, c, 0);
      mbar_wait(sb + B_XT, 0);
#pragma unroll
      for (int i = 0; i < 8; i++)
        asm volatile("ldmatrix.sync.aligned.m8n8.x4.shared.b16 {%0,%1,%2,%3}, [%4];"
                     : "=r"(pk[32 + 4 * i]), "=r"(pk[33 + 4 * i]), "=r"(pk[34 + 4 * i]), "=r"(pk[35 + 4 * i]) : "r"((xa ^ ((i & 3) << 5)) + (i >> 2) * 16384) : "memory");
      p2_step<5, 1, true, true>(accs, c, 0);
      p2_step<0, 1, true, true>(accs, c, 1);
      p2_step<1, 1, false, false>(accs, c, 1);
      if (wg == 1) bar_sync(BAR_LAG, 256);
      p2_step<2, 1, false, false>(accs, c, 1);
      p2_step<3, 1, false, false>(accs, c, 1);
      p2_step<4, 1, false, false>(accs, c, 1);
      p2_step<5, 1, false, false>(accs, c, 1);
      if (wg == 0) bar_arrive(BAR_LAG, 256);
      wg_wait<0>();
      if (t0) TS(32 + wg * 16);
#pragma unroll
      for (int i = 0; i < 8; i++) {
        uint32_t v[4];
#pragma unroll
        for (int k = 0; k < 4; k++) v[k] = fma2(pack2(accs[8 * i + 2 * k], accs[1 + 8 * i + 2 * k]), pk[4 * i + k], pk[32 + 4 * i + k]);
        asm volatile("stmatrix.sync.aligned.m8n8.x4.shared.b16 [%0], {%1,%2,%3,%4};" ::"r"((xa ^ ((i & 3) << 5)) + (i >> 2) * 16384), "r"(v[0]), "r"(v[1]), "r"(v[2]), "r"(v[3]) : "memory");
        if (i == 3 || i == 7) {
          asm volatile("fence.proxy.async.shared::cta;" ::: "memory");
          __syncwarp();
          if (lane == 0) tma3d_store(&mp.out, sb + OFF_X + (i >> 2) * 16384 + warp * 2048, j * 128 + (i >> 2) * 64, m * 64 + w * 16, wg);
        }
      }
      if (lane == 0) { asm volatile("cp.async.bulk.commit_group;\ncp.async.bulk.wait_group.read 0;" ::: "memory"); }
      if (t0) TS(33 + wg * 16);
    }
  }
}

typedef CUresult (*EncodeFn)(CUtensorMap*, CUtensorMapDataType, cuuint32_t, void*, const cuuint64_t*, const cuuint64_t*, const cuuint32_t*, const cuuint32_t*,
                             CUtensorMapInterleave, CUtensorMapSwizzle, CUtensorMapL2promotion, CUtensorMapFloatOOBfill);

void encode(EncodeFn fn, CUtensorMap* tm, const void* p, int rank, const cuuint64_t* dims, const cuuint64_t* strides, const cuuint32_t* box) {
  const cuuint32_t es[5] = {1, 1, 1, 1, 1};
  fn(tm, CU_TENSOR_MAP_DATA_TYPE_BFLOAT16, rank, const_cast<void*>(p), dims, strides, box, es, CU_TENSOR_MAP_INTERLEAVE_NONE, CU_TENSOR_MAP_SWIZZLE_128B,
     CU_TENSOR_MAP_L2_PROMOTION_L2_128B, CU_TENSOR_MAP_FLOAT_OOB_FILL_NONE);
}

}

extern "C" void kernel_launch(void* const* d_in, const int* in_sizes, int n_in, void* d_out, int out_size) {
  (void)in_sizes; (void)n_in; (void)out_size;
  static EncodeFn fn = nullptr;
  static void* xn_ptr = nullptr;
  if (!fn) {
    void* p = nullptr;
    cudaDriverEntryPointQueryResult qr;
    cudaGetDriverEntryPoint("cuTensorMapEncodeTiled", &p, cudaEnableDefault, &qr);
    fn = (EncodeFn)p;
    cudaGetSymbolAddress(&xn_ptr, g_xn);
    cudaFuncSetAttribute(fused_kernel, cudaFuncAttributeMaxDynamicSharedMemorySize, SMEM_BYTES);
  }
  const void *x = d_in[0], *wqkv = d_in[1], *wo = d_in[2], *wg = d_in[4], *wu = d_in[5], *wd = d_in[6];
  Maps mp;
  {
    const cuuint64_t dims[3] = {DM, SEQ / 2, 2}, st[2] = {DM * 4, DM * 2};
    const cuuint32_t box_in[3] = {64, 64, 2}, box_out[3] = {64, 16, 1};
    encode(fn, &mp.x, x, 3, dims, st, box_in);
    encode(fn, &mp.out, d_out, 3, dims, st, box_out);
  }
  {
    const cuuint64_t dims[2] = {DM, SEQ}, st[1] = {DM * 2};
    const cuuint32_t box[2] = {64, 128};
    encode(fn, &mp.xn, xn_ptr, 2, dims, st, box);
  }
  {
    const cuuint32_t box[2] = {64, 64};
    const cuuint64_t dq[2] = {3 * DM, DM}, sq[1] = {3 * DM * 2}, df[2] = {DFF, DM}, sf[1] = {DFF * 2};
    encode(fn, &mp.wqkv, wqkv, 2, dq, sq, box);
    encode(fn, &mp.wg, wg, 2, df, sf, box);
    encode(fn, &mp.wu, wu, 2, df, sf, box);
  }
  {
    const cuuint32_t box[5] = {64, 2, 4, 4, 2};
    const cuuint64_t st[4] = {DM * 2, 8 * DM * 2, 2 * DM * 2, 32 * DM * 2};
    const cuuint64_t dd[5] = {DM, 2, 4, 4, DFF / 32}, dw[5] = {DM, 2, 4, 4, DM / 32};
    encode(fn, &mp.wd, wd, 5, dd, st, box);
    const cuuint64_t so[4] = {DM * 2, 2 * DM * 2, 8 * DM * 2, 32 * DM * 2};
    encode(fn, &mp.wo, wo, 5, dw, so, box);
  }
  fused_kernel<<<NCTA, 384, SMEM_BYTES>>>(mp, (const uint4*)x);
}
```

```cpp
#include <cuda_runtime.h>
#include <cuda_bf16.h>
#include <cuda.h>
#include <stdint.h>

#define CS_KB 6
#define LN_EARLY 0
#define LN_KB 3

#define EVICT_FIRST 0x12F0000000000000ull
#define EVICT_NORMAL 0x1000000000000000ull
#define HINT_W EVICT_FIRST
#define HINT_H EVICT_FIRST
#define HINT_LAST EVICT_FIRST

namespace {

constexpr int SEQ = 2048, DM = 1024, DFF = 3584;
constexpr int NCTA = 128;

constexpr uint32_t SM_BASE = 0x400;
constexpr uint32_t P1_STAGE = 49152, P2_STAGE = 32768;
constexpr uint32_t OFF_X = 196608;
constexpr uint32_t OFF_CS = 229376;
constexpr uint32_t OFF_STATS = OFF_CS + 1088;
constexpr uint32_t OFF_BAR = OFF_STATS + 1024;
constexpr uint32_t OFF_LAND = 5 * P2_STAGE;
constexpr uint32_t B_F1 = OFF_BAR, B_E1 = B_F1 + 32, B_F2 = B_E1 + 32, B_E2 = B_F2 + 40;
constexpr uint32_t B_DEP = B_E2 + 40;
constexpr uint32_t B_AUX = B_DEP + 40, B_CS = B_AUX + 8, B_XT = B_CS + 8, B_EX = B_XT + 8, B_HALO = B_EX + 16, OFF_EPOCH = B_HALO + 16;
constexpr uint32_t SMEM_BYTES = 232448;
constexpr uint32_t AT_V = 0, AT_K = 8192, AT_REM = 11264, AT_WG = 15360;

__device__ uint4 g_xn[SEQ * DM / 8];
__device__ float2 g_stats[SEQ];
__device__ ulonglong2 g_cspart[8 * 16 * 128];
__device__ uint4 g_halo[2 * 128 * 2 * 128];
__device__ uint4 g_o[16 * 16 * 1024];
__device__ uint4 g_h[16 * 56 * 1024];
constexpr int FL_XN = 0, FL_H = 16, FL_HALO = 80, FL_N = FL_HALO + 256;
__device__ unsigned g_flags[FL_N * 32];
__device__ unsigned g_epoch[NCTA * 2];
#define TG(i) do {} while (0)
#define TS(i) do {} while (0)

struct Maps { CUtensorMap x, xn, out, wqkv, wg, wu, wd, wo; };

__device__ __forceinline__ void mbar_init(uint32_t bar, uint32_t cnt) { asm volatile("mbarrier.init.shared::cta.b64 [%0], %1;" ::"r"(bar), "r"(cnt)); }
__device__ __forceinline__ void mbar_expect_tx(uint32_t bar, uint32_t bytes) { asm volatile("mbarrier.arrive.expect_tx.shared::cta.b64 _, [%0], %1;" ::"r"(bar), "r"(bytes) : "memory"); }
__device__ __forceinline__ void mbar_arrive(uint32_t bar) { asm volatile("mbarrier.arrive.shared::cta.b64 _, [%0];" ::"r"(bar) : "memory"); }
__device__ __forceinline__ void mbar_arrive_cl(uint32_t bar) { asm volatile("mbarrier.arrive.shared::cluster.b64 _, [%0];" ::"r"(bar) : "memory"); }
__device__ __forceinline__ uint32_t mapa(uint32_t a, uint32_t cta) { uint32_t r; asm("mapa.shared::cluster.u32 %0, %1, %2;" : "=r"(r) : "r"(a), "r"(cta)); return r; }
__device__ __forceinline__ void mbar_wait(uint32_t bar, uint32_t parity) {
  asm volatile("{\n.reg .pred p;\n.reg .u32 n;\nmov.u32 n, 0;\nLAB_WAIT:\nmbarrier.try_wait.parity.shared::cta.b64 p, [%0], %1;\n@p bra LAB_DONE;\n"
               "add.u32 n, n, 1;\nsetp.gt.u32 p, n, 4000000;\n@p trap;\nbra LAB_WAIT;\nLAB_DONE:\n}" ::"r"(bar), "r"(parity) : "memory");
}
__device__ __forceinline__ void flag_wait(const unsigned* f, unsigned target) {
  asm volatile("{\n.reg .pred p;\n.reg .u32 n, v;\nmov.u32 n, 0;\nLAB_WAIT:\nld.relaxed.gpu.global.u32 v, [%0];\nsub.u32 v, v, %1;\nsetp.ge.s32 p, v, 0;\n@p bra LAB_DONE;\n"
               "nanosleep.u32 100;\nadd.u32 n, n, 1;\nsetp.gt.u32 p, n, 4000000;\n@p trap;\nbra LAB_WAIT;\nLAB_DONE:\nfence.acquire.gpu;\n}" ::"l"(f), "r"(target) : "memory");
}
__device__ __forceinline__ void flag_add(unsigned* f) { asm volatile("red.release.gpu.global.add.u32 [%0], 1;" ::"l"(f) : "memory"); }
__device__ __forceinline__ void fence_async() { asm volatile("fence.proxy.async.global;" ::: "memory"); }
__device__ __forceinline__ bool elect_one() { uint32_t p; asm volatile("{\n.reg .pred P;\nelect.sync _|P, 0xffffffff;\nselp.u32 %0, 1, 0, P;\n}" : "=r"(p)); return p; }
__device__ __forceinline__ void bar_sync(int id, int n) { asm volatile("bar.sync %0, %1;" ::"r"(id), "r"(n) : "memory"); }
__device__ __forceinline__ void bar_arrive(int id, int n) { asm volatile("bar.arrive %0, %1;" ::"r"(id), "r"(n) : "memory"); }

__device__ __forceinline__ void tma2d(uint32_t dst, const CUtensorMap* tm, uint32_t bar, int c0, int c1, uint64_t hint) {
  asm volatile("cp.async.bulk.tensor.2d.shared::cluster.global.mbarrier::complete_tx::bytes.L2::cache_hint [%0], [%1, {%3, %4}], [%2], %5;" ::"r"(dst), "l"(tm), "r"(bar), "r"(c0), "r"(c1), "l"(hint) : "memory");
}
__device__ __forceinline__ void tma2d_mc(uint32_t dst, const CUtensorMap* tm, uint32_t bar, int c0, int c1, uint64_t hint) {
  asm volatile("cp.async.bulk.tensor.2d.shared::cluster.global.mbarrier::complete_tx::bytes.multicast::cluster.L2::cache_hint [%0], [%1, {%3, %4}], [%2], %5, %6;" ::"r"(dst), "l"(tm), "r"(bar), "r"(c0), "r"(c1), "h"((uint16_t)3), "l"(hint) : "memory");
}
__device__ __forceinline__ void tma3d(uint32_t dst, const CUtensorMap* tm, uint32_t bar, int c0, int c1, int c2, uint64_t hint) {
  asm volatile("cp.async.bulk.tensor.3d.shared::cluster.global.mbarrier::complete_tx::bytes.L2::cache_hint [%0], [%1, {%3, %4, %5}], [%2], %6;" ::"r"(dst), "l"(tm), "r"(bar), "r"(c0), "r"(c1), "r"(c2), "l"(hint) : "memory");
}
__device__ __forceinline__ void tma5d(uint32_t dst, const CUtensorMap* tm, uint32_t bar, int c0, int c4, uint64_t hint) {
  asm volatile("cp.async.bulk.tensor.5d.shared::cluster.global.mbarrier::complete_tx::bytes.L2::cache_hint [%0], [%1, {%3, %5, %5, %5, %4}], [%2], %6;" ::"r"(dst), "l"(tm), "r"(bar), "r"(c0), "r"(c4), "r"(0), "l"(hint) : "memory");
}
__device__ __forceinline__ void tma3d_store(const CUtensorMap* tm, uint32_t src, int c0, int c1, int c2) {
  asm volatile("cp.async.bulk.tensor.3d.global.shared::cta.bulk_group [%0, {%2, %3, %4}], [%1];" ::"l"(tm), "r"(src), "r"(c0), "r"(c1), "r"(c2) : "memory");
}
__device__ __forceinline__ void bulk_load(uint32_t dst, const void* src, uint32_t bytes, uint32_t bar, uint64_t hint) {
  asm volatile("cp.async.bulk.shared::cluster.global.mbarrier::complete_tx::bytes.L2::cache_hint [%0], [%1], %2, [%3], %4;" ::"r"(dst), "l"(src), "r"(bytes), "r"(bar), "l"(hint) : "memory");
}
__device__ __forceinline__ void bulk_load_mc(uint32_t dst, const void* src, uint32_t bytes, uint32_t bar, uint64_t hint) {
  asm volatile("cp.async.bulk.shared::cluster.global.mbarrier::complete_tx::bytes.multicast::cluster.L2::cache_hint [%0], [%1], %2, [%3], %4, %5;" ::"r"(dst), "l"(src), "r"(bytes), "r"(bar), "h"((uint16_t)3), "l"(hint) : "memory");
}
__device__ __forceinline__ uint4 lds128(uint32_t a) { uint4 v; asm volatile("ld.shared.v4.b32 {%0,%1,%2,%3}, [%4];" : "=r"(v.x), "=r"(v.y), "=r"(v.z), "=r"(v.w) : "r"(a) : "memory"); return v; }
__device__ __forceinline__ uint2 lds64(uint32_t a) { uint2 v; asm volatile("ld.shared.v2.b32 {%0,%1}, [%2];" : "=r"(v.x), "=r"(v.y) : "r"(a) : "memory"); return v; }
__device__ __forceinline__ void sts128(uint32_t a, uint4 v) { asm volatile("st.shared.v4.b32 [%0], {%1,%2,%3,%4};" ::"r"(a), "r"(v.x), "r"(v.y), "r"(v.z), "r"(v.w) : "memory"); }
__device__ __forceinline__ void stg128(void* p, uint32_t a, uint32_t b, uint32_t c, uint32_t d) { asm volatile("st.global.v4.b32 [%0], {%1,%2,%3,%4};" ::"l"(p), "r"(a), "r"(b), "r"(c), "r"(d) : "memory"); }

__device__ __forceinline__ uint32_t pack2(float lo, float hi) { uint32_t r; asm("cvt.rn.bf16x2.f32 %0, %1, %2;" : "=r"(r) : "f"(hi), "f"(lo)); return r; }
__device__ __forceinline__ float lo_f(uint32_t v) { return __uint_as_float(v << 16); }
__device__ __forceinline__ float hi_f(uint32_t v) { return __uint_as_float(v & 0xffff0000u); }
__device__ __forceinline__ float bf16r(float v) { return lo_f(pack2(v, 0.f)); }
__device__ __forceinline__ uint32_t mul2(uint32_t a, uint32_t b) { uint32_t r; asm("mul.rn.bf16x2 %0, %1, %2;" : "=r"(r) : "r"(a), "r"(b)); return r; }
__device__ __forceinline__ uint32_t sub2(uint32_t a, uint32_t b) { uint32_t r; asm("sub.rn.bf16x2 %0, %1, %2;" : "=r"(r) : "r"(a), "r"(b)); return r; }
__device__ __forceinline__ uint32_t fma2(uint32_t a, uint32_t b, uint32_t c) { uint32_t r; asm("fma.rn.bf16x2 %0, %1, %2, %3;" : "=r"(r) : "r"(a), "r"(b), "r"(c)); return r; }
__device__ __forceinline__ uint32_t max2(uint32_t a, uint32_t b) { uint32_t r; asm("max.bf16x2 %0, %1, %2;" : "=r"(r) : "r"(a), "r"(b)); return r; }
__device__ __forceinline__ float ex2f(float x) { float y; asm("ex2.approx.ftz.f32 %0, %1;" : "=f"(y) : "f"(x)); return y; }
__device__ __forceinline__ float rcpf(float x) { float y; asm("rcp.approx.ftz.f32 %0, %1;" : "=f"(y) : "f"(x)); return y; }
__device__ __forceinline__ float gelu2(float g) {
  float z = g * fmaf(g * g, 0.035677408136300125f, 0.7978845608028654f), t;
  asm("tanh.approx.f32 %0, %1;" : "=f"(t) : "f"(z));
  return fmaf(g, t, g);
}

__device__ __forceinline__ float silu_half(float z) { float t; asm("tanh.approx.f32 %0, %1;" : "=f"(t) : "f"(z)); return fmaf(z, t, z); }

__device__ __forceinline__ void wg_fence() { asm volatile("wgmma.fence.sync.aligned;" ::: "memory"); }
__device__ __forceinline__ void wg_commit() { asm volatile("wgmma.commit_group.sync.aligned;" ::: "memory"); }
template <int N> __device__ __forceinline__ void wg_wait() { asm volatile("wgmma.wait_group.sync.aligned %0;" ::"n"(N) : "memory"); }
#define A8(o) "+f"(d[(o)]), "+f"(d[(o) + 1]), "+f"(d[(o) + 2]), "+f"(d[(o) + 3]), "+f"(d[(o) + 4]), "+f"(d[(o) + 5]), "+f"(d[(o) + 6]), "+f"(d[(o) + 7])
#define A64(o) A8(o), A8((o) + 8), A8((o) + 16), A8((o) + 24), A8((o) + 32), A8((o) + 40), A8((o) + 48), A8((o) + 56)
#define REGS0_63 "%0,%1,%2,%3,%4,%5,%6,%7,%8,%9,%10,%11,%12,%13,%14,%15,%16,%17,%18,%19,%20,%21,%22,%23,%24,%25,%26,%27,%28,%29,%30,%31," \
                 "%32,%33,%34,%35,%36,%37,%38,%39,%40,%41,%42,%43,%44,%45,%46,%47,%48,%49,%50,%51,%52,%53,%54,%55,%56,%57,%58,%59,%60,%61,%62,%63"
#define REGS64_127 "%64,%65,%66,%67,%68,%69,%70,%71,%72,%73,%74,%75,%76,%77,%78,%79,%80,%81,%82,%83,%84,%85,%86,%87,%88,%89,%90,%91,%92,%93,%94,%95," \
                   "%96,%97,%98,%99,%100,%101,%102,%103,%104,%105,%106,%107,%108,%109,%110,%111,%112,%113,%114,%115,%116,%117,%118,%119,%120,%121,%122,%123,%124,%125,%126,%127"
template <int ACCUM> __device__ __forceinline__ void wgmma256(float (&d)[128], uint32_t a_lo, uint32_t a_hi, uint32_t b_lo) {
  asm volatile("{\n.reg .pred p;\n.reg .b64 da, db;\nsetp.ne.b32 p, %131, 0;\nmov.b64 da, {%128, %129};\nmov.b64 db, {%130, 0x40000040};\n"
               "wgmma.mma_async.sync.aligned.m64n256k16.f32.bf16.bf16 {" REGS0_63 "," REGS64_127 "}, da, db, p, 1, 1, 0, 1;\n}"
               : A64(0), A64(64) : "r"(a_lo), "r"(a_hi), "r"(b_lo), "n"(ACCUM));
}
template <int ACCUM> __device__ __forceinline__ void wgmma128(float (&d)[64], uint32_t a_lo, uint32_t b_lo) {
  asm volatile("{\n.reg .pred p;\n.reg .b64 da, db;\nsetp.ne.b32 p, %66, 0;\nmov.b64 da, {%64, 0x80000020};\nmov.b64 db, {%65, 0x40000040};\n"
               "wgmma.mma_async.sync.aligned.m64n128k16.f32.bf16.bf16 {" REGS0_63 "}, da, db, p, 1, 1, 0, 1;\n}"
               : A64(0) : "r"(a_lo), "r"(b_lo), "n"(ACCUM));
}
template <int ACCUM> __device__ __forceinline__ void hmma(float (&c)[4], uint32_t a0, uint32_t a1, uint32_t a2, uint32_t a3, uint32_t b0, uint32_t b1) {
  if (ACCUM)
    asm volatile("mma.sync.aligned.m16n8k16.row.col.f32.bf16.bf16.f32 {%0,%1,%2,%3}, {%4,%5,%6,%7}, {%8,%9}, {%0,%1,%2,%3};"
                 : "+f"(c[0]), "+f"(c[1]), "+f"(c[2]), "+f"(c[3]) : "r"(a0), "r"(a1), "r"(a2), "r"(a3), "r"(b0), "r"(b1));
  else
    asm volatile("mma.sync.aligned.m16n8k16.row.col.f32.bf16.bf16.f32 {%0,%1,%2,%3}, {%4,%5,%6,%7}, {%8,%9}, {%10,%10,%10,%10};"
                 : "=f"(c[0]), "=f"(c[1]), "=f"(c[2]), "=f"(c[3]) : "r"(a0), "r"(a1), "r"(a2), "r"(a3), "r"(b0), "r"(b1), "f"(0.f));
}
__device__ __forceinline__ uint32_t movm(uint32_t a) { uint32_t d; asm volatile("movmatrix.sync.aligned.m8n8.trans.b16 %0, %1;" : "=r"(d) : "r"(a)); return d; }
__device__ __forceinline__ void sched_fence(uint32_t zero) {
  asm volatile("{\n.reg .pred p;\n.reg .u32 n;\nmov.u32 n, %0;\nLAB_F:\nsetp.eq.u32 p, n, 0;\n@p bra.uni LAB_D;\nnanosleep.u32 n;\nsub.u32 n, n, 1;\nbra.uni LAB_F;\nLAB_D:\n}" ::"r"(zero) : "memory");
}
__device__ __forceinline__ uint4 ldsm(uint32_t a) { uint4 v; asm volatile("ldmatrix.sync.aligned.m8n8.x4.shared.b16 {%0,%1,%2,%3}, [%4];" : "=r"(v.x), "=r"(v.y), "=r"(v.z), "=r"(v.w) : "r"(a) : "memory"); return v; }
__device__ __forceinline__ uint4 ldsm_t(uint32_t a) { uint4 v; asm volatile("ldmatrix.sync.aligned.m8n8.x4.trans.shared.b16 {%0,%1,%2,%3}, [%4];" : "=r"(v.x), "=r"(v.y), "=r"(v.z), "=r"(v.w) : "r"(a) : "memory"); return v; }

constexpr int BAR_LAG = 1, BAR_MMA = 2, BAR_EV = 3;

struct Cons {
  uint32_t sb;
  uint32_t a0, a1, ah;
  uint32_t rel;
  bool do_rel;
  int wg;
  uint32_t zero;
};
#define STEP_TS() do {} while (0)
constexpr uint32_t DB_LO = ((SM_BASE + 16384) >> 4) | ((8192 >> 4) << 16);

template <int ST, int ACCUM, bool WAIT = true> __device__ __forceinline__ void p1_issue(float (&acc)[128], const Cons& c, uint32_t parity) {
  if (WAIT) mbar_wait(c.sb + B_F1 + 8 * ST, parity);
  STEP_TS();
  wg_fence();
  constexpr uint32_t so = ST * (P1_STAGE >> 4);
  wgmma256<ACCUM>(acc, c.a0 + so, c.ah, DB_LO + so);
  wgmma256<1>(acc, c.a0 + so + 2, c.ah, DB_LO + so + 128);
  wgmma256<1>(acc, c.a1 + so, c.ah, DB_LO + so + 256);
  wgmma256<1>(acc, c.a1 + so + 2, c.ah, DB_LO + so + 384);
  wg_commit();
}
__device__ __forceinline__ void release(const Cons& c, uint32_t bar) { if (c.do_rel) mbar_arrive_cl(c.rel + bar); }
template <int KB, bool WAIT = true> __device__ __forceinline__ void p1_step(float (&acc)[128], const Cons& c) {
  if (KB == 14) { if (c.wg == 1) bar_sync(BAR_LAG, 256); }
  p1_issue<KB & 3, KB != 0, WAIT>(acc, c, (KB >> 2) & 1);
  if (KB == 15) { if (c.wg == 0) bar_arrive(BAR_LAG, 256); }
  if (KB > 0) { wg_wait<1>(); release(c, B_E1 + 8 * ((KB - 1) & 3)); }
  if (KB == 15) { wg_wait<0>(); release(c, B_E1 + 8 * 3); }
}
template <int A, int B> __device__ __forceinline__ void p1_range(float (&acc)[128], const Cons& c) {
  if constexpr (A < B) { p1_step<A>(acc, c); p1_range<A + 1, B>(acc, c); }
}
template <int T> __device__ __forceinline__ void p2_step(float (&acc)[64], const Cons& c) {
  if (T == 12) { if (c.wg == 1) bar_sync(BAR_LAG, 256); }
  mbar_wait(c.sb + B_F2 + 8 * (T % 5), (T / 5) & 1);
  STEP_TS();
  wg_fence();
  constexpr uint32_t so = (T % 5) * (P2_STAGE >> 4);
  wgmma128<T != 0>(acc, c.a0 + so, DB_LO + so);
  wgmma128<1>(acc, c.a0 + so + 2, DB_LO + so + 128);
  wgmma128<1>(acc, c.a1 + so, DB_LO + so + 256);
  wgmma128<1>(acc, c.a1 + so + 2, DB_LO + so + 384);
  wg_commit();
  if (T == 15) { if (c.wg == 0) bar_arrive(BAR_LAG, 256); }
  if (T <= 11) { wg_wait<1>(); release(c, T ? B_E2 + 8 * ((T + 4) % 5) : B_E1 + 8 * 3); }
}

template <int P> __device__ __forceinline__ void geglu_piece(const uint32_t (&pk)[64], uint8_t* dst) {
  constexpr int cg = P >> 1, r = P & 1;
  uint32_t v[4];
#pragma unroll
  for (int i = 0; i < 4; i++) {
    const uint32_t g = pk[2 * (4 * cg + i) + r];
    v[i] = mul2(pack2(gelu2(lo_f(g)), gelu2(hi_f(g))), pk[32 + 2 * (4 * cg + i) + r]);
  }
  stg128(dst + cg * 8192 + r * 512, v[0], v[1], v[2], v[3]);
}
template <int KB> __device__ __forceinline__ void geglu_tile(float (&acc)[128], const uint32_t (&pk)[64], const Cons& c, uint8_t* dst, int ev) {
  if constexpr (KB < 14) {
    p1_step<KB>(acc, c);
    if (KB >= 1 && KB <= 8) geglu_piece<(KB - 1) & 7>(pk, dst);
    if (KB == 8) bar_arrive(ev, 288);
    geglu_tile<KB + 1>(acc, pk, c, dst, ev);
  }
}

__device__ __forceinline__ void attn_tile(float (&acc)[128], const uint32_t (&pk)[64], const Cons& c, int round, int warp, int m, uint8_t* hdst, uint8_t* odst) {
  const int lane = threadIdx.x & 31, w = warp & 3, rho = lane >> 2, q = lane & 3;
  const uint32_t at = c.sb + OFF_X + c.wg * AT_WG, swz = (lane ^ (lane >> 3)) << 4;
  uint32_t gg[16];
  p1_step<0>(acc, c);
  p1_step<1>(acc, c);
#pragma unroll
  for (int i = 0; i < 4; i++) {
    const int h = i & 1, r = i >> 1;
    sts128(at + AT_V + (2 * w + r) * 1024 + h * 512 + swz, make_uint4(pk[32 + 8 * h + r], pk[34 + 8 * h + r], pk[36 + 8 * h + r], pk[38 + 8 * h + r]));
  }
  if (w < 3) {
#pragma unroll
    for (int i = 0; i < 8; i++) asm volatile("st.shared.b32 [%0], %1;" ::"r"(at + AT_K + w * 1024 + i * 128 + lane * 4), "r"(pk[17 + 2 * i]) : "memory");
  } else {
    uint8_t* g = (uint8_t*)g_halo + ((round * 128 + blockIdx.x) * 2 + c.wg) * 2048;
#pragma unroll
    for (int i = 0; i < 8; i++) asm volatile("st.global.b32 [%0], %1;" ::"l"(g + i * 128 + lane * 4), "r"(pk[17 + 2 * i]) : "memory");
#pragma unroll
    for (int h = 0; h < 2; h++) stg128(g + 1024 + h * 512 + swz, pk[33 + 8 * h], pk[35 + 8 * h], pk[37 + 8 * h], pk[39 + 8 * h]);
    bar_arrive(BAR_EV + 2 + round, 96);
  }
  __syncwarp();
  if (lane == 0) mbar_arrive(c.sb + B_HALO + 8 * round);
  if (round) {
#pragma unroll
    for (int p = 0; p < 4; p++) asm volatile("ld.global.cg.v4.b32 {%0,%1,%2,%3}, [%4];" : "=r"(gg[4 * p]), "=r"(gg[4 * p + 1]), "=r"(gg[4 * p + 2]), "=r"(gg[4 * p + 3]) : "l"(hdst + (p >> 1) * 8192 + (p & 1) * 512) : "memory");
  }
  auto gu_piece = [&](int p) {
    uint32_t v[4];
#pragma unroll
    for (int i = 0; i < 4; i++) {
      const uint32_t g = pk[48 + 8 * (p >> 1) + 2 * i + (p & 1)];
      v[i] = round ? mul2(gg[4 * p + i], g) : pack2(gelu2(lo_f(g)), gelu2(hi_f(g)));
    }
    stg128(hdst + (p >> 1) * 8192 + (p & 1) * 512, v[0], v[1], v[2], v[3]);
  };
  p1_step<2>(acc, c);
  p1_step<3>(acc, c); gu_piece(0);
  p1_step<4>(acc, c); gu_piece(1);
  p1_step<5>(acc, c); gu_piece(2);
  p1_step<6>(acc, c); gu_piece(3);
  p1_step<7>(acc, c);
  p1_step<8>(acc, c);
  const bool first = m == 0 && w == 0;
  uint32_t kl[16];
  mbar_wait(c.sb + B_HALO + 8 * round, 0);
  {
    const uint32_t ka = at + lane * 4 + (w ? AT_K + (w - 1) * 1024 : (first ? AT_K : AT_REM + round * 2048));
#pragma unroll
    for (int i = 0; i < 8; i++) {
      asm volatile("ld.shared.b32 %0, [%1];" : "=r"(kl[2 * i]) : "r"(ka + i * 128) : "memory");
      kl[2 * i + 1] = pk[16 + 2 * i] | c.zero;
    }
  }
  float st[4][4];
  mbar_wait(c.sb + B_F1 + 8 * 1, 0);
  bar_sync(BAR_MMA, 256);
#pragma unroll
  for (int ks = 0; ks < 2; ks++) {
#pragma unroll
    for (int h = 0; h < 2; h++) {
      const int o = 8 * h + 4 * ks;
      if (ks == 0) { hmma<0>(st[2 * h], kl[o], kl[o + 1], kl[o + 2], kl[o + 3], pk[o], pk[o + 2]); hmma<0>(st[2 * h + 1], pk[16 + o], pk[17 + o], pk[18 + o], pk[19 + o], pk[o + 1], pk[o + 3]); }
      else { hmma<1>(st[2 * h], kl[o], kl[o + 1], kl[o + 2], kl[o + 3], pk[o], pk[o + 2]); hmma<1>(st[2 * h + 1], pk[16 + o], pk[17 + o], pk[18 + o], pk[19 + o], pk[o + 1], pk[o + 3]); }
    }
  }
  sched_fence(c.zero);
  p1_step<9, false>(acc, c);
  sched_fence(c.zero);
  const bool le0 = 2 * q <= rho, le1 = 2 * q + 1 <= rho;
  uint32_t la[2], lb[2], mx[2];
#pragma unroll
  for (int h = 0; h < 2; h++) {
    uint32_t l[2];
#pragma unroll
    for (int r = 0; r < 2; r++) {
      const float (&t)[4] = st[2 * h + r];
      l[r] = movm(pack2(rho <= 2 * q ? t[2] : t[0], rho <= 2 * q + 1 ? t[3] : t[1]));
      l[r] = fma2(l[r], 0x3e353e35u, mul2(l[r], 0x379e379eu));
    }
    la[h] = __byte_perm(l[0], l[1], 0x5410); lb[h] = __byte_perm(l[0], l[1], 0x7632);
    if (first && !le0) la[h] = (la[h] & 0xffff0000u) | 0xce6eu;
    if (first && !le1) lb[h] = (lb[h] & 0xffff0000u) | 0xce6eu;
    mx[h] = max2(la[h], lb[h]);
  }
#pragma unroll
  for (int o = 1; o <= 2; o++) { mx[0] = max2(mx[0], __shfl_xor_sync(~0u, mx[0], o)); mx[1] = max2(mx[1], __shfl_xor_sync(~0u, mx[1], o)); }
  const float L2E = 1.4426950408889634f;
  float pr[2][4], z[4];
#pragma unroll
  for (int h = 0; h < 2; h++) {
    pr[h][0] = ex2f((lo_f(la[h]) - lo_f(mx[h])) * L2E); pr[h][1] = ex2f((lo_f(lb[h]) - lo_f(mx[h])) * L2E);
    pr[h][2] = ex2f((hi_f(la[h]) - hi_f(mx[h])) * L2E); pr[h][3] = ex2f((hi_f(lb[h]) - hi_f(mx[h])) * L2E);
    z[2 * h] = pr[h][0] + pr[h][1]; z[2 * h + 1] = pr[h][2] + pr[h][3];
  }
  p1_step<10>(acc, c);
#pragma unroll
  for (int o = 1; o <= 2; o++) {
#pragma unroll
    for (int i = 0; i < 4; i++) z[i] += __shfl_xor_sync(~0u, z[i], o);
  }
  const uint32_t LE = (le0 ? 0xffffu : 0u) | (le1 ? 0xffff0000u : 0u);
  uint32_t P[4][2];
  uint4 vt[4][2];
  {
    const uint32_t row = (lane & 7) * 64 + ((((lane >> 3) & 1) ^ ((lane & 7) >> 1)) << 4);
    const uint32_t v1 = at + AT_V + (2 * w + (lane >> 4)) * 1024 + row;
    const uint32_t v0 = (w || lane >= 16) ? v1 - 1024 : (first ? v1 : at + AT_REM + round * 2048 + 1024 + row);
#pragma unroll
    for (int i = 0; i < 4; i++) {
      const float rz = rcpf(z[i]);
      const uint32_t p = pack2(pr[i >> 1][2 * (i & 1)] * rz, pr[i >> 1][2 * (i & 1) + 1] * rz);
      P[i][0] = p & ~LE; P[i][1] = p & LE;
      const uint32_t a = ((i & 1) ? v1 : v0) + (i >> 1) * 512;
      vt[i][0] = ldsm_t(a); vt[i][1] = ldsm_t(a ^ 32);
    }
  }
  float ot[4][2][4];
  mbar_wait(c.sb + B_F1 + 8 * 3, 0);
  bar_sync(BAR_MMA, 256);
#pragma unroll
  for (int i = 0; i < 8; i++) { const uint4& v = vt[i >> 1][i & 1]; hmma<0>(ot[i >> 1][i & 1], v.x, v.y, v.z, v.w, P[i >> 1][0], P[i >> 1][1]); }
  sched_fence(c.zero);
  p1_step<11, false>(acc, c);
  sched_fence(c.zero);
  auto o_piece = [&](int i) {
    stg128(odst + (i >> 1) * 8192 + (i & 1) * 512, movm(pack2(ot[i][0][0], ot[i][0][1])), movm(pack2(ot[i][0][2], ot[i][0][3])), movm(pack2(ot[i][1][0], ot[i][1][1])), movm(pack2(ot[i][1][2], ot[i][1][3])));
  };
  o_piece(0); o_piece(1);
  p1_step<12>(acc, c);
  o_piece(2); o_piece(3);
  if (round) bar_arrive(BAR_EV + 4, 288);
  p1_step<13>(acc, c);
}

__device__ __forceinline__ void ln_stats(const uint32_t* raw, float& mb, float& rinv) {
  float f[32], s = 0.f, s2 = 0.f;
#pragma unroll
  for (int i = 0; i < 16; i++) { f[2 * i] = lo_f(raw[i]); f[2 * i + 1] = hi_f(raw[i]); s += f[2 * i]; s2 += f[2 * i + 1]; }
  s += s2;
#pragma unroll
  for (int o = 16; o; o >>= 1) s += __shfl_xor_sync(~0u, s, o);
  const float mean = s * (1.0f / DM);
  float v = 0.f, v2 = 0.f;
#pragma unroll
  for (int i = 0; i < 16; i++) { const float a = f[2 * i] - mean, b = f[2 * i + 1] - mean; v = fmaf(a, a, v); v2 = fmaf(b, b, v2); }
  v += v2;
#pragma unroll
  for (int o = 16; o; o >>= 1) v += __shfl_xor_sync(~0u, v, o);
  mb = bf16r(mean);
  float sd;
  asm("sqrt.approx.ftz.f32 %0, %1;" : "=f"(sd) : "f"(bf16r(bf16r(v * (1.0f / DM)) + 1e-5f)));
  rinv = rcpf(bf16r(sd));
}
__device__ __forceinline__ void ln_store(const uint32_t* raw, float mb, float rinv, uint4* dst) {
  const uint32_t m2 = pack2(mb, mb);
#pragma unroll
  for (int c = 0; c < 4; c++) {
    uint32_t v[4];
#pragma unroll
    for (int i = 0; i < 4; i++) { const uint32_t t = sub2(raw[4 * c + i], m2); v[i] = pack2(lo_f(t) * rinv, hi_f(t) * rinv); }
    stg128(dst + 32 * c, v[0], v[1], v[2], v[3]);
  }
}

__global__ void __cluster_dims__(2, 1, 1) __launch_bounds__(384, 1)
fused_kernel(const __grid_constant__ Maps mp, const uint4* __restrict__ x) {
  extern __shared__ __align__(1024) uint8_t smem_raw[];
  const uint32_t sb = (uint32_t)__cvta_generic_to_shared(smem_raw);
  const unsigned t_start = 0;
  const int warp = __shfl_sync(~0u, threadIdx.x >> 5, 0), lane = threadIdx.x & 31;
  const int m = blockIdx.x & 15, j = blockIdx.x >> 4, rank = blockIdx.x & 1;
  const int m2 = blockIdx.x >> 3, j2 = blockIdx.x & 7;
  if (warp == 0) {
    if (elect_one()) {
      for (int s = 0; s < 4; s++) mbar_init(sb + B_F1 + 8 * s, 1);
      asm volatile("fence.mbarrier_init.release.cluster;" ::: "memory");
      TS(0); TG(51);
#pragma unroll 1
      for (int kb = 0; kb < 4; kb++) {
        const uint32_t sa = sb + kb * P1_STAGE, fb = sb + B_F1 + 8 * kb;
        mbar_expect_tx(fb, P1_STAGE);
        tma3d(sa, &mp.x, fb, kb * 64, m * 64, 0, EVICT_NORMAL);
        tma2d(sa + 16384, &mp.wg, fb, j * 128, kb * 64, EVICT_NORMAL); tma2d(sa + 32768, &mp.wu, fb, j * 128, kb * 64, EVICT_NORMAL);
        tma2d(sa + 24576, &mp.wg, fb, j * 128 + 64, kb * 64, EVICT_NORMAL); tma2d(sa + 40960, &mp.wu, fb, j * 128 + 64, kb * 64, EVICT_NORMAL);
      }
      TS(7);
    }
    __syncwarp();
  }

  if (warp >= 8) {
    asm volatile("setmaxnreg.dec.sync.aligned.u32 40;");
    if (warp == 9) {
      if (elect_one()) {
        if ((sb & 0xffffff) != SM_BASE) asm volatile("trap;");
        for (int s = 0; s < 4; s++) mbar_init(sb + B_E1 + 8 * s, 4);
        for (int s = 0; s < 5; s++) { mbar_init(sb + B_F2 + 8 * s, 1); mbar_init(sb + B_E2 + 8 * s, 4); }
        for (int s = 0; s < 5; s++) mbar_init(sb + B_DEP + 8 * s, 1);
        mbar_init(sb + B_AUX, 9); mbar_init(sb + B_XT, 1); mbar_init(sb + B_CS, 1);
        for (int s = 0; s < 2; s++) { mbar_init(sb + B_EX + 8 * s, 1); mbar_expect_tx(sb + B_EX + 8 * s, 16384); mbar_init(sb + B_HALO + 8 * s, 9); }
        asm volatile("fence.mbarrier_init.release.cluster;" ::: "memory");
      }
      __syncwarp();
    }
    asm volatile("barrier.cluster.arrive.relaxed.aligned;\nbarrier.cluster.wait.aligned;" ::: "memory");
    if (warp == 8) {
      if (elect_one()) {
        uint32_t par = 0;
        for (int i = 1; i < 8; i++) asm volatile("prefetch.tensormap [%0];" ::"l"(&mp.x + i) : "memory");
        for (int R = 0; R < 5; R++) {
          const CUtensorMap *mb0, *mb1;
          int n0, n1;
          if (R == 1 || R == 2) {
            mb0 = &mp.wqkv; n0 = 64 * (j + 8 * (R - 1)) + rank * 2048;
            mb1 = rank ? (R == 1 ? &mp.wg : &mp.wu) : &mp.wqkv; n1 = rank ? 1024 + 64 * j : n0 + 1024;
          } else {
            mb0 = mb1 = rank ? &mp.wu : &mp.wg;
            n0 = 128 * j + (R ? 1024 * R - 1536 : 0); n1 = n0 + 64;
          }
          if (R == 1) { mbar_wait(sb + B_DEP, 0); TS(1); }
#pragma unroll 1
          for (int kb = R ? 0 : 4; kb < 16; kb++) {
            if (R == 0 && kb == CS_KB) {
              const uint32_t cb = sb + B_CS, d = sb + OFF_X;
              mbar_expect_tx(cb, 32768);
              tma2d(d, &mp.wg, cb, n0, m * 64, EVICT_NORMAL); tma2d(d + 8192, &mp.wg, cb, n1, m * 64, EVICT_NORMAL);
              tma2d(d + 16384, &mp.wu, cb, n0, m * 64, EVICT_NORMAL); tma2d(d + 24576, &mp.wu, cb, n1, m * 64, EVICT_NORMAL);
            }
            const int st = kb & 3;
            const uint32_t sa = sb + st * P1_STAGE, fb = sb + B_F1 + 8 * st;
            mbar_wait(sb + B_E1 + 8 * st, par);
            mbar_expect_tx(fb, P1_STAGE);
            if (R == 0) tma3d(sa, &mp.x, fb, kb * 64, m * 64, 0, EVICT_NORMAL); else tma2d(sa, &mp.xn, fb, kb * 64, m * 128, R == 4 ? HINT_LAST : EVICT_NORMAL);
            tma2d_mc(sa + 16384 + rank * 16384, mb0, fb, n0, kb * 64, HINT_W);
            tma2d_mc(sa + 24576 + rank * 16384, mb1, fb, n1, kb * 64, HINT_W);
            if (R == 4 && kb == 4 + j2) {
              mbar_expect_tx(sb + B_XT, 32768);
              tma3d(sb + OFF_X, &mp.x, sb + B_XT, j2 * 128, m2 * 64, 0, HINT_LAST); tma3d(sb + OFF_X + 16384, &mp.x, sb + B_XT, j2 * 128 + 64, m2 * 64, 0, HINT_LAST);
            }
            if (st == 3) par ^= 1;
          }
        }
#pragma unroll 1
        for (int i = 0; i < 28; i++) {
          if (i == 0 || i == 8 || i == 12 || i == 20) { mbar_wait(sb + B_DEP + 8 * (1 + ((i + 4) >> 3)), 0); TS(2 + ((i + 4) >> 3)); }
          const int st = i & 3, kb = 2 * i + rank;
          const uint32_t sa = sb + st * P1_STAGE, fb = sb + B_F1 + 8 * st;
          mbar_wait(sb + B_E1 + 8 * st, par);
          mbar_expect_tx(fb, P1_STAGE);
          bulk_load(sa, g_h + (m2 * 56 + kb) * 1024, 16384, fb, HINT_H);
          tma5d(sa + 16384, &mp.wd, fb, j2 * 128, kb * 2, HINT_W); tma5d(sa + 24576, &mp.wd, fb, j2 * 128 + 64, kb * 2, HINT_W);
          tma5d(sa + 32768, &mp.wd, fb, (j2 ^ 1) * 128, kb * 2, HINT_W); tma5d(sa + 40960, &mp.wd, fb, (j2 ^ 1) * 128 + 64, kb * 2, HINT_W);
          if (st == 3) par ^= 1;
        }
        int st = 0; uint32_t par2 = 1;
#pragma unroll 1
        for (int t = 0; t < 16; t++) {
          const uint32_t sa = sb + st * P2_STAGE, fb = sb + B_F2 + 8 * st;
          if (t < 5) mbar_wait(sb + B_E1 + 8 * ((2 * t + 1) / 3), par); else mbar_wait(sb + B_E2 + 8 * st, par2);
          mbar_expect_tx(fb, P2_STAGE);
          bulk_load_mc(sa + rank * 8192, g_o + (m2 * 16 + t) * 1024 + rank * 512, 8192, fb, HINT_H);
          tma2d(sa + 16384, &mp.wo, fb, j2 * 128, t * 64, HINT_W); tma2d(sa + 24576, &mp.wo, fb, j2 * 128 + 64, t * 64, HINT_W);
          if (++st == 5) { st = 0; par2 ^= 1; }
        }
      }
    } else if (warp == 9) {
#pragma unroll 1
      for (int e = 0; e < 7; e++) {
        const bool halo = e == 2 || e == 3;
        bar_sync(BAR_EV + e, halo ? 96 : 288);
        if (lane == 0) {
          const int f = e == 0 ? FL_XN + m : (halo ? FL_HALO + (e - 2) * 128 + blockIdx.x : FL_H + m * 4 + (e == 1 ? 0 : e - 3));
          TS(10 + 2 * e); TG(52 + e);
          flag_add(&g_flags[f * 32]);
          if (e < 6) TS(11 + 2 * e);
        }
        __syncwarp();
      }
    } else if (warp == 10) {
      unsigned e = 0;
      if (lane == 0) {
        unsigned* ep = &g_epoch[blockIdx.x * 2];
        e = *ep + 1; *ep = e;
        flag_wait(&g_flags[(FL_XN + m) * 32], e * 8u);
        fence_async();
        asm volatile("st.shared.b32 [%0], %1;" ::"r"(sb + OFF_EPOCH), "r"(e) : "memory");
        mbar_arrive(sb + B_DEP);
        TS(8);
      }
      __syncwarp();
      const uint4* sp = (const uint4*)(g_stats + m * 128);
      const uint4 s0 = __ldcg(sp + lane), s1 = __ldcg(sp + 32 + lane);
      sts128(sb + OFF_STATS + lane * 16, s0); sts128(sb + OFF_STATS + 512 + lane * 16, s1);
      __syncwarp();
      if (lane == 0) {
        mbar_arrive(sb + B_AUX);
#pragma unroll 1
        for (int g = 0; g < 4; g++) {
          flag_wait(&g_flags[(FL_H + m2 * 4 + g) * 32], e * 8u);
          fence_async();
          mbar_arrive(sb + B_DEP + 8 * (1 + g));
        }
      }
    } else {
      unsigned e = 0;
      if (lane == 0) { unsigned* ep = &g_epoch[blockIdx.x * 2 + 1]; e = *ep + 1; *ep = e; }
      float cs[8] = {0, 0, 0, 0, 0, 0, 0, 0};
      mbar_wait(sb + B_CS, 0);
      const uint32_t base = sb + OFF_X + (lane >> 3) * 8192;
#pragma unroll 1
      for (int k0 = 0; k0 < 64; k0 += 8) {
#pragma unroll
        for (int k = 0; k < 8; k++) {
          const uint4 v = lds128(base + (k0 + k) * 128 + (((lane & 7) ^ k) << 4));
          cs[0] += lo_f(v.x); cs[1] += hi_f(v.x); cs[2] += lo_f(v.y); cs[3] += hi_f(v.y);
          cs[4] += lo_f(v.z); cs[5] += hi_f(v.z); cs[6] += lo_f(v.w); cs[7] += hi_f(v.w);
        }
      }
      e = __shfl_sync(~0u, e, 0);
      ulonglong2* part = g_cspart + (j * 16 + m) * 128 + lane;
#pragma unroll
      for (int i = 0; i < 4; i++)
        asm volatile("{\n.reg .b64 a, b;\nmov.b64 a, {%1, %3};\nmov.b64 b, {%2, %3};\nst.relaxed.gpu.global.v2.b64 [%0], {a, b};\n}" ::"l"(part + 32 * i), "r"(__float_as_uint(cs[2 * i])), "r"(__float_as_uint(cs[2 * i + 1])), "r"(e) : "memory");
      asm volatile("fence.proxy.async.shared::cta;" ::: "memory");
      if (lane == 0) TS(9);
      if (elect_one()) {
#pragma unroll 1
        for (int r = 0; r < 2; r++) {
          const uint32_t hb = sb + B_HALO + 8 * r;
          if (m) {
            flag_wait(&g_flags[(FL_HALO + r * 128 + blockIdx.x - 1) * 32], e);
            fence_async();
            mbar_expect_tx(hb, 4096);
            for (int g = 0; g < 2; g++) bulk_load(sb + OFF_X + g * AT_WG + AT_REM + r * 2048, g_halo + ((r * 128 + blockIdx.x - 1) * 2 + g) * 128, 2048, hb, EVICT_FIRST);
          } else {
            mbar_arrive(hb);
          }
          TS(34 + r);
        }
      }
    }
  } else {
    asm volatile("barrier.cluster.arrive.relaxed.aligned;" ::: "memory");
    asm volatile("setmaxnreg.inc.sync.aligned.u32 232;");
    const int wg = warp >> 2, w = warp & 3;
    Cons c;
    c.sb = sb; c.wg = wg; c.zero = warp >> 8;
    c.a0 = ((SM_BASE + wg * 8192) >> 4) | (1u << 16); c.a1 = c.a0 + 4; c.ah = 0x40000040;
    c.rel = mapa(sb, threadIdx.x & 1);
    c.do_rel = (threadIdx.x & 127) < 2;
    const bool t0 = (threadIdx.x & 127) == 0;
    (void)t0;
    float acc[128];
    uint32_t pk[64];
    const int rho = lane >> 2, q = lane & 3;

    {
      const int prow = 16 * j + 2 * warp;
      const uint4* xr = x + (size_t)(128 * m + 2 * (prow & 63) + (prow >> 6)) * 128 + lane;
      uint4* xo = g_xn + (size_t)(128 * m + prow) * 128 + lane;
      float mb, rinv;
      if (t0) TS(23 + wg * 16);
      if (LN_EARLY < 2) asm volatile("barrier.cluster.wait.aligned;" ::: "memory");
      if (!LN_EARLY) p1_step<0>(acc, c);
#pragma unroll
      for (int i = 0; i < 8; i++) {
        asm volatile("ld.global.nc.v4.b32 {%0,%1,%2,%3}, [%4];" : "=r"(pk[4 * i]), "=r"(pk[4 * i + 1]), "=r"(pk[4 * i + 2]), "=r"(pk[4 * i + 3]) : "l"(xr + (i >> 2) * 256 + (i & 3) * 32));
      }
      if (LN_EARLY == 2) asm volatile("barrier.cluster.wait.aligned;" ::: "memory");
      if (LN_EARLY) p1_step<0>(acc, c);
      if (t0) TS(24 + wg * 16);
      p1_range<1, LN_KB + 1>(acc, c);
      ln_stats(pk, mb, rinv);
      if (lane == 0) g_stats[128 * m + prow] = make_float2(mb, rinv);
      p1_step<LN_KB + 1>(acc, c);
      ln_store(pk, mb, rinv, xo);
      p1_step<LN_KB + 2>(acc, c);
      ln_stats(pk + 16, mb, rinv);
      if (lane == 0) g_stats[128 * m + prow + 1] = make_float2(mb, rinv);
      p1_step<LN_KB + 3>(acc, c);
      ln_store(pk + 16, mb, rinv, xo + 128);
      bar_arrive(BAR_EV, 288);
      p1_range<LN_KB + 4, 13>(acc, c);
      const unsigned long long* cp = (const unsigned long long*)g_cspart + j * 4096 + threadIdx.x;
      unsigned long long part[16];
#pragma unroll
      for (int i = 0; i < 16; i++) asm volatile("ld.relaxed.gpu.global.b64 %0, [%1];" : "=l"(part[i]) : "l"(cp + i * 256) : "memory");
      p1_step<13>(acc, c);
      {
        mbar_wait(sb + B_DEP, 0);
        uint32_t e;
        asm volatile("ld.shared.b32 %0, [%1];" : "=r"(e) : "r"(sb + OFF_EPOCH) : "memory");
        float csum = 0.f;
        uint32_t bad = 0;
#pragma unroll
        for (int i = 0; i < 16; i++) { bad |= (uint32_t)(part[i] >> 32) ^ e; csum += __uint_as_float((uint32_t)part[i]); }
        if (bad) {
          csum = 0.f;
#pragma unroll 1
          for (int i = 0; i < 16; i++) {
            uint32_t val;
            asm volatile("{\n.reg .pred p;\n.reg .b64 v;\n.reg .b32 b, n;\nmov.u32 n, 0;\nLAB_CHK:\nld.relaxed.gpu.global.b64 v, [%1];\nmov.b64 {%0, b}, v;\nsetp.eq.u32 p, b, %2;\n@p bra LAB_OK;\n"
                         "add.u32 n, n, 1;\nsetp.gt.u32 p, n, 4000000;\n@p trap;\nbra LAB_CHK;\nLAB_OK:\n}" : "=r"(val) : "l"(cp + i * 256), "r"(e) : "memory");
            csum += __uint_as_float(val);
          }
        }
        asm volatile("st.shared.b32 [%0], %1;" ::"r"(sb + OFF_CS + threadIdx.x * 4 + (threadIdx.x >> 6) * 16), "f"(csum) : "memory");
        __syncwarp();
        if (lane == 0) mbar_arrive(sb + B_AUX);
      }
      p1_step<14>(acc, c);
      mbar_wait(sb + B_AUX, 0);
#pragma unroll
      for (int i = 0; i < 16; i++) { const uint4 v = lds128(sb + OFF_CS + q * 272 + i * 16); pk[4 * i] = v.x; pk[4 * i + 1] = v.y; pk[4 * i + 2] = v.z; pk[4 * i + 3] = v.w; }
      const uint2 sa = lds64(sb + OFF_STATS + (warp * 16 + rho) * 8), sc = lds64(sb + OFF_STATS + (warp * 16 + 8 + rho) * 8);
      p1_step<15>(acc, c);
      const float m0 = -__uint_as_float(sa.x), r0 = __uint_as_float(sa.y), m1 = -__uint_as_float(sc.x), r1 = __uint_as_float(sc.y);
#pragma unroll
      for (int n = 0; n < 32; n++) {
        const float c0 = __uint_as_float(pk[2 * n]), c1 = __uint_as_float(pk[2 * n + 1]);
        pk[2 * n] = pack2(fmaf(m0, c0, acc[4 * n]) * r0, fmaf(m0, c1, acc[4 * n + 1]) * r0);
        pk[2 * n + 1] = pack2(fmaf(m1, c0, acc[4 * n + 2]) * r1, fmaf(m1, c1, acc[4 * n + 3]) * r1);
      }
      if (t0) TS(25 + wg * 16);
    }
    const uint32_t img = warp * 1024 + ((lane ^ (lane >> 3)) << 4);
#pragma unroll 1
    for (int R = 1;; R++) {
      uint8_t* hb = (uint8_t*)g_h + (size_t)m * 56 * 16384 + img;
      if (R == 2 || R == 3) {
        attn_tile(acc, pk, c, R - 2, warp, m, hb + (16 + j) * 16384, (uint8_t*)g_o + (m * 16 + j + 8 * (R - 2)) * 16384 + img);
      } else {
        if (R == 5) { c.a0 = ((SM_BASE + wg * 4096) >> 4) | (1u << 16); c.a1 = c.a0 + 512; c.ah = 0x80000020; }
        geglu_tile<0>(acc, pk, c, hb + (2 * j + (R == 1 ? 0 : 16 * R - 40)) * 16384, BAR_EV + (R == 1 ? 1 : R + 1));
        if (R == 5) break;
      }
      p1_range<14, 16>(acc, c);
#pragma unroll
      for (int i = 0; i < 64; i++) pk[i] = pack2(acc[2 * i], acc[2 * i + 1]);
      if (t0) TS(25 + R + wg * 16);
    }
    if (t0) TS(30 + wg * 16);
    p1_issue<2, 1>(acc, c, 1); wg_wait<1>(); release(c, B_E1 + 8);
    p1_issue<3, 1>(acc, c, 1); wg_wait<1>(); release(c, B_E1 + 16);
#pragma unroll 1
    for (int it = 4; it < 7; it++) {
      p1_issue<0, 1>(acc, c, it & 1); wg_wait<1>(); release(c, B_E1 + 24);
      p1_issue<1, 1>(acc, c, it & 1); wg_wait<1>(); release(c, B_E1);
      p1_issue<2, 1>(acc, c, it & 1); wg_wait<1>(); release(c, B_E1 + 8);
      p1_issue<3, 1>(acc, c, it & 1); wg_wait<1>(); release(c, B_E1 + 16);
    }
    if (t0) TS(31 + wg * 16);
    {
      float accs[64];
      const uint32_t peer = mapa(sb, rank ^ 1);
      auto send_piece = [&](int p) {
        asm volatile("st.async.weak.shared::cluster.mbarrier::complete_tx::bytes.v4.b32 [%0], {%1,%2,%3,%4}, [%5];" ::"r"(peer + OFF_LAND + p * 4096 + threadIdx.x * 16),
                     "r"(pack2(acc[64 + 8 * p], acc[65 + 8 * p])), "r"(pack2(acc[66 + 8 * p], acc[67 + 8 * p])), "r"(pack2(acc[68 + 8 * p], acc[69 + 8 * p])), "r"(pack2(acc[70 + 8 * p], acc[71 + 8 * p])),
                     "r"(peer + B_EX + 8 * wg) : "memory");
      };
      auto silu_piece = [&](int p) {
        const uint4 r = lds128(sb + OFF_LAND + p * 4096 + threadIdx.x * 16);
        const uint32_t rr[4] = {r.x, r.y, r.z, r.w};
#pragma unroll
        for (int i = 0; i < 4; i++) {
          const float a = acc[8 * p + 2 * i] + lo_f(rr[i]), b = acc[8 * p + 2 * i + 1] + hi_f(rr[i]);
          pk[4 * p + i] = pack2(silu_half(a * 0.25f), silu_half(b * 0.25f));
        }
      };
      const uint32_t xa = sb + OFF_X + (warp * 16 + (lane & 15)) * 128 + (((lane >> 4) ^ (lane & 7)) << 4);
      p2_step<0>(accs, c);
      p2_step<1>(accs, c);
      mbar_wait(sb + B_E1 + 24, 0);
      send_piece(0); send_piece(1); send_piece(2); send_piece(3);
      p2_step<2>(accs, c);
      send_piece(4); send_piece(5); send_piece(6); send_piece(7);
      p2_step<3>(accs, c);
      mbar_wait(sb + B_XT, 0);
#pragma unroll
      for (int i = 0; i < 8; i++) { const uint4 v = ldsm((xa ^ ((i & 3) << 5)) + (i >> 2) * 16384); pk[32 + 4 * i] = v.x; pk[33 + 4 * i] = v.y; pk[34 + 4 * i] = v.z; pk[35 + 4 * i] = v.w; }
      p2_step<4>(accs, c);
      mbar_wait(sb + B_EX + 8 * wg, 0);
      silu_piece(0);
      p2_step<5>(accs, c); silu_piece(1);
      p2_step<6>(accs, c); silu_piece(2);
      p2_step<7>(accs, c); silu_piece(3);
      p2_step<8>(accs, c); silu_piece(4);
      p2_step<9>(accs, c); silu_piece(5);
      p2_step<10>(accs, c); silu_piece(6);
      p2_step<11>(accs, c); silu_piece(7);
      p2_step<12>(accs, c); p2_step<13>(accs, c); p2_step<14>(accs, c); p2_step<15>(accs, c);
      wg_wait<0>();
      if (t0) TS(32 + wg * 16);
#pragma unroll
      for (int i = 0; i < 8; i++) {
        uint32_t v[4];
#pragma unroll
        for (int k = 0; k < 4; k++) v[k] = fma2(pack2(accs[8 * i + 2 * k], accs[1 + 8 * i + 2 * k]), pk[4 * i + k], pk[32 + 4 * i + k]);
        asm volatile("stmatrix.sync.aligned.m8n8.x4.shared.b16 [%0], {%1,%2,%3,%4};" ::"r"((xa ^ ((i & 3) << 5)) + (i >> 2) * 16384), "r"(v[0]), "r"(v[1]), "r"(v[2]), "r"(v[3]) : "memory");
        if (i == 3 || i == 7) {
          asm volatile("fence.proxy.async.shared::cta;" ::: "memory");
          __syncwarp();
          if (elect_one()) tma3d_store(&mp.out, sb + OFF_X + (i >> 2) * 16384 + warp * 2048, j2 * 128 + (i >> 2) * 64, m2 * 64 + w * 16, wg);
        }
      }
      if (elect_one()) { asm volatile("cp.async.bulk.commit_group;\ncp.async.bulk.wait_group.read 0;" ::: "memory"); }
      if (t0) { TS(33 + wg * 16); if (wg) TG(59); }
    }
  }
}

typedef CUresult (*EncodeFn)(CUtensorMap*, CUtensorMapDataType, cuuint32_t, void*, const cuuint64_t*, const cuuint64_t*, const cuuint32_t*, const cuuint32_t*,
                             CUtensorMapInterleave, CUtensorMapSwizzle, CUtensorMapL2promotion, CUtensorMapFloatOOBfill);

void encode(EncodeFn fn, CUtensorMap* tm, const void* p, int rank, const cuuint64_t* dims, const cuuint64_t* strides, const cuuint32_t* box) {
  const cuuint32_t es[5] = {1, 1, 1, 1, 1};
  fn(tm, CU_TENSOR_MAP_DATA_TYPE_BFLOAT16, rank, const_cast<void*>(p), dims, strides, box, es, CU_TENSOR_MAP_INTERLEAVE_NONE, CU_TENSOR_MAP_SWIZZLE_128B,
     CU_TENSOR_MAP_L2_PROMOTION_L2_128B, CU_TENSOR_MAP_FLOAT_OOB_FILL_NONE);
}

}

extern "C" void kernel_launch(void* const* d_in, const int* in_sizes, int n_in, void* d_out, int out_size) {
  (void)in_sizes; (void)n_in; (void)out_size;
  static EncodeFn fn = nullptr;
  static void* xn_ptr = nullptr;
  if (!fn) {
    void* p = nullptr;
    cudaDriverEntryPointQueryResult qr;
    cudaGetDriverEntryPoint("cuTensorMapEncodeTiled", &p, cudaEnableDefault, &qr);
    fn = (EncodeFn)p;
    cudaGetSymbolAddress(&xn_ptr, g_xn);
    cudaFuncSetAttribute(fused_kernel, cudaFuncAttributeMaxDynamicSharedMemorySize, SMEM_BYTES);
  }
  const void *x = d_in[0], *wqkv = d_in[1], *wo = d_in[2], *wg = d_in[4], *wu = d_in[5], *wd = d_in[6];
  Maps mp;
  {
    const cuuint64_t dims[3] = {DM, SEQ / 2, 2}, st[2] = {DM * 4, DM * 2};
    const cuuint32_t box_in[3] = {64, 64, 2}, box_out[3] = {64, 16, 1};
    encode(fn, &mp.x, x, 3, dims, st, box_in);
    encode(fn, &mp.out, d_out, 3, dims, st, box_out);
  }
  {
    const cuuint64_t dims[2] = {DM, SEQ}, st[1] = {DM * 2};
    const cuuint32_t box[2] = {64, 128};
    encode(fn, &mp.xn, xn_ptr, 2, dims, st, box);
  }
  {
    const cuuint32_t box[2] = {64, 64};
    const cuuint64_t dq[2] = {3 * DM, DM}, sq[1] = {3 * DM * 2}, df[2] = {DFF, DM}, sf[1] = {DFF * 2}, dw[2] = {DM, DM}, sw[1] = {DM * 2};
    encode(fn, &mp.wqkv, wqkv, 2, dq, sq, box);
    encode(fn, &mp.wg, wg, 2, df, sf, box);
    encode(fn, &mp.wu, wu, 2, df, sf, box);
    encode(fn, &mp.wo, wo, 2, dw, sw, box);
  }
  {
    const cuuint32_t box[5] = {64, 2, 4, 4, 2};
    const cuuint64_t st[4] = {DM * 2, 8 * DM * 2, 2 * DM * 2, 32 * DM * 2};
    const cuuint64_t dd[5] = {DM, 2, 4, 4, DFF / 32};
    encode(fn, &mp.wd, wd, 5, dd, st, box);
  }
  fused_kernel<<<NCTA, 384, SMEM_BYTES>>>(mp, (const uint4*)x);
}
```

```cpp
#include <cuda_runtime.h>
#include <cuda_bf16.h>
#include <cuda.h>
#include <stdint.h>

#define LN_LD 0
#define PROMO CU_TENSOR_MAP_L2_PROMOTION_L2_128B
#define G_KB 12
#define DEFER_R 0
#define CS_KB 8
#define LN_KB 4

#define EVICT_FIRST 0x12F0000000000000ull
#define EVICT_NORMAL 0x1000000000000000ull
#define HINT_W EVICT_FIRST
#define HINT_H EVICT_FIRST
#define HINT_LAST EVICT_FIRST

namespace {

constexpr int SEQ = 2048, DM = 1024, DFF = 3584;
constexpr int NCTA = 128;

constexpr uint32_t SM_BASE = 0x400;
constexpr uint32_t P1_STAGE = 49152, P2_STAGE = 32768;
constexpr uint32_t OFF_X = 196608;
constexpr uint32_t OFF_CS = 229376;
constexpr uint32_t OFF_BAR = OFF_CS + 1088;
constexpr uint32_t OFF_LAND = 5 * P2_STAGE;
constexpr uint32_t B_F1 = OFF_BAR, B_E1 = B_F1 + 32, B_F2 = B_E1 + 32, B_E2 = B_F2 + 40;
constexpr uint32_t B_DEP = B_E2 + 40;
constexpr uint32_t B_AUX = B_DEP + 40, B_CS = B_AUX + 8, B_XT = B_CS + 8, B_EX = B_XT + 8, B_HALO = B_EX + 32, B_EP = B_HALO + 16, OFF_EPOCH = B_EP + 8;
constexpr uint32_t SMEM_BYTES = 232448;
constexpr uint32_t AT_V = 0, AT_K = 8192, AT_REM = 11264, AT_WG = 15360;

constexpr int FL_XN = 0, FL_H = 16, FL_HALO = 80, FL_N = FL_HALO + 256;
struct __align__(1024) Scratch {
  uint4 h[16 * 56 * 1024];
  uint4 o[16 * 16 * 1024];
  uint4 xn[SEQ * DM / 8];
  uint4 halo[2 * 128 * 2 * 128];
  ulonglong2 cspart[8 * 16 * 128];
  unsigned long long stats[SEQ];
  unsigned flags[FL_N * 32];
  unsigned epoch[NCTA * 2];
};
__device__ Scratch g_scratch;
#define TG(i) do {} while (0)
#define TS(i) do {} while (0)

struct Maps { CUtensorMap x, xn, out, wqkv, wg, wu, wd, wo; };

__device__ __forceinline__ void mbar_init(uint32_t bar, uint32_t cnt) { asm volatile("mbarrier.init.shared::cta.b64 [%0], %1;" ::"r"(bar), "r"(cnt)); }
__device__ __forceinline__ void mbar_expect_tx(uint32_t bar, uint32_t bytes) { asm volatile("mbarrier.arrive.expect_tx.shared::cta.b64 _, [%0], %1;" ::"r"(bar), "r"(bytes) : "memory"); }
__device__ __forceinline__ void mbar_arrive(uint32_t bar) { asm volatile("mbarrier.arrive.shared::cta.b64 _, [%0];" ::"r"(bar) : "memory"); }
__device__ __forceinline__ void mbar_arrive_cl(uint32_t bar) { asm volatile("mbarrier.arrive.shared::cluster.b64 _, [%0];" ::"r"(bar) : "memory"); }
__device__ __forceinline__ uint32_t mapa(uint32_t a, uint32_t cta) { uint32_t r; asm("mapa.shared::cluster.u32 %0, %1, %2;" : "=r"(r) : "r"(a), "r"(cta)); return r; }
__device__ __forceinline__ void mbar_wait(uint32_t bar, uint32_t parity) {
  asm volatile("{\n.reg .pred p;\n.reg .u32 n;\nmov.u32 n, 0;\nLAB_WAIT:\nmbarrier.try_wait.parity.shared::cta.b64 p, [%0], %1;\n@p bra LAB_DONE;\n"
               "add.u32 n, n, 1;\nsetp.gt.u32 p, n, 4000000;\n@p trap;\nbra LAB_WAIT;\nLAB_DONE:\n}" ::"r"(bar), "r"(parity) : "memory");
}
__device__ __forceinline__ void flag_wait(const unsigned* f, unsigned target) {
  asm volatile("{\n.reg .pred p;\n.reg .u32 n, v;\nmov.u32 n, 0;\nLAB_WAIT:\nld.relaxed.gpu.global.u32 v, [%0];\nsub.u32 v, v, %1;\nsetp.ge.s32 p, v, 0;\n@p bra LAB_DONE;\n"
               "nanosleep.u32 100;\nadd.u32 n, n, 1;\nsetp.gt.u32 p, n, 4000000;\n@p trap;\nbra LAB_WAIT;\nLAB_DONE:\nfence.acquire.gpu;\n}" ::"l"(f), "r"(target) : "memory");
}
__device__ __forceinline__ void flag_add(unsigned* f) { asm volatile("red.release.gpu.global.add.u32 [%0], 1;" ::"l"(f) : "memory"); }
__device__ __forceinline__ void fence_async() { asm volatile("fence.proxy.async.global;" ::: "memory"); }
__device__ __forceinline__ bool elect_one() { uint32_t p; asm volatile("{\n.reg .pred P;\nelect.sync _|P, 0xffffffff;\nselp.u32 %0, 1, 0, P;\n}" : "=r"(p)); return p; }
__device__ __forceinline__ void bar_sync(int id, int n) { asm volatile("bar.sync %0, %1;" ::"r"(id), "r"(n) : "memory"); }
__device__ __forceinline__ void bar_arrive(int id, int n) { asm volatile("bar.arrive %0, %1;" ::"r"(id), "r"(n) : "memory"); }

__device__ __forceinline__ void tma2d(uint32_t dst, const CUtensorMap* tm, uint32_t bar, int c0, int c1, uint64_t hint) {
  asm volatile("cp.async.bulk.tensor.2d.shared::cluster.global.mbarrier::complete_tx::bytes.L2::cache_hint [%0], [%1, {%3, %4}], [%2], %5;" ::"r"(dst), "l"(tm), "r"(bar), "r"(c0), "r"(c1), "l"(hint) : "memory");
}
__device__ __forceinline__ void tma2d_mc(uint32_t dst, const CUtensorMap* tm, uint32_t bar, int c0, int c1, uint64_t hint) {
  asm volatile("cp.async.bulk.tensor.2d.shared::cluster.global.mbarrier::complete_tx::bytes.multicast::cluster.L2::cache_hint [%0], [%1, {%3, %4}], [%2], %5, %6;" ::"r"(dst), "l"(tm), "r"(bar), "r"(c0), "r"(c1), "h"((uint16_t)3), "l"(hint) : "memory");
}
__device__ __forceinline__ void tma3d(uint32_t dst, const CUtensorMap* tm, uint32_t bar, int c0, int c1, int c2, uint64_t hint) {
  asm volatile("cp.async.bulk.tensor.3d.shared::cluster.global.mbarrier::complete_tx::bytes.L2::cache_hint [%0], [%1, {%3, %4, %5}], [%2], %6;" ::"r"(dst), "l"(tm), "r"(bar), "r"(c0), "r"(c1), "r"(c2), "l"(hint) : "memory");
}
__device__ __forceinline__ void tma5d(uint32_t dst, const CUtensorMap* tm, uint32_t bar, int c0, int c4, uint64_t hint) {
  asm volatile("cp.async.bulk.tensor.5d.shared::cluster.global.mbarrier::complete_tx::bytes.L2::cache_hint [%0], [%1, {%3, %5, %5, %5, %4}], [%2], %6;" ::"r"(dst), "l"(tm), "r"(bar), "r"(c0), "r"(c4), "r"(0), "l"(hint) : "memory");
}
__device__ __forceinline__ void tma3d_store(const CUtensorMap* tm, uint32_t src, int c0, int c1, int c2) {
  asm volatile("cp.async.bulk.tensor.3d.global.shared::cta.bulk_group [%0, {%2, %3, %4}], [%1];" ::"l"(tm), "r"(src), "r"(c0), "r"(c1), "r"(c2) : "memory");
}
__device__ __forceinline__ void bulk_load(uint32_t dst, const void* src, uint32_t bytes, uint32_t bar, uint64_t hint) {
  asm volatile("cp.async.bulk.shared::cluster.global.mbarrier::complete_tx::bytes.L2::cache_hint [%0], [%1], %2, [%3], %4;" ::"r"(dst), "l"(src), "r"(bytes), "r"(bar), "l"(hint) : "memory");
}
__device__ __forceinline__ void bulk_load_mc(uint32_t dst, const void* src, uint32_t bytes, uint32_t bar, uint64_t hint) {
  asm volatile("cp.async.bulk.shared::cluster.global.mbarrier::complete_tx::bytes.multicast::cluster.L2::cache_hint [%0], [%1], %2, [%3], %4, %5;" ::"r"(dst), "l"(src), "r"(bytes), "r"(bar), "h"((uint16_t)3), "l"(hint) : "memory");
}
__device__ __forceinline__ uint4 lds128(uint32_t a) { uint4 v; asm volatile("ld.shared.v4.b32 {%0,%1,%2,%3}, [%4];" : "=r"(v.x), "=r"(v.y), "=r"(v.z), "=r"(v.w) : "r"(a) : "memory"); return v; }
__device__ __forceinline__ void sts128(uint32_t a, uint4 v) { asm volatile("st.shared.v4.b32 [%0], {%1,%2,%3,%4};" ::"r"(a), "r"(v.x), "r"(v.y), "r"(v.z), "r"(v.w) : "memory"); }
__device__ __forceinline__ void stg128(void* p, uint32_t a, uint32_t b, uint32_t c, uint32_t d) { asm volatile("st.global.v4.b32 [%0], {%1,%2,%3,%4};" ::"l"(p), "r"(a), "r"(b), "r"(c), "r"(d) : "memory"); }

__device__ __forceinline__ uint32_t pack2(float lo, float hi) { uint32_t r; asm("cvt.rn.bf16x2.f32 %0, %1, %2;" : "=r"(r) : "f"(hi), "f"(lo)); return r; }
__device__ __forceinline__ float lo_f(uint32_t v) { return __uint_as_float(v << 16); }
__device__ __forceinline__ float hi_f(uint32_t v) { return __uint_as_float(v & 0xffff0000u); }
__device__ __forceinline__ float bf16r(float v) { return lo_f(pack2(v, 0.f)); }
__device__ __forceinline__ uint32_t mul2(uint32_t a, uint32_t b) { uint32_t r; asm("mul.rn.bf16x2 %0, %1, %2;" : "=r"(r) : "r"(a), "r"(b)); return r; }
__device__ __forceinline__ uint32_t sub2(uint32_t a, uint32_t b) { uint32_t r; asm("sub.rn.bf16x2 %0, %1, %2;" : "=r"(r) : "r"(a), "r"(b)); return r; }
__device__ __forceinline__ uint32_t fma2(uint32_t a, uint32_t b, uint32_t c) { uint32_t r; asm("fma.rn.bf16x2 %0, %1, %2, %3;" : "=r"(r) : "r"(a), "r"(b), "r"(c)); return r; }
__device__ __forceinline__ uint32_t max2(uint32_t a, uint32_t b) { uint32_t r; asm("max.bf16x2 %0, %1, %2;" : "=r"(r) : "r"(a), "r"(b)); return r; }
__device__ __forceinline__ float ex2f(float x) { float y; asm("ex2.approx.ftz.f32 %0, %1;" : "=f"(y) : "f"(x)); return y; }
__device__ __forceinline__ float rcpf(float x) { float y; asm("rcp.approx.ftz.f32 %0, %1;" : "=f"(y) : "f"(x)); return y; }
__device__ __forceinline__ float gelu2(float g) {
  float z = g * fmaf(g * g, 0.035677408136300125f, 0.7978845608028654f), t;
  asm("tanh.approx.f32 %0, %1;" : "=f"(t) : "f"(z));
  return fmaf(g, t, g);
}

__device__ __forceinline__ float silu_half(float z) { float t; asm("tanh.approx.f32 %0, %1;" : "=f"(t) : "f"(z)); return fmaf(z, t, z); }

__device__ __forceinline__ void wg_fence() { asm volatile("wgmma.fence.sync.aligned;" ::: "memory"); }
__device__ __forceinline__ void wg_commit() { asm volatile("wgmma.commit_group.sync.aligned;" ::: "memory"); }
template <int N> __device__ __forceinline__ void wg_wait() { asm volatile("wgmma.wait_group.sync.aligned %0;" ::"n"(N) : "memory"); }
#define A8(o) "+f"(d[(o)]), "+f"(d[(o) + 1]), "+f"(d[(o) + 2]), "+f"(d[(o) + 3]), "+f"(d[(o) + 4]), "+f"(d[(o) + 5]), "+f"(d[(o) + 6]), "+f"(d[(o) + 7])
#define A64(o) A8(o), A8((o) + 8), A8((o) + 16), A8((o) + 24), A8((o) + 32), A8((o) + 40), A8((o) + 48), A8((o) + 56)
#define REGS0_63 "%0,%1,%2,%3,%4,%5,%6,%7,%8,%9,%10,%11,%12,%13,%14,%15,%16,%17,%18,%19,%20,%21,%22,%23,%24,%25,%26,%27,%28,%29,%30,%31," \
                 "%32,%33,%34,%35,%36,%37,%38,%39,%40,%41,%42,%43,%44,%45,%46,%47,%48,%49,%50,%51,%52,%53,%54,%55,%56,%57,%58,%59,%60,%61,%62,%63"
#define REGS64_127 "%64,%65,%66,%67,%68,%69,%70,%71,%72,%73,%74,%75,%76,%77,%78,%79,%80,%81,%82,%83,%84,%85,%86,%87,%88,%89,%90,%91,%92,%93,%94,%95," \
                   "%96,%97,%98,%99,%100,%101,%102,%103,%104,%105,%106,%107,%108,%109,%110,%111,%112,%113,%114,%115,%116,%117,%118,%119,%120,%121,%122,%123,%124,%125,%126,%127"
template <int ACCUM> __device__ __forceinline__ void wgmma256(float (&d)[128], uint32_t a_lo, uint32_t a_hi, uint32_t b_lo) {
  asm volatile("{\n.reg .pred p;\n.reg .b64 da, db;\nsetp.ne.b32 p, %131, 0;\nmov.b64 da, {%128, %129};\nmov.b64 db, {%130, 0x40000040};\n"
               "wgmma.mma_async.sync.aligned.m64n256k16.f32.bf16.bf16 {" REGS0_63 "," REGS64_127 "}, da, db, p, 1, 1, 0, 1;\n}"
               : A64(0), A64(64) : "r"(a_lo), "r"(a_hi), "r"(b_lo), "n"(ACCUM));
}
template <int ACCUM> __device__ __forceinline__ void wgmma128(float (&d)[64], uint32_t a_lo, uint32_t b_lo) {
  asm volatile("{\n.reg .pred p;\n.reg .b64 da, db;\nsetp.ne.b32 p, %66, 0;\nmov.b64 da, {%64, 0x80000020};\nmov.b64 db, {%65, 0x40000040};\n"
               "wgmma.mma_async.sync.aligned.m64n128k16.f32.bf16.bf16 {" REGS0_63 "}, da, db, p, 1, 1, 0, 1;\n}"
               : A64(0) : "r"(a_lo), "r"(b_lo), "n"(ACCUM));
}
template <int ACCUM> __device__ __forceinline__ void hmma(float (&c)[4], uint32_t a0, uint32_t a1, uint32_t a2, uint32_t a3, uint32_t b0, uint32_t b1) {
  if (ACCUM)
    asm volatile("mma.sync.aligned.m16n8k16.row.col.f32.bf16.bf16.f32 {%0,%1,%2,%3}, {%4,%5,%6,%7}, {%8,%9}, {%0,%1,%2,%3};"
                 : "+f"(c[0]), "+f"(c[1]), "+f"(c[2]), "+f"(c[3]) : "r"(a0), "r"(a1), "r"(a2), "r"(a3), "r"(b0), "r"(b1));
  else
    asm volatile("mma.sync.aligned.m16n8k16.row.col.f32.bf16.bf16.f32 {%0,%1,%2,%3}, {%4,%5,%6,%7}, {%8,%9}, {%10,%10,%10,%10};"
                 : "=f"(c[0]), "=f"(c[1]), "=f"(c[2]), "=f"(c[3]) : "r"(a0), "r"(a1), "r"(a2), "r"(a3), "r"(b0), "r"(b1), "f"(0.f));
}
__device__ __forceinline__ uint32_t movm(uint32_t a) { uint32_t d; asm volatile("movmatrix.sync.aligned.m8n8.trans.b16 %0, %1;" : "=r"(d) : "r"(a)); return d; }
template <int N> __device__ __forceinline__ void pin(uint32_t* r) {
#pragma unroll
  for (int i = 0; i < N; i++) asm volatile("" : "+r"(r[i]));
}
template <int N> __device__ __forceinline__ void pin(float* r) {
#pragma unroll
  for (int i = 0; i < N; i++) asm volatile("" : "+f"(r[i]));
}
__device__ __forceinline__ void sched_fence(uint32_t zero) {
  asm volatile("{\n.reg .pred p;\n.reg .u32 n;\nmov.u32 n, %0;\nLAB_F:\nsetp.eq.u32 p, n, 0;\n@p bra.uni LAB_D;\nnanosleep.u32 n;\nsub.u32 n, n, 1;\nbra.uni LAB_F;\nLAB_D:\n}" ::"r"(zero) : "memory");
}
__device__ __forceinline__ uint4 ldsm(uint32_t a) { uint4 v; asm volatile("ldmatrix.sync.aligned.m8n8.x4.shared.b16 {%0,%1,%2,%3}, [%4];" : "=r"(v.x), "=r"(v.y), "=r"(v.z), "=r"(v.w) : "r"(a) : "memory"); return v; }
__device__ __forceinline__ uint4 ldsm_t(uint32_t a) { uint4 v; asm volatile("ldmatrix.sync.aligned.m8n8.x4.trans.shared.b16 {%0,%1,%2,%3}, [%4];" : "=r"(v.x), "=r"(v.y), "=r"(v.z), "=r"(v.w) : "r"(a) : "memory"); return v; }

constexpr int BAR_LAG = 1, BAR_MMA = 2, BAR_EV = 3;

struct Cons {
  uint32_t sb;
  uint32_t a0, a1, ah;
  uint32_t rel;
  bool do_rel;
  int wg;
  uint32_t zero;
};
#define REL_TS(n) TS(64 + (n))
constexpr uint32_t DB_LO = ((SM_BASE + 16384) >> 4) | ((8192 >> 4) << 16);

template <int ST, int ACCUM, bool WAIT = true> __device__ __forceinline__ void p1_issue(float (&acc)[128], const Cons& c, uint32_t parity) {
  if (WAIT) mbar_wait(c.sb + B_F1 + 8 * ST, parity);
  wg_fence();
  constexpr uint32_t so = ST * (P1_STAGE >> 4);
  wgmma256<ACCUM>(acc, c.a0 + so, c.ah, DB_LO + so);
  wgmma256<1>(acc, c.a0 + so + 2, c.ah, DB_LO + so + 128);
  wgmma256<1>(acc, c.a1 + so, c.ah, DB_LO + so + 256);
  wgmma256<1>(acc, c.a1 + so + 2, c.ah, DB_LO + so + 384);
  wg_commit();
}
__device__ __forceinline__ void release(const Cons& c, uint32_t bar) { if (c.do_rel) mbar_arrive_cl(c.rel + bar); }
template <int KB, bool WAIT = true, int LAG = 2> __device__ __forceinline__ void p1_step(float (&acc)[128], const Cons& c) {
  if (KB == 16 - LAG) { if (c.wg == 1) { wg_wait<0>(); release(c, B_E1 + 8 * ((KB - 1) & 3)); bar_sync(BAR_LAG, 256); } }
  p1_issue<KB & 3, KB != 0, WAIT>(acc, c, (KB >> 2) & 1);
  if (KB == 15) { if (c.wg == 0) bar_arrive(BAR_LAG, 256); }
  if (KB > 0) { wg_wait<1>(); if (KB != 16 - LAG || c.wg == 0) release(c, B_E1 + 8 * ((KB - 1) & 3)); }
  if (KB == 15) { wg_wait<0>(); release(c, B_E1 + 8 * 3); }
}
template <int A, int B> __device__ __forceinline__ void p1_range(float (&acc)[128], const Cons& c) {
  if constexpr (A < B) { p1_step<A>(acc, c); p1_range<A + 1, B>(acc, c); }
}
template <int T> __device__ __forceinline__ void p2_step(float (&acc)[64], const Cons& c) {
  if (T == 12) { if (c.wg == 1) bar_sync(BAR_LAG, 256); }
  mbar_wait(c.sb + B_F2 + 8 * (T % 5), (T / 5) & 1);
  wg_fence();
  constexpr uint32_t so = (T % 5) * (P2_STAGE >> 4);
  wgmma128<T != 0>(acc, c.a0 + so, DB_LO + so);
  wgmma128<1>(acc, c.a0 + so + 2, DB_LO + so + 128);
  wgmma128<1>(acc, c.a1 + so, DB_LO + so + 256);
  wgmma128<1>(acc, c.a1 + so + 2, DB_LO + so + 384);
  wg_commit();
  if (T == 15) { if (c.wg == 0) bar_arrive(BAR_LAG, 256); }
  if (T <= 11) { wg_wait<1>(); release(c, T ? B_E2 + 8 * ((T + 4) % 5) : B_E1 + 8 * 3); }
}

template <int P> __device__ __forceinline__ void geglu_piece(const uint32_t (&pk)[64], uint8_t* dst, const float (&rs)[2]) {
  constexpr int cg = P >> 1, r = P & 1;
  uint32_t v[4];
#pragma unroll
  for (int i = 0; i < 4; i++) {
    const uint32_t g = pk[2 * (4 * cg + i) + r];
    v[i] = mul2(pack2(gelu2(lo_f(g)), gelu2(hi_f(g))), pk[32 + 2 * (4 * cg + i) + r]);
  }
  stg128(dst + cg * 8192 + r * 512, v[0], v[1], v[2], v[3]);
}
template <int KB> __device__ __forceinline__ void geglu_tile(float (&acc)[128], const uint32_t (&pk)[64], const Cons& c, uint8_t* dst, int ev, const float (&rs)[2]) {
  if constexpr (KB < 14) {
    p1_step<KB>(acc, c);
    if (KB >= 1 && KB <= 8) geglu_piece<(KB - 1) & 7>(pk, dst, rs);
    if (KB == 8) bar_arrive(ev, 288);
    geglu_tile<KB + 1>(acc, pk, c, dst, ev, rs);
  }
}

__device__ __forceinline__ void attn_tile(float (&acc)[128], const uint32_t (&pk)[64], const Cons& c, int round, int warp, int m, Scratch* gs, uint8_t* hdst, uint8_t* odst) {
  const int lane = threadIdx.x & 31, w = warp & 3, rho = lane >> 2, q = lane & 3;
  const uint32_t at = c.sb + OFF_X + c.wg * AT_WG, swz = (lane ^ (lane >> 3)) << 4;
  uint32_t gg[16];
  p1_step<0>(acc, c);
  p1_step<1>(acc, c);
#pragma unroll
  for (int i = 0; i < 4; i++) {
    const int h = i & 1, r = i >> 1;
    sts128(at + AT_V + (2 * w + r) * 1024 + h * 512 + swz, make_uint4(pk[32 + 8 * h + r], pk[34 + 8 * h + r], pk[36 + 8 * h + r], pk[38 + 8 * h + r]));
  }
  if (w < 3) {
#pragma unroll
    for (int i = 0; i < 8; i++) asm volatile("st.shared.b32 [%0], %1;" ::"r"(at + AT_K + w * 1024 + i * 128 + lane * 4), "r"(pk[17 + 2 * i]) : "memory");
  } else {
    uint8_t* g = (uint8_t*)gs->halo + ((round * 128 + blockIdx.x) * 2 + c.wg) * 2048;
#pragma unroll
    for (int i = 0; i < 8; i++) asm volatile("st.global.b32 [%0], %1;" ::"l"(g + i * 128 + lane * 4), "r"(pk[17 + 2 * i]) : "memory");
#pragma unroll
    for (int h = 0; h < 2; h++) stg128(g + 1024 + h * 512 + swz, pk[33 + 8 * h], pk[35 + 8 * h], pk[37 + 8 * h], pk[39 + 8 * h]);
    bar_arrive(BAR_EV + 2 + round, 96);
  }
  __syncwarp();
  if (lane == 0) mbar_arrive(c.sb + B_HALO + 8 * round);
  if (round) {
#pragma unroll
    for (int p = 0; p < 4; p++) asm volatile("ld.global.cg.v4.b32 {%0,%1,%2,%3}, [%4];" : "=r"(gg[4 * p]), "=r"(gg[4 * p + 1]), "=r"(gg[4 * p + 2]), "=r"(gg[4 * p + 3]) : "l"(hdst + (p >> 1) * 8192 + (p & 1) * 512) : "memory");
  }
  auto gu_piece = [&](int p) {
    uint32_t v[4];
#pragma unroll
    for (int i = 0; i < 4; i++) {
      const uint32_t g = pk[48 + 8 * (p >> 1) + 2 * i + (p & 1)];
      v[i] = round ? mul2(gg[4 * p + i], g) : pack2(gelu2(lo_f(g)), gelu2(hi_f(g)));
    }
    stg128(hdst + (p >> 1) * 8192 + (p & 1) * 512, v[0], v[1], v[2], v[3]);
  };
  p1_step<2>(acc, c);
  p1_step<3>(acc, c); gu_piece(0);
  p1_step<4>(acc, c); gu_piece(1);
  p1_step<5>(acc, c); gu_piece(2);
  p1_step<6>(acc, c); gu_piece(3);
  p1_step<7>(acc, c);
  p1_step<8>(acc, c);
  const bool first = m == 0 && w == 0;
  uint32_t kl[16];
  mbar_wait(c.sb + B_HALO + 8 * round, 0);
  {
    const uint32_t ka = at + lane * 4 + (w ? AT_K + (w - 1) * 1024 : (first ? AT_K : AT_REM + round * 2048));
#pragma unroll
    for (int i = 0; i < 8; i++) {
      asm volatile("ld.shared.b32 %0, [%1];" : "=r"(kl[2 * i]) : "r"(ka + i * 128) : "memory");
      kl[2 * i + 1] = pk[16 + 2 * i] | c.zero;
    }
  }
  float st[4][4];
  pin<16>(kl);
  bar_sync(BAR_MMA, 256);
  mbar_wait(c.sb + B_F1 + 8 * 1, 0);
#pragma unroll
  for (int ks = 0; ks < 2; ks++) {
#pragma unroll
    for (int h = 0; h < 2; h++) {
      const int o = 8 * h + 4 * ks;
      if (ks == 0) { hmma<0>(st[2 * h], kl[o], kl[o + 1], kl[o + 2], kl[o + 3], pk[o], pk[o + 2]); hmma<0>(st[2 * h + 1], pk[16 + o], pk[17 + o], pk[18 + o], pk[19 + o], pk[o + 1], pk[o + 3]); }
      else { hmma<1>(st[2 * h], kl[o], kl[o + 1], kl[o + 2], kl[o + 3], pk[o], pk[o + 2]); hmma<1>(st[2 * h + 1], pk[16 + o], pk[17 + o], pk[18 + o], pk[19 + o], pk[o + 1], pk[o + 3]); }
    }
  }
  sched_fence(c.zero);
  bar_sync(BAR_MMA, 256);
  p1_step<9, false>(acc, c);
  sched_fence(c.zero);
  pin<16>(&st[0][0]);
  const bool le0 = 2 * q <= rho, le1 = 2 * q + 1 <= rho;
  uint32_t la[2], lb[2], mx[2];
#pragma unroll
  for (int h = 0; h < 2; h++) {
    uint32_t l[2];
#pragma unroll
    for (int r = 0; r < 2; r++) {
      const float (&t)[4] = st[2 * h + r];
      l[r] = movm(pack2(rho <= 2 * q ? t[2] : t[0], rho <= 2 * q + 1 ? t[3] : t[1]));
      l[r] = fma2(l[r], 0x3e353e35u, mul2(l[r], 0x379e379eu));
    }
    la[h] = __byte_perm(l[0], l[1], 0x5410); lb[h] = __byte_perm(l[0], l[1], 0x7632);
    if (first && !le0) la[h] = (la[h] & 0xffff0000u) | 0xce6eu;
    if (first && !le1) lb[h] = (lb[h] & 0xffff0000u) | 0xce6eu;
    mx[h] = max2(la[h], lb[h]);
  }
#pragma unroll
  for (int o = 1; o <= 2; o++) { mx[0] = max2(mx[0], __shfl_xor_sync(~0u, mx[0], o)); mx[1] = max2(mx[1], __shfl_xor_sync(~0u, mx[1], o)); }
  const float L2E = 1.4426950408889634f;
  float pr[2][4], z[4];
#pragma unroll
  for (int h = 0; h < 2; h++) {
    pr[h][0] = ex2f((lo_f(la[h]) - lo_f(mx[h])) * L2E); pr[h][1] = ex2f((lo_f(lb[h]) - lo_f(mx[h])) * L2E);
    pr[h][2] = ex2f((hi_f(la[h]) - hi_f(mx[h])) * L2E); pr[h][3] = ex2f((hi_f(lb[h]) - hi_f(mx[h])) * L2E);
    z[2 * h] = pr[h][0] + pr[h][1]; z[2 * h + 1] = pr[h][2] + pr[h][3];
  }
  p1_step<10>(acc, c);
#pragma unroll
  for (int o = 1; o <= 2; o++) {
#pragma unroll
    for (int i = 0; i < 4; i++) z[i] += __shfl_xor_sync(~0u, z[i], o);
  }
  const uint32_t LE = (le0 ? 0xffffu : 0u) | (le1 ? 0xffff0000u : 0u);
  uint32_t P[4][2];
  uint4 vt[4][2];
  {
    const uint32_t row = (lane & 7) * 64 + ((((lane >> 3) & 1) ^ ((lane & 7) >> 1)) << 4);
    const uint32_t v1 = at + AT_V + (2 * w + (lane >> 4)) * 1024 + row;
    const uint32_t v0 = (w || lane >= 16) ? v1 - 1024 : (first ? v1 : at + AT_REM + round * 2048 + 1024 + row);
#pragma unroll
    for (int i = 0; i < 4; i++) {
      const float rz = rcpf(z[i]);
      const uint32_t p = pack2(pr[i >> 1][2 * (i & 1)] * rz, pr[i >> 1][2 * (i & 1) + 1] * rz);
      P[i][0] = p & ~LE; P[i][1] = p & LE;
      const uint32_t a = ((i & 1) ? v1 : v0) + (i >> 1) * 512;
      vt[i][0] = ldsm_t(a); vt[i][1] = ldsm_t(a ^ 32);
    }
  }
  float ot[4][2][4];
  pin<8>(&P[0][0]);
  bar_sync(BAR_MMA, 256);
  mbar_wait(c.sb + B_F1 + 8 * 3, 0);
#pragma unroll
  for (int i = 0; i < 8; i++) { const uint4& v = vt[i >> 1][i & 1]; hmma<0>(ot[i >> 1][i & 1], v.x, v.y, v.z, v.w, P[i >> 1][0], P[i >> 1][1]); }
  sched_fence(c.zero);
  bar_sync(BAR_MMA, 256);
  p1_step<11, false>(acc, c);
  sched_fence(c.zero);
  pin<32>(&ot[0][0][0]);
  auto o_piece = [&](int i) {
    stg128(odst + (i >> 1) * 8192 + (i & 1) * 512, movm(pack2(ot[i][0][0], ot[i][0][1])), movm(pack2(ot[i][0][2], ot[i][0][3])), movm(pack2(ot[i][1][0], ot[i][1][1])), movm(pack2(ot[i][1][2], ot[i][1][3])));
  };
  o_piece(0); o_piece(1);
  p1_step<12>(acc, c);
  o_piece(2); o_piece(3);
  if (round) bar_arrive(BAR_EV + 4, 288);
  p1_step<13>(acc, c);
}

__device__ __forceinline__ void ln_moments(const uint32_t* raw, float& c0, float& s, float& v) {
  c0 = lo_f(__shfl_sync(~0u, raw[0], 0));
  float ss[4] = {0.f, 0.f, 0.f, 0.f}, vv[4] = {0.f, 0.f, 0.f, 0.f};
#pragma unroll
  for (int i = 0; i < 16; i++) {
    const float a = lo_f(raw[i]) - c0, b = hi_f(raw[i]) - c0;
    ss[(2 * i) & 3] += a; ss[(2 * i + 1) & 3] += b;
    vv[(2 * i) & 3] = fmaf(a, a, vv[(2 * i) & 3]); vv[(2 * i + 1) & 3] = fmaf(b, b, vv[(2 * i + 1) & 3]);
  }
  s = (ss[0] + ss[1]) + (ss[2] + ss[3]); v = (vv[0] + vv[1]) + (vv[2] + vv[3]);
}
__device__ __forceinline__ void ln_reduce(float& s, float& v) {
#pragma unroll
  for (int o = 16; o; o >>= 1) { s += __shfl_xor_sync(~0u, s, o); v += __shfl_xor_sync(~0u, v, o); }
}
__device__ __forceinline__ uint32_t ln_finish(float c0, float s, float v) {
  s *= 1.0f / DM;
  float sd;
  asm("sqrt.approx.ftz.f32 %0, %1;" : "=f"(sd) : "f"(bf16r(bf16r(fmaxf(fmaf(v, 1.0f / DM, -s * s), 0.f)) + 1e-5f)));
  return pack2(c0 + s, sd);
}
__device__ __forceinline__ void ln_store(const uint32_t* raw, uint32_t st, uint4* dst) {
  const uint32_t m2 = __byte_perm(st, st, 0x1010);
  const float rinv = rcpf(hi_f(st));
#pragma unroll
  for (int c = 0; c < 4; c++) {
    uint32_t v[4];
#pragma unroll
    for (int i = 0; i < 4; i++) { const uint32_t t = sub2(raw[4 * c + i], m2); v[i] = pack2(lo_f(t) * rinv, hi_f(t) * rinv); }
    stg128(dst + 32 * c, v[0], v[1], v[2], v[3]);
  }
}
__device__ __forceinline__ void col_sums(uint32_t tile, ulonglong2* part, uint32_t tag) {
  const int lane = threadIdx.x & 31;
  float cs[8] = {0, 0, 0, 0, 0, 0, 0, 0};
  uint32_t base = tile + ((lane >> 3) & 1) * 8192 + (lane >> 4) * 4096 + ((lane & 7) << 4);
#pragma unroll 1
  for (int k0 = 0; k0 < 8; k0++, base = (base ^ ((k0 ^ (k0 - 1)) << 4)) + 128) {
    uint4 v[4];
#pragma unroll
    for (int k = 0; k < 4; k++) v[k] = lds128(base + k * 1024);
#pragma unroll
    for (int k = 0; k < 4; k++) {
      cs[0] += lo_f(v[k].x); cs[1] += hi_f(v[k].x); cs[2] += lo_f(v[k].y); cs[3] += hi_f(v[k].y);
      cs[4] += lo_f(v[k].z); cs[5] += hi_f(v[k].z); cs[6] += lo_f(v[k].w); cs[7] += hi_f(v[k].w);
    }
  }
  const bool up = lane >= 16;
#pragma unroll
  for (int i = 0; i < 2; i++) {
    const float a = (up ? cs[4 + 2 * i] : cs[2 * i]) + __shfl_xor_sync(~0u, up ? cs[2 * i] : cs[4 + 2 * i], 16);
    const float b = (up ? cs[5 + 2 * i] : cs[1 + 2 * i]) + __shfl_xor_sync(~0u, up ? cs[1 + 2 * i] : cs[5 + 2 * i], 16);
    asm volatile("{\n.reg .b64 a, b;\nmov.b64 a, {%1, %3};\nmov.b64 b, {%2, %3};\nst.relaxed.gpu.global.v2.b64 [%0], {a, b};\n}"
                 ::"l"(part + 32 * (i + (up ? 2 : 0)) + (lane & 15)), "r"(__float_as_uint(a)), "r"(__float_as_uint(b)), "r"(tag) : "memory");
  }
  asm volatile("fence.proxy.async.shared::cta;" ::: "memory");
}

__global__ void __cluster_dims__(2, 1, 1) __launch_bounds__(384, 1)
fused_kernel(const __grid_constant__ Maps mp, const uint4* __restrict__ x, Scratch* gs) {
  extern __shared__ __align__(1024) uint8_t smem_raw[];
  const uint32_t sb = (uint32_t)__cvta_generic_to_shared(smem_raw);
  const unsigned t_start = 0;
  const int warp = __shfl_sync(~0u, threadIdx.x >> 5, 0), lane = threadIdx.x & 31;
  const int m = blockIdx.x & 15, j = blockIdx.x >> 4, rank = blockIdx.x & 1;
  const int m2 = blockIdx.x >> 3, j2 = blockIdx.x & 7;
  if (warp == 0) {
    if (elect_one()) {
      for (int s = 0; s < 4; s++) mbar_init(sb + B_F1 + 8 * s, 1);
      asm volatile("fence.mbarrier_init.release.cluster;" ::: "memory");
      TS(0); TG(51);
#pragma unroll 1
      for (int kb = 0; kb < 4; kb++) {
        const uint32_t sa = sb + kb * P1_STAGE, fb = sb + B_F1 + 8 * kb;
        mbar_expect_tx(fb, P1_STAGE);
        tma3d(sa, &mp.x, fb, kb * 64, m * 64, 0, EVICT_NORMAL);
        tma2d(sa + 16384, &mp.wg, fb, j * 128, kb * 64, EVICT_NORMAL); tma2d(sa + 32768, &mp.wu, fb, j * 128, kb * 64, EVICT_NORMAL);
        tma2d(sa + 24576, &mp.wg, fb, j * 128 + 64, kb * 64, EVICT_NORMAL); tma2d(sa + 40960, &mp.wu, fb, j * 128 + 64, kb * 64, EVICT_NORMAL);
      }
      TS(7);
    }
    __syncwarp();
  }

  if (warp >= 8) {
    asm volatile("setmaxnreg.dec.sync.aligned.u32 40;");
    if (warp == 9) {
      if (elect_one()) {
        if ((sb & 0xffffff) != SM_BASE) asm volatile("trap;");
        for (int s = 0; s < 4; s++) mbar_init(sb + B_E1 + 8 * s, 4);
        for (int s = 0; s < 5; s++) { mbar_init(sb + B_F2 + 8 * s, 1); mbar_init(sb + B_E2 + 8 * s, 4); }
        for (int s = 0; s < 5; s++) mbar_init(sb + B_DEP + 8 * s, 1);
        mbar_init(sb + B_AUX, 8); mbar_init(sb + B_EP, 1); mbar_init(sb + B_XT, 1); mbar_init(sb + B_CS, 1);
        for (int s = 0; s < 4; s++) { mbar_init(sb + B_EX + 8 * s, 1); mbar_expect_tx(sb + B_EX + 8 * s, 8192); }
        mbar_init(sb + B_HALO, 9); mbar_init(sb + B_HALO + 8, 9);
        asm volatile("fence.mbarrier_init.release.cluster;" ::: "memory");
      }
      __syncwarp();
    }
    asm volatile("barrier.cluster.arrive.relaxed.aligned;\nbarrier.cluster.wait.aligned;" ::: "memory");
    if (warp == 8) {
      if (elect_one()) {
        uint32_t par = 0;
        for (int i = 1; i < 8; i++) asm volatile("prefetch.tensormap [%0];" ::"l"(&mp.x + i) : "memory");
        for (int R = 0; R < 5; R++) {
          const CUtensorMap *mb0, *mb1;
          int n0, n1;
          if (R == 1 || R == 2) {
            mb0 = &mp.wqkv; n0 = 64 * (j + 8 * (R - 1)) + rank * 2048;
            mb1 = rank ? (R == 1 ? &mp.wg : &mp.wu) : &mp.wqkv; n1 = rank ? 1024 + 64 * j : n0 + 1024;
          } else {
            mb0 = mb1 = rank ? &mp.wu : &mp.wg;
            n0 = 128 * j + (R ? 1024 * R - 1536 : 0); n1 = n0 + 64;
          }
#pragma unroll 1
          for (int kb = R ? 0 : 4; kb < 16; kb++) {
            if (R == 0 && kb == (CS_KB)) {
              const uint32_t cb = sb + B_CS, d = sb + OFF_X;
              mbar_expect_tx(cb, 32768);
              tma2d(d, &mp.wg, cb, n0, m * 64, EVICT_NORMAL); tma2d(d + 8192, &mp.wg, cb, n1, m * 64, EVICT_NORMAL);
              tma2d(d + 16384, &mp.wu, cb, n0, m * 64, EVICT_NORMAL); tma2d(d + 24576, &mp.wu, cb, n1, m * 64, EVICT_NORMAL);
            }
            const int st = kb & 3;
            const uint32_t sa = sb + st * P1_STAGE, fb = sb + B_F1 + 8 * st;
            mbar_wait(sb + B_E1 + 8 * st, par);
            REL_TS(R * 16 + kb - 4);
            mbar_expect_tx(fb, P1_STAGE);
            tma2d_mc(sa + 16384 + rank * 16384, mb0, fb, n0, kb * 64, HINT_W);
            tma2d_mc(sa + 24576 + rank * 16384, mb1, fb, n1, kb * 64, HINT_W);
            if (R == 0) {
              tma3d(sa, &mp.x, fb, kb * 64, m * 64, 0, EVICT_NORMAL);
            } else {
              if (R == 1 && kb == 0) { mbar_wait(sb + B_DEP, 0); TS(1); }
              tma2d(sa, &mp.xn, fb, kb * 64, m * 128, R == 4 ? HINT_LAST : EVICT_NORMAL);
            }
            if (R == 4 && kb == 4 + j2) {
              mbar_expect_tx(sb + B_XT, 32768);
              tma3d(sb + OFF_X, &mp.x, sb + B_XT, j2 * 128, m2 * 64, 0, HINT_LAST); tma3d(sb + OFF_X + 16384, &mp.x, sb + B_XT, j2 * 128 + 64, m2 * 64, 0, HINT_LAST);
            }
            if (st == 3) par ^= 1;
          }
        }
#pragma unroll 1
        for (int i = 0; i < 28; i++) {
          if (i == 0 || i == 8 || i == 12 || i == 20) { mbar_wait(sb + B_DEP + 8 * (1 + ((i + 4) >> 3)), 0); TS(2 + ((i + 4) >> 3)); }
          const int st = i & 3, kb = 2 * i + rank;
          const uint32_t sa = sb + st * P1_STAGE, fb = sb + B_F1 + 8 * st;
          mbar_wait(sb + B_E1 + 8 * st, par);
          REL_TS(76 + i);
          mbar_expect_tx(fb, P1_STAGE);
          bulk_load(sa, gs->h + (m2 * 56 + kb) * 1024, 16384, fb, HINT_H);
          tma5d(sa + 16384, &mp.wd, fb, j2 * 128, kb * 2, HINT_W); tma5d(sa + 24576, &mp.wd, fb, j2 * 128 + 64, kb * 2, HINT_W);
          tma5d(sa + 32768, &mp.wd, fb, (j2 ^ 1) * 128, kb * 2, HINT_W); tma5d(sa + 40960, &mp.wd, fb, (j2 ^ 1) * 128 + 64, kb * 2, HINT_W);
          if (st == 3) par ^= 1;
        }
        int st = 0; uint32_t par2 = 1;
#pragma unroll 1
        for (int t = 0; t < 16; t++) {
          const uint32_t sa = sb + st * P2_STAGE, fb = sb + B_F2 + 8 * st;
          if (t < 5) mbar_wait(sb + B_E1 + 8 * ((2 * t + 1) / 3), par); else mbar_wait(sb + B_E2 + 8 * st, par2);
          REL_TS(104 + t);
          mbar_expect_tx(fb, P2_STAGE);
          bulk_load_mc(sa + rank * 8192, gs->o + (m2 * 16 + t) * 1024 + rank * 512, 8192, fb, HINT_H);
          tma2d(sa + 16384, &mp.wo, fb, j2 * 128, t * 64, HINT_W); tma2d(sa + 24576, &mp.wo, fb, j2 * 128 + 64, t * 64, HINT_W);
          if (++st == 5) { st = 0; par2 ^= 1; }
        }
      }
    } else if (warp == 9) {
#pragma unroll 1
      for (int e = 0; e < 7; e++) {
        const bool halo = e == 2 || e == 3;
        bar_sync(BAR_EV + e, halo ? 96 : 288);
        if (lane == 0) {
          const int f = e == 0 ? FL_XN + m : (halo ? FL_HALO + (e - 2) * 128 + blockIdx.x : FL_H + m * 4 + (e == 1 ? 0 : e - 3));
          TS(10 + 2 * e); TG(52 + e);
          flag_add(&gs->flags[f * 32]);
          if (e < 6) TS(11 + 2 * e);
        }
        __syncwarp();
      }
    } else {
      unsigned e = 0;
      if (lane == 0) {
        unsigned* ep = &gs->epoch[blockIdx.x * 2 + warp - 10];
        e = *ep + 1; *ep = e;
        if (warp == 10) { asm volatile("st.shared.b32 [%0], %1;" ::"r"(sb + OFF_EPOCH), "r"(e) : "memory"); mbar_arrive(sb + B_EP); }
      }
      e = __shfl_sync(~0u, e, 0);
      mbar_wait(sb + B_CS, 0);
      if (lane == 0 && warp == 11) TS(6);
      col_sums(sb + OFF_X + (warp - 10) * 16384, gs->cspart + (j * 16 + m) * 128 + (warp - 10) * 16, e);
      if (lane == 0 && warp == 11) TS(9);
      if (warp == 10) {
        if (lane == 0) {
#pragma unroll 1
          for (int g = 0; g < 5; g++) {
            flag_wait(&gs->flags[(g ? FL_H + m2 * 4 + g - 1 : FL_XN + m) * 32], e * 8u);
            fence_async();
            mbar_arrive(sb + B_DEP + 8 * g);
            if (g == 0) TS(8);
          }
        }
      } else
      if (elect_one()) {
#pragma unroll 1
        for (int r = 0; r < 2; r++) {
          const uint32_t hb = sb + B_HALO + 8 * r;
          if (m) {
            flag_wait(&gs->flags[(FL_HALO + r * 128 + blockIdx.x - 1) * 32], e);
            fence_async();
            mbar_expect_tx(hb, 4096);
            for (int g = 0; g < 2; g++) bulk_load(sb + OFF_X + g * AT_WG + AT_REM + r * 2048, gs->halo + ((r * 128 + blockIdx.x - 1) * 2 + g) * 128, 2048, hb, EVICT_FIRST);
          } else {
            mbar_arrive(hb);
          }
          TS(34 + r);
        }
      }
    }
  } else {
    asm volatile("barrier.cluster.arrive.relaxed.aligned;" ::: "memory");
    asm volatile("setmaxnreg.inc.sync.aligned.u32 232;");
    const int wg = warp >> 2, w = warp & 3;
    Cons c;
    c.sb = sb; c.wg = wg; c.zero = warp >> 8;
    c.a0 = ((SM_BASE + wg * 8192) >> 4) | (1u << 16); c.a1 = c.a0 + 4; c.ah = 0x40000040;
    c.rel = mapa(sb, threadIdx.x & 1);
    c.do_rel = (threadIdx.x & 127) < 2;
    constexpr bool t0 = false;
    float acc[128];
    uint32_t pk[64];
    float rs[2];
    const int rho = lane >> 2, q = lane & 3;

    {
      const int prow = 16 * j + 2 * warp;
      const uint4* xr = x + (size_t)(128 * m + 2 * (prow & 63) + (prow >> 6)) * 128 + lane;
      uint4* xo = gs->xn + (size_t)(128 * m + prow) * 128 + lane;
      float c0[2], mo[4];
      uint32_t st[2];
      uint32_t e;
      asm volatile("" : "+l"(xr), "+l"(xo));
      if (t0) TS(23 + wg * 16);
      asm volatile("barrier.cluster.wait.aligned;" ::: "memory");
      p1_range<0, LN_LD + 1>(acc, c);
      if (t0) TS(24 + wg * 16);
#pragma unroll
      for (int i = 0; i < 8; i++) {
        asm volatile("ld.global.nc.v4.b32 {%0,%1,%2,%3}, [%4];" : "=r"(pk[4 * i]), "=r"(pk[4 * i + 1]), "=r"(pk[4 * i + 2]), "=r"(pk[4 * i + 3]) : "l"(xr + (i >> 2) * 256 + (i & 3) * 32));
      }
      p1_range<LN_LD + 1, LN_KB + 1>(acc, c);
      sched_fence(c.zero);

      pin<16>(pk); ln_moments(pk, c0[0], mo[0], mo[1]); pin<2>(mo);
      p1_step<LN_KB + 1>(acc, c);
      sched_fence(c.zero);
      pin<16>(pk + 16); ln_moments(pk + 16, c0[1], mo[2], mo[3]); ln_reduce(mo[0], mo[1]); pin<4>(mo);
      p1_step<LN_KB + 2>(acc, c);
      mbar_wait(sb + B_EP, 0);
      asm volatile("ld.shared.b32 %0, [%1];" : "=r"(e) : "r"(sb + OFF_EPOCH) : "memory");
      pin<2>(mo); st[0] = ln_finish(c0[0], mo[0], mo[1]); ln_reduce(mo[2], mo[3]); pin<1>(st); pin<2>(mo + 2);
      p1_step<LN_KB + 3>(acc, c);
      sched_fence(c.zero);
      pin<1>(st); pin<2>(mo + 2);
      st[1] = ln_finish(c0[1], mo[2], mo[3]);
      ln_store(pk, st[0], xo);
      if (lane == 0)
        asm volatile("{\n.reg .b64 a, b;\nmov.b64 a, {%1, %3};\nmov.b64 b, {%2, %3};\nst.relaxed.gpu.global.v2.b64 [%0], {a, b};\n}" ::"l"(gs->stats + 128 * m + prow), "r"(st[0]), "r"(st[1]), "r"(e) : "memory");
      p1_step<LN_KB + 4>(acc, c);
      sched_fence(c.zero);
      pin<1>(st + 1); ln_store(pk + 16, st[1], xo + 128);
      bar_arrive(BAR_EV, 288);
      p1_range<LN_KB + 5, G_KB + 1>(acc, c);
      sched_fence(c.zero);
      const unsigned long long* cp = (const unsigned long long*)gs->cspart + j * 4096 + threadIdx.x;
      const unsigned long long* sp = gs->stats + 128 * m + warp * 16 + rho;
      unsigned long long part[18];
      auto gather = [&]() {
#pragma unroll
        for (int i = 0; i < 18; i++) asm volatile("ld.relaxed.gpu.global.b64 %0, [%1];" : "=l"(part[i]) : "l"(i < 16 ? cp + i * 256 : sp + (i - 16) * 8) : "memory");
      };
      gather();
      p1_range<G_KB + 1, 14>(acc, c);
      sched_fence(c.zero);
      {
        float csum;
        for (int tries = 0;; tries++) {
          uint32_t bad = 0;
          csum = 0.f;
#pragma unroll
          for (int i = 0; i < 18; i++) { bad |= (uint32_t)(part[i] >> 32) ^ e; if (i < 16) csum += __uint_as_float((uint32_t)part[i]); }
          if (!__any_sync(~0u, bad != 0) || tries > (1 << 20)) break;
          gather();
        }
        asm volatile("st.shared.b32 [%0], %1;" ::"r"(sb + OFF_CS + threadIdx.x * 4 + (threadIdx.x >> 6) * 16), "f"(csum) : "memory");
        __syncwarp();
        if (lane == 0) mbar_arrive(sb + B_AUX);
        mo[0] = -lo_f((uint32_t)part[16]); mo[1] = rcpf(hi_f((uint32_t)part[16])); mo[2] = -lo_f((uint32_t)part[17]); mo[3] = rcpf(hi_f((uint32_t)part[17]));
        pin<4>(mo);
      }
      p1_step<14>(acc, c);
      p1_issue<3, 1>(acc, c, 1);
      if (wg == 0) bar_arrive(BAR_LAG, 256);
      mbar_wait(sb + B_AUX, 0);
#pragma unroll
      for (int i = 0; i < 16; i++) { const uint4 v = lds128(sb + OFF_CS + q * 272 + i * 16); pk[4 * i] = v.x; pk[4 * i + 1] = v.y; pk[4 * i + 2] = v.z; pk[4 * i + 3] = v.w; }
      wg_wait<1>(); release(c, B_E1 + 16);
      wg_wait<0>(); release(c, B_E1 + 24);
      const float m0 = mo[0], r0 = mo[1], m1 = mo[2], r1 = mo[3];
#pragma unroll
      for (int n = 0; n < 32; n++) {
        const float c0 = __uint_as_float(pk[2 * n]), c1 = __uint_as_float(pk[2 * n + 1]);
        if (DEFER_R == 2 || (DEFER_R == 1 && n >= 16)) {
          pk[2 * n] = pack2(fmaf(m0, c0, acc[4 * n]), fmaf(m0, c1, acc[4 * n + 1]));
          pk[2 * n + 1] = pack2(fmaf(m1, c0, acc[4 * n + 2]), fmaf(m1, c1, acc[4 * n + 3]));
        } else {
          pk[2 * n] = pack2(fmaf(m0, c0, acc[4 * n]) * r0, fmaf(m0, c1, acc[4 * n + 1]) * r0);
          pk[2 * n + 1] = pack2(fmaf(m1, c0, acc[4 * n + 2]) * r1, fmaf(m1, c1, acc[4 * n + 3]) * r1);
        }
      }
      rs[0] = r0; rs[1] = r1;
      if (t0) TS(25 + wg * 16);
    }
    const uint32_t img = warp * 1024 + ((lane ^ (lane >> 3)) << 4);
#pragma unroll 1
    for (int R = 1;; R++) {
      uint8_t* hb = (uint8_t*)gs->h + (size_t)m * 56 * 16384 + img;
      if (R == 2 || R == 3) {
        attn_tile(acc, pk, c, R - 2, warp, m, gs, hb + (16 + j) * 16384, (uint8_t*)gs->o + (m * 16 + j + 8 * (R - 2)) * 16384 + img);
      } else {
        if (R == 5) { c.a0 = ((SM_BASE + wg * 4096) >> 4) | (1u << 16); c.a1 = c.a0 + 512; c.ah = 0x80000020; }
        geglu_tile<0>(acc, pk, c, hb + (2 * j + (R == 1 ? 0 : 16 * R - 40)) * 16384, BAR_EV + (R == 1 ? 1 : R + 1), rs);
        rs[0] = rs[1] = 1.0f;
        if (R == 5) break;
      }
      p1_range<14, 16>(acc, c);
#pragma unroll
      for (int i = 0; i < 64; i++) pk[i] = pack2(acc[2 * i], acc[2 * i + 1]);
      if (t0) TS(25 + R + wg * 16);
    }
    if (t0) TS(30 + wg * 16);
    p1_issue<2, 1>(acc, c, 1); wg_wait<1>(); release(c, B_E1 + 8);
    p1_issue<3, 1>(acc, c, 1); wg_wait<1>(); release(c, B_E1 + 16);
#pragma unroll 1
    for (int it = 4; it < 7; it++) {
      p1_issue<0, 1>(acc, c, it & 1); wg_wait<1>(); release(c, B_E1 + 24);
      p1_issue<1, 1>(acc, c, it & 1); wg_wait<1>(); release(c, B_E1);
      p1_issue<2, 1>(acc, c, it & 1); wg_wait<1>(); release(c, B_E1 + 8);
      p1_issue<3, 1>(acc, c, it & 1); wg_wait<1>(); release(c, B_E1 + 16);
    }
    if (t0) TS(31 + wg * 16);
    {
      float accs[64];
      const uint32_t peer = mapa(sb, rank ^ 1);
      auto send_piece = [&](int p) {
        asm volatile("st.async.weak.shared::cluster.mbarrier::complete_tx::bytes.v4.b32 [%0], {%1,%2,%3,%4}, [%5];" ::"r"(peer + OFF_LAND + p * 4096 + threadIdx.x * 16),
                     "r"(pack2(acc[64 + 8 * p], acc[65 + 8 * p])), "r"(pack2(acc[66 + 8 * p], acc[67 + 8 * p])), "r"(pack2(acc[68 + 8 * p], acc[69 + 8 * p])), "r"(pack2(acc[70 + 8 * p], acc[71 + 8 * p])),
                     "r"(peer + B_EX + 16 * wg + 8 * (p >> 2)) : "memory");
      };
      auto silu_piece = [&](int p) {
        const uint4 r = lds128(sb + OFF_LAND + p * 4096 + threadIdx.x * 16);
        const uint32_t rr[4] = {r.x, r.y, r.z, r.w};
#pragma unroll
        for (int i = 0; i < 4; i++) {
          const float a = acc[8 * p + 2 * i] + lo_f(rr[i]), b = acc[8 * p + 2 * i + 1] + hi_f(rr[i]);
          pk[4 * p + i] = pack2(silu_half(a * 0.25f), silu_half(b * 0.25f));
        }
        pin<4>(pk + 4 * p);
      };
      const uint32_t xa = sb + OFF_X + (warp * 16 + (lane & 15)) * 128 + (((lane >> 4) ^ (lane & 7)) << 4);
      auto x_piece = [&](int i) { const uint4 v = ldsm((xa ^ ((i & 3) << 5)) + (i >> 2) * 16384); pk[32 + 4 * i] = v.x; pk[33 + 4 * i] = v.y; pk[34 + 4 * i] = v.z; pk[35 + 4 * i] = v.w; };
      p2_step<0>(accs, c);
      p2_step<1>(accs, c);
      mbar_wait(sb + B_E1 + 24, 0);
      send_piece(0); send_piece(1);
      p2_step<2>(accs, c); sched_fence(c.zero); send_piece(2); send_piece(3);
      p2_step<3>(accs, c); sched_fence(c.zero); send_piece(4); send_piece(5);
      p2_step<4>(accs, c); sched_fence(c.zero); send_piece(6); send_piece(7);
      p2_step<5>(accs, c);
      mbar_wait(sb + B_XT, 0);
      mbar_wait(sb + B_EX + 16 * wg, 0);
      silu_piece(0); x_piece(0);
      p2_step<6>(accs, c); sched_fence(c.zero); silu_piece(1); x_piece(1);
      p2_step<7>(accs, c); sched_fence(c.zero); silu_piece(2); x_piece(2);
      p2_step<8>(accs, c); sched_fence(c.zero); silu_piece(3); x_piece(3);
      p2_step<9>(accs, c);
      mbar_wait(sb + B_EX + 16 * wg + 8, 0);
      silu_piece(4); x_piece(4);
      p2_step<10>(accs, c); sched_fence(c.zero); silu_piece(5); x_piece(5);
      p2_step<11>(accs, c); sched_fence(c.zero); silu_piece(6); x_piece(6);
      p2_step<12>(accs, c); p2_step<13>(accs, c); p2_step<14>(accs, c); p2_step<15>(accs, c);
      sched_fence(c.zero); silu_piece(7); x_piece(7);
      wg_wait<0>();
      if (t0) TS(32 + wg * 16);
#pragma unroll
      for (int i = 0; i < 8; i++) {
        uint32_t v[4];
#pragma unroll
        for (int k = 0; k < 4; k++) v[k] = fma2(pack2(accs[8 * i + 2 * k], accs[1 + 8 * i + 2 * k]), pk[4 * i + k], pk[32 + 4 * i + k]);
        asm volatile("stmatrix.sync.aligned.m8n8.x4.shared.b16 [%0], {%1,%2,%3,%4};" ::"r"((xa ^ ((i & 3) << 5)) + (i >> 2) * 16384), "r"(v[0]), "r"(v[1]), "r"(v[2]), "r"(v[3]) : "memory");
        if (i == 3 || i == 7) {
          asm volatile("fence.proxy.async.shared::cta;" ::: "memory");
          __syncwarp();
          if (elect_one()) tma3d_store(&mp.out, sb + OFF_X + (i >> 2) * 16384 + warp * 2048, j2 * 128 + (i >> 2) * 64, m2 * 64 + w * 16, wg);
        }
      }
      if (elect_one()) { asm volatile("cp.async.bulk.commit_group;\ncp.async.bulk.wait_group.read 0;" ::: "memory"); }
      if ((threadIdx.x & 127) == 0) { TS(33 + wg * 16); if (wg) TG(59); }
    }
  }
}

typedef CUresult (*EncodeFn)(CUtensorMap*, CUtensorMapDataType, cuuint32_t, void*, const cuuint64_t*, const cuuint64_t*, const cuuint32_t*, const cuuint32_t*,
                             CUtensorMapInterleave, CUtensorMapSwizzle, CUtensorMapL2promotion, CUtensorMapFloatOOBfill);

void encode(EncodeFn fn, CUtensorMap* tm, const void* p, int rank, const cuuint64_t* dims, const cuuint64_t* strides, const cuuint32_t* box) {
  const cuuint32_t es[5] = {1, 1, 1, 1, 1};
  fn(tm, CU_TENSOR_MAP_DATA_TYPE_BFLOAT16, rank, const_cast<void*>(p), dims, strides, box, es, CU_TENSOR_MAP_INTERLEAVE_NONE, CU_TENSOR_MAP_SWIZZLE_128B,
     PROMO, CU_TENSOR_MAP_FLOAT_OOB_FILL_NONE);
}

}

extern "C" void kernel_launch(void* const* d_in, const int* in_sizes, int n_in, void* d_out, int out_size) {
  (void)in_sizes; (void)n_in; (void)out_size;
  static EncodeFn fn = nullptr;
  static Scratch* gs = nullptr;
  if (!fn) {
    void* p = nullptr;
    cudaDriverEntryPointQueryResult qr;
    cudaGetDriverEntryPoint("cuTensorMapEncodeTiled", &p, cudaEnableDefault, &qr);
    fn = (EncodeFn)p;
    cudaGetSymbolAddress((void**)&gs, g_scratch);
    cudaFuncSetAttribute(fused_kernel, cudaFuncAttributeMaxDynamicSharedMemorySize, SMEM_BYTES);
  }
  const void *x = d_in[0], *wqkv = d_in[1], *wo = d_in[2], *wg = d_in[4], *wu = d_in[5], *wd = d_in[6];
  Maps mp;
  {
    const cuuint64_t dims[3] = {DM, SEQ / 2, 2}, st[2] = {DM * 4, DM * 2};
    const cuuint32_t box_in[3] = {64, 64, 2}, box_out[3] = {64, 16, 1};
    encode(fn, &mp.x, x, 3, dims, st, box_in);
    encode(fn, &mp.out, d_out, 3, dims, st, box_out);
  }
  {
    const cuuint64_t dims[2] = {DM, SEQ}, st[1] = {DM * 2};
    const cuuint32_t box[2] = {64, 128};
    encode(fn, &mp.xn, gs->xn, 2, dims, st, box);
  }
  {
    const cuuint32_t box[2] = {64, 64};
    const cuuint64_t dq[2] = {3 * DM, DM}, sq[1] = {3 * DM * 2}, df[2] = {DFF, DM}, sf[1] = {DFF * 2}, dw[2] = {DM, DM}, sw[1] = {DM * 2};
    encode(fn, &mp.wqkv, wqkv, 2, dq, sq, box);
    encode(fn, &mp.wg, wg, 2, df, sf, box);
    encode(fn, &mp.wu, wu, 2, df, sf, box);
    encode(fn, &mp.wo, wo, 2, dw, sw, box);
  }
  {
    const cuuint32_t box[5] = {64, 2, 4, 4, 2};
    const cuuint64_t st[4] = {DM * 2, 8 * DM * 2, 2 * DM * 2, 32 * DM * 2};
    const cuuint64_t dd[5] = {DM, 2, 4, 4, DFF / 32};
    encode(fn, &mp.wd, wd, 5, dd, st, box);
  }
  fused_kernel<<<NCTA, 384, SMEM_BYTES>>>(mp, (const uint4*)x, gs);
}
```

```cpp
#include <cuda_runtime.h>
#include <cuda_bf16.h>
#include <cuda.h>
#include <stdint.h>

#define LN_LD 0
#define PROMO CU_TENSOR_MAP_L2_PROMOTION_L2_128B
#define G_KB 12
#define DEFER_R 2
#define CS_KB 8
#define LN_KB 4

#define EVICT_FIRST 0x12F0000000000000ull
#define EVICT_NORMAL 0x1000000000000000ull
#define HINT_W EVICT_FIRST
#define HINT_H EVICT_FIRST
#define HINT_LAST EVICT_FIRST

namespace {

constexpr int SEQ = 2048, DM = 1024, DFF = 3584;
constexpr int NCTA = 128;

constexpr uint32_t SM_BASE = 0x400;
constexpr uint32_t P1_STAGE = 49152, P2_STAGE = 32768;
constexpr uint32_t OFF_X = 196608;
constexpr uint32_t OFF_CS = 229376;
constexpr uint32_t OFF_BAR = OFF_CS + 1088;
constexpr uint32_t OFF_LAND = 5 * P2_STAGE;
constexpr uint32_t B_F1 = OFF_BAR, B_E1 = B_F1 + 32, B_F2 = B_E1 + 32, B_E2 = B_F2 + 40;
constexpr uint32_t B_DEP = B_E2 + 40;
constexpr uint32_t B_AUX = B_DEP + 40, B_CS = B_AUX + 8, B_XT = B_CS + 8, B_EX = B_XT + 8, B_HALO = B_EX + 32, B_EP = B_HALO + 16, OFF_EPOCH = B_EP + 8;
constexpr uint32_t SMEM_BYTES = 232448;
constexpr uint32_t AT_V = 0, AT_K = 8192, AT_REM = 11264, AT_WG = 15360;

constexpr int FL_XN = 0, FL_H = 16, FL_HALO = 80, FL_N = FL_HALO + 256;
struct __align__(1024) Scratch {
  uint4 h[16 * 56 * 1024];
  uint4 o[16 * 16 * 1024];
  uint4 xn[SEQ * DM / 8];
  uint4 halo[2 * 128 * 2 * 128];
  ulonglong2 cspart[8 * 16 * 128];
  unsigned long long stats[SEQ];
  unsigned flags[FL_N * 32];
  unsigned epoch[NCTA * 2];
};
__device__ Scratch g_scratch;
#define TG(i) do {} while (0)
#define TS(i) do {} while (0)

struct Maps { CUtensorMap x, xn, out, wqkv, wg, wu, wd, wo; };

__device__ __forceinline__ void mbar_init(uint32_t bar, uint32_t cnt) { asm volatile("mbarrier.init.shared::cta.b64 [%0], %1;" ::"r"(bar), "r"(cnt)); }
__device__ __forceinline__ void mbar_expect_tx(uint32_t bar, uint32_t bytes) { asm volatile("mbarrier.arrive.expect_tx.shared::cta.b64 _, [%0], %1;" ::"r"(bar), "r"(bytes) : "memory"); }
__device__ __forceinline__ void mbar_arrive(uint32_t bar) { asm volatile("mbarrier.arrive.shared::cta.b64 _, [%0];" ::"r"(bar) : "memory"); }
__device__ __forceinline__ void mbar_arrive_cl(uint32_t bar) { asm volatile("mbarrier.arrive.shared::cluster.b64 _, [%0];" ::"r"(bar) : "memory"); }
__device__ __forceinline__ uint32_t mapa(uint32_t a, uint32_t cta) { uint32_t r; asm("mapa.shared::cluster.u32 %0, %1, %2;" : "=r"(r) : "r"(a), "r"(cta)); return r; }
__device__ __forceinline__ void mbar_wait(uint32_t bar, uint32_t parity) {
  asm volatile("{\n.reg .pred p;\n.reg .u32 n;\nmov.u32 n, 0;\nLAB_WAIT:\nmbarrier.try_wait.parity.shared::cta.b64 p, [%0], %1;\n@p bra LAB_DONE;\n"
               "add.u32 n, n, 1;\nsetp.gt.u32 p, n, 4000000;\n@p trap;\nbra LAB_WAIT;\nLAB_DONE:\n}" ::"r"(bar), "r"(parity) : "memory");
}
__device__ __forceinline__ void flag_wait(const unsigned* f, unsigned target) {
  asm volatile("{\n.reg .pred p;\n.reg .u32 n, v;\nmov.u32 n, 0;\nLAB_WAIT:\nld.relaxed.gpu.global.u32 v, [%0];\nsub.u32 v, v, %1;\nsetp.ge.s32 p, v, 0;\n@p bra LAB_DONE;\n"
               "nanosleep.u32 100;\nadd.u32 n, n, 1;\nsetp.gt.u32 p, n, 4000000;\n@p trap;\nbra LAB_WAIT;\nLAB_DONE:\nfence.acquire.gpu;\n}" ::"l"(f), "r"(target) : "memory");
}
__device__ __forceinline__ void flag_add(unsigned* f) { asm volatile("red.release.gpu.global.add.u32 [%0], 1;" ::"l"(f) : "memory"); }
__device__ __forceinline__ void fence_async() { asm volatile("fence.proxy.async.global;" ::: "memory"); }
__device__ __forceinline__ bool elect_one() { uint32_t p; asm volatile("{\n.reg .pred P;\nelect.sync _|P, 0xffffffff;\nselp.u32 %0, 1, 0, P;\n}" : "=r"(p)); return p; }
__device__ __forceinline__ void bar_sync(int id, int n) { asm volatile("bar.sync %0, %1;" ::"r"(id), "r"(n) : "memory"); }
__device__ __forceinline__ void bar_arrive(int id, int n) { asm volatile("bar.arrive %0, %1;" ::"r"(id), "r"(n) : "memory"); }

__device__ __forceinline__ void tma2d(uint32_t dst, const CUtensorMap* tm, uint32_t bar, int c0, int c1, uint64_t hint) {
  asm volatile("cp.async.bulk.tensor.2d.shared::cluster.global.mbarrier::complete_tx::bytes.L2::cache_hint [%0], [%1, {%3, %4}], [%2], %5;" ::"r"(dst), "l"(tm), "r"(bar), "r"(c0), "r"(c1), "l"(hint) : "memory");
}
__device__ __forceinline__ void tma2d_mc(uint32_t dst, const CUtensorMap* tm, uint32_t bar, int c0, int c1, uint64_t hint) {
  asm volatile("cp.async.bulk.tensor.2d.shared::cluster.global.mbarrier::complete_tx::bytes.multicast::cluster.L2::cache_hint [%0], [%1, {%3, %4}], [%2], %5, %6;" ::"r"(dst), "l"(tm), "r"(bar), "r"(c0), "r"(c1), "h"((uint16_t)3), "l"(hint) : "memory");
}
__device__ __forceinline__ void tma3d(uint32_t dst, const CUtensorMap* tm, uint32_t bar, int c0, int c1, int c2, uint64_t hint) {
  asm volatile("cp.async.bulk.tensor.3d.shared::cluster.global.mbarrier::complete_tx::bytes.L2::cache_hint [%0], [%1, {%3, %4, %5}], [%2], %6;" ::"r"(dst), "l"(tm), "r"(bar), "r"(c0), "r"(c1), "r"(c2), "l"(hint) : "memory");
}
__device__ __forceinline__ void tma5d(uint32_t dst, const CUtensorMap* tm, uint32_t bar, int c0, int c4, uint64_t hint) {
  asm volatile("cp.async.bulk.tensor.5d.shared::cluster.global.mbarrier::complete_tx::bytes.L2::cache_hint [%0], [%1, {%3, %5, %5, %5, %4}], [%2], %6;" ::"r"(dst), "l"(tm), "r"(bar), "r"(c0), "r"(c4), "r"(0), "l"(hint) : "memory");
}
__device__ __forceinline__ void tma3d_store(const CUtensorMap* tm, uint32_t src, int c0, int c1, int c2) {
  asm volatile("cp.async.bulk.tensor.3d.global.shared::cta.bulk_group [%0, {%2, %3, %4}], [%1];" ::"l"(tm), "r"(src), "r"(c0), "r"(c1), "r"(c2) : "memory");
}
__device__ __forceinline__ void bulk_load(uint32_t dst, const void* src, uint32_t bytes, uint32_t bar, uint64_t hint) {
  asm volatile("cp.async.bulk.shared::cluster.global.mbarrier::complete_tx::bytes.L2::cache_hint [%0], [%1], %2, [%3], %4;" ::"r"(dst), "l"(src), "r"(bytes), "r"(bar), "l"(hint) : "memory");
}
__device__ __forceinline__ void bulk_load_mc(uint32_t dst, const void* src, uint32_t bytes, uint32_t bar, uint64_t hint) {
  asm volatile("cp.async.bulk.shared::cluster.global.mbarrier::complete_tx::bytes.multicast::cluster.L2::cache_hint [%0], [%1], %2, [%3], %4, %5;" ::"r"(dst), "l"(src), "r"(bytes), "r"(bar), "h"((uint16_t)3), "l"(hint) : "memory");
}
__device__ __forceinline__ uint4 lds128(uint32_t a) { uint4 v; asm volatile("ld.shared.v4.b32 {%0,%1,%2,%3}, [%4];" : "=r"(v.x), "=r"(v.y), "=r"(v.z), "=r"(v.w) : "r"(a) : "memory"); return v; }
__device__ __forceinline__ void sts128(uint32_t a, uint4 v) { asm volatile("st.shared.v4.b32 [%0], {%1,%2,%3,%4};" ::"r"(a), "r"(v.x), "r"(v.y), "r"(v.z), "r"(v.w) : "memory"); }
__device__ __forceinline__ void stg128(void* p, uint32_t a, uint32_t b, uint32_t c, uint32_t d) { asm volatile("st.global.v4.b32 [%0], {%1,%2,%3,%4};" ::"l"(p), "r"(a), "r"(b), "r"(c), "r"(d) : "memory"); }

__device__ __forceinline__ uint32_t pack2(float lo, float hi) { uint32_t r; asm("cvt.rn.bf16x2.f32 %0, %1, %2;" : "=r"(r) : "f"(hi), "f"(lo)); return r; }
__device__ __forceinline__ float lo_f(uint32_t v) { return __uint_as_float(v << 16); }
__device__ __forceinline__ float hi_f(uint32_t v) { return __uint_as_float(v & 0xffff0000u); }
__device__ __forceinline__ float bf16r(float v) { return lo_f(pack2(v, 0.f)); }
__device__ __forceinline__ uint32_t mul2(uint32_t a, uint32_t b) { uint32_t r; asm("mul.rn.bf16x2 %0, %1, %2;" : "=r"(r) : "r"(a), "r"(b)); return r; }
__device__ __forceinline__ uint32_t sub2(uint32_t a, uint32_t b) { uint32_t r; asm("sub.rn.bf16x2 %0, %1, %2;" : "=r"(r) : "r"(a), "r"(b)); return r; }
__device__ __forceinline__ uint32_t fma2(uint32_t a, uint32_t b, uint32_t c) { uint32_t r; asm("fma.rn.bf16x2 %0, %1, %2, %3;" : "=r"(r) : "r"(a), "r"(b), "r"(c)); return r; }
__device__ __forceinline__ uint32_t max2(uint32_t a, uint32_t b) { uint32_t r; asm("max.bf16x2 %0, %1, %2;" : "=r"(r) : "r"(a), "r"(b)); return r; }
__device__ __forceinline__ float ex2f(float x) { float y; asm("ex2.approx.ftz.f32 %0, %1;" : "=f"(y) : "f"(x)); return y; }
__device__ __forceinline__ float rcpf(float x) { float y; asm("rcp.approx.ftz.f32 %0, %1;" : "=f"(y) : "f"(x)); return y; }
__device__ __forceinline__ float gelu2(float g) {
  float z = g * fmaf(g * g, 0.035677408136300125f, 0.7978845608028654f), t;
  asm("tanh.approx.f32 %0, %1;" : "=f"(t) : "f"(z));
  return fmaf(g, t, g);
}

__device__ __forceinline__ float silu_half(float z) { float t; asm("tanh.approx.f32 %0, %1;" : "=f"(t) : "f"(z)); return fmaf(z, t, z); }

__device__ __forceinline__ void wg_fence() { asm volatile("wgmma.fence.sync.aligned;" ::: "memory"); }
__device__ __forceinline__ void wg_commit() { asm volatile("wgmma.commit_group.sync.aligned;" ::: "memory"); }
template <int N> __device__ __forceinline__ void wg_wait() { asm volatile("wgmma.wait_group.sync.aligned %0;" ::"n"(N) : "memory"); }
#define A8(o) "+f"(d[(o)]), "+f"(d[(o) + 1]), "+f"(d[(o) + 2]), "+f"(d[(o) + 3]), "+f"(d[(o) + 4]), "+f"(d[(o) + 5]), "+f"(d[(o) + 6]), "+f"(d[(o) + 7])
#define A64(o) A8(o), A8((o) + 8), A8((o) + 16), A8((o) + 24), A8((o) + 32), A8((o) + 40), A8((o) + 48), A8((o) + 56)
#define REGS0_63 "%0,%1,%2,%3,%4,%5,%6,%7,%8,%9,%10,%11,%12,%13,%14,%15,%16,%17,%18,%19,%20,%21,%22,%23,%24,%25,%26,%27,%28,%29,%30,%31," \
                 "%32,%33,%34,%35,%36,%37,%38,%39,%40,%41,%42,%43,%44,%45,%46,%47,%48,%49,%50,%51,%52,%53,%54,%55,%56,%57,%58,%59,%60,%61,%62,%63"
#define REGS64_127 "%64,%65,%66,%67,%68,%69,%70,%71,%72,%73,%74,%75,%76,%77,%78,%79,%80,%81,%82,%83,%84,%85,%86,%87,%88,%89,%90,%91,%92,%93,%94,%95," \
                   "%96,%97,%98,%99,%100,%101,%102,%103,%104,%105,%106,%107,%108,%109,%110,%111,%112,%113,%114,%115,%116,%117,%118,%119,%120,%121,%122,%123,%124,%125,%126,%127"
template <int ACCUM> __device__ __forceinline__ void wgmma256(float (&d)[128], uint32_t a_lo, uint32_t a_hi, uint32_t b_lo) {
  asm volatile("{\n.reg .pred p;\n.reg .b64 da, db;\nsetp.ne.b32 p, %131, 0;\nmov.b64 da, {%128, %129};\nmov.b64 db, {%130, 0x40000040};\n"
               "wgmma.mma_async.sync.aligned.m64n256k16.f32.bf16.bf16 {" REGS0_63 "," REGS64_127 "}, da, db, p, 1, 1, 0, 1;\n}"
               : A64(0), A64(64) : "r"(a_lo), "r"(a_hi), "r"(b_lo), "n"(ACCUM));
}
template <int ACCUM> __device__ __forceinline__ void wgmma128(float (&d)[64], uint32_t a_lo, uint32_t b_lo) {
  asm volatile("{\n.reg .pred p;\n.reg .b64 da, db;\nsetp.ne.b32 p, %66, 0;\nmov.b64 da, {%64, 0x80000020};\nmov.b64 db, {%65, 0x40000040};\n"
               "wgmma.mma_async.sync.aligned.m64n128k16.f32.bf16.bf16 {" REGS0_63 "}, da, db, p, 1, 1, 0, 1;\n}"
               : A64(0) : "r"(a_lo), "r"(b_lo), "n"(ACCUM));
}
template <int ACCUM> __device__ __forceinline__ void hmma(float (&c)[4], uint32_t a0, uint32_t a1, uint32_t a2, uint32_t a3, uint32_t b0, uint32_t b1) {
  if (ACCUM)
    asm volatile("mma.sync.aligned.m16n8k16.row.col.f32.bf16.bf16.f32 {%0,%1,%2,%3}, {%4,%5,%6,%7}, {%8,%9}, {%0,%1,%2,%3};"
                 : "+f"(c[0]), "+f"(c[1]), "+f"(c[2]), "+f"(c[3]) : "r"(a0), "r"(a1), "r"(a2), "r"(a3), "r"(b0), "r"(b1));
  else
    asm volatile("mma.sync.aligned.m16n8k16.row.col.f32.bf16.bf16.f32 {%0,%1,%2,%3}, {%4,%5,%6,%7}, {%8,%9}, {%10,%10,%10,%10};"
                 : "=f"(c[0]), "=f"(c[1]), "=f"(c[2]), "=f"(c[3]) : "r"(a0), "r"(a1), "r"(a2), "r"(a3), "r"(b0), "r"(b1), "f"(0.f));
}
__device__ __forceinline__ uint32_t movm(uint32_t a) { uint32_t d; asm volatile("movmatrix.sync.aligned.m8n8.trans.b16 %0, %1;" : "=r"(d) : "r"(a)); return d; }
template <int N> __device__ __forceinline__ void pin(uint32_t* r) {
#pragma unroll
  for (int i = 0; i < N; i++) asm volatile("" : "+r"(r[i]));
}
template <int N> __device__ __forceinline__ void pin(float* r) {
#pragma unroll
  for (int i = 0; i < N; i++) asm volatile("" : "+f"(r[i]));
}
__device__ __forceinline__ void sched_fence(uint32_t zero) {
  asm volatile("{\n.reg .pred p;\n.reg .u32 n;\nmov.u32 n, %0;\nLAB_F:\nsetp.eq.u32 p, n, 0;\n@p bra.uni LAB_D;\nnanosleep.u32 n;\nsub.u32 n, n, 1;\nbra.uni LAB_F;\nLAB_D:\n}" ::"r"(zero) : "memory");
}
__device__ __forceinline__ uint4 ldsm(uint32_t a) { uint4 v; asm volatile("ldmatrix.sync.aligned.m8n8.x4.shared.b16 {%0,%1,%2,%3}, [%4];" : "=r"(v.x), "=r"(v.y), "=r"(v.z), "=r"(v.w) : "r"(a) : "memory"); return v; }
__device__ __forceinline__ uint4 ldsm_t(uint32_t a) { uint4 v; asm volatile("ldmatrix.sync.aligned.m8n8.x4.trans.shared.b16 {%0,%1,%2,%3}, [%4];" : "=r"(v.x), "=r"(v.y), "=r"(v.z), "=r"(v.w) : "r"(a) : "memory"); return v; }

constexpr int BAR_LAG = 1, BAR_MMA = 2, BAR_EV = 3;

struct Cons {
  uint32_t sb;
  uint32_t a0, a1, ah;
  uint32_t rel;
  bool do_rel;
  int wg;
  uint32_t zero;
};
#define REL_TS(n) TS(64 + (n))
constexpr uint32_t DB_LO = ((SM_BASE + 16384) >> 4) | ((8192 >> 4) << 16);

template <int ST, int ACCUM, bool WAIT = true> __device__ __forceinline__ void p1_issue(float (&acc)[128], const Cons& c, uint32_t parity) {
  if (WAIT) mbar_wait(c.sb + B_F1 + 8 * ST, parity);
  wg_fence();
  constexpr uint32_t so = ST * (P1_STAGE >> 4);
  wgmma256<ACCUM>(acc, c.a0 + so, c.ah, DB_LO + so);
  wgmma256<1>(acc, c.a0 + so + 2, c.ah, DB_LO + so + 128);
  wgmma256<1>(acc, c.a1 + so, c.ah, DB_LO + so + 256);
  wgmma256<1>(acc, c.a1 + so + 2, c.ah, DB_LO + so + 384);
  wg_commit();
}
__device__ __forceinline__ void release(const Cons& c, uint32_t bar) { if (c.do_rel) mbar_arrive_cl(c.rel + bar); }
template <int KB, bool WAIT = true, int LAG = 2> __device__ __forceinline__ void p1_step(float (&acc)[128], const Cons& c) {
  if (KB == 16 - LAG) { if (c.wg == 1) { wg_wait<0>(); release(c, B_E1 + 8 * ((KB - 1) & 3)); bar_sync(BAR_LAG, 256); } }
  p1_issue<KB & 3, KB != 0, WAIT>(acc, c, (KB >> 2) & 1);
  if (KB == 15) { if (c.wg == 0) bar_arrive(BAR_LAG, 256); }
  if (KB > 0) { wg_wait<1>(); if (KB != 16 - LAG || c.wg == 0) release(c, B_E1 + 8 * ((KB - 1) & 3)); }
  if (KB == 15) { wg_wait<0>(); release(c, B_E1 + 8 * 3); }
}
template <int A, int B> __device__ __forceinline__ void p1_range(float (&acc)[128], const Cons& c) {
  if constexpr (A < B) { p1_step<A>(acc, c); p1_range<A + 1, B>(acc, c); }
}
template <int T> __device__ __forceinline__ void p2_step(float (&acc)[64], const Cons& c) {
  if (T == 12) { if (c.wg == 1) bar_sync(BAR_LAG, 256); }
  mbar_wait(c.sb + B_F2 + 8 * (T % 5), (T / 5) & 1);
  wg_fence();
  constexpr uint32_t so = (T % 5) * (P2_STAGE >> 4);
  wgmma128<T != 0>(acc, c.a0 + so, DB_LO + so);
  wgmma128<1>(acc, c.a0 + so + 2, DB_LO + so + 128);
  wgmma128<1>(acc, c.a1 + so, DB_LO + so + 256);
  wgmma128<1>(acc, c.a1 + so + 2, DB_LO + so + 384);
  wg_commit();
  if (T == 15) { if (c.wg == 0) bar_arrive(BAR_LAG, 256); }
  if (T <= 11) { wg_wait<1>(); release(c, T ? B_E2 + 8 * ((T + 4) % 5) : B_E1 + 8 * 3); }
}

template <int P> __device__ __forceinline__ void geglu_piece(const uint32_t (&pk)[64], uint8_t* dst, const float (&rs)[2]) {
  constexpr int cg = P >> 1, r = P & 1;
  uint32_t v[4];
#pragma unroll
  for (int i = 0; i < 4; i++) {
    const uint32_t g = pk[2 * (4 * cg + i) + r];
    v[i] = mul2(pack2(gelu2(lo_f(g) * rs[r]) * rs[r], gelu2(hi_f(g) * rs[r]) * rs[r]), pk[32 + 2 * (4 * cg + i) + r]);
  }
  stg128(dst + cg * 8192 + r * 512, v[0], v[1], v[2], v[3]);
}
template <int KB> __device__ __forceinline__ void geglu_tile(float (&acc)[128], const uint32_t (&pk)[64], const Cons& c, uint8_t* dst, int ev, const float (&rs)[2]) {
  if constexpr (KB < 14) {
    p1_step<KB>(acc, c);
    if (KB >= 1 && KB <= 8) geglu_piece<(KB - 1) & 7>(pk, dst, rs);
    if (KB == 8) bar_arrive(ev, 288);
    geglu_tile<KB + 1>(acc, pk, c, dst, ev, rs);
  }
}

__device__ __forceinline__ void attn_tile(float (&acc)[128], const uint32_t (&pk)[64], const Cons& c, int round, int warp, int m, Scratch* gs, uint8_t* hdst, uint8_t* odst) {
  const int lane = threadIdx.x & 31, w = warp & 3, rho = lane >> 2, q = lane & 3;
  const uint32_t at = c.sb + OFF_X + c.wg * AT_WG, swz = (lane ^ (lane >> 3)) << 4;
  uint32_t gg[16];
  p1_step<0>(acc, c);
  p1_step<1>(acc, c);
#pragma unroll
  for (int i = 0; i < 4; i++) {
    const int h = i & 1, r = i >> 1;
    sts128(at + AT_V + (2 * w + r) * 1024 + h * 512 + swz, make_uint4(pk[32 + 8 * h + r], pk[34 + 8 * h + r], pk[36 + 8 * h + r], pk[38 + 8 * h + r]));
  }
  if (w < 3) {
#pragma unroll
    for (int i = 0; i < 8; i++) asm volatile("st.shared.b32 [%0], %1;" ::"r"(at + AT_K + w * 1024 + i * 128 + lane * 4), "r"(pk[17 + 2 * i]) : "memory");
  } else {
    uint8_t* g = (uint8_t*)gs->halo + ((round * 128 + blockIdx.x) * 2 + c.wg) * 2048;
#pragma unroll
    for (int i = 0; i < 8; i++) asm volatile("st.global.b32 [%0], %1;" ::"l"(g + i * 128 + lane * 4), "r"(pk[17 + 2 * i]) : "memory");
#pragma unroll
    for (int h = 0; h < 2; h++) stg128(g + 1024 + h * 512 + swz, pk[33 + 8 * h], pk[35 + 8 * h], pk[37 + 8 * h], pk[39 + 8 * h]);
    bar_arrive(BAR_EV + 2 + round, 96);
  }
  __syncwarp();
  if (lane == 0) mbar_arrive(c.sb + B_HALO + 8 * round);
  if (round) {
#pragma unroll
    for (int p = 0; p < 4; p++) asm volatile("ld.global.cg.v4.b32 {%0,%1,%2,%3}, [%4];" : "=r"(gg[4 * p]), "=r"(gg[4 * p + 1]), "=r"(gg[4 * p + 2]), "=r"(gg[4 * p + 3]) : "l"(hdst + (p >> 1) * 8192 + (p & 1) * 512) : "memory");
  }
  auto gu_piece = [&](int p) {
    uint32_t v[4];
#pragma unroll
    for (int i = 0; i < 4; i++) {
      const uint32_t g = pk[48 + 8 * (p >> 1) + 2 * i + (p & 1)];
      v[i] = round ? mul2(gg[4 * p + i], g) : pack2(gelu2(lo_f(g)), gelu2(hi_f(g)));
    }
    stg128(hdst + (p >> 1) * 8192 + (p & 1) * 512, v[0], v[1], v[2], v[3]);
  };
  p1_step<2>(acc, c);
  p1_step<3>(acc, c); gu_piece(0);
  p1_step<4>(acc, c); gu_piece(1);
  p1_step<5>(acc, c); gu_piece(2);
  p1_step<6>(acc, c); gu_piece(3);
  p1_step<7>(acc, c);
  p1_step<8>(acc, c);
  const bool first = m == 0 && w == 0;
  uint32_t kl[16];
  mbar_wait(c.sb + B_HALO + 8 * round, 0);
  {
    const uint32_t ka = at + lane * 4 + (w ? AT_K + (w - 1) * 1024 : (first ? AT_K : AT_REM + round * 2048));
#pragma unroll
    for (int i = 0; i < 8; i++) {
      asm volatile("ld.shared.b32 %0, [%1];" : "=r"(kl[2 * i]) : "r"(ka + i * 128) : "memory");
      kl[2 * i + 1] = pk[16 + 2 * i] | c.zero;
    }
  }
  float st[4][4];
  pin<16>(kl);
  bar_sync(BAR_MMA, 256);
  mbar_wait(c.sb + B_F1 + 8 * 1, 0);
#pragma unroll
  for (int ks = 0; ks < 2; ks++) {
#pragma unroll
    for (int h = 0; h < 2; h++) {
      const int o = 8 * h + 4 * ks;
      if (ks == 0) { hmma<0>(st[2 * h], kl[o], kl[o + 1], kl[o + 2], kl[o + 3], pk[o], pk[o + 2]); hmma<0>(st[2 * h + 1], pk[16 + o], pk[17 + o], pk[18 + o], pk[19 + o], pk[o + 1], pk[o + 3]); }
      else { hmma<1>(st[2 * h], kl[o], kl[o + 1], kl[o + 2], kl[o + 3], pk[o], pk[o + 2]); hmma<1>(st[2 * h + 1], pk[16 + o], pk[17 + o], pk[18 + o], pk[19 + o], pk[o + 1], pk[o + 3]); }
    }
  }
  sched_fence(c.zero);
  bar_sync(BAR_MMA, 256);
  p1_step<9, false>(acc, c);
  sched_fence(c.zero);
  pin<16>(&st[0][0]);
  const bool le0 = 2 * q <= rho, le1 = 2 * q + 1 <= rho;
  uint32_t la[2], lb[2], mx[2];
#pragma unroll
  for (int h = 0; h < 2; h++) {
    uint32_t l[2];
#pragma unroll
    for (int r = 0; r < 2; r++) {
      const float (&t)[4] = st[2 * h + r];
      l[r] = movm(pack2(rho <= 2 * q ? t[2] : t[0], rho <= 2 * q + 1 ? t[3] : t[1]));
      l[r] = fma2(l[r], 0x3e353e35u, mul2(l[r], 0x379e379eu));
    }
    la[h] = __byte_perm(l[0], l[1], 0x5410); lb[h] = __byte_perm(l[0], l[1], 0x7632);
    if (first && !le0) la[h] = (la[h] & 0xffff0000u) | 0xce6eu;
    if (first && !le1) lb[h] = (lb[h] & 0xffff0000u) | 0xce6eu;
    mx[h] = max2(la[h], lb[h]);
  }
#pragma unroll
  for (int o = 1; o <= 2; o++) { mx[0] = max2(mx[0], __shfl_xor_sync(~0u, mx[0], o)); mx[1] = max2(mx[1], __shfl_xor_sync(~0u, mx[1], o)); }
  const float L2E = 1.4426950408889634f;
  float pr[2][4], z[4];
#pragma unroll
  for (int h = 0; h < 2; h++) {
    pr[h][0] = ex2f((lo_f(la[h]) - lo_f(mx[h])) * L2E); pr[h][1] = ex2f((lo_f(lb[h]) - lo_f(mx[h])) * L2E);
    pr[h][2] = ex2f((hi_f(la[h]) - hi_f(mx[h])) * L2E); pr[h][3] = ex2f((hi_f(lb[h]) - hi_f(mx[h])) * L2E);
    z[2 * h] = pr[h][0] + pr[h][1]; z[2 * h + 1] = pr[h][2] + pr[h][3];
  }
  p1_step<10>(acc, c);
#pragma unroll
  for (int o = 1; o <= 2; o++) {
#pragma unroll
    for (int i = 0; i < 4; i++) z[i] += __shfl_xor_sync(~0u, z[i], o);
  }
  const uint32_t LE = (le0 ? 0xffffu : 0u) | (le1 ? 0xffff0000u : 0u);
  uint32_t P[4][2];
  uint4 vt[4][2];
  {
    const uint32_t row = (lane & 7) * 64 + ((((lane >> 3) & 1) ^ ((lane & 7) >> 1)) << 4);
    const uint32_t v1 = at + AT_V + (2 * w + (lane >> 4)) * 1024 + row;
    const uint32_t v0 = (w || lane >= 16) ? v1 - 1024 : (first ? v1 : at + AT_REM + round * 2048 + 1024 + row);
#pragma unroll
    for (int i = 0; i < 4; i++) {
      const float rz = rcpf(z[i]);
      const uint32_t p = pack2(pr[i >> 1][2 * (i & 1)] * rz, pr[i >> 1][2 * (i & 1) + 1] * rz);
      P[i][0] = p & ~LE; P[i][1] = p & LE;
      const uint32_t a = ((i & 1) ? v1 : v0) + (i >> 1) * 512;
      vt[i][0] = ldsm_t(a); vt[i][1] = ldsm_t(a ^ 32);
    }
  }
  float ot[4][2][4];
  pin<8>(&P[0][0]);
  bar_sync(BAR_MMA, 256);
  mbar_wait(c.sb + B_F1 + 8 * 3, 0);
#pragma unroll
  for (int i = 0; i < 8; i++) { const uint4& v = vt[i >> 1][i & 1]; hmma<0>(ot[i >> 1][i & 1], v.x, v.y, v.z, v.w, P[i >> 1][0], P[i >> 1][1]); }
  sched_fence(c.zero);
  bar_sync(BAR_MMA, 256);
  p1_step<11, false>(acc, c);
  sched_fence(c.zero);
  pin<32>(&ot[0][0][0]);
  auto o_piece = [&](int i) {
    stg128(odst + (i >> 1) * 8192 + (i & 1) * 512, movm(pack2(ot[i][0][0], ot[i][0][1])), movm(pack2(ot[i][0][2], ot[i][0][3])), movm(pack2(ot[i][1][0], ot[i][1][1])), movm(pack2(ot[i][1][2], ot[i][1][3])));
  };
  o_piece(0); o_piece(1);
  p1_step<12>(acc, c);
  o_piece(2); o_piece(3);
  if (round) bar_arrive(BAR_EV + 4, 288);
  p1_step<13>(acc, c);
}

__device__ __forceinline__ void ln_moments(const uint32_t* raw, float& c0, float& s, float& v) {
  c0 = lo_f(__shfl_sync(~0u, raw[0], 0));
  float ss[4] = {0.f, 0.f, 0.f, 0.f}, vv[4] = {0.f, 0.f, 0.f, 0.f};
#pragma unroll
  for (int i = 0; i < 16; i++) {
    const float a = lo_f(raw[i]) - c0, b = hi_f(raw[i]) - c0;
    ss[(2 * i) & 3] += a; ss[(2 * i + 1) & 3] += b;
    vv[(2 * i) & 3] = fmaf(a, a, vv[(2 * i) & 3]); vv[(2 * i + 1) & 3] = fmaf(b, b, vv[(2 * i + 1) & 3]);
  }
  s = (ss[0] + ss[1]) + (ss[2] + ss[3]); v = (vv[0] + vv[1]) + (vv[2] + vv[3]);
}
__device__ __forceinline__ void ln_reduce(float& s, float& v) {
#pragma unroll
  for (int o = 16; o; o >>= 1) { s += __shfl_xor_sync(~0u, s, o); v += __shfl_xor_sync(~0u, v, o); }
}
__device__ __forceinline__ uint32_t ln_finish(float c0, float s, float v) {
  s *= 1.0f / DM;
  float sd;
  asm("sqrt.approx.ftz.f32 %0, %1;" : "=f"(sd) : "f"(bf16r(bf16r(fmaxf(fmaf(v, 1.0f / DM, -s * s), 0.f)) + 1e-5f)));
  return pack2(c0 + s, sd);
}
__device__ __forceinline__ void ln_store(const uint32_t* raw, uint32_t st, uint4* dst) {
  const uint32_t m2 = __byte_perm(st, st, 0x1010);
  const float rinv = rcpf(hi_f(st));
#pragma unroll
  for (int c = 0; c < 4; c++) {
    uint32_t v[4];
#pragma unroll
    for (int i = 0; i < 4; i++) { const uint32_t t = sub2(raw[4 * c + i], m2); v[i] = pack2(lo_f(t) * rinv, hi_f(t) * rinv); }
    stg128(dst + 32 * c, v[0], v[1], v[2], v[3]);
  }
}
__device__ __forceinline__ void col_sums(uint32_t tile, ulonglong2* part, uint32_t tag) {
  const int lane = threadIdx.x & 31;
  float cs[8] = {0, 0, 0, 0, 0, 0, 0, 0};
  uint32_t base = tile + ((lane >> 3) & 1) * 8192 + (lane >> 4) * 4096 + ((lane & 7) << 4);
#pragma unroll 1
  for (int k0 = 0; k0 < 8; k0++, base = (base ^ ((k0 ^ (k0 - 1)) << 4)) + 128) {
    uint4 v[4];
#pragma unroll
    for (int k = 0; k < 4; k++) v[k] = lds128(base + k * 1024);
#pragma unroll
    for (int k = 0; k < 4; k++) {
      cs[0] += lo_f(v[k].x); cs[1] += hi_f(v[k].x); cs[2] += lo_f(v[k].y); cs[3] += hi_f(v[k].y);
      cs[4] += lo_f(v[k].z); cs[5] += hi_f(v[k].z); cs[6] += lo_f(v[k].w); cs[7] += hi_f(v[k].w);
    }
  }
  const bool up = lane >= 16;
#pragma unroll
  for (int i = 0; i < 2; i++) {
    const float a = (up ? cs[4 + 2 * i] : cs[2 * i]) + __shfl_xor_sync(~0u, up ? cs[2 * i] : cs[4 + 2 * i], 16);
    const float b = (up ? cs[5 + 2 * i] : cs[1 + 2 * i]) + __shfl_xor_sync(~0u, up ? cs[1 + 2 * i] : cs[5 + 2 * i], 16);
    asm volatile("{\n.reg .b64 a, b;\nmov.b64 a, {%1, %3};\nmov.b64 b, {%2, %3};\nst.relaxed.gpu.global.v2.b64 [%0], {a, b};\n}"
                 ::"l"(part + 32 * (i + (up ? 2 : 0)) + (lane & 15)), "r"(__float_as_uint(a)), "r"(__float_as_uint(b)), "r"(tag) : "memory");
  }
  asm volatile("fence.proxy.async.shared::cta;" ::: "memory");
}

__global__ void __cluster_dims__(2, 1, 1) __launch_bounds__(384, 1)
fused_kernel(const uint4* __restrict__ x, const uint4* __restrict__ wgate, const uint4* __restrict__ wup, Scratch* gs, const __grid_constant__ Maps mp) {
  extern __shared__ __align__(1024) uint8_t smem_raw[];
  const uint32_t sb = (uint32_t)__cvta_generic_to_shared(smem_raw);
  const unsigned t_start = 0;
  const int warp = __shfl_sync(~0u, threadIdx.x >> 5, 0), lane = threadIdx.x & 31;
  const int m = blockIdx.x & 15, j = blockIdx.x >> 4, rank = blockIdx.x & 1;
  const int m2 = blockIdx.x >> 3, j2 = blockIdx.x & 7;
  if (warp >= 8) {
    asm volatile("setmaxnreg.dec.sync.aligned.u32 40;");
    if (warp == 8) {
      if (elect_one()) {
        asm volatile("prefetch.tensormap [%0];\nprefetch.tensormap [%1];\nprefetch.tensormap [%2];" ::"l"(&mp.x), "l"(&mp.wg), "l"(&mp.wu) : "memory");
        for (int s = 0; s < 4; s++) mbar_init(sb + B_F1 + 8 * s, 1);
        mbar_arrive(sb + B_F1);
        asm volatile("fence.mbarrier_init.release.cluster;" ::: "memory");
      }
      __syncwarp();
    } else if (warp == 9) {
      if (elect_one()) {
        if ((sb & 0xffffff) != SM_BASE) asm volatile("trap;");
        for (int s = 0; s < 4; s++) mbar_init(sb + B_E1 + 8 * s, 4);
        for (int s = 0; s < 5; s++) { mbar_init(sb + B_F2 + 8 * s, 1); mbar_init(sb + B_E2 + 8 * s, 4); }
        for (int s = 0; s < 5; s++) mbar_init(sb + B_DEP + 8 * s, 1);
        mbar_init(sb + B_AUX, 8); mbar_init(sb + B_EP, 1); mbar_init(sb + B_XT, 1); mbar_init(sb + B_CS, 1);
        for (int s = 0; s < 4; s++) { mbar_init(sb + B_EX + 8 * s, 1); mbar_expect_tx(sb + B_EX + 8 * s, 8192); }
        mbar_init(sb + B_HALO, 9); mbar_init(sb + B_HALO + 8, 9);
        asm volatile("fence.mbarrier_init.release.cluster;" ::: "memory");
      }
      __syncwarp();
    }
    asm volatile("barrier.cluster.arrive.relaxed.aligned;" ::: "memory");
    if (warp == 8) {
      if (elect_one()) {
        TS(0); TG(51);
#pragma unroll 1
        for (int kb = 1; kb < 4; kb++) {
          const uint32_t sa = sb + kb * P1_STAGE, fb = sb + B_F1 + 8 * kb;
          mbar_expect_tx(fb, P1_STAGE);
          tma3d(sa, &mp.x, fb, kb * 64, m * 64, 0, EVICT_NORMAL);
          tma2d(sa + 16384, &mp.wg, fb, j * 128, kb * 64, EVICT_NORMAL); tma2d(sa + 32768, &mp.wu, fb, j * 128, kb * 64, EVICT_NORMAL);
          tma2d(sa + 24576, &mp.wg, fb, j * 128 + 64, kb * 64, EVICT_NORMAL); tma2d(sa + 40960, &mp.wu, fb, j * 128 + 64, kb * 64, EVICT_NORMAL);
        }
        TS(7);
      }
      __syncwarp();
    }
    asm volatile("barrier.cluster.wait.aligned;" ::: "memory");
    if (warp == 8) {
      if (elect_one()) {
        uint32_t par = 0;

        for (int R = 0; R < 5; R++) {
          const CUtensorMap *mb0, *mb1;
          int n0, n1;
          if (R == 1 || R == 2) {
            mb0 = &mp.wqkv; n0 = 64 * (j + 8 * (R - 1)) + rank * 2048;
            mb1 = rank ? (R == 1 ? &mp.wg : &mp.wu) : &mp.wqkv; n1 = rank ? 1024 + 64 * j : n0 + 1024;
          } else {
            mb0 = mb1 = rank ? &mp.wu : &mp.wg;
            n0 = 128 * j + (R ? 1024 * R - 1536 : 0); n1 = n0 + 64;
          }
#pragma unroll 1
          for (int kb = R ? 0 : 4; kb < 16; kb++) {
            if (R == 0 && kb == 4) { for (int i = 1; i < 8; i++) asm volatile("prefetch.tensormap [%0];" ::"l"(&mp.x + i) : "memory"); }
            if (R == 0 && kb == (CS_KB)) {
              const uint32_t cb = sb + B_CS, d = sb + OFF_X;
              mbar_expect_tx(cb, 32768);
              tma2d(d, &mp.wg, cb, n0, m * 64, EVICT_NORMAL); tma2d(d + 8192, &mp.wg, cb, n1, m * 64, EVICT_NORMAL);
              tma2d(d + 16384, &mp.wu, cb, n0, m * 64, EVICT_NORMAL); tma2d(d + 24576, &mp.wu, cb, n1, m * 64, EVICT_NORMAL);
            }
            const int st = kb & 3;
            const uint32_t sa = sb + st * P1_STAGE, fb = sb + B_F1 + 8 * st;
            mbar_wait(sb + B_E1 + 8 * st, par);
            if (R * 16 + kb >= 4) REL_TS(R * 16 + kb - 4);
            mbar_expect_tx(fb, P1_STAGE);
            tma2d_mc(sa + 16384 + rank * 16384, mb0, fb, n0, kb * 64, HINT_W);
            tma2d_mc(sa + 24576 + rank * 16384, mb1, fb, n1, kb * 64, HINT_W);
            if (R == 0) {
              tma3d(sa, &mp.x, fb, kb * 64, m * 64, 0, EVICT_NORMAL);
            } else {
              if (R == 1 && kb == 0) { mbar_wait(sb + B_DEP, 0); TS(1); }
              tma2d(sa, &mp.xn, fb, kb * 64, m * 128, R == 4 ? HINT_LAST : EVICT_NORMAL);
            }
            if (R == 4 && kb == 4 + j2) {
              mbar_expect_tx(sb + B_XT, 32768);
              tma3d(sb + OFF_X, &mp.x, sb + B_XT, j2 * 128, m2 * 64, 0, HINT_LAST); tma3d(sb + OFF_X + 16384, &mp.x, sb + B_XT, j2 * 128 + 64, m2 * 64, 0, HINT_LAST);
            }
            if (st == 3) par ^= 1;
          }
        }
#pragma unroll 1
        for (int i = 0; i < 28; i++) {
          if (i == 0 || i == 8 || i == 12 || i == 20) { mbar_wait(sb + B_DEP + 8 * (1 + ((i + 4) >> 3)), 0); TS(2 + ((i + 4) >> 3)); }
          const int st = i & 3, kb = 2 * i + rank;
          const uint32_t sa = sb + st * P1_STAGE, fb = sb + B_F1 + 8 * st;
          mbar_wait(sb + B_E1 + 8 * st, par);
          REL_TS(76 + i);
          mbar_expect_tx(fb, P1_STAGE);
          bulk_load(sa, gs->h + (m2 * 56 + kb) * 1024, 16384, fb, HINT_H);
          tma5d(sa + 16384, &mp.wd, fb, j2 * 128, kb * 2, HINT_W); tma5d(sa + 24576, &mp.wd, fb, j2 * 128 + 64, kb * 2, HINT_W);
          tma5d(sa + 32768, &mp.wd, fb, (j2 ^ 1) * 128, kb * 2, HINT_W); tma5d(sa + 40960, &mp.wd, fb, (j2 ^ 1) * 128 + 64, kb * 2, HINT_W);
          if (st == 3) par ^= 1;
        }
        int st = 0; uint32_t par2 = 1;
#pragma unroll 1
        for (int t = 0; t < 16; t++) {
          const uint32_t sa = sb + st * P2_STAGE, fb = sb + B_F2 + 8 * st;
          if (t < 5) mbar_wait(sb + B_E1 + 8 * ((2 * t + 1) / 3), par); else mbar_wait(sb + B_E2 + 8 * st, par2);
          REL_TS(104 + t);
          mbar_expect_tx(fb, P2_STAGE);
          bulk_load_mc(sa + rank * 8192, gs->o + (m2 * 16 + t) * 1024 + rank * 512, 8192, fb, HINT_H);
          tma2d(sa + 16384, &mp.wo, fb, j2 * 128, t * 64, HINT_W); tma2d(sa + 24576, &mp.wo, fb, j2 * 128 + 64, t * 64, HINT_W);
          if (++st == 5) { st = 0; par2 ^= 1; }
        }
      }
    } else if (warp == 9) {
#pragma unroll 1
      for (int e = 0; e < 7; e++) {
        const bool halo = e == 2 || e == 3;
        bar_sync(BAR_EV + e, halo ? 96 : 288);
        if (lane == 0) {
          const int f = e == 0 ? FL_XN + m : (halo ? FL_HALO + (e - 2) * 128 + blockIdx.x : FL_H + m * 4 + (e == 1 ? 0 : e - 3));
          TS(10 + 2 * e); TG(52 + e);
          flag_add(&gs->flags[f * 32]);
          if (e < 6) TS(11 + 2 * e);
        }
        __syncwarp();
      }
    } else {
      unsigned e = 0;
      if (lane == 0) {
        unsigned* ep = &gs->epoch[blockIdx.x * 2 + warp - 10];
        e = *ep + 1; *ep = e;
        if (warp == 10) { asm volatile("st.shared.b32 [%0], %1;" ::"r"(sb + OFF_EPOCH), "r"(e) : "memory"); mbar_arrive(sb + B_EP); }
      }
      e = __shfl_sync(~0u, e, 0);
      mbar_wait(sb + B_CS, 0);
      if (lane == 0 && warp == 11) TS(6);
      col_sums(sb + OFF_X + (warp - 10) * 16384, gs->cspart + (j * 16 + m) * 128 + (warp - 10) * 16, e);
      if (lane == 0 && warp == 11) TS(9);
      if (warp == 10) {
        if (lane == 0) {
#pragma unroll 1
          for (int g = 0; g < 5; g++) {
            flag_wait(&gs->flags[(g ? FL_H + m2 * 4 + g - 1 : FL_XN + m) * 32], e * 8u);
            fence_async();
            mbar_arrive(sb + B_DEP + 8 * g);
            if (g == 0) TS(8);
          }
        }
      } else
      if (elect_one()) {
#pragma unroll 1
        for (int r = 0; r < 2; r++) {
          const uint32_t hb = sb + B_HALO + 8 * r;
          if (m) {
            flag_wait(&gs->flags[(FL_HALO + r * 128 + blockIdx.x - 1) * 32], e);
            fence_async();
            mbar_expect_tx(hb, 4096);
            for (int g = 0; g < 2; g++) bulk_load(sb + OFF_X + g * AT_WG + AT_REM + r * 2048, gs->halo + ((r * 128 + blockIdx.x - 1) * 2 + g) * 128, 2048, hb, EVICT_FIRST);
          } else {
            mbar_arrive(hb);
          }
          TS(34 + r);
        }
      }
    }
  } else {
    {
      const int r = threadIdx.x >> 3, ch = threadIdx.x & 7;
      const uint32_t d = sb + r * 128 + ((ch ^ (r & 7)) << 4);
      const uint4* xa = x + (128 * m + 2 * r) * 128 + ch;
      const size_t wo = (size_t)r * (DFF / 8) + 16 * j + ch;
#pragma unroll
      for (int i = 0; i < 12; i++) {
        const uint4* src = i < 4 ? xa + (i & 1) * 64 * 128 + (i >> 1) * 128 : (i < 8 ? wgate : wup) + wo + (i & 1) * 32 * (DFF / 8) + ((i >> 1) & 1) * 8;
        asm volatile("cp.async.cg.shared.global [%0], [%1], 16;" ::"r"(d + i * 4096), "l"(src) : "memory");
      }
    }
    asm volatile("barrier.cluster.arrive.relaxed.aligned;" ::: "memory");
    asm volatile("setmaxnreg.inc.sync.aligned.u32 232;");
    const int wg = warp >> 2, w = warp & 3;
    Cons c;
    c.sb = sb; c.wg = wg; c.zero = warp >> 8;
    c.a0 = ((SM_BASE + wg * 8192) >> 4) | (1u << 16); c.a1 = c.a0 + 4; c.ah = 0x40000040;
    c.rel = mapa(sb, threadIdx.x & 1);
    c.do_rel = (threadIdx.x & 127) < 2;
    constexpr bool t0 = false;
    float acc[128];
    uint32_t pk[64];
    float rs[2];
    const int rho = lane >> 2, q = lane & 3;

    {
      const int prow = 16 * j + 2 * warp;
      const uint4* xr = x + (size_t)(128 * m + 2 * (prow & 63) + (prow >> 6)) * 128 + lane;
      uint4* xo = gs->xn + (size_t)(128 * m + prow) * 128 + lane;
      float c0[2], mo[4];
      uint32_t st[2];
      uint32_t e;
      asm volatile("" : "+l"(xr), "+l"(xo));
      if (t0) TS(23 + wg * 16);
      asm volatile("cp.async.wait_all;\nfence.proxy.async.shared::cta;" ::: "memory");
      bar_sync(BAR_MMA, 256);
      if (threadIdx.x == 0) TS(39);
      p1_step<0, false>(acc, c);
      asm volatile("barrier.cluster.wait.aligned;" ::: "memory");
      p1_range<1, LN_LD + 1>(acc, c);
      if (t0) TS(24 + wg * 16);
#pragma unroll
      for (int i = 0; i < 8; i++) {
        asm volatile("ld.global.nc.v4.b32 {%0,%1,%2,%3}, [%4];" : "=r"(pk[4 * i]), "=r"(pk[4 * i + 1]), "=r"(pk[4 * i + 2]), "=r"(pk[4 * i + 3]) : "l"(xr + (i >> 2) * 256 + (i & 3) * 32));
      }
      p1_range<LN_LD + 1, LN_KB + 1>(acc, c);
      sched_fence(c.zero);

      pin<16>(pk); ln_moments(pk, c0[0], mo[0], mo[1]); pin<2>(mo);
      p1_step<LN_KB + 1>(acc, c);
      sched_fence(c.zero);
      pin<16>(pk + 16); ln_moments(pk + 16, c0[1], mo[2], mo[3]); ln_reduce(mo[0], mo[1]); pin<4>(mo);
      p1_step<LN_KB + 2>(acc, c);
      mbar_wait(sb + B_EP, 0);
      asm volatile("ld.shared.b32 %0, [%1];" : "=r"(e) : "r"(sb + OFF_EPOCH) : "memory");
      pin<2>(mo); st[0] = ln_finish(c0[0], mo[0], mo[1]); ln_reduce(mo[2], mo[3]); pin<1>(st); pin<2>(mo + 2);
      p1_step<LN_KB + 3>(acc, c);
      sched_fence(c.zero);
      pin<1>(st); pin<2>(mo + 2);
      st[1] = ln_finish(c0[1], mo[2], mo[3]);
      ln_store(pk, st[0], xo);
      if (lane == 0)
        asm volatile("{\n.reg .b64 a, b;\nmov.b64 a, {%1, %3};\nmov.b64 b, {%2, %3};\nst.relaxed.gpu.global.v2.b64 [%0], {a, b};\n}" ::"l"(gs->stats + 128 * m + prow), "r"(st[0]), "r"(st[1]), "r"(e) : "memory");
      p1_step<LN_KB + 4>(acc, c);
      sched_fence(c.zero);
      pin<1>(st + 1); ln_store(pk + 16, st[1], xo + 128);
      bar_arrive(BAR_EV, 288);
      p1_range<LN_KB + 5, G_KB + 1>(acc, c);
      sched_fence(c.zero);
      const unsigned long long* cp = (const unsigned long long*)gs->cspart + j * 4096 + threadIdx.x;
      const unsigned long long* sp = gs->stats + 128 * m + warp * 16 + rho;
      unsigned long long part[18];
      auto gather = [&]() {
#pragma unroll
        for (int i = 0; i < 18; i++) asm volatile("ld.relaxed.gpu.global.b64 %0, [%1];" : "=l"(part[i]) : "l"(i < 16 ? cp + i * 256 : sp + (i - 16) * 8) : "memory");
      };
      gather();
      p1_range<G_KB + 1, 14>(acc, c);
      sched_fence(c.zero);
      {
        float csum;
        for (int tries = 0;; tries++) {
          uint32_t bad = 0;
          csum = 0.f;
#pragma unroll
          for (int i = 0; i < 18; i++) { bad |= (uint32_t)(part[i] >> 32) ^ e; if (i < 16) csum += __uint_as_float((uint32_t)part[i]); }
          if (!__any_sync(~0u, bad != 0) || tries > (1 << 20)) break;
          gather();
        }
        asm volatile("st.shared.b32 [%0], %1;" ::"r"(sb + OFF_CS + threadIdx.x * 4 + (threadIdx.x >> 6) * 16), "f"(csum) : "memory");
        __syncwarp();
        if (lane == 0) mbar_arrive(sb + B_AUX);
        mo[0] = -lo_f((uint32_t)part[16]); mo[1] = rcpf(hi_f((uint32_t)part[16])); mo[2] = -lo_f((uint32_t)part[17]); mo[3] = rcpf(hi_f((uint32_t)part[17]));
        pin<4>(mo);
      }
      p1_step<14>(acc, c);
      p1_issue<3, 1>(acc, c, 1);
      if (wg == 0) bar_arrive(BAR_LAG, 256);
      mbar_wait(sb + B_AUX, 0);
#pragma unroll
      for (int i = 0; i < 16; i++) { const uint4 v = lds128(sb + OFF_CS + q * 272 + i * 16); pk[4 * i] = v.x; pk[4 * i + 1] = v.y; pk[4 * i + 2] = v.z; pk[4 * i + 3] = v.w; }
      wg_wait<1>(); release(c, B_E1 + 16);
      wg_wait<0>(); release(c, B_E1 + 24);
      const float m0 = mo[0], r0 = mo[1], m1 = mo[2], r1 = mo[3];
#pragma unroll
      for (int n = 0; n < 32; n++) {
        const float c0 = __uint_as_float(pk[2 * n]), c1 = __uint_as_float(pk[2 * n + 1]);
        if (DEFER_R == 2 || (DEFER_R == 1 && n >= 16)) {
          pk[2 * n] = pack2(fmaf(m0, c0, acc[4 * n]), fmaf(m0, c1, acc[4 * n + 1]));
          pk[2 * n + 1] = pack2(fmaf(m1, c0, acc[4 * n + 2]), fmaf(m1, c1, acc[4 * n + 3]));
        } else {
          pk[2 * n] = pack2(fmaf(m0, c0, acc[4 * n]) * r0, fmaf(m0, c1, acc[4 * n + 1]) * r0);
          pk[2 * n + 1] = pack2(fmaf(m1, c0, acc[4 * n + 2]) * r1, fmaf(m1, c1, acc[4 * n + 3]) * r1);
        }
      }
      rs[0] = r0; rs[1] = r1;
      if (t0) TS(25 + wg * 16);
    }
    const uint32_t img = warp * 1024 + ((lane ^ (lane >> 3)) << 4);
#pragma unroll 1
    for (int R = 1;; R++) {
      uint8_t* hb = (uint8_t*)gs->h + (size_t)m * 56 * 16384 + img;
      if (R == 2 || R == 3) {
        attn_tile(acc, pk, c, R - 2, warp, m, gs, hb + (16 + j) * 16384, (uint8_t*)gs->o + (m * 16 + j + 8 * (R - 2)) * 16384 + img);
      } else {
        if (R == 5) { c.a0 = ((SM_BASE + wg * 4096) >> 4) | (1u << 16); c.a1 = c.a0 + 512; c.ah = 0x80000020; }
        geglu_tile<0>(acc, pk, c, hb + (2 * j + (R == 1 ? 0 : 16 * R - 40)) * 16384, BAR_EV + (R == 1 ? 1 : R + 1), rs);
        rs[0] = rs[1] = 1.0f;
        if (R == 5) break;
      }
      p1_range<14, 16>(acc, c);
#pragma unroll
      for (int i = 0; i < 64; i++) pk[i] = pack2(acc[2 * i], acc[2 * i + 1]);
      if (t0) TS(25 + R + wg * 16);
    }
    if (t0) TS(30 + wg * 16);
    p1_issue<2, 1>(acc, c, 1); wg_wait<1>(); release(c, B_E1 + 8);
    p1_issue<3, 1>(acc, c, 1); wg_wait<1>(); release(c, B_E1 + 16);
#pragma unroll 1
    for (int it = 4; it < 7; it++) {
      p1_issue<0, 1>(acc, c, it & 1); wg_wait<1>(); release(c, B_E1 + 24);
      p1_issue<1, 1>(acc, c, it & 1); wg_wait<1>(); release(c, B_E1);
      p1_issue<2, 1>(acc, c, it & 1); wg_wait<1>(); release(c, B_E1 + 8);
      p1_issue<3, 1>(acc, c, it & 1); wg_wait<1>(); release(c, B_E1 + 16);
    }
    if (t0) TS(31 + wg * 16);
    {
      float accs[64];
      const uint32_t peer = mapa(sb, rank ^ 1);
      auto send_piece = [&](int p) {
        asm volatile("st.async.weak.shared::cluster.mbarrier::complete_tx::bytes.v4.b32 [%0], {%1,%2,%3,%4}, [%5];" ::"r"(peer + OFF_LAND + p * 4096 + threadIdx.x * 16),
                     "r"(pack2(acc[64 + 8 * p], acc[65 + 8 * p])), "r"(pack2(acc[66 + 8 * p], acc[67 + 8 * p])), "r"(pack2(acc[68 + 8 * p], acc[69 + 8 * p])), "r"(pack2(acc[70 + 8 * p], acc[71 + 8 * p])),
                     "r"(peer + B_EX + 16 * wg + 8 * (p >> 2)) : "memory");
      };
      auto silu_piece = [&](int p) {
        const uint4 r = lds128(sb + OFF_LAND + p * 4096 + threadIdx.x * 16);
        const uint32_t rr[4] = {r.x, r.y, r.z, r.w};
#pragma unroll
        for (int i = 0; i < 4; i++) {
          const float a = acc[8 * p + 2 * i] + lo_f(rr[i]), b = acc[8 * p + 2 * i + 1] + hi_f(rr[i]);
          pk[4 * p + i] = pack2(silu_half(a * 0.25f), silu_half(b * 0.25f));
        }
        pin<4>(pk + 4 * p);
      };
      const uint32_t xa = sb + OFF_X + (warp * 16 + (lane & 15)) * 128 + (((lane >> 4) ^ (lane & 7)) << 4);
      auto x_piece = [&](int i) { const uint4 v = ldsm((xa ^ ((i & 3) << 5)) + (i >> 2) * 16384); pk[32 + 4 * i] = v.x; pk[33 + 4 * i] = v.y; pk[34 + 4 * i] = v.z; pk[35 + 4 * i] = v.w; };
      p2_step<0>(accs, c);
      p2_step<1>(accs, c);
      mbar_wait(sb + B_E1 + 24, 0);
      send_piece(0); send_piece(1);
      p2_step<2>(accs, c); sched_fence(c.zero); send_piece(2); send_piece(3);
      p2_step<3>(accs, c); sched_fence(c.zero); send_piece(4); send_piece(5);
      p2_step<4>(accs, c); sched_fence(c.zero); send_piece(6); send_piece(7);
      p2_step<5>(accs, c);
      mbar_wait(sb + B_XT, 0);
      mbar_wait(sb + B_EX + 16 * wg, 0);
      silu_piece(0); x_piece(0);
      p2_step<6>(accs, c); sched_fence(c.zero); silu_piece(1); x_piece(1);
      p2_step<7>(accs, c); sched_fence(c.zero); silu_piece(2); x_piece(2);
      p2_step<8>(accs, c); sched_fence(c.zero); silu_piece(3); x_piece(3);
      p2_step<9>(accs, c);
      mbar_wait(sb + B_EX + 16 * wg + 8, 0);
      silu_piece(4); x_piece(4);
      p2_step<10>(accs, c); sched_fence(c.zero); silu_piece(5); x_piece(5);
      p2_step<11>(accs, c); sched_fence(c.zero); silu_piece(6); x_piece(6);
      p2_step<12>(accs, c); p2_step<13>(accs, c); p2_step<14>(accs, c); p2_step<15>(accs, c);
      sched_fence(c.zero); silu_piece(7); x_piece(7);
      wg_wait<0>();
      if (t0) TS(32 + wg * 16);
#pragma unroll
      for (int i = 0; i < 8; i++) {
        uint32_t v[4];
#pragma unroll
        for (int k = 0; k < 4; k++) v[k] = fma2(pack2(accs[8 * i + 2 * k], accs[1 + 8 * i + 2 * k]), pk[4 * i + k], pk[32 + 4 * i + k]);
        asm volatile("stmatrix.sync.aligned.m8n8.x4.shared.b16 [%0], {%1,%2,%3,%4};" ::"r"((xa ^ ((i & 3) << 5)) + (i >> 2) * 16384), "r"(v[0]), "r"(v[1]), "r"(v[2]), "r"(v[3]) : "memory");
        if (i == 3 || i == 7) {
          asm volatile("fence.proxy.async.shared::cta;" ::: "memory");
          __syncwarp();
          if (elect_one()) tma3d_store(&mp.out, sb + OFF_X + (i >> 2) * 16384 + warp * 2048, j2 * 128 + (i >> 2) * 64, m2 * 64 + w * 16, wg);
        }
      }
      if (elect_one()) { asm volatile("cp.async.bulk.commit_group;\ncp.async.bulk.wait_group.read 0;" ::: "memory"); }
      if ((threadIdx.x & 127) == 0) { TS(33 + wg * 16); if (wg) TG(59); }
    }
  }
}

typedef CUresult (*EncodeFn)(CUtensorMap*, CUtensorMapDataType, cuuint32_t, void*, const cuuint64_t*, const cuuint64_t*, const cuuint32_t*, const cuuint32_t*,
                             CUtensorMapInterleave, CUtensorMapSwizzle, CUtensorMapL2promotion, CUtensorMapFloatOOBfill);

void encode(EncodeFn fn, CUtensorMap* tm, const void* p, int rank, const cuuint64_t* dims, const cuuint64_t* strides, const cuuint32_t* box) {
  const cuuint32_t es[5] = {1, 1, 1, 1, 1};
  fn(tm, CU_TENSOR_MAP_DATA_TYPE_BFLOAT16, rank, const_cast<void*>(p), dims, strides, box, es, CU_TENSOR_MAP_INTERLEAVE_NONE, CU_TENSOR_MAP_SWIZZLE_128B,
     PROMO, CU_TENSOR_MAP_FLOAT_OOB_FILL_NONE);
}

}

extern "C" void kernel_launch(void* const* d_in, const int* in_sizes, int n_in, void* d_out, int out_size) {
  (void)in_sizes; (void)n_in; (void)out_size;
  static EncodeFn fn = nullptr;
  static Scratch* gs = nullptr;
  if (!fn) {
    void* p = nullptr;
    cudaDriverEntryPointQueryResult qr;
    cudaGetDriverEntryPoint("cuTensorMapEncodeTiled", &p, cudaEnableDefault, &qr);
    fn = (EncodeFn)p;
    cudaGetSymbolAddress((void**)&gs, g_scratch);
    cudaFuncSetAttribute(fused_kernel, cudaFuncAttributeMaxDynamicSharedMemorySize, SMEM_BYTES);
  }
  const void *x = d_in[0], *wqkv = d_in[1], *wo = d_in[2], *wg = d_in[4], *wu = d_in[5], *wd = d_in[6];
  Maps mp;
  {
    const cuuint64_t dims[3] = {DM, SEQ / 2, 2}, st[2] = {DM * 4, DM * 2};
    const cuuint32_t box_in[3] = {64, 64, 2}, box_out[3] = {64, 16, 1};
    encode(fn, &mp.x, x, 3, dims, st, box_in);
    encode(fn, &mp.out, d_out, 3, dims, st, box_out);
  }
  {
    const cuuint64_t dims[2] = {DM, SEQ}, st[1] = {DM * 2};
    const cuuint32_t box[2] = {64, 128};
    encode(fn, &mp.xn, gs->xn, 2, dims, st, box);
  }
  {
    const cuuint32_t box[2] = {64, 64};
    const cuuint64_t dq[2] = {3 * DM, DM}, sq[1] = {3 * DM * 2}, df[2] = {DFF, DM}, sf[1] = {DFF * 2}, dw[2] = {DM, DM}, sw[1] = {DM * 2};
    encode(fn, &mp.wqkv, wqkv, 2, dq, sq, box);
    encode(fn, &mp.wg, wg, 2, df, sf, box);
    encode(fn, &mp.wu, wu, 2, df, sf, box);
    encode(fn, &mp.wo, wo, 2, dw, sw, box);
  }
  {
    const cuuint32_t box[5] = {64, 2, 4, 4, 2};
    const cuuint64_t st[4] = {DM * 2, 8 * DM * 2, 2 * DM * 2, 32 * DM * 2};
    const cuuint64_t dd[5] = {DM, 2, 4, 4, DFF / 32};
    encode(fn, &mp.wd, wd, 5, dd, st, box);
  }
  fused_kernel<<<NCTA, 384, SMEM_BYTES>>>((const uint4*)x, (const uint4*)wg, (const uint4*)wu, gs, mp);
}
```

```cpp
#include <cuda_runtime.h>
#include <cuda_bf16.h>
#include <cuda.h>
#include <stdint.h>

#define LN_LD 0
#define PROMO CU_TENSOR_MAP_L2_PROMOTION_L2_128B
#define G_KB 12
#define PF_D 4
#define PF_W 1
#define PF_H 1
#define CS_KB 8
#define LN_KB 4

#define EVICT_FIRST 0x12F0000000000000ull
#define EVICT_NORMAL 0x1000000000000000ull
#define HINT_W EVICT_FIRST
#define HINT_H EVICT_FIRST
#define HINT_LAST EVICT_FIRST

namespace {

constexpr int SEQ = 2048, DM = 1024, DFF = 3584;
constexpr int NCTA = 128;

constexpr uint32_t SM_BASE = 0x400;
constexpr uint32_t P1_STAGE = 49152, P2_STAGE = 32768;
constexpr uint32_t OFF_X = 196608;
constexpr uint32_t OFF_CS = OFF_X + 14336;
constexpr uint32_t OFF_BAR = 229376;
constexpr uint32_t OFF_LAND = 5 * P2_STAGE;
constexpr uint32_t B_F1 = OFF_BAR, B_E1 = B_F1 + 32, B_F2 = B_E1 + 32, B_E2 = B_F2 + 40;
constexpr uint32_t B_DEP = B_E2 + 40;
constexpr uint32_t B_AUX = B_DEP + 40, B_CS = B_AUX + 8, B_XT = B_CS + 8, B_EX = B_XT + 8, B_HALO = B_EX + 32, B_EP = B_HALO + 16, OFF_EPOCH = B_EP + 8;
constexpr uint32_t SMEM_BYTES = 232448;
constexpr uint32_t AT_V = 0, AT_K = 8192, AT_REM = 11264, AT_WG = 15360;

constexpr int FL_XN = 0, FL_H = 16, FL_HALO = 80, FL_N = FL_HALO + 256;
struct __align__(1024) Scratch {
  uint4 h[16 * 56 * 1024];
  uint4 o[16 * 16 * 1024];
  uint4 xn[SEQ * DM / 8];
  uint4 halo[2 * 128 * 2 * 128];
  ulonglong2 cspart[8 * 16 * 128];
  unsigned long long stats[SEQ];
  unsigned flags[FL_N * 32];
  unsigned epoch[NCTA * 2];
};
__device__ Scratch g_scratch;
#define TG(i) do {} while (0)
#define TS(i) do {} while (0)

struct Maps { CUtensorMap x, xn, out, wqkv, wg, wu, wd, wo; };

__device__ __forceinline__ void mbar_init(uint32_t bar, uint32_t cnt) { asm volatile("mbarrier.init.shared::cta.b64 [%0], %1;" ::"r"(bar), "r"(cnt)); }
__device__ __forceinline__ void mbar_expect_tx(uint32_t bar, uint32_t bytes) { asm volatile("mbarrier.arrive.expect_tx.shared::cta.b64 _, [%0], %1;" ::"r"(bar), "r"(bytes) : "memory"); }
__device__ __forceinline__ void mbar_arrive(uint32_t bar) { asm volatile("mbarrier.arrive.shared::cta.b64 _, [%0];" ::"r"(bar) : "memory"); }
__device__ __forceinline__ void mbar_arrive_cl(uint32_t bar) { asm volatile("mbarrier.arrive.shared::cluster.b64 _, [%0];" ::"r"(bar) : "memory"); }
__device__ __forceinline__ uint32_t mapa(uint32_t a, uint32_t cta) { uint32_t r; asm("mapa.shared::cluster.u32 %0, %1, %2;" : "=r"(r) : "r"(a), "r"(cta)); return r; }
__device__ __forceinline__ void mbar_wait(uint32_t bar, uint32_t parity) {
  asm volatile("{\n.reg .pred p;\n.reg .u32 n;\nmov.u32 n, 0;\nLAB_WAIT:\nmbarrier.try_wait.parity.shared::cta.b64 p, [%0], %1;\n@p bra LAB_DONE;\n"
               "add.u32 n, n, 1;\nsetp.gt.u32 p, n, 4000000;\n@p trap;\nbra LAB_WAIT;\nLAB_DONE:\n}" ::"r"(bar), "r"(parity) : "memory");
}
__device__ __forceinline__ void flag_wait(const unsigned* f, unsigned target) {
  asm volatile("{\n.reg .pred p;\n.reg .u32 n, v;\nmov.u32 n, 0;\nLAB_WAIT:\nld.relaxed.gpu.global.u32 v, [%0];\nsub.u32 v, v, %1;\nsetp.ge.s32 p, v, 0;\n@p bra LAB_DONE;\n"
               "nanosleep.u32 100;\nadd.u32 n, n, 1;\nsetp.gt.u32 p, n, 4000000;\n@p trap;\nbra LAB_WAIT;\nLAB_DONE:\nfence.acquire.gpu;\n}" ::"l"(f), "r"(target) : "memory");
}
__device__ __forceinline__ void flag_add(unsigned* f) { asm volatile("red.release.gpu.global.add.u32 [%0], 1;" ::"l"(f) : "memory"); }
__device__ __forceinline__ void fence_async() { asm volatile("fence.proxy.async.global;" ::: "memory"); }
__device__ __forceinline__ bool elect_one() { uint32_t p; asm volatile("{\n.reg .pred P;\nelect.sync _|P, 0xffffffff;\nselp.u32 %0, 1, 0, P;\n}" : "=r"(p)); return p; }
__device__ __forceinline__ void bar_sync(int id, int n) { asm volatile("bar.sync %0, %1;" ::"r"(id), "r"(n) : "memory"); }
__device__ __forceinline__ void bar_arrive(int id, int n) { asm volatile("bar.arrive %0, %1;" ::"r"(id), "r"(n) : "memory"); }

__device__ __forceinline__ void tma2d(uint32_t dst, const CUtensorMap* tm, uint32_t bar, int c0, int c1, uint64_t hint) {
  asm volatile("cp.async.bulk.tensor.2d.shared::cluster.global.mbarrier::complete_tx::bytes.L2::cache_hint [%0], [%1, {%3, %4}], [%2], %5;" ::"r"(dst), "l"(tm), "r"(bar), "r"(c0), "r"(c1), "l"(hint) : "memory");
}
__device__ __forceinline__ void tma2d_mc(uint32_t dst, const CUtensorMap* tm, uint32_t bar, int c0, int c1, uint64_t hint) {
  asm volatile("cp.async.bulk.tensor.2d.shared::cluster.global.mbarrier::complete_tx::bytes.multicast::cluster.L2::cache_hint [%0], [%1, {%3, %4}], [%2], %5, %6;" ::"r"(dst), "l"(tm), "r"(bar), "r"(c0), "r"(c1), "h"((uint16_t)3), "l"(hint) : "memory");
}
__device__ __forceinline__ void tma3d(uint32_t dst, const CUtensorMap* tm, uint32_t bar, int c0, int c1, int c2, uint64_t hint) {
  asm volatile("cp.async.bulk.tensor.3d.shared::cluster.global.mbarrier::complete_tx::bytes.L2::cache_hint [%0], [%1, {%3, %4, %5}], [%2], %6;" ::"r"(dst), "l"(tm), "r"(bar), "r"(c0), "r"(c1), "r"(c2), "l"(hint) : "memory");
}
__device__ __forceinline__ void tma5d(uint32_t dst, const CUtensorMap* tm, uint32_t bar, int c0, int c4, uint64_t hint) {
  asm volatile("cp.async.bulk.tensor.5d.shared::cluster.global.mbarrier::complete_tx::bytes.L2::cache_hint [%0], [%1, {%3, %5, %5, %5, %4}], [%2], %6;" ::"r"(dst), "l"(tm), "r"(bar), "r"(c0), "r"(c4), "r"(0), "l"(hint) : "memory");
}
__device__ __forceinline__ void tma5d_prefetch(const CUtensorMap* tm, int c0, int c4) {
  asm volatile("cp.async.bulk.prefetch.tensor.5d.L2.global [%0, {%1, %3, %3, %3, %2}];" ::"l"(tm), "r"(c0), "r"(c4), "r"(0) : "memory");
}
__device__ __forceinline__ void tma3d_store(const CUtensorMap* tm, uint32_t src, int c0, int c1, int c2) {
  asm volatile("cp.async.bulk.tensor.3d.global.shared::cta.bulk_group [%0, {%2, %3, %4}], [%1];" ::"l"(tm), "r"(src), "r"(c0), "r"(c1), "r"(c2) : "memory");
}
__device__ __forceinline__ void bulk_load(uint32_t dst, const void* src, uint32_t bytes, uint32_t bar, uint64_t hint) {
  asm volatile("cp.async.bulk.shared::cluster.global.mbarrier::complete_tx::bytes.L2::cache_hint [%0], [%1], %2, [%3], %4;" ::"r"(dst), "l"(src), "r"(bytes), "r"(bar), "l"(hint) : "memory");
}
__device__ __forceinline__ void bulk_load_mc(uint32_t dst, const void* src, uint32_t bytes, uint32_t bar, uint64_t hint) {
  asm volatile("cp.async.bulk.shared::cluster.global.mbarrier::complete_tx::bytes.multicast::cluster.L2::cache_hint [%0], [%1], %2, [%3], %4, %5;" ::"r"(dst), "l"(src), "r"(bytes), "r"(bar), "h"((uint16_t)3), "l"(hint) : "memory");
}
__device__ __forceinline__ uint4 lds128(uint32_t a) { uint4 v; asm volatile("ld.shared.v4.b32 {%0,%1,%2,%3}, [%4];" : "=r"(v.x), "=r"(v.y), "=r"(v.z), "=r"(v.w) : "r"(a) : "memory"); return v; }
__device__ __forceinline__ void sts128(uint32_t a, uint4 v) { asm volatile("st.shared.v4.b32 [%0], {%1,%2,%3,%4};" ::"r"(a), "r"(v.x), "r"(v.y), "r"(v.z), "r"(v.w) : "memory"); }
__device__ __forceinline__ void stg128(void* p, uint32_t a, uint32_t b, uint32_t c, uint32_t d) { asm volatile("st.global.v4.b32 [%0], {%1,%2,%3,%4};" ::"l"(p), "r"(a), "r"(b), "r"(c), "r"(d) : "memory"); }

__device__ __forceinline__ uint32_t pack2(float lo, float hi) { uint32_t r; asm("cvt.rn.bf16x2.f32 %0, %1, %2;" : "=r"(r) : "f"(hi), "f"(lo)); return r; }
__device__ __forceinline__ float lo_f(uint32_t v) { return __uint_as_float(v << 16); }
__device__ __forceinline__ float hi_f(uint32_t v) { return __uint_as_float(v & 0xffff0000u); }
__device__ __forceinline__ float bf16r(float v) { return lo_f(pack2(v, 0.f)); }
__device__ __forceinline__ uint32_t mul2(uint32_t a, uint32_t b) { uint32_t r; asm("mul.rn.bf16x2 %0, %1, %2;" : "=r"(r) : "r"(a), "r"(b)); return r; }
__device__ __forceinline__ uint32_t sub2(uint32_t a, uint32_t b) { uint32_t r; asm("sub.rn.bf16x2 %0, %1, %2;" : "=r"(r) : "r"(a), "r"(b)); return r; }
__device__ __forceinline__ uint32_t fma2(uint32_t a, uint32_t b, uint32_t c) { uint32_t r; asm("fma.rn.bf16x2 %0, %1, %2, %3;" : "=r"(r) : "r"(a), "r"(b), "r"(c)); return r; }
__device__ __forceinline__ uint32_t max2(uint32_t a, uint32_t b) { uint32_t r; asm("max.bf16x2 %0, %1, %2;" : "=r"(r) : "r"(a), "r"(b)); return r; }
__device__ __forceinline__ float ex2f(float x) { float y; asm("ex2.approx.ftz.f32 %0, %1;" : "=f"(y) : "f"(x)); return y; }
__device__ __forceinline__ float rcpf(float x) { float y; asm("rcp.approx.ftz.f32 %0, %1;" : "=f"(y) : "f"(x)); return y; }
__device__ __forceinline__ float gelu2(float g) {
  float z = g * fmaf(g * g, 0.035677408136300125f, 0.7978845608028654f), t;
  asm("tanh.approx.f32 %0, %1;" : "=f"(t) : "f"(z));
  return fmaf(g, t, g);
}

__device__ __forceinline__ float silu_half(float z) { float t; asm("tanh.approx.f32 %0, %1;" : "=f"(t) : "f"(z)); return fmaf(z, t, z); }

__device__ __forceinline__ void wg_fence() { asm volatile("wgmma.fence.sync.aligned;" ::: "memory"); }
__device__ __forceinline__ void wg_commit() { asm volatile("wgmma.commit_group.sync.aligned;" ::: "memory"); }
template <int N> __device__ __forceinline__ void wg_wait() { asm volatile("wgmma.wait_group.sync.aligned %0;" ::"n"(N) : "memory"); }
#define A8(o) "+f"(d[(o)]), "+f"(d[(o) + 1]), "+f"(d[(o) + 2]), "+f"(d[(o) + 3]), "+f"(d[(o) + 4]), "+f"(d[(o) + 5]), "+f"(d[(o) + 6]), "+f"(d[(o) + 7])
#define A64(o) A8(o), A8((o) + 8), A8((o) + 16), A8((o) + 24), A8((o) + 32), A8((o) + 40), A8((o) + 48), A8((o) + 56)
#define REGS0_63 "%0,%1,%2,%3,%4,%5,%6,%7,%8,%9,%10,%11,%12,%13,%14,%15,%16,%17,%18,%19,%20,%21,%22,%23,%24,%25,%26,%27,%28,%29,%30,%31," \
                 "%32,%33,%34,%35,%36,%37,%38,%39,%40,%41,%42,%43,%44,%45,%46,%47,%48,%49,%50,%51,%52,%53,%54,%55,%56,%57,%58,%59,%60,%61,%62,%63"
#define REGS64_127 "%64,%65,%66,%67,%68,%69,%70,%71,%72,%73,%74,%75,%76,%77,%78,%79,%80,%81,%82,%83,%84,%85,%86,%87,%88,%89,%90,%91,%92,%93,%94,%95," \
                   "%96,%97,%98,%99,%100,%101,%102,%103,%104,%105,%106,%107,%108,%109,%110,%111,%112,%113,%114,%115,%116,%117,%118,%119,%120,%121,%122,%123,%124,%125,%126,%127"
template <int ACCUM> __device__ __forceinline__ void wgmma256(float (&d)[128], uint32_t a_lo, uint32_t a_hi, uint32_t b_lo) {
  asm volatile("{\n.reg .pred p;\n.reg .b64 da, db;\nsetp.ne.b32 p, %131, 0;\nmov.b64 da, {%128, %129};\nmov.b64 db, {%130, 0x40000040};\n"
               "wgmma.mma_async.sync.aligned.m64n256k16.f32.bf16.bf16 {" REGS0_63 "," REGS64_127 "}, da, db, p, 1, 1, 0, 1;\n}"
               : A64(0), A64(64) : "r"(a_lo), "r"(a_hi), "r"(b_lo), "n"(ACCUM));
}
__device__ __forceinline__ void wgmma256_rs(float (&d)[128], uint32_t a0, uint32_t a1, uint32_t z0, uint32_t z1, uint32_t b_lo) {
  asm volatile("{\n.reg .b64 db;\nmov.b64 db, {%132, 0x00000008};\n"
               "wgmma.mma_async.sync.aligned.m64n256k16.f32.bf16.bf16 {" REGS0_63 "," REGS64_127 "}, {%128,%129,%130,%131}, db, 1, 1, 1, 0;\n}"
               : A64(0), A64(64) : "r"(a0), "r"(a1), "r"(z0), "r"(z1), "r"(b_lo));
}
template <int ACCUM> __device__ __forceinline__ void wgmma128(float (&d)[64], uint32_t a_lo, uint32_t b_lo) {
  asm volatile("{\n.reg .pred p;\n.reg .b64 da, db;\nsetp.ne.b32 p, %66, 0;\nmov.b64 da, {%64, 0x80000020};\nmov.b64 db, {%65, 0x40000040};\n"
               "wgmma.mma_async.sync.aligned.m64n128k16.f32.bf16.bf16 {" REGS0_63 "}, da, db, p, 1, 1, 0, 1;\n}"
               : A64(0) : "r"(a_lo), "r"(b_lo), "n"(ACCUM));
}
template <int ACCUM> __device__ __forceinline__ void hmma(float (&c)[4], uint32_t a0, uint32_t a1, uint32_t a2, uint32_t a3, uint32_t b0, uint32_t b1) {
  if (ACCUM)
    asm volatile("mma.sync.aligned.m16n8k16.row.col.f32.bf16.bf16.f32 {%0,%1,%2,%3}, {%4,%5,%6,%7}, {%8,%9}, {%0,%1,%2,%3};"
                 : "+f"(c[0]), "+f"(c[1]), "+f"(c[2]), "+f"(c[3]) : "r"(a0), "r"(a1), "r"(a2), "r"(a3), "r"(b0), "r"(b1));
  else
    asm volatile("mma.sync.aligned.m16n8k16.row.col.f32.bf16.bf16.f32 {%0,%1,%2,%3}, {%4,%5,%6,%7}, {%8,%9}, {%10,%10,%10,%10};"
                 : "=f"(c[0]), "=f"(c[1]), "=f"(c[2]), "=f"(c[3]) : "r"(a0), "r"(a1), "r"(a2), "r"(a3), "r"(b0), "r"(b1), "f"(0.f));
}
__device__ __forceinline__ uint32_t movm(uint32_t a) { uint32_t d; asm volatile("movmatrix.sync.aligned.m8n8.trans.b16 %0, %1;" : "=r"(d) : "r"(a)); return d; }
template <int N> __device__ __forceinline__ void pin(uint32_t* r) {
#pragma unroll
  for (int i = 0; i < N; i++) asm volatile("" : "+r"(r[i]));
}
template <int N> __device__ __forceinline__ void pin(float* r) {
#pragma unroll
  for (int i = 0; i < N; i++) asm volatile("" : "+f"(r[i]));
}
__device__ __forceinline__ void sched_fence(uint32_t zero) {
  asm volatile("{\n.reg .pred p;\n.reg .u32 n;\nmov.u32 n, %0;\nLAB_F:\nsetp.eq.u32 p, n, 0;\n@p bra.uni LAB_D;\nnanosleep.u32 n;\nsub.u32 n, n, 1;\nbra.uni LAB_F;\nLAB_D:\n}" ::"r"(zero) : "memory");
}
__device__ __forceinline__ uint4 ldsm(uint32_t a) { uint4 v; asm volatile("ldmatrix.sync.aligned.m8n8.x4.shared.b16 {%0,%1,%2,%3}, [%4];" : "=r"(v.x), "=r"(v.y), "=r"(v.z), "=r"(v.w) : "r"(a) : "memory"); return v; }
__device__ __forceinline__ uint4 ldsm_t(uint32_t a) { uint4 v; asm volatile("ldmatrix.sync.aligned.m8n8.x4.trans.shared.b16 {%0,%1,%2,%3}, [%4];" : "=r"(v.x), "=r"(v.y), "=r"(v.z), "=r"(v.w) : "r"(a) : "memory"); return v; }

constexpr int BAR_LAG = 1, BAR_MMA = 2, BAR_EV = 3;

struct Cons {
  uint32_t sb;
  uint32_t a0, a1, ah;
  uint32_t rel;
  bool do_rel;
  int wg;
  uint32_t zero;
};
#define REL_TS(n) TS(64 + (n))
constexpr uint32_t DB_LO = ((SM_BASE + 16384) >> 4) | ((8192 >> 4) << 16);

template <int ST, int ACCUM, bool WAIT = true> __device__ __forceinline__ void p1_issue(float (&acc)[128], const Cons& c, uint32_t parity) {
  if (WAIT) mbar_wait(c.sb + B_F1 + 8 * ST, parity);
  wg_fence();
  constexpr uint32_t so = ST * (P1_STAGE >> 4);
  wgmma256<ACCUM>(acc, c.a0 + so, c.ah, DB_LO + so);
  wgmma256<1>(acc, c.a0 + so + 2, c.ah, DB_LO + so + 128);
  wgmma256<1>(acc, c.a1 + so, c.ah, DB_LO + so + 256);
  wgmma256<1>(acc, c.a1 + so + 2, c.ah, DB_LO + so + 384);
  wg_commit();
}
__device__ __forceinline__ void release(const Cons& c, uint32_t bar) { if (c.do_rel) mbar_arrive_cl(c.rel + bar); }
template <int KB, bool WAIT = true, int LAG = 2> __device__ __forceinline__ void p1_step(float (&acc)[128], const Cons& c) {
  if (KB == 16 - LAG) { if (c.wg == 1) { wg_wait<0>(); release(c, B_E1 + 8 * ((KB - 1) & 3)); bar_sync(BAR_LAG, 256); } }
  p1_issue<KB & 3, KB != 0, WAIT>(acc, c, (KB >> 2) & 1);
  if (KB == 15) { if (c.wg == 0) bar_arrive(BAR_LAG, 256); }
  if (KB > 0) { wg_wait<1>(); if (KB != 16 - LAG || c.wg == 0) release(c, B_E1 + 8 * ((KB - 1) & 3)); }
  if (KB == 15) { wg_wait<0>(); release(c, B_E1 + 8 * 3); }
}
template <int A, int B> __device__ __forceinline__ void p1_range(float (&acc)[128], const Cons& c) {
  if constexpr (A < B) { p1_step<A>(acc, c); p1_range<A + 1, B>(acc, c); }
}
template <int T> __device__ __forceinline__ void p2_step(float (&acc)[64], const Cons& c) {
  if (T == 12) { if (c.wg == 1) bar_sync(BAR_LAG, 256); }
  mbar_wait(c.sb + B_F2 + 8 * (T % 5), (T / 5) & 1);
  wg_fence();
  constexpr uint32_t so = (T % 5) * (P2_STAGE >> 4);
  wgmma128<T != 0>(acc, c.a0 + so, DB_LO + so);
  wgmma128<1>(acc, c.a0 + so + 2, DB_LO + so + 128);
  wgmma128<1>(acc, c.a1 + so, DB_LO + so + 256);
  wgmma128<1>(acc, c.a1 + so + 2, DB_LO + so + 384);
  wg_commit();
  if (T == 15) { if (c.wg == 0) bar_arrive(BAR_LAG, 256); }
  if (T <= 11) { wg_wait<1>(); release(c, T ? B_E2 + 8 * ((T + 4) % 5) : B_E1 + 8 * 3); }
}

template <int P> __device__ __forceinline__ void geglu_piece(const uint32_t (&pk)[64], uint8_t* dst, const float (&rs)[2]) {
  constexpr int cg = P >> 1, r = P & 1;
  uint32_t v[4];
#pragma unroll
  for (int i = 0; i < 4; i++) {
    const uint32_t g = pk[2 * (4 * cg + i) + r];
    v[i] = mul2(pack2(gelu2(lo_f(g) * rs[r]) * rs[r], gelu2(hi_f(g) * rs[r]) * rs[r]), pk[32 + 2 * (4 * cg + i) + r]);
  }
  stg128(dst + cg * 8192 + r * 512, v[0], v[1], v[2], v[3]);
}
template <int KB> __device__ __forceinline__ void geglu_tile(float (&acc)[128], const uint32_t (&pk)[64], const Cons& c, uint8_t* dst, int ev, const float (&rs)[2]) {
  if constexpr (KB < 14) {
    p1_step<KB>(acc, c);
    if (KB >= 1 && KB <= 8) geglu_piece<(KB - 1) & 7>(pk, dst, rs);
    if (KB == 8) bar_arrive(ev, 288);
    geglu_tile<KB + 1>(acc, pk, c, dst, ev, rs);
  }
}

__device__ __forceinline__ void attn_tile(float (&acc)[128], const uint32_t (&pk)[64], const Cons& c, int round, int warp, int m, Scratch* gs, uint8_t* hdst, uint8_t* odst) {
  const int lane = threadIdx.x & 31, w = warp & 3, rho = lane >> 2, q = lane & 3;
  const uint32_t at = c.sb + OFF_X + c.wg * AT_WG, swz = (lane ^ (lane >> 3)) << 4;
  uint32_t gg[16];
  p1_step<0>(acc, c);
  p1_step<1>(acc, c);
#pragma unroll
  for (int i = 0; i < 4; i++) {
    const int h = i & 1, r = i >> 1;
    sts128(at + AT_V + (2 * w + r) * 1024 + h * 512 + swz, make_uint4(pk[32 + 8 * h + r], pk[34 + 8 * h + r], pk[36 + 8 * h + r], pk[38 + 8 * h + r]));
  }
  if (w < 3) {
#pragma unroll
    for (int i = 0; i < 8; i++) asm volatile("st.shared.b32 [%0], %1;" ::"r"(at + AT_K + w * 1024 + i * 128 + lane * 4), "r"(pk[17 + 2 * i]) : "memory");
  } else {
    uint8_t* g = (uint8_t*)gs->halo + ((round * 128 + blockIdx.x) * 2 + c.wg) * 2048;
#pragma unroll
    for (int i = 0; i < 8; i++) asm volatile("st.global.b32 [%0], %1;" ::"l"(g + i * 128 + lane * 4), "r"(pk[17 + 2 * i]) : "memory");
#pragma unroll
    for (int h = 0; h < 2; h++) stg128(g + 1024 + h * 512 + swz, pk[33 + 8 * h], pk[35 + 8 * h], pk[37 + 8 * h], pk[39 + 8 * h]);
    bar_arrive(BAR_EV + 2 + round, 96);
  }
  __syncwarp();
  if (lane == 0) mbar_arrive(c.sb + B_HALO + 8 * round);
  if (round) {
#pragma unroll
    for (int p = 0; p < 4; p++) asm volatile("ld.global.cg.v4.b32 {%0,%1,%2,%3}, [%4];" : "=r"(gg[4 * p]), "=r"(gg[4 * p + 1]), "=r"(gg[4 * p + 2]), "=r"(gg[4 * p + 3]) : "l"(hdst + (p >> 1) * 8192 + (p & 1) * 512) : "memory");
  }
  auto gu_piece = [&](int p) {
    uint32_t v[4];
#pragma unroll
    for (int i = 0; i < 4; i++) {
      const uint32_t g = pk[48 + 8 * (p >> 1) + 2 * i + (p & 1)];
      v[i] = round ? mul2(gg[4 * p + i], g) : pack2(gelu2(lo_f(g)), gelu2(hi_f(g)));
    }
    stg128(hdst + (p >> 1) * 8192 + (p & 1) * 512, v[0], v[1], v[2], v[3]);
  };
  p1_step<2>(acc, c);
  p1_step<3>(acc, c); gu_piece(0);
  p1_step<4>(acc, c); gu_piece(1);
  p1_step<5>(acc, c); gu_piece(2);
  p1_step<6>(acc, c); gu_piece(3);
  p1_step<7>(acc, c);
  p1_step<8>(acc, c);
  const bool first = m == 0 && w == 0;
  uint32_t kl[16];
  mbar_wait(c.sb + B_HALO + 8 * round, 0);
  {
    const uint32_t ka = at + lane * 4 + (w ? AT_K + (w - 1) * 1024 : (first ? AT_K : AT_REM + round * 2048));
#pragma unroll
    for (int i = 0; i < 8; i++) {
      asm volatile("ld.shared.b32 %0, [%1];" : "=r"(kl[2 * i]) : "r"(ka + i * 128) : "memory");
      kl[2 * i + 1] = pk[16 + 2 * i] | c.zero;
    }
  }
  float st[4][4];
  pin<16>(kl);
  bar_sync(BAR_MMA, 256);
  mbar_wait(c.sb + B_F1 + 8 * 1, 0);
#pragma unroll
  for (int ks = 0; ks < 2; ks++) {
#pragma unroll
    for (int h = 0; h < 2; h++) {
      const int o = 8 * h + 4 * ks;
      if (ks == 0) { hmma<0>(st[2 * h], kl[o], kl[o + 1], kl[o + 2], kl[o + 3], pk[o], pk[o + 2]); hmma<0>(st[2 * h + 1], pk[16 + o], pk[17 + o], pk[18 + o], pk[19 + o], pk[o + 1], pk[o + 3]); }
      else { hmma<1>(st[2 * h], kl[o], kl[o + 1], kl[o + 2], kl[o + 3], pk[o], pk[o + 2]); hmma<1>(st[2 * h + 1], pk[16 + o], pk[17 + o], pk[18 + o], pk[19 + o], pk[o + 1], pk[o + 3]); }
    }
  }
  sched_fence(c.zero);
  bar_sync(BAR_MMA, 256);
  p1_step<9, false>(acc, c);
  sched_fence(c.zero);
  pin<16>(&st[0][0]);
  const bool le0 = 2 * q <= rho, le1 = 2 * q + 1 <= rho;
  uint32_t la[2], lb[2], mx[2];
#pragma unroll
  for (int h = 0; h < 2; h++) {
    uint32_t l[2];
#pragma unroll
    for (int r = 0; r < 2; r++) {
      const float (&t)[4] = st[2 * h + r];
      l[r] = movm(pack2(rho <= 2 * q ? t[2] : t[0], rho <= 2 * q + 1 ? t[3] : t[1]));
      l[r] = fma2(l[r], 0x3e353e35u, mul2(l[r], 0x379e379eu));
    }
    la[h] = __byte_perm(l[0], l[1], 0x5410); lb[h] = __byte_perm(l[0], l[1], 0x7632);
    if (first && !le0) la[h] = (la[h] & 0xffff0000u) | 0xce6eu;
    if (first && !le1) lb[h] = (lb[h] & 0xffff0000u) | 0xce6eu;
    mx[h] = max2(la[h], lb[h]);
  }
#pragma unroll
  for (int o = 1; o <= 2; o++) { mx[0] = max2(mx[0], __shfl_xor_sync(~0u, mx[0], o)); mx[1] = max2(mx[1], __shfl_xor_sync(~0u, mx[1], o)); }
  const float L2E = 1.4426950408889634f;
  float pr[2][4], z[4];
#pragma unroll
  for (int h = 0; h < 2; h++) {
    pr[h][0] = ex2f((lo_f(la[h]) - lo_f(mx[h])) * L2E); pr[h][1] = ex2f((lo_f(lb[h]) - lo_f(mx[h])) * L2E);
    pr[h][2] = ex2f((hi_f(la[h]) - hi_f(mx[h])) * L2E); pr[h][3] = ex2f((hi_f(lb[h]) - hi_f(mx[h])) * L2E);
    z[2 * h] = pr[h][0] + pr[h][1]; z[2 * h + 1] = pr[h][2] + pr[h][3];
  }
  p1_step<10>(acc, c);
#pragma unroll
  for (int o = 1; o <= 2; o++) {
#pragma unroll
    for (int i = 0; i < 4; i++) z[i] += __shfl_xor_sync(~0u, z[i], o);
  }
  const uint32_t LE = (le0 ? 0xffffu : 0u) | (le1 ? 0xffff0000u : 0u);
  uint32_t P[4][2];
  uint4 vt[4][2];
  {
    const uint32_t row = (lane & 7) * 64 + ((((lane >> 3) & 1) ^ ((lane & 7) >> 1)) << 4);
    const uint32_t v1 = at + AT_V + (2 * w + (lane >> 4)) * 1024 + row;
    const uint32_t v0 = (w || lane >= 16) ? v1 - 1024 : (first ? v1 : at + AT_REM + round * 2048 + 1024 + row);
#pragma unroll
    for (int i = 0; i < 4; i++) {
      const float rz = rcpf(z[i]);
      const uint32_t p = pack2(pr[i >> 1][2 * (i & 1)] * rz, pr[i >> 1][2 * (i & 1) + 1] * rz);
      P[i][0] = p & ~LE; P[i][1] = p & LE;
      const uint32_t a = ((i & 1) ? v1 : v0) + (i >> 1) * 512;
      vt[i][0] = ldsm_t(a); vt[i][1] = ldsm_t(a ^ 32);
    }
  }
  float ot[4][2][4];
  pin<8>(&P[0][0]);
  bar_sync(BAR_MMA, 256);
  mbar_wait(c.sb + B_F1 + 8 * 3, 0);
#pragma unroll
  for (int i = 0; i < 8; i++) { const uint4& v = vt[i >> 1][i & 1]; hmma<0>(ot[i >> 1][i & 1], v.x, v.y, v.z, v.w, P[i >> 1][0], P[i >> 1][1]); }
  sched_fence(c.zero);
  bar_sync(BAR_MMA, 256);
  p1_step<11, false>(acc, c);
  sched_fence(c.zero);
  pin<32>(&ot[0][0][0]);
  auto o_piece = [&](int i) {
    stg128(odst + (i >> 1) * 8192 + (i & 1) * 512, movm(pack2(ot[i][0][0], ot[i][0][1])), movm(pack2(ot[i][0][2], ot[i][0][3])), movm(pack2(ot[i][1][0], ot[i][1][1])), movm(pack2(ot[i][1][2], ot[i][1][3])));
  };
  o_piece(0); o_piece(1);
  p1_step<12>(acc, c);
  o_piece(2); o_piece(3);
  if (round) bar_arrive(BAR_EV + 4, 288);
  p1_step<13>(acc, c);
}

__device__ __forceinline__ void ln_moments(const uint32_t* raw, float& c0, float& s, float& v) {
  c0 = lo_f(__shfl_sync(~0u, raw[0], 0));
  float ss[4] = {0.f, 0.f, 0.f, 0.f}, vv[4] = {0.f, 0.f, 0.f, 0.f};
#pragma unroll
  for (int i = 0; i < 16; i++) {
    const float a = lo_f(raw[i]) - c0, b = hi_f(raw[i]) - c0;
    ss[(2 * i) & 3] += a; ss[(2 * i + 1) & 3] += b;
    vv[(2 * i) & 3] = fmaf(a, a, vv[(2 * i) & 3]); vv[(2 * i + 1) & 3] = fmaf(b, b, vv[(2 * i + 1) & 3]);
  }
  s = (ss[0] + ss[1]) + (ss[2] + ss[3]); v = (vv[0] + vv[1]) + (vv[2] + vv[3]);
}
__device__ __forceinline__ void ln_reduce(float& s, float& v) {
#pragma unroll
  for (int o = 16; o; o >>= 1) { s += __shfl_xor_sync(~0u, s, o); v += __shfl_xor_sync(~0u, v, o); }
}
__device__ __forceinline__ uint32_t ln_finish(float c0, float s, float v) {
  s *= 1.0f / DM;
  float sd;
  asm("sqrt.approx.ftz.f32 %0, %1;" : "=f"(sd) : "f"(bf16r(bf16r(fmaxf(fmaf(v, 1.0f / DM, -s * s), 0.f)) + 1e-5f)));
  return pack2(c0 + s, sd);
}
__device__ __forceinline__ void ln_store(const uint32_t* raw, uint32_t st, uint4* dst) {
  const uint32_t m2 = __byte_perm(st, st, 0x1010);
  const float rinv = rcpf(hi_f(st));
#pragma unroll
  for (int c = 0; c < 4; c++) {
    uint32_t v[4];
#pragma unroll
    for (int i = 0; i < 4; i++) { const uint32_t t = sub2(raw[4 * c + i], m2); v[i] = pack2(lo_f(t) * rinv, hi_f(t) * rinv); }
    stg128(dst + 32 * c, v[0], v[1], v[2], v[3]);
  }
}
__device__ __forceinline__ void col_sums(uint32_t tile, ulonglong2* part, uint32_t tag) {
  const int lane = threadIdx.x & 31;
  float cs[8] = {0, 0, 0, 0, 0, 0, 0, 0};
  uint32_t base = tile + ((lane >> 3) & 1) * 8192 + (lane >> 4) * 4096 + ((lane & 7) << 4);
#pragma unroll 1
  for (int k0 = 0; k0 < 8; k0++, base = (base ^ ((k0 ^ (k0 - 1)) << 4)) + 128) {
    uint4 v[4];
#pragma unroll
    for (int k = 0; k < 4; k++) v[k] = lds128(base + k * 1024);
#pragma unroll
    for (int k = 0; k < 4; k++) {
      cs[0] += lo_f(v[k].x); cs[1] += hi_f(v[k].x); cs[2] += lo_f(v[k].y); cs[3] += hi_f(v[k].y);
      cs[4] += lo_f(v[k].z); cs[5] += hi_f(v[k].z); cs[6] += lo_f(v[k].w); cs[7] += hi_f(v[k].w);
    }
  }
  const bool up = lane >= 16;
#pragma unroll
  for (int i = 0; i < 2; i++) {
    const float a = (up ? cs[4 + 2 * i] : cs[2 * i]) + __shfl_xor_sync(~0u, up ? cs[2 * i] : cs[4 + 2 * i], 16);
    const float b = (up ? cs[5 + 2 * i] : cs[1 + 2 * i]) + __shfl_xor_sync(~0u, up ? cs[1 + 2 * i] : cs[5 + 2 * i], 16);
    asm volatile("{\n.reg .b64 a, b;\nmov.b64 a, {%1, %3};\nmov.b64 b, {%2, %3};\nst.relaxed.gpu.global.v2.b64 [%0], {a, b};\n}"
                 ::"l"(part + 32 * (i + (up ? 2 : 0)) + (lane & 15)), "r"(__float_as_uint(a)), "r"(__float_as_uint(b)), "r"(tag) : "memory");
  }
  asm volatile("fence.proxy.async.shared::cta;" ::: "memory");
}

__global__ void __cluster_dims__(2, 1, 1) __launch_bounds__(384, 1)
fused_kernel(const uint4* __restrict__ x, const uint4* __restrict__ wgate, const uint4* __restrict__ wup, Scratch* gs, const __grid_constant__ Maps mp) {
  extern __shared__ __align__(1024) uint8_t smem_raw[];
  const uint32_t sb = (uint32_t)__cvta_generic_to_shared(smem_raw);
  const unsigned t_start = 0;
  const int warp = __shfl_sync(~0u, threadIdx.x >> 5, 0), lane = threadIdx.x & 31;
  const int m = blockIdx.x & 15, j = blockIdx.x >> 4, rank = blockIdx.x & 1;
  const int m2 = blockIdx.x >> 3, j2 = blockIdx.x & 7;
  if (warp >= 8) {
    asm volatile("setmaxnreg.dec.sync.aligned.u32 40;");
    if (warp == 8) {
      if (elect_one()) {
        asm volatile("prefetch.tensormap [%0];\nprefetch.tensormap [%1];\nprefetch.tensormap [%2];" ::"l"(&mp.x), "l"(&mp.wg), "l"(&mp.wu) : "memory");
        for (int s = 0; s < 4; s++) mbar_init(sb + B_F1 + 8 * s, 1);
        mbar_arrive(sb + B_F1);
        asm volatile("fence.mbarrier_init.release.cluster;" ::: "memory");
      }
      __syncwarp();
    } else if (warp == 9) {
      if (elect_one()) {
        if ((sb & 0xffffff) != SM_BASE) asm volatile("trap;");
        for (int s = 0; s < 4; s++) mbar_init(sb + B_E1 + 8 * s, 4);
        for (int s = 0; s < 5; s++) { mbar_init(sb + B_F2 + 8 * s, 1); mbar_init(sb + B_E2 + 8 * s, 4); }
        for (int s = 0; s < 5; s++) mbar_init(sb + B_DEP + 8 * s, 1);
        mbar_init(sb + B_AUX, 8); mbar_init(sb + B_EP, 1); mbar_init(sb + B_XT, 1); mbar_init(sb + B_CS, 1);
        for (int s = 0; s < 4; s++) { mbar_init(sb + B_EX + 8 * s, 1); mbar_expect_tx(sb + B_EX + 8 * s, 8192); }
        mbar_init(sb + B_HALO, 9); mbar_init(sb + B_HALO + 8, 9);
        asm volatile("fence.mbarrier_init.release.cluster;" ::: "memory");
      }
      __syncwarp();
    }
    asm volatile("barrier.cluster.arrive.relaxed.aligned;" ::: "memory");
    if (warp == 8) {
      if (elect_one()) {
        TS(0); TG(51);
#pragma unroll 1
        for (int kb = 1; kb < 4; kb++) {
          const uint32_t sa = sb + kb * P1_STAGE, fb = sb + B_F1 + 8 * kb;
          mbar_expect_tx(fb, P1_STAGE);
          tma3d(sa, &mp.x, fb, kb * 64, m * 64, 0, EVICT_NORMAL);
          tma2d(sa + 16384, &mp.wg, fb, j * 128, kb * 64, EVICT_NORMAL); tma2d(sa + 32768, &mp.wu, fb, j * 128, kb * 64, EVICT_NORMAL);
          tma2d(sa + 24576, &mp.wg, fb, j * 128 + 64, kb * 64, EVICT_NORMAL); tma2d(sa + 40960, &mp.wu, fb, j * 128 + 64, kb * 64, EVICT_NORMAL);
        }
        TS(7);
      }
      __syncwarp();
    }
    asm volatile("barrier.cluster.wait.aligned;" ::: "memory");
    if (warp == 8) {
      if (elect_one()) {
        uint32_t par = 0;

        auto d_prefetch = [&](int i) {
          if (PF_W && (m2 >> 2) == (i & 3)) tma5d_prefetch(&mp.wd, (j2 >> 1) * 256 + (m2 & 3) * 64, (2 * i + rank) * 2);
          if (PF_H && i < 8) asm volatile("cp.async.bulk.prefetch.L2.global [%0], 4096;" ::"l"(gs->h + (m2 * 56 + 2 * i + rank) * 1024 + (j2 >> 1) * 256) : "memory");
        };
        for (int R = 0; R < 5; R++) {
          const CUtensorMap *mb0, *mb1;
          int n0, n1;
          if (R == 1 || R == 2) {
            mb0 = &mp.wqkv; n0 = 64 * (j + 8 * (R - 1)) + rank * 2048;
            mb1 = rank ? (R == 1 ? &mp.wg : &mp.wu) : &mp.wqkv; n1 = rank ? 1024 + 64 * j : n0 + 1024;
          } else {
            mb0 = mb1 = rank ? &mp.wu : &mp.wg;
            n0 = 128 * j + (R ? 1024 * R - 1536 : 0); n1 = n0 + 64;
          }
#pragma unroll 1
          for (int kb = R ? 0 : 4; kb < 16; kb++) {
            if (R == 0 && kb == 4) { for (int i = 1; i < 8; i++) asm volatile("prefetch.tensormap [%0];" ::"l"(&mp.x + i) : "memory"); }
            if (R == 0 && kb == (CS_KB)) {
              const uint32_t cb = sb + B_CS, d = sb + OFF_X;
              mbar_expect_tx(cb, 32768);
              tma2d(d, &mp.wg, cb, n0, m * 64, EVICT_NORMAL); tma2d(d + 8192, &mp.wg, cb, n1, m * 64, EVICT_NORMAL);
              tma2d(d + 16384, &mp.wu, cb, n0, m * 64, EVICT_NORMAL); tma2d(d + 24576, &mp.wu, cb, n1, m * 64, EVICT_NORMAL);
            }
            const int st = kb & 3;
            const uint32_t sa = sb + st * P1_STAGE, fb = sb + B_F1 + 8 * st;
            mbar_wait(sb + B_E1 + 8 * st, par);
            if (R * 16 + kb >= 4) REL_TS(R * 16 + kb - 4);
            mbar_expect_tx(fb, P1_STAGE);
            tma2d_mc(sa + 16384 + rank * 16384, mb0, fb, n0, kb * 64, HINT_W);
            tma2d_mc(sa + 24576 + rank * 16384, mb1, fb, n1, kb * 64, HINT_W);
            if (R == 0) {
              tma3d(sa, &mp.x, fb, kb * 64, m * 64, 0, EVICT_NORMAL);
            } else {
              if (R == 1 && kb == 0) { mbar_wait(sb + B_DEP, 0); TS(1); }
              tma2d(sa, &mp.xn, fb, kb * 64, m * 128, R == 4 ? HINT_LAST : EVICT_NORMAL);
            }
            if (R == 4 && kb >= 16 - PF_D) { if (kb == 16 - PF_D) mbar_wait(sb + B_DEP + 8, 0); d_prefetch(kb + PF_D - 16); }
            if (R == 4 && kb == 4 + j2) {
              mbar_expect_tx(sb + B_XT, 32768);
              tma3d(sb + OFF_X, &mp.x, sb + B_XT, j2 * 128, m2 * 64, 0, HINT_LAST); tma3d(sb + OFF_X + 16384, &mp.x, sb + B_XT, j2 * 128 + 64, m2 * 64, 0, HINT_LAST);
            }
            if (st == 3) par ^= 1;
          }
        }
#pragma unroll 1
        for (int i = 0; i < 28; i++) {
          if (i == 0 || i == 8 || i == 12 || i == 20) { mbar_wait(sb + B_DEP + 8 * (1 + ((i + 4) >> 3)), 0); TS(2 + ((i + 4) >> 3)); }
          const int st = i & 3, kb = 2 * i + rank;
          const uint32_t sa = sb + st * P1_STAGE, fb = sb + B_F1 + 8 * st;
          mbar_wait(sb + B_E1 + 8 * st, par);
          REL_TS(76 + i);
          mbar_expect_tx(fb, P1_STAGE);
          bulk_load(sa, gs->h + (m2 * 56 + kb) * 1024, 16384, fb, HINT_H);
          tma5d(sa + 16384, &mp.wd, fb, j2 * 128, kb * 2, HINT_W); tma5d(sa + 24576, &mp.wd, fb, j2 * 128 + 64, kb * 2, HINT_W);
          tma5d(sa + 32768, &mp.wd, fb, (j2 ^ 1) * 128, kb * 2, HINT_W); tma5d(sa + 40960, &mp.wd, fb, (j2 ^ 1) * 128 + 64, kb * 2, HINT_W);
          if (i + PF_D < 28) d_prefetch(i + PF_D);
          if (st == 3) par ^= 1;
        }
        int st = 0; uint32_t par2 = 1;
#pragma unroll 1
        for (int t = 0; t < 16; t++) {
          const uint32_t sa = sb + st * P2_STAGE, fb = sb + B_F2 + 8 * st;
          if (t < 5) mbar_wait(sb + B_E1 + 8 * ((2 * t + 1) / 3), par); else mbar_wait(sb + B_E2 + 8 * st, par2);
          REL_TS(104 + t);
          mbar_expect_tx(fb, P2_STAGE);
          bulk_load_mc(sa + rank * 8192, gs->o + (m2 * 16 + t) * 1024 + rank * 512, 8192, fb, HINT_H);
          tma2d(sa + 16384, &mp.wo, fb, j2 * 128, t * 64, HINT_W); tma2d(sa + 24576, &mp.wo, fb, j2 * 128 + 64, t * 64, HINT_W);
          if (++st == 5) { st = 0; par2 ^= 1; }
        }
      }
    } else if (warp == 9) {
#pragma unroll 1
      for (int e = 0; e < 7; e++) {
        const bool halo = e == 2 || e == 3;
        bar_sync(BAR_EV + e, halo ? 96 : 288);
        if (lane == 0) {
          const int f = e == 0 ? FL_XN + m : (halo ? FL_HALO + (e - 2) * 128 + blockIdx.x : FL_H + m * 4 + (e == 1 ? 0 : e - 3));
          TS(10 + 2 * e); TG(52 + e);
          flag_add(&gs->flags[f * 32]);
          if (e < 6) TS(11 + 2 * e);
        }
        __syncwarp();
      }
    } else {
      unsigned e = 0;
      if (lane == 0) {
        unsigned* ep = &gs->epoch[blockIdx.x * 2 + warp - 10];
        e = *ep + 1; *ep = e;
        if (warp == 10) { asm volatile("st.shared.b32 [%0], %1;" ::"r"(sb + OFF_EPOCH), "r"(e) : "memory"); mbar_arrive(sb + B_EP); }
      }
      e = __shfl_sync(~0u, e, 0);
      mbar_wait(sb + B_CS, 0);
      if (lane == 0 && warp == 11) TS(6);
      col_sums(sb + OFF_X + (warp - 10) * 16384, gs->cspart + (j * 16 + m) * 128 + (warp - 10) * 16, e);
      if (lane == 0 && warp == 11) TS(9);
      if (warp == 10) {
        if (lane == 0) {
#pragma unroll 1
          for (int g = 0; g < 5; g++) {
            flag_wait(&gs->flags[(g ? FL_H + m2 * 4 + g - 1 : FL_XN + m) * 32], e * 8u);
            fence_async();
            mbar_arrive(sb + B_DEP + 8 * g);
            if (g == 0) TS(8);
          }
        }
      } else
      if (elect_one()) {
#pragma unroll 1
        for (int r = 0; r < 2; r++) {
          const uint32_t hb = sb + B_HALO + 8 * r;
          if (m) {
            flag_wait(&gs->flags[(FL_HALO + r * 128 + blockIdx.x - 1) * 32], e);
            fence_async();
            mbar_expect_tx(hb, 4096);
            for (int g = 0; g < 2; g++) bulk_load(sb + OFF_X + g * AT_WG + AT_REM + r * 2048, gs->halo + ((r * 128 + blockIdx.x - 1) * 2 + g) * 128, 2048, hb, EVICT_FIRST);
          } else {
            mbar_arrive(hb);
          }
          TS(34 + r);
        }
      }
    }
  } else {
    {
      const int r = threadIdx.x >> 3, ch = threadIdx.x & 7;
      const uint32_t d = sb + r * 128 + ((ch ^ (r & 7)) << 4);
      const uint4* xa = x + (128 * m + 2 * r) * 128 + ch;
      const size_t wo = (size_t)r * (DFF / 8) + 16 * j + ch;
#pragma unroll
      for (int i = 0; i < 12; i++) {
        const uint4* src = i < 4 ? xa + (i & 1) * 64 * 128 + (i >> 1) * 128 : (i < 8 ? wgate : wup) + wo + (i & 1) * 32 * (DFF / 8) + ((i >> 1) & 1) * 8;
        asm volatile("cp.async.cg.shared.global [%0], [%1], 16;" ::"r"(d + i * 4096), "l"(src) : "memory");
      }
    }
    asm volatile("barrier.cluster.arrive.relaxed.aligned;" ::: "memory");
    asm volatile("setmaxnreg.inc.sync.aligned.u32 232;");
    const int wg = warp >> 2, w = warp & 3;
    Cons c;
    c.sb = sb; c.wg = wg; c.zero = warp >> 8;
    c.a0 = ((SM_BASE + wg * 8192) >> 4) | (1u << 16); c.a1 = c.a0 + 4; c.ah = 0x40000040;
    c.rel = mapa(sb, threadIdx.x & 1);
    c.do_rel = (threadIdx.x & 127) < 2;
    constexpr bool t0 = false;
    float acc[128];
    uint32_t pk[64];
    float rs[2];
    const int rho = lane >> 2, q = lane & 3;

    {
      const int prow = 16 * j + 2 * warp;
      const uint4* xr = x + (size_t)(128 * m + 2 * (prow & 63) + (prow >> 6)) * 128 + lane;
      uint4* xo = gs->xn + (size_t)(128 * m + prow) * 128 + lane;
      float c0[2], mo[4];
      uint32_t st[2];
      uint32_t e;
      asm volatile("" : "+l"(xr), "+l"(xo));
      if (t0) TS(23 + wg * 16);
      asm volatile("cp.async.wait_all;\nfence.proxy.async.shared::cta;" ::: "memory");
      bar_sync(BAR_MMA, 256);
      if (threadIdx.x == 0) TS(39);
      p1_step<0, false>(acc, c);
      asm volatile("barrier.cluster.wait.aligned;" ::: "memory");
      p1_range<1, LN_LD + 1>(acc, c);
      if (t0) TS(24 + wg * 16);
#pragma unroll
      for (int i = 0; i < 8; i++) {
        asm volatile("ld.global.nc.v4.b32 {%0,%1,%2,%3}, [%4];" : "=r"(pk[4 * i]), "=r"(pk[4 * i + 1]), "=r"(pk[4 * i + 2]), "=r"(pk[4 * i + 3]) : "l"(xr + (i >> 2) * 256 + (i & 3) * 32));
      }
      p1_range<LN_LD + 1, LN_KB + 1>(acc, c);
      sched_fence(c.zero);

      pin<16>(pk); ln_moments(pk, c0[0], mo[0], mo[1]); pin<2>(mo);
      p1_step<LN_KB + 1>(acc, c);
      sched_fence(c.zero);
      pin<16>(pk + 16); ln_moments(pk + 16, c0[1], mo[2], mo[3]); ln_reduce(mo[0], mo[1]); pin<4>(mo);
      p1_step<LN_KB + 2>(acc, c);
      mbar_wait(sb + B_EP, 0);
      asm volatile("ld.shared.b32 %0, [%1];" : "=r"(e) : "r"(sb + OFF_EPOCH) : "memory");
      pin<2>(mo); st[0] = ln_finish(c0[0], mo[0], mo[1]); ln_reduce(mo[2], mo[3]); pin<1>(st); pin<2>(mo + 2);
      p1_step<LN_KB + 3>(acc, c);
      sched_fence(c.zero);
      pin<1>(st); pin<2>(mo + 2);
      st[1] = ln_finish(c0[1], mo[2], mo[3]);
      ln_store(pk, st[0], xo);
      if (lane == 0)
        asm volatile("{\n.reg .b64 a, b;\nmov.b64 a, {%1, %3};\nmov.b64 b, {%2, %3};\nst.relaxed.gpu.global.v2.b64 [%0], {a, b};\n}" ::"l"(gs->stats + 128 * m + prow), "r"(st[0]), "r"(st[1]), "r"(e) : "memory");
      p1_step<LN_KB + 4>(acc, c);
      sched_fence(c.zero);
      pin<1>(st + 1); ln_store(pk + 16, st[1], xo + 128);
      bar_arrive(BAR_EV, 288);
      p1_range<LN_KB + 5, G_KB + 1>(acc, c);
      sched_fence(c.zero);
      const unsigned long long* cp = (const unsigned long long*)gs->cspart + j * 4096 + threadIdx.x;
      const unsigned long long* sp = gs->stats + 128 * m + warp * 16 + rho;
      unsigned long long part[18];
      auto gather = [&]() {
#pragma unroll
        for (int i = 0; i < 18; i++) asm volatile("ld.relaxed.gpu.global.b64 %0, [%1];" : "=l"(part[i]) : "l"(i < 16 ? cp + i * 256 : sp + (i - 16) * 8) : "memory");
      };
      gather();
      auto validate = [&]() {
        float csum;
        for (int tries = 0;; tries++) {
          uint32_t bad = 0;
          csum = 0.f;
#pragma unroll
          for (int i = 0; i < 18; i++) { bad |= (uint32_t)(part[i] >> 32) ^ e; if (i < 16) csum += __uint_as_float((uint32_t)part[i]); }
          if (!__any_sync(~0u, bad != 0) || tries > (1 << 20)) break;
          gather();
        }
        const float hi = bf16r(csum), mid = bf16r(csum - hi);
        sts128(sb + OFF_CS + ((threadIdx.x & 62) * 4 + (threadIdx.x >> 6) * 2 + (threadIdx.x & 1)) * 16, make_uint4(pack2(hi, mid), pack2(csum - hi - mid, 0.f), 0, 0));
        asm volatile("fence.proxy.async.shared::cta;" ::: "memory");
        __syncwarp();
        if (lane == 0) mbar_arrive(sb + B_AUX);
      };
      p1_range<G_KB + 1, 14>(acc, c);
      if (wg == 1) validate();
      p1_step<14>(acc, c);
      p1_issue<3, 1>(acc, c, 1);
      if (wg == 0) validate();
      const uint32_t keep = q == 0 ? 0xffffffffu : (q == 1 ? 0xffffu : 0u);
      const uint32_t a0 = (__byte_perm((uint32_t)part[16], 0, 0x1010) ^ 0x80008000u) & keep, a1 = (__byte_perm((uint32_t)part[17], 0, 0x1010) ^ 0x80008000u) & keep;
      mbar_wait(sb + B_AUX, 0);
      wg_fence();
      wgmma256_rs(acc, a0, a1, 0, 0, (SM_BASE + OFF_CS) >> 4);
      wg_commit();
      if (wg == 0) bar_arrive(BAR_LAG, 256);
      rs[0] = rcpf(hi_f((uint32_t)part[16])); rs[1] = rcpf(hi_f((uint32_t)part[17]));
      wg_wait<2>(); release(c, B_E1 + 16);
      wg_wait<0>(); release(c, B_E1 + 24);
#pragma unroll
      for (int i = 0; i < 64; i++) pk[i] = pack2(acc[2 * i], acc[2 * i + 1]);
      if (t0) TS(25 + wg * 16);
    }
    const uint32_t img = warp * 1024 + ((lane ^ (lane >> 3)) << 4);
#pragma unroll 1
    for (int R = 1;; R++) {
      uint8_t* hb = (uint8_t*)gs->h + (size_t)m * 56 * 16384 + img;
      if (R == 2 || R == 3) {
        attn_tile(acc, pk, c, R - 2, warp, m, gs, hb + (16 + j) * 16384, (uint8_t*)gs->o + (m * 16 + j + 8 * (R - 2)) * 16384 + img);
      } else {
        if (R == 5) { c.a0 = ((SM_BASE + wg * 4096) >> 4) | (1u << 16); c.a1 = c.a0 + 512; c.ah = 0x80000020; }
        geglu_tile<0>(acc, pk, c, hb + (2 * j + (R == 1 ? 0 : 16 * R - 40)) * 16384, BAR_EV + (R == 1 ? 1 : R + 1), rs);
        rs[0] = rs[1] = 1.0f;
        if (R == 5) break;
      }
      p1_range<14, 16>(acc, c);
#pragma unroll
      for (int i = 0; i < 64; i++) pk[i] = pack2(acc[2 * i], acc[2 * i + 1]);
      if (t0) TS(25 + R + wg * 16);
    }
    if (t0) TS(30 + wg * 16);
    p1_issue<2, 1>(acc, c, 1); wg_wait<1>(); release(c, B_E1 + 8);
    p1_issue<3, 1>(acc, c, 1); wg_wait<1>(); release(c, B_E1 + 16);
#pragma unroll 1
    for (int it = 4; it < 7; it++) {
      p1_issue<0, 1>(acc, c, it & 1); wg_wait<1>(); release(c, B_E1 + 24);
      p1_issue<1, 1>(acc, c, it & 1); wg_wait<1>(); release(c, B_E1);
      p1_issue<2, 1>(acc, c, it & 1); wg_wait<1>(); release(c, B_E1 + 8);
      p1_issue<3, 1>(acc, c, it & 1); wg_wait<1>(); release(c, B_E1 + 16);
    }
    if (t0) TS(31 + wg * 16);
    {
      float accs[64];
      const uint32_t peer = mapa(sb, rank ^ 1);
      auto send_piece = [&](int p) {
        asm volatile("st.async.weak.shared::cluster.mbarrier::complete_tx::bytes.v4.b32 [%0], {%1,%2,%3,%4}, [%5];" ::"r"(peer + OFF_LAND + p * 4096 + threadIdx.x * 16),
                     "r"(pack2(acc[64 + 8 * p], acc[65 + 8 * p])), "r"(pack2(acc[66 + 8 * p], acc[67 + 8 * p])), "r"(pack2(acc[68 + 8 * p], acc[69 + 8 * p])), "r"(pack2(acc[70 + 8 * p], acc[71 + 8 * p])),
                     "r"(peer + B_EX + 16 * wg + 8 * (p >> 2)) : "memory");
      };
      auto silu_piece = [&](int p) {
        const uint4 r = lds128(sb + OFF_LAND + p * 4096 + threadIdx.x * 16);
        const uint32_t rr[4] = {r.x, r.y, r.z, r.w};
#pragma unroll
        for (int i = 0; i < 4; i++) {
          const float a = acc[8 * p + 2 * i] + lo_f(rr[i]), b = acc[8 * p + 2 * i + 1] + hi_f(rr[i]);
          pk[4 * p + i] = pack2(silu_half(a * 0.25f), silu_half(b * 0.25f));
        }
        pin<4>(pk + 4 * p);
      };
      const uint32_t xa = sb + OFF_X + (warp * 16 + (lane & 15)) * 128 + (((lane >> 4) ^ (lane & 7)) << 4);
      auto x_piece = [&](int i) { const uint4 v = ldsm((xa ^ ((i & 3) << 5)) + (i >> 2) * 16384); pk[32 + 4 * i] = v.x; pk[33 + 4 * i] = v.y; pk[34 + 4 * i] = v.z; pk[35 + 4 * i] = v.w; };
      p2_step<0>(accs, c);
      p2_step<1>(accs, c);
      mbar_wait(sb + B_E1 + 24, 0);
      send_piece(0); send_piece(1);
      p2_step<2>(accs, c); sched_fence(c.zero); send_piece(2); send_piece(3);
      p2_step<3>(accs, c); sched_fence(c.zero); send_piece(4); send_piece(5);
      p2_step<4>(accs, c); sched_fence(c.zero); send_piece(6); send_piece(7);
      p2_step<5>(accs, c);
      mbar_wait(sb + B_XT, 0);
      mbar_wait(sb + B_EX + 16 * wg, 0);
      silu_piece(0); x_piece(0);
      p2_step<6>(accs, c); sched_fence(c.zero); silu_piece(1); x_piece(1);
      p2_step<7>(accs, c); sched_fence(c.zero); silu_piece(2); x_piece(2);
      p2_step<8>(accs, c); sched_fence(c.zero); silu_piece(3); x_piece(3);
      p2_step<9>(accs, c);
      mbar_wait(sb + B_EX + 16 * wg + 8, 0);
      silu_piece(4); x_piece(4);
      p2_step<10>(accs, c); sched_fence(c.zero); silu_piece(5); x_piece(5);
      p2_step<11>(accs, c); sched_fence(c.zero); silu_piece(6); x_piece(6);
      p2_step<12>(accs, c); p2_step<13>(accs, c); p2_step<14>(accs, c); p2_step<15>(accs, c);
      sched_fence(c.zero); silu_piece(7); x_piece(7);
      wg_wait<0>();
      if (t0) TS(32 + wg * 16);
#pragma unroll
      for (int i = 0; i < 8; i++) {
        uint32_t v[4];
#pragma unroll
        for (int k = 0; k < 4; k++) v[k] = fma2(pack2(accs[8 * i + 2 * k], accs[1 + 8 * i + 2 * k]), pk[4 * i + k], pk[32 + 4 * i + k]);
        asm volatile("stmatrix.sync.aligned.m8n8.x4.shared.b16 [%0], {%1,%2,%3,%4};" ::"r"((xa ^ ((i & 3) << 5)) + (i >> 2) * 16384), "r"(v[0]), "r"(v[1]), "r"(v[2]), "r"(v[3]) : "memory");
        if (i == 3 || i == 7) {
          asm volatile("fence.proxy.async.shared::cta;" ::: "memory");
          __syncwarp();
          if (elect_one()) tma3d_store(&mp.out, sb + OFF_X + (i >> 2) * 16384 + warp * 2048, j2 * 128 + (i >> 2) * 64, m2 * 64 + w * 16, wg);
        }
      }
      if (elect_one()) { asm volatile("cp.async.bulk.commit_group;\ncp.async.bulk.wait_group.read 0;" ::: "memory"); }
      if ((threadIdx.x & 127) == 0) { TS(33 + wg * 16); if (wg) TG(59); }
    }
  }
}

typedef CUresult (*EncodeFn)(CUtensorMap*, CUtensorMapDataType, cuuint32_t, void*, const cuuint64_t*, const cuuint64_t*, const cuuint32_t*, const cuuint32_t*,
                             CUtensorMapInterleave, CUtensorMapSwizzle, CUtensorMapL2promotion, CUtensorMapFloatOOBfill);

void encode(EncodeFn fn, CUtensorMap* tm, const void* p, int rank, const cuuint64_t* dims, const cuuint64_t* strides, const cuuint32_t* box) {
  const cuuint32_t es[5] = {1, 1, 1, 1, 1};
  fn(tm, CU_TENSOR_MAP_DATA_TYPE_BFLOAT16, rank, const_cast<void*>(p), dims, strides, box, es, CU_TENSOR_MAP_INTERLEAVE_NONE, CU_TENSOR_MAP_SWIZZLE_128B,
     PROMO, CU_TENSOR_MAP_FLOAT_OOB_FILL_NONE);
}

}

extern "C" void kernel_launch(void* const* d_in, const int* in_sizes, int n_in, void* d_out, int out_size) {
  (void)in_sizes; (void)n_in; (void)out_size;
  static EncodeFn fn = nullptr;
  static Scratch* gs = nullptr;
  if (!fn) {
    void* p = nullptr;
    cudaDriverEntryPointQueryResult qr;
    cudaGetDriverEntryPoint("cuTensorMapEncodeTiled", &p, cudaEnableDefault, &qr);
    fn = (EncodeFn)p;
    cudaGetSymbolAddress((void**)&gs, g_scratch);
    cudaFuncSetAttribute(fused_kernel, cudaFuncAttributeMaxDynamicSharedMemorySize, SMEM_BYTES);
  }
  const void *x = d_in[0], *wqkv = d_in[1], *wo = d_in[2], *wg = d_in[4], *wu = d_in[5], *wd = d_in[6];
  Maps mp;
  {
    const cuuint64_t dims[3] = {DM, SEQ / 2, 2}, st[2] = {DM * 4, DM * 2};
    const cuuint32_t box_in[3] = {64, 64, 2}, box_out[3] = {64, 16, 1};
    encode(fn, &mp.x, x, 3, dims, st, box_in);
    encode(fn, &mp.out, d_out, 3, dims, st, box_out);
  }
  {
    const cuuint64_t dims[2] = {DM, SEQ}, st[1] = {DM * 2};
    const cuuint32_t box[2] = {64, 128};
    encode(fn, &mp.xn, gs->xn, 2, dims, st, box);
  }
  {
    const cuuint32_t box[2] = {64, 64};
    const cuuint64_t dq[2] = {3 * DM, DM}, sq[1] = {3 * DM * 2}, df[2] = {DFF, DM}, sf[1] = {DFF * 2}, dw[2] = {DM, DM}, sw[1] = {DM * 2};
    encode(fn, &mp.wqkv, wqkv, 2, dq, sq, box);
    encode(fn, &mp.wg, wg, 2, df, sf, box);
    encode(fn, &mp.wu, wu, 2, df, sf, box);
    encode(fn, &mp.wo, wo, 2, dw, sw, box);
  }
  {
    const cuuint32_t box[5] = {64, 2, 4, 4, 2};
    const cuuint64_t st[4] = {DM * 2, 8 * DM * 2, 2 * DM * 2, 32 * DM * 2};
    const cuuint64_t dd[5] = {DM, 2, 4, 4, DFF / 32};
    encode(fn, &mp.wd, wd, 5, dd, st, box);
  }
  fused_kernel<<<NCTA, 384, SMEM_BYTES>>>((const uint4*)x, (const uint4*)wg, (const uint4*)wu, gs, mp);
}
```

```cpp
#include <cuda_runtime.h>
#include <cuda_bf16.h>
#include <cuda.h>
#include <stdint.h>

#define LN_LD 0
#define PROMO CU_TENSOR_MAP_L2_PROMOTION_L2_128B
#define G_KB 12
#define PF_D 4
#define PF_W 1
#define PF_H 1
#define PF_SLEEP 250
#define PF_S 16
#define SEND_MODE 3
#define XEARLY 1
#define LAG2 4
#define ROT 2
#define CS_KB 8
#define LN_KB 4

#define EVICT_FIRST 0x12F0000000000000ull
#define EVICT_NORMAL 0x1000000000000000ull
#define HINT_W EVICT_FIRST
#define HINT_H EVICT_FIRST
#define HINT_LAST EVICT_FIRST

namespace {

constexpr int SEQ = 2048, DM = 1024, DFF = 3584;
constexpr int NMAIN = 128, NCTA = 132;

constexpr uint32_t SM_BASE = 0x400;
constexpr uint32_t P1_STAGE = 49152, P2_STAGE = 32768;
constexpr uint32_t OFF_X = 196608;
constexpr uint32_t OFF_CS = OFF_X + 14336;
constexpr uint32_t OFF_BAR = 229376;
constexpr int NS2 = XEARLY ? 5 : 6;
constexpr uint32_t OFF_LAND = XEARLY ? (ROT ? 5 : 2) * P2_STAGE : OFF_X;
constexpr uint32_t OFF_XT = XEARLY ? OFF_X : (ROT ? 4 : 1) * P2_STAGE;
constexpr uint32_t B_F1 = OFF_BAR, B_E1 = B_F1 + 32, B_F2 = B_E1 + 32, B_E2 = B_F2 + 48;
constexpr uint32_t B_DEP = B_E2 + 48;
constexpr uint32_t B_AUX = B_DEP + 48, B_CS = B_AUX + 8, B_XT = B_CS + 8, B_EX = B_XT + 8, B_HALO = B_EX + 64, B_EP = B_HALO + 16, OFF_EPOCH = B_EP + 8;
constexpr uint32_t SMEM_BYTES = 232448;
constexpr uint32_t AT_V = 0, AT_K = 8192, AT_REM = 11264, AT_WG = 15360;

constexpr int FL_XN = 0, FL_H = 16, FL_P = 80, FL_HALO = 96, FL_N = FL_HALO + 256;
struct __align__(1024) Scratch {
  uint4 h[16 * 56 * 1024];
  uint4 o[16 * 16 * 1024];
  uint4 xn[SEQ * DM / 8];
  uint4 dpart[128 * 8 * 256];
  uint4 halo[2 * 128 * 2 * 128];
  ulonglong2 cspart[8 * 16 * 128];
  unsigned long long stats[SEQ];
  unsigned flags[FL_N * 32];
  unsigned epoch[NCTA * 2];
};
__device__ Scratch g_scratch;
#define TG(i) do {} while (0)
#define TSV(i, v) do {} while (0)
#define TS(i) do {} while (0)

struct Maps { CUtensorMap x, xn, out, wqkv, wg, wu, wd, wo; };

__device__ __forceinline__ void mbar_init(uint32_t bar, uint32_t cnt) { asm volatile("mbarrier.init.shared::cta.b64 [%0], %1;" ::"r"(bar), "r"(cnt)); }
__device__ __forceinline__ void mbar_expect_tx(uint32_t bar, uint32_t bytes) { asm volatile("mbarrier.arrive.expect_tx.shared::cta.b64 _, [%0], %1;" ::"r"(bar), "r"(bytes) : "memory"); }
__device__ __forceinline__ void mbar_arrive(uint32_t bar) { asm volatile("mbarrier.arrive.shared::cta.b64 _, [%0];" ::"r"(bar) : "memory"); }
__device__ __forceinline__ void mbar_arrive_cl(uint32_t bar) { asm volatile("mbarrier.arrive.shared::cluster.b64 _, [%0];" ::"r"(bar) : "memory"); }
__device__ __forceinline__ uint32_t mapa(uint32_t a, uint32_t cta) { uint32_t r; asm("mapa.shared::cluster.u32 %0, %1, %2;" : "=r"(r) : "r"(a), "r"(cta)); return r; }
__device__ __forceinline__ void mbar_wait(uint32_t bar, uint32_t parity) {
  asm volatile("{\n.reg .pred p;\n.reg .u32 n;\nmov.u32 n, 0;\nLAB_WAIT:\nmbarrier.try_wait.parity.shared::cta.b64 p, [%0], %1;\n@p bra LAB_DONE;\n"
               "add.u32 n, n, 1;\nsetp.gt.u32 p, n, 4000000;\n@p trap;\nbra LAB_WAIT;\nLAB_DONE:\n}" ::"r"(bar), "r"(parity) : "memory");
}
__device__ __forceinline__ void flag_wait(const unsigned* f, unsigned target) {
  asm volatile("{\n.reg .pred p;\n.reg .u32 n, v;\nmov.u32 n, 0;\nLAB_WAIT:\nld.relaxed.gpu.global.u32 v, [%0];\nsub.u32 v, v, %1;\nsetp.ge.s32 p, v, 0;\n@p bra LAB_DONE;\n"
               "nanosleep.u32 100;\nadd.u32 n, n, 1;\nsetp.gt.u32 p, n, 4000000;\n@p trap;\nbra LAB_WAIT;\nLAB_DONE:\nfence.acquire.gpu;\n}" ::"l"(f), "r"(target) : "memory");
}
__device__ __forceinline__ void flag_add(unsigned* f) { asm volatile("red.release.gpu.global.add.u32 [%0], 1;" ::"l"(f) : "memory"); }
__device__ __forceinline__ void fence_async() { asm volatile("fence.proxy.async.global;" ::: "memory"); }
__device__ __forceinline__ bool elect_one() { uint32_t p; asm volatile("{\n.reg .pred P;\nelect.sync _|P, 0xffffffff;\nselp.u32 %0, 1, 0, P;\n}" : "=r"(p)); return p; }
__device__ __forceinline__ void bar_sync(int id, int n) { asm volatile("bar.sync %0, %1;" ::"r"(id), "r"(n) : "memory"); }
__device__ __forceinline__ void bar_arrive(int id, int n) { asm volatile("bar.arrive %0, %1;" ::"r"(id), "r"(n) : "memory"); }

__device__ __forceinline__ void tma2d(uint32_t dst, const CUtensorMap* tm, uint32_t bar, int c0, int c1, uint64_t hint) {
  asm volatile("cp.async.bulk.tensor.2d.shared::cluster.global.mbarrier::complete_tx::bytes.L2::cache_hint [%0], [%1, {%3, %4}], [%2], %5;" ::"r"(dst), "l"(tm), "r"(bar), "r"(c0), "r"(c1), "l"(hint) : "memory");
}
__device__ __forceinline__ void tma2d_mc(uint32_t dst, const CUtensorMap* tm, uint32_t bar, int c0, int c1, uint64_t hint) {
  asm volatile("cp.async.bulk.tensor.2d.shared::cluster.global.mbarrier::complete_tx::bytes.multicast::cluster.L2::cache_hint [%0], [%1, {%3, %4}], [%2], %5, %6;" ::"r"(dst), "l"(tm), "r"(bar), "r"(c0), "r"(c1), "h"((uint16_t)3), "l"(hint) : "memory");
}
__device__ __forceinline__ void tma3d(uint32_t dst, const CUtensorMap* tm, uint32_t bar, int c0, int c1, int c2, uint64_t hint) {
  asm volatile("cp.async.bulk.tensor.3d.shared::cluster.global.mbarrier::complete_tx::bytes.L2::cache_hint [%0], [%1, {%3, %4, %5}], [%2], %6;" ::"r"(dst), "l"(tm), "r"(bar), "r"(c0), "r"(c1), "r"(c2), "l"(hint) : "memory");
}
__device__ __forceinline__ void tma5d(uint32_t dst, const CUtensorMap* tm, uint32_t bar, int c0, int c4, uint64_t hint) {
  asm volatile("cp.async.bulk.tensor.5d.shared::cluster.global.mbarrier::complete_tx::bytes.L2::cache_hint [%0], [%1, {%3, %5, %5, %5, %4}], [%2], %6;" ::"r"(dst), "l"(tm), "r"(bar), "r"(c0), "r"(c4), "r"(0), "l"(hint) : "memory");
}
__device__ __forceinline__ void tma5d_prefetch(const CUtensorMap* tm, int c0, int c4) {
  asm volatile("cp.async.bulk.prefetch.tensor.5d.L2.global [%0, {%1, %3, %3, %3, %2}];" ::"l"(tm), "r"(c0), "r"(c4), "r"(0) : "memory");
}
__device__ __forceinline__ void tma3d_store(const CUtensorMap* tm, uint32_t src, int c0, int c1, int c2) {
  asm volatile("cp.async.bulk.tensor.3d.global.shared::cta.bulk_group [%0, {%2, %3, %4}], [%1];" ::"l"(tm), "r"(src), "r"(c0), "r"(c1), "r"(c2) : "memory");
}
__device__ __forceinline__ void bulk_load(uint32_t dst, const void* src, uint32_t bytes, uint32_t bar, uint64_t hint) {
  asm volatile("cp.async.bulk.shared::cluster.global.mbarrier::complete_tx::bytes.L2::cache_hint [%0], [%1], %2, [%3], %4;" ::"r"(dst), "l"(src), "r"(bytes), "r"(bar), "l"(hint) : "memory");
}
__device__ __forceinline__ void bulk_load_mc(uint32_t dst, const void* src, uint32_t bytes, uint32_t bar, uint64_t hint) {
  asm volatile("cp.async.bulk.shared::cluster.global.mbarrier::complete_tx::bytes.multicast::cluster.L2::cache_hint [%0], [%1], %2, [%3], %4, %5;" ::"r"(dst), "l"(src), "r"(bytes), "r"(bar), "h"((uint16_t)3), "l"(hint) : "memory");
}
__device__ __forceinline__ uint4 lds128(uint32_t a) { uint4 v; asm volatile("ld.shared.v4.b32 {%0,%1,%2,%3}, [%4];" : "=r"(v.x), "=r"(v.y), "=r"(v.z), "=r"(v.w) : "r"(a) : "memory"); return v; }
__device__ __forceinline__ void sts128(uint32_t a, uint4 v) { asm volatile("st.shared.v4.b32 [%0], {%1,%2,%3,%4};" ::"r"(a), "r"(v.x), "r"(v.y), "r"(v.z), "r"(v.w) : "memory"); }
__device__ __forceinline__ void stg128(void* p, uint32_t a, uint32_t b, uint32_t c, uint32_t d) { asm volatile("st.global.v4.b32 [%0], {%1,%2,%3,%4};" ::"l"(p), "r"(a), "r"(b), "r"(c), "r"(d) : "memory"); }

__device__ __forceinline__ uint32_t pack2(float lo, float hi) { uint32_t r; asm("cvt.rn.bf16x2.f32 %0, %1, %2;" : "=r"(r) : "f"(hi), "f"(lo)); return r; }
__device__ __forceinline__ float lo_f(uint32_t v) { return __uint_as_float(v << 16); }
__device__ __forceinline__ float hi_f(uint32_t v) { return __uint_as_float(v & 0xffff0000u); }
__device__ __forceinline__ float bf16r(float v) { return lo_f(pack2(v, 0.f)); }
__device__ __forceinline__ uint32_t mul2(uint32_t a, uint32_t b) { uint32_t r; asm("mul.rn.bf16x2 %0, %1, %2;" : "=r"(r) : "r"(a), "r"(b)); return r; }
__device__ __forceinline__ uint32_t add2(uint32_t a, uint32_t b) { uint32_t r; asm("add.rn.bf16x2 %0, %1, %2;" : "=r"(r) : "r"(a), "r"(b)); return r; }
__device__ __forceinline__ uint32_t sub2(uint32_t a, uint32_t b) { uint32_t r; asm("sub.rn.bf16x2 %0, %1, %2;" : "=r"(r) : "r"(a), "r"(b)); return r; }
__device__ __forceinline__ uint32_t fma2(uint32_t a, uint32_t b, uint32_t c) { uint32_t r; asm("fma.rn.bf16x2 %0, %1, %2, %3;" : "=r"(r) : "r"(a), "r"(b), "r"(c)); return r; }
__device__ __forceinline__ uint32_t max2(uint32_t a, uint32_t b) { uint32_t r; asm("max.bf16x2 %0, %1, %2;" : "=r"(r) : "r"(a), "r"(b)); return r; }
__device__ __forceinline__ float ex2f(float x) { float y; asm("ex2.approx.ftz.f32 %0, %1;" : "=f"(y) : "f"(x)); return y; }
__device__ __forceinline__ float rcpf(float x) { float y; asm("rcp.approx.ftz.f32 %0, %1;" : "=f"(y) : "f"(x)); return y; }
__device__ __forceinline__ float gelu2(float g) {
  float z = g * fmaf(g * g, 0.035677408136300125f, 0.7978845608028654f), t;
  asm("tanh.approx.f32 %0, %1;" : "=f"(t) : "f"(z));
  return fmaf(g, t, g);
}

__device__ __forceinline__ float silu_half(float z) { float t; asm("tanh.approx.f32 %0, %1;" : "=f"(t) : "f"(z)); return fmaf(z, t, z); }

__device__ __forceinline__ void wg_fence() { asm volatile("wgmma.fence.sync.aligned;" ::: "memory"); }
__device__ __forceinline__ void wg_commit() { asm volatile("wgmma.commit_group.sync.aligned;" ::: "memory"); }
template <int N> __device__ __forceinline__ void wg_wait() { asm volatile("wgmma.wait_group.sync.aligned %0;" ::"n"(N) : "memory"); }
#define A8(o) "+f"(d[(o)]), "+f"(d[(o) + 1]), "+f"(d[(o) + 2]), "+f"(d[(o) + 3]), "+f"(d[(o) + 4]), "+f"(d[(o) + 5]), "+f"(d[(o) + 6]), "+f"(d[(o) + 7])
#define A64(o) A8(o), A8((o) + 8), A8((o) + 16), A8((o) + 24), A8((o) + 32), A8((o) + 40), A8((o) + 48), A8((o) + 56)
#define REGS0_63 "%0,%1,%2,%3,%4,%5,%6,%7,%8,%9,%10,%11,%12,%13,%14,%15,%16,%17,%18,%19,%20,%21,%22,%23,%24,%25,%26,%27,%28,%29,%30,%31," \
                 "%32,%33,%34,%35,%36,%37,%38,%39,%40,%41,%42,%43,%44,%45,%46,%47,%48,%49,%50,%51,%52,%53,%54,%55,%56,%57,%58,%59,%60,%61,%62,%63"
#define REGS64_127 "%64,%65,%66,%67,%68,%69,%70,%71,%72,%73,%74,%75,%76,%77,%78,%79,%80,%81,%82,%83,%84,%85,%86,%87,%88,%89,%90,%91,%92,%93,%94,%95," \
                   "%96,%97,%98,%99,%100,%101,%102,%103,%104,%105,%106,%107,%108,%109,%110,%111,%112,%113,%114,%115,%116,%117,%118,%119,%120,%121,%122,%123,%124,%125,%126,%127"
template <int ACCUM> __device__ __forceinline__ void wgmma256(float (&d)[128], uint32_t a_lo, uint32_t a_hi, uint32_t b_lo) {
  asm volatile("{\n.reg .pred p;\n.reg .b64 da, db;\nsetp.ne.b32 p, %131, 0;\nmov.b64 da, {%128, %129};\nmov.b64 db, {%130, 0x40000040};\n"
               "wgmma.mma_async.sync.aligned.m64n256k16.f32.bf16.bf16 {" REGS0_63 "," REGS64_127 "}, da, db, p, 1, 1, 0, 1;\n}"
               : A64(0), A64(64) : "r"(a_lo), "r"(a_hi), "r"(b_lo), "n"(ACCUM));
}
__device__ __forceinline__ void wgmma256_rs(float (&d)[128], uint32_t a0, uint32_t a1, uint32_t z0, uint32_t z1, uint32_t b_lo) {
  asm volatile("{\n.reg .b64 db;\nmov.b64 db, {%132, 0x00000008};\n"
               "wgmma.mma_async.sync.aligned.m64n256k16.f32.bf16.bf16 {" REGS0_63 "," REGS64_127 "}, {%128,%129,%130,%131}, db, 1, 1, 1, 0;\n}"
               : A64(0), A64(64) : "r"(a0), "r"(a1), "r"(z0), "r"(z1), "r"(b_lo));
}
template <int ACCUM> __device__ __forceinline__ void wgmma128(float (&d)[64], uint32_t a_lo, uint32_t b_lo) {
  asm volatile("{\n.reg .pred p;\n.reg .b64 da, db;\nsetp.ne.b32 p, %66, 0;\nmov.b64 da, {%64, 0x80000020};\nmov.b64 db, {%65, 0x40000040};\n"
               "wgmma.mma_async.sync.aligned.m64n128k16.f32.bf16.bf16 {" REGS0_63 "}, da, db, p, 1, 1, 0, 1;\n}"
               : A64(0) : "r"(a_lo), "r"(b_lo), "n"(ACCUM));
}
template <int ACCUM> __device__ __forceinline__ void hmma(float (&c)[4], uint32_t a0, uint32_t a1, uint32_t a2, uint32_t a3, uint32_t b0, uint32_t b1) {
  if (ACCUM)
    asm volatile("mma.sync.aligned.m16n8k16.row.col.f32.bf16.bf16.f32 {%0,%1,%2,%3}, {%4,%5,%6,%7}, {%8,%9}, {%0,%1,%2,%3};"
                 : "+f"(c[0]), "+f"(c[1]), "+f"(c[2]), "+f"(c[3]) : "r"(a0), "r"(a1), "r"(a2), "r"(a3), "r"(b0), "r"(b1));
  else
    asm volatile("mma.sync.aligned.m16n8k16.row.col.f32.bf16.bf16.f32 {%0,%1,%2,%3}, {%4,%5,%6,%7}, {%8,%9}, {%10,%10,%10,%10};"
                 : "=f"(c[0]), "=f"(c[1]), "=f"(c[2]), "=f"(c[3]) : "r"(a0), "r"(a1), "r"(a2), "r"(a3), "r"(b0), "r"(b1), "f"(0.f));
}
__device__ __forceinline__ uint32_t movm(uint32_t a) { uint32_t d; asm volatile("movmatrix.sync.aligned.m8n8.trans.b16 %0, %1;" : "=r"(d) : "r"(a)); return d; }
template <int N> __device__ __forceinline__ void pin(uint32_t* r) {
#pragma unroll
  for (int i = 0; i < N; i++) asm volatile("" : "+r"(r[i]));
}
template <int N> __device__ __forceinline__ void pin(float* r) {
#pragma unroll
  for (int i = 0; i < N; i++) asm volatile("" : "+f"(r[i]));
}
__device__ __forceinline__ void sched_fence(uint32_t zero) {
  asm volatile("{\n.reg .pred p;\n.reg .u32 n;\nmov.u32 n, %0;\nLAB_F:\nsetp.eq.u32 p, n, 0;\n@p bra.uni LAB_D;\nnanosleep.u32 n;\nsub.u32 n, n, 1;\nbra.uni LAB_F;\nLAB_D:\n}" ::"r"(zero) : "memory");
}
__device__ __forceinline__ uint4 ldsm(uint32_t a) { uint4 v; asm volatile("ldmatrix.sync.aligned.m8n8.x4.shared.b16 {%0,%1,%2,%3}, [%4];" : "=r"(v.x), "=r"(v.y), "=r"(v.z), "=r"(v.w) : "r"(a) : "memory"); return v; }
__device__ __forceinline__ uint4 ldsm_t(uint32_t a) { uint4 v; asm volatile("ldmatrix.sync.aligned.m8n8.x4.trans.shared.b16 {%0,%1,%2,%3}, [%4];" : "=r"(v.x), "=r"(v.y), "=r"(v.z), "=r"(v.w) : "r"(a) : "memory"); return v; }

constexpr int BAR_LAG = 1, BAR_MMA = 2, BAR_EV = 3;

struct Cons {
  uint32_t sb;
  uint32_t a0, a1, ah;
  uint32_t rel;
  bool do_rel;
  int wg;
  uint32_t zero;
};
#define REL_TS(n) TS(64 + (n))
constexpr uint32_t DB_LO = ((SM_BASE + 16384) >> 4) | ((8192 >> 4) << 16);

template <int ST, int ACCUM, bool WAIT = true> __device__ __forceinline__ void p1_issue(float (&acc)[128], const Cons& c, uint32_t parity) {
  if (WAIT) mbar_wait(c.sb + B_F1 + 8 * ST, parity);
  wg_fence();
  constexpr uint32_t so = (ST ^ ROT) * (P1_STAGE >> 4);
  wgmma256<ACCUM>(acc, c.a0 + so, c.ah, DB_LO + so);
  wgmma256<1>(acc, c.a0 + so + 2, c.ah, DB_LO + so + 128);
  wgmma256<1>(acc, c.a1 + so, c.ah, DB_LO + so + 256);
  wgmma256<1>(acc, c.a1 + so + 2, c.ah, DB_LO + so + 384);
  wg_commit();
}
__device__ __forceinline__ void release(const Cons& c, uint32_t bar) { if (c.do_rel) mbar_arrive_cl(c.rel + bar); }
template <int KB, bool WAIT = true, int LAG = 2> __device__ __forceinline__ void p1_step(float (&acc)[128], const Cons& c) {
  if (KB == 16 - LAG) { if (c.wg == 1) { wg_wait<0>(); release(c, B_E1 + 8 * ((KB - 1) & 3)); bar_sync(BAR_LAG, 256); } }
  p1_issue<KB & 3, KB != 0, WAIT>(acc, c, (KB >> 2) & 1);
  if (KB == 15) { if (c.wg == 0) bar_arrive(BAR_LAG, 256); }
  if (KB > 0) { wg_wait<1>(); if (KB != 16 - LAG || c.wg == 0) release(c, B_E1 + 8 * ((KB - 1) & 3)); }
  if (KB == 15) { wg_wait<0>(); release(c, B_E1 + 8 * 3); }
}
template <int A, int B> __device__ __forceinline__ void p1_range(float (&acc)[128], const Cons& c) {
  if constexpr (A < B) { p1_step<A>(acc, c); p1_range<A + 1, B>(acc, c); }
}
template <int T> __device__ __forceinline__ void p2_step(float (&acc)[64], const Cons& c) {
  if (T == 16 - LAG2) { if (c.wg == 1) bar_sync(BAR_LAG, 256); }
  mbar_wait(c.sb + B_F2 + 8 * (T % NS2), (T / NS2) & 1);
  wg_fence();
  constexpr uint32_t so = ((T % NS2 + (ROT ? 0 : 3)) % 6) * (P2_STAGE >> 4);
  wgmma128<T != 0>(acc, c.a0 + so, DB_LO + so);
  wgmma128<1>(acc, c.a0 + so + 2, DB_LO + so + 128);
  wgmma128<1>(acc, c.a1 + so, DB_LO + so + 256);
  wgmma128<1>(acc, c.a1 + so + 2, DB_LO + so + 384);
  wg_commit();
  if (T == 15) { if (c.wg == 0) bar_arrive(BAR_LAG, 256); }
  if (T <= 11) { wg_wait<1>(); release(c, T ? B_E2 + 8 * ((T + NS2 - 1) % NS2) : B_E1 + 8); }
}

template <int P> __device__ __forceinline__ void geglu_piece(const uint32_t (&pk)[64], uint8_t* dst, const float (&rs)[2]) {
  constexpr int cg = P >> 1, r = P & 1;
  const float rq = rs[r] * 0.25f;
  uint32_t v[4];
#pragma unroll
  for (int i = 0; i < 4; i++) {
    const uint32_t g = pk[2 * (4 * cg + i) + r];
    v[i] = mul2(pack2(gelu2(lo_f(g) * rs[r]) * rq, gelu2(hi_f(g) * rs[r]) * rq), pk[32 + 2 * (4 * cg + i) + r]);
  }
  stg128(dst + cg * 8192 + r * 512, v[0], v[1], v[2], v[3]);
}
template <int KB> __device__ __forceinline__ void geglu_tile(float (&acc)[128], const uint32_t (&pk)[64], const Cons& c, uint8_t* dst, int ev, const float (&rs)[2]) {
  if constexpr (KB < 14) {
    p1_step<KB>(acc, c);
    if (KB >= 1 && KB <= 8) geglu_piece<(KB - 1) & 7>(pk, dst, rs);
    if (KB == 8) bar_arrive(ev, 288);
    geglu_tile<KB + 1>(acc, pk, c, dst, ev, rs);
  }
}

__device__ __forceinline__ void attn_tile(float (&acc)[128], const uint32_t (&pk)[64], const Cons& c, int round, int warp, int m, Scratch* gs, uint8_t* hdst, uint8_t* odst) {
  const int lane = threadIdx.x & 31, w = warp & 3, rho = lane >> 2, q = lane & 3;
  const uint32_t at = c.sb + OFF_X + c.wg * AT_WG, swz = (lane ^ (lane >> 3)) << 4;
  uint32_t gg[16];
  p1_step<0>(acc, c);
  p1_step<1>(acc, c);
#pragma unroll
  for (int i = 0; i < 4; i++) {
    const int h = i & 1, r = i >> 1;
    sts128(at + AT_V + (2 * w + r) * 1024 + h * 512 + swz, make_uint4(pk[32 + 8 * h + r], pk[34 + 8 * h + r], pk[36 + 8 * h + r], pk[38 + 8 * h + r]));
  }
  if (w < 3) {
#pragma unroll
    for (int i = 0; i < 8; i++) asm volatile("st.shared.b32 [%0], %1;" ::"r"(at + AT_K + w * 1024 + i * 128 + lane * 4), "r"(pk[17 + 2 * i]) : "memory");
  } else {
    uint8_t* g = (uint8_t*)gs->halo + ((round * 128 + blockIdx.x) * 2 + c.wg) * 2048;
#pragma unroll
    for (int i = 0; i < 8; i++) asm volatile("st.global.b32 [%0], %1;" ::"l"(g + i * 128 + lane * 4), "r"(pk[17 + 2 * i]) : "memory");
#pragma unroll
    for (int h = 0; h < 2; h++) stg128(g + 1024 + h * 512 + swz, pk[33 + 8 * h], pk[35 + 8 * h], pk[37 + 8 * h], pk[39 + 8 * h]);
    bar_arrive(BAR_EV + 2 + round, 96);
  }
  __syncwarp();
  if (lane == 0) mbar_arrive(c.sb + B_HALO + 8 * round);
  if (round) {
#pragma unroll
    for (int p = 0; p < 4; p++) asm volatile("ld.global.cg.v4.b32 {%0,%1,%2,%3}, [%4];" : "=r"(gg[4 * p]), "=r"(gg[4 * p + 1]), "=r"(gg[4 * p + 2]), "=r"(gg[4 * p + 3]) : "l"(hdst + (p >> 1) * 8192 + (p & 1) * 512) : "memory");
  }
  auto gu_piece = [&](int p) {
    uint32_t v[4];
#pragma unroll
    for (int i = 0; i < 4; i++) {
      const uint32_t g = pk[48 + 8 * (p >> 1) + 2 * i + (p & 1)];
      v[i] = mul2(round ? gg[4 * p + i] : 0x3e803e80u, round ? g : pack2(gelu2(lo_f(g)), gelu2(hi_f(g))));
    }
    stg128(hdst + (p >> 1) * 8192 + (p & 1) * 512, v[0], v[1], v[2], v[3]);
  };
  p1_step<2>(acc, c);
  p1_step<3>(acc, c); gu_piece(0);
  p1_step<4>(acc, c); gu_piece(1);
  p1_step<5>(acc, c); gu_piece(2);
  p1_step<6>(acc, c); gu_piece(3);
  p1_step<7>(acc, c);
  p1_step<8>(acc, c);
  const bool first = m == 0 && w == 0;
  uint32_t kl[16];
  mbar_wait(c.sb + B_HALO + 8 * round, 0);
  {
    const uint32_t ka = at + lane * 4 + (w ? AT_K + (w - 1) * 1024 : (first ? AT_K : AT_REM + round * 2048));
#pragma unroll
    for (int i = 0; i < 8; i++) {
      asm volatile("ld.shared.b32 %0, [%1];" : "=r"(kl[2 * i]) : "r"(ka + i * 128) : "memory");
      kl[2 * i + 1] = pk[16 + 2 * i] | c.zero;
    }
  }
  float st[4][4];
  pin<16>(kl);
  bar_sync(BAR_MMA, 256);
  mbar_wait(c.sb + B_F1 + 8 * 1, 0);
#pragma unroll
  for (int ks = 0; ks < 2; ks++) {
#pragma unroll
    for (int h = 0; h < 2; h++) {
      const int o = 8 * h + 4 * ks;
      if (ks == 0) { hmma<0>(st[2 * h], kl[o], kl[o + 1], kl[o + 2], kl[o + 3], pk[o], pk[o + 2]); hmma<0>(st[2 * h + 1], pk[16 + o], pk[17 + o], pk[18 + o], pk[19 + o], pk[o + 1], pk[o + 3]); }
      else { hmma<1>(st[2 * h], kl[o], kl[o + 1], kl[o + 2], kl[o + 3], pk[o], pk[o + 2]); hmma<1>(st[2 * h + 1], pk[16 + o], pk[17 + o], pk[18 + o], pk[19 + o], pk[o + 1], pk[o + 3]); }
    }
  }
  sched_fence(c.zero);
  bar_sync(BAR_MMA, 256);
  p1_step<9, false>(acc, c);
  sched_fence(c.zero);
  pin<16>(&st[0][0]);
  const bool le0 = 2 * q <= rho, le1 = 2 * q + 1 <= rho;
  uint32_t la[2], lb[2], mx[2];
#pragma unroll
  for (int h = 0; h < 2; h++) {
    uint32_t l[2];
#pragma unroll
    for (int r = 0; r < 2; r++) {
      const float (&t)[4] = st[2 * h + r];
      l[r] = movm(pack2(rho <= 2 * q ? t[2] : t[0], rho <= 2 * q + 1 ? t[3] : t[1]));
      l[r] = fma2(l[r], 0x3e353e35u, mul2(l[r], 0x379e379eu));
    }
    la[h] = __byte_perm(l[0], l[1], 0x5410); lb[h] = __byte_perm(l[0], l[1], 0x7632);
    if (first && !le0) la[h] = (la[h] & 0xffff0000u) | 0xce6eu;
    if (first && !le1) lb[h] = (lb[h] & 0xffff0000u) | 0xce6eu;
    mx[h] = max2(la[h], lb[h]);
  }
#pragma unroll
  for (int o = 1; o <= 2; o++) { mx[0] = max2(mx[0], __shfl_xor_sync(~0u, mx[0], o)); mx[1] = max2(mx[1], __shfl_xor_sync(~0u, mx[1], o)); }
  const float L2E = 1.4426950408889634f;
  float pr[2][4], z[4];
#pragma unroll
  for (int h = 0; h < 2; h++) {
    pr[h][0] = ex2f((lo_f(la[h]) - lo_f(mx[h])) * L2E); pr[h][1] = ex2f((lo_f(lb[h]) - lo_f(mx[h])) * L2E);
    pr[h][2] = ex2f((hi_f(la[h]) - hi_f(mx[h])) * L2E); pr[h][3] = ex2f((hi_f(lb[h]) - hi_f(mx[h])) * L2E);
    z[2 * h] = pr[h][0] + pr[h][1]; z[2 * h + 1] = pr[h][2] + pr[h][3];
  }
  p1_step<10>(acc, c);
#pragma unroll
  for (int o = 1; o <= 2; o++) {
#pragma unroll
    for (int i = 0; i < 4; i++) z[i] += __shfl_xor_sync(~0u, z[i], o);
  }
  const uint32_t LE = (le0 ? 0xffffu : 0u) | (le1 ? 0xffff0000u : 0u);
  uint32_t P[4][2];
  uint4 vt[4][2];
  {
    const uint32_t row = (lane & 7) * 64 + ((((lane >> 3) & 1) ^ ((lane & 7) >> 1)) << 4);
    const uint32_t v1 = at + AT_V + (2 * w + (lane >> 4)) * 1024 + row;
    const uint32_t v0 = (w || lane >= 16) ? v1 - 1024 : (first ? v1 : at + AT_REM + round * 2048 + 1024 + row);
#pragma unroll
    for (int i = 0; i < 4; i++) {
      const float rz = rcpf(z[i]);
      const uint32_t p = pack2(pr[i >> 1][2 * (i & 1)] * rz, pr[i >> 1][2 * (i & 1) + 1] * rz);
      P[i][0] = p & ~LE; P[i][1] = p & LE;
      const uint32_t a = ((i & 1) ? v1 : v0) + (i >> 1) * 512;
      vt[i][0] = ldsm_t(a); vt[i][1] = ldsm_t(a ^ 32);
    }
  }
  float ot[4][2][4];
  pin<8>(&P[0][0]);
  bar_sync(BAR_MMA, 256);
  mbar_wait(c.sb + B_F1 + 8 * 3, 0);
#pragma unroll
  for (int i = 0; i < 8; i++) { const uint4& v = vt[i >> 1][i & 1]; hmma<0>(ot[i >> 1][i & 1], v.x, v.y, v.z, v.w, P[i >> 1][0], P[i >> 1][1]); }
  sched_fence(c.zero);
  bar_sync(BAR_MMA, 256);
  p1_step<11, false>(acc, c);
  sched_fence(c.zero);
  pin<32>(&ot[0][0][0]);
  auto o_piece = [&](int i) {
    stg128(odst + (i >> 1) * 8192 + (i & 1) * 512, movm(pack2(ot[i][0][0], ot[i][0][1])), movm(pack2(ot[i][0][2], ot[i][0][3])), movm(pack2(ot[i][1][0], ot[i][1][1])), movm(pack2(ot[i][1][2], ot[i][1][3])));
  };
  o_piece(0); o_piece(1);
  p1_step<12>(acc, c);
  o_piece(2); o_piece(3);
  if (round) bar_arrive(BAR_EV + 4, 288);
  p1_step<13>(acc, c);
}

__device__ __forceinline__ void ln_moments(const uint32_t* raw, float& c0, float& s, float& v) {
  c0 = lo_f(__shfl_sync(~0u, raw[0], 0));
  float ss[4] = {0.f, 0.f, 0.f, 0.f}, vv[4] = {0.f, 0.f, 0.f, 0.f};
#pragma unroll
  for (int i = 0; i < 16; i++) {
    const float a = lo_f(raw[i]) - c0, b = hi_f(raw[i]) - c0;
    ss[(2 * i) & 3] += a; ss[(2 * i + 1) & 3] += b;
    vv[(2 * i) & 3] = fmaf(a, a, vv[(2 * i) & 3]); vv[(2 * i + 1) & 3] = fmaf(b, b, vv[(2 * i + 1) & 3]);
  }
  s = (ss[0] + ss[1]) + (ss[2] + ss[3]); v = (vv[0] + vv[1]) + (vv[2] + vv[3]);
}
__device__ __forceinline__ void ln_reduce(float& s, float& v) {
#pragma unroll
  for (int o = 16; o; o >>= 1) { s += __shfl_xor_sync(~0u, s, o); v += __shfl_xor_sync(~0u, v, o); }
}
__device__ __forceinline__ uint32_t ln_finish(float c0, float s, float v) {
  s *= 1.0f / DM;
  float sd;
  asm("sqrt.approx.ftz.f32 %0, %1;" : "=f"(sd) : "f"(bf16r(bf16r(fmaxf(fmaf(v, 1.0f / DM, -s * s), 0.f)) + 1e-5f)));
  return pack2(c0 + s, sd);
}
__device__ __forceinline__ void ln_store(const uint32_t* raw, uint32_t st, uint4* dst) {
  const uint32_t m2 = __byte_perm(st, st, 0x1010);
  const float rinv = rcpf(hi_f(st));
#pragma unroll
  for (int c = 0; c < 4; c++) {
    uint32_t v[4];
#pragma unroll
    for (int i = 0; i < 4; i++) { const uint32_t t = sub2(raw[4 * c + i], m2); v[i] = pack2(lo_f(t) * rinv, hi_f(t) * rinv); }
    stg128(dst + 32 * c, v[0], v[1], v[2], v[3]);
  }
}
__device__ __forceinline__ void col_sums(uint32_t tile, ulonglong2* part, uint32_t tag) {
  const int lane = threadIdx.x & 31;
  float cs[8] = {0, 0, 0, 0, 0, 0, 0, 0};
  uint32_t base = tile + ((lane >> 3) & 1) * 8192 + (lane >> 4) * 4096 + ((lane & 7) << 4);
#pragma unroll 1
  for (int k0 = 0; k0 < 8; k0++, base = (base ^ ((k0 ^ (k0 - 1)) << 4)) + 128) {
    uint4 v[4];
#pragma unroll
    for (int k = 0; k < 4; k++) v[k] = lds128(base + k * 1024);
#pragma unroll
    for (int k = 0; k < 4; k++) {
      cs[0] += lo_f(v[k].x); cs[1] += hi_f(v[k].x); cs[2] += lo_f(v[k].y); cs[3] += hi_f(v[k].y);
      cs[4] += lo_f(v[k].z); cs[5] += hi_f(v[k].z); cs[6] += lo_f(v[k].w); cs[7] += hi_f(v[k].w);
    }
  }
  const bool up = lane >= 16;
#pragma unroll
  for (int i = 0; i < 2; i++) {
    const float a = (up ? cs[4 + 2 * i] : cs[2 * i]) + __shfl_xor_sync(~0u, up ? cs[2 * i] : cs[4 + 2 * i], 16);
    const float b = (up ? cs[5 + 2 * i] : cs[1 + 2 * i]) + __shfl_xor_sync(~0u, up ? cs[1 + 2 * i] : cs[5 + 2 * i], 16);
    asm volatile("{\n.reg .b64 a, b;\nmov.b64 a, {%1, %3};\nmov.b64 b, {%2, %3};\nst.relaxed.gpu.global.v2.b64 [%0], {a, b};\n}"
                 ::"l"(part + 32 * (i + (up ? 2 : 0)) + (lane & 15)), "r"(__float_as_uint(a)), "r"(__float_as_uint(b)), "r"(tag) : "memory");
  }
  asm volatile("fence.proxy.async.shared::cta;" ::: "memory");
}

__global__ void __cluster_dims__(2, 1, 1) __launch_bounds__(384, 1)
fused_kernel(const uint4* __restrict__ x, const uint4* __restrict__ wgate, const uint4* __restrict__ wup, Scratch* gs, const __grid_constant__ Maps mp) {
  extern __shared__ __align__(1024) uint8_t smem_raw[];
  const uint32_t sb = (uint32_t)__cvta_generic_to_shared(smem_raw);
  const unsigned t_start = 0;
  const int warp = __shfl_sync(~0u, threadIdx.x >> 5, 0), lane = threadIdx.x & 31;
  const int m = blockIdx.x & 15, j = blockIdx.x >> 4, rank = blockIdx.x & 1;
  const int m2 = blockIdx.x >> 3, j2 = blockIdx.x & 7;
  const bool helper = blockIdx.x >= NMAIN;
  if (warp >= 8) {
    asm volatile("setmaxnreg.dec.sync.aligned.u32 40;");
    if (warp == 8) {
      if (elect_one()) {
        asm volatile("prefetch.tensormap [%0];\nprefetch.tensormap [%1];\nprefetch.tensormap [%2];" ::"l"(&mp.x), "l"(&mp.wg), "l"(&mp.wu) : "memory");
        for (int s = 0; s < 4; s++) mbar_init(sb + B_F1 + 8 * s, 1);
        if (!helper) mbar_arrive(sb + B_F1);
        asm volatile("fence.mbarrier_init.release.cluster;" ::: "memory");
      }
      __syncwarp();
    } else if (warp == 9) {
      if (elect_one()) {
        if ((sb & 0xffffff) != SM_BASE) asm volatile("trap;");
        for (int s = 0; s < 4; s++) mbar_init(sb + B_E1 + 8 * s, 4);
        for (int s = 0; s < 6; s++) { mbar_init(sb + B_F2 + 8 * s, 1); mbar_init(sb + B_E2 + 8 * s, 4); }
        for (int s = 0; s < 6; s++) mbar_init(sb + B_DEP + 8 * s, 1);
        mbar_init(sb + B_AUX, 8); mbar_init(sb + B_EP, 1); mbar_init(sb + B_XT, 1); mbar_init(sb + B_CS, 1);
        for (int s = 0; s < 8; s++) { mbar_init(sb + B_EX + 8 * s, 1); mbar_expect_tx(sb + B_EX + 8 * s, 4096); }
        mbar_init(sb + B_HALO, 9); mbar_init(sb + B_HALO + 8, 9);
        asm volatile("fence.mbarrier_init.release.cluster;" ::: "memory");
      }
      __syncwarp();
    }
    asm volatile("barrier.cluster.arrive.relaxed.aligned;" ::: "memory");
    if (warp == 8 && !helper) {
      if (elect_one()) {
        TS(0); TG(51);
#pragma unroll 1
        for (int kb = 1; kb < 4; kb++) {
          const uint32_t sa = sb + (kb ^ ROT) * P1_STAGE, fb = sb + B_F1 + 8 * kb;
          mbar_expect_tx(fb, P1_STAGE);
          tma3d(sa, &mp.x, fb, kb * 64, m * 64, 0, EVICT_NORMAL);
          tma2d(sa + 16384, &mp.wg, fb, j * 128, kb * 64, EVICT_NORMAL); tma2d(sa + 32768, &mp.wu, fb, j * 128, kb * 64, EVICT_NORMAL);
          tma2d(sa + 24576, &mp.wg, fb, j * 128 + 64, kb * 64, EVICT_NORMAL); tma2d(sa + 40960, &mp.wu, fb, j * 128 + 64, kb * 64, EVICT_NORMAL);
        }
        TS(7);
      }
      __syncwarp();
    }
    asm volatile("barrier.cluster.wait.aligned;" ::: "memory");
    if (helper) {
      if (warp == 8) {
        unsigned e = 0;
        if (elect_one()) {
#pragma unroll 1
          for (int i = 0; i < 16; i++) {
            const uint32_t fb = sb + B_F1 + 8 * (i >> 2);
            if (!(i & 3)) mbar_expect_tx(fb, P1_STAGE);
            tma5d(sb + ((i >> 2) ^ ROT) * P1_STAGE + 16384 + (i & 3) * 8192, &mp.wd, fb, (blockIdx.x - NMAIN) * 256 + (i & 3) * 64, (i >> 2) * 2, HINT_W);
          }
        }
        if (lane == 0) { unsigned* ep = &gs->epoch[blockIdx.x * 2]; e = *ep + 1; *ep = e; }
        e = __shfl_sync(~0u, e, 0);
        if (lane < 16) flag_wait(&gs->flags[(FL_H + lane * 4) * 32], e * 8u);
        __syncwarp();
        if (elect_one()) {
          fence_async();
          TS(0);
#pragma unroll 1
          for (int i = 0; i < 64; i++) {
            const uint32_t fb = sb + B_F1 + 8 * (i & 3);
            if (i >= 4) { mbar_wait(sb + B_E1 + 8 * (i & 3), ~(i >> 2) & 1); mbar_expect_tx(fb, 16384); }
            bulk_load(sb + ((i & 3) ^ ROT) * P1_STAGE, gs->h + ((i >> 2) * 56 + (i & 3)) * 1024, 16384, fb, EVICT_NORMAL);
          }
        }
      } else if (warp == 9) {
#pragma unroll 1
        for (int t = 0; t < 16; t++) {
          bar_sync(BAR_EV + (t & 1), 288);
          if (lane == 0) { flag_add(&gs->flags[(FL_P + t) * 32]); TS(64 + t); }
          __syncwarp();
        }
      }
    } else if (warp == 8) {
      if (elect_one()) {
        uint32_t par = 0;

        auto x_load = [&]() {
          mbar_expect_tx(sb + B_XT, 32768);
          tma3d(sb + OFF_XT, &mp.x, sb + B_XT, j2 * 128, m2 * 64, 0, HINT_LAST); tma3d(sb + OFF_XT + 16384, &mp.x, sb + B_XT, j2 * 128 + 64, m2 * 64, 0, HINT_LAST);
        };
        auto d_prefetch = [&](int i) {
          if (PF_W == 1 && (m2 >> 2) == (i & 3)) tma5d_prefetch(&mp.wd, (j2 >> 1) * 256 + (m2 & 3) * 64, (2 * i + 4 + rank) * 2);
          if (PF_H == 1 && i < 6) asm volatile("cp.async.bulk.prefetch.L2.global [%0], 4096;" ::"l"(gs->h + (m2 * 56 + 2 * i + 4 + rank) * 1024 + (j2 >> 1) * 256) : "memory");
        };
        for (int R = 0; R < 5; R++) {
          const CUtensorMap *mb0, *mb1;
          int n0, n1;
          if (R == 1 || R == 2) {
            mb0 = &mp.wqkv; n0 = 64 * (j + 8 * (R - 1)) + rank * 2048;
            mb1 = rank ? (R == 1 ? &mp.wg : &mp.wu) : &mp.wqkv; n1 = rank ? 1024 + 64 * j : n0 + 1024;
          } else {
            mb0 = mb1 = rank ? &mp.wu : &mp.wg;
            n0 = 128 * j + (R ? 1024 * R - 1536 : 0); n1 = n0 + 64;
          }
#pragma unroll 1
          for (int kb = R ? 0 : 4; kb < 16; kb++) {
            if (R == 0 && kb == 4) { for (int i = 1; i < 8; i++) asm volatile("prefetch.tensormap [%0];" ::"l"(&mp.x + i) : "memory"); }
            if (R == 0 && kb == (CS_KB)) {
              const uint32_t cb = sb + B_CS, d = sb + OFF_X;
              mbar_expect_tx(cb, 32768);
              tma2d(d, &mp.wg, cb, n0, m * 64, EVICT_NORMAL); tma2d(d + 8192, &mp.wg, cb, n1, m * 64, EVICT_NORMAL);
              tma2d(d + 16384, &mp.wu, cb, n0, m * 64, EVICT_NORMAL); tma2d(d + 24576, &mp.wu, cb, n1, m * 64, EVICT_NORMAL);
            }
            const int st = kb & 3;
            const uint32_t sa = sb + (st ^ ROT) * P1_STAGE, fb = sb + B_F1 + 8 * st;
            mbar_wait(sb + B_E1 + 8 * st, par);
            if (R * 16 + kb >= 4) REL_TS(R * 16 + kb - 4);
            mbar_expect_tx(fb, P1_STAGE);
            tma2d_mc(sa + 16384 + rank * 16384, mb0, fb, n0, kb * 64, HINT_W);
            tma2d_mc(sa + 24576 + rank * 16384, mb1, fb, n1, kb * 64, HINT_W);
            if (R == 0) {
              tma3d(sa, &mp.x, fb, kb * 64, m * 64, 0, EVICT_NORMAL);
            } else {
              if (R == 1 && kb == 0) { mbar_wait(sb + B_DEP, 0); TS(1); }
              tma2d(sa, &mp.xn, fb, kb * 64, m * 128, R == 4 ? HINT_LAST : EVICT_NORMAL);
            }
            if (XEARLY && R == 4 && kb == 4 + j2) x_load();
            if (R == 4 && kb >= 16 - PF_D) { if (kb == 16 - PF_D) mbar_wait(sb + B_DEP + 8, 0); d_prefetch(kb + PF_D - 16); }
            if (st == 3) par ^= 1;
          }
        }
#pragma unroll 1
        for (int i = 0; i < 26; i++) {
          const int st = i & 3, kb = 2 * i + 4 + rank;
          const uint32_t sa = sb + (st ^ ROT) * P1_STAGE, fb = sb + B_F1 + 8 * st;
          mbar_wait(sb + B_E1 + 8 * st, par);
          REL_TS(76 + i);
          mbar_expect_tx(fb, P1_STAGE);
          tma5d(sa + 16384, &mp.wd, fb, j2 * 128, kb * 2, HINT_W); tma5d(sa + 24576, &mp.wd, fb, j2 * 128 + 64, kb * 2, HINT_W);
          tma5d(sa + 32768, &mp.wd, fb, (j2 ^ 1) * 128, kb * 2, HINT_W); tma5d(sa + 40960, &mp.wd, fb, (j2 ^ 1) * 128 + 64, kb * 2, HINT_W);
          if (i == 0 || i == 6 || i == 10 || i == 18) { mbar_wait(sb + B_DEP + 8 * (1 + ((i + 6) >> 3)), 0); TS(2 + ((i + 6) >> 3)); }
          bulk_load(sa, gs->h + (m2 * 56 + kb) * 1024, 16384, fb, HINT_H);
          if (i + PF_D < 26) d_prefetch(i + PF_D);
          if (!XEARLY && i == 8 + j2) {
            asm volatile("cp.async.bulk.prefetch.tensor.3d.L2.global [%0, {%1, %2, %3}];" ::"l"(&mp.x), "r"(j2 * 128), "r"(m2 * 64), "r"(0) : "memory");
            asm volatile("cp.async.bulk.prefetch.tensor.3d.L2.global [%0, {%1, %2, %3}];" ::"l"(&mp.x), "r"(j2 * 128 + 64), "r"(m2 * 64), "r"(0) : "memory");
          }
          if (i >= PF_S && i < PF_S + 8) {
            asm volatile("cp.async.bulk.prefetch.L2.global [%0], 4096;" ::"l"(gs->o + (m2 * 16 + 2 * (i - PF_S)) * 1024 + j2 * 256) : "memory");
            if ((m2 >> 1) == i - PF_S) {
              asm volatile("cp.async.bulk.prefetch.tensor.2d.L2.global [%0, {%1, %2}];" ::"l"(&mp.wo), "r"(j2 * 128), "r"(m2 * 64) : "memory");
              asm volatile("cp.async.bulk.prefetch.tensor.2d.L2.global [%0, {%1, %2}];" ::"l"(&mp.wo), "r"(j2 * 128 + 64), "r"(m2 * 64) : "memory");
            }
          }
          if (st == 3) par ^= 1;
        }
        int st = 0; uint32_t par2 = 1;
#pragma unroll 1
        for (int t = 0; t < 16; t++) {
          const uint32_t sa = sb + (ROT ? st : (st < 3 ? st + 3 : st - 3)) * P2_STAGE, fb = sb + B_F2 + 8 * st;
          if (t < NS2) mbar_wait(sb + B_E1 + 8 * (((2 * t + 1) / 3 + 2) & 3), t < 3); else mbar_wait(sb + B_E2 + 8 * st, par2);
          REL_TS(102 + t);
          mbar_expect_tx(fb, P2_STAGE);
          bulk_load_mc(sa + rank * 8192, gs->o + (m2 * 16 + t) * 1024 + rank * 512, 8192, fb, HINT_H);
          tma2d(sa + 16384, &mp.wo, fb, j2 * 128, t * 64, HINT_W); tma2d(sa + 24576, &mp.wo, fb, j2 * 128 + 64, t * 64, HINT_W);
          if (++st == NS2) { st = 0; par2 ^= 1; }
        }
        if (!XEARLY) { mbar_wait(sb + B_E2 + 8 * 4, 1); x_load(); }
      }
    } else if (warp == 9) {
#pragma unroll 1
      for (int e = 0; e < 7; e++) {
        const bool halo = e == 2 || e == 3;
        bar_sync(BAR_EV + e, halo ? 96 : 288);
        if (lane == 0) {
          const int f = e == 0 ? FL_XN + m : (halo ? FL_HALO + (e - 2) * 128 + blockIdx.x : FL_H + m * 4 + (e == 1 ? 0 : e - 3));
          TS(10 + 2 * e); TG(52 + e);
          flag_add(&gs->flags[f * 32]);
          if (e < 6) TS(11 + 2 * e);
        }
        __syncwarp();
      }
    } else {
      unsigned e = 0;
      if (lane == 0) {
        unsigned* ep = &gs->epoch[blockIdx.x * 2 + warp - 10];
        e = *ep + 1; *ep = e;
        if (warp == 10) { asm volatile("st.shared.b32 [%0], %1;" ::"r"(sb + OFF_EPOCH), "r"(e) : "memory"); mbar_arrive(sb + B_EP); }
      }
      e = __shfl_sync(~0u, e, 0);
      mbar_wait(sb + B_CS, 0);
      if (lane == 0 && warp == 11) TS(6);
      col_sums(sb + OFF_X + (warp - 10) * 16384, gs->cspart + (j * 16 + m) * 128 + (warp - 10) * 16, e);
      if (lane == 0 && warp == 11) TS(9);
      if (warp == 10) {
        if (lane == 0) {
#pragma unroll 1
          for (int g = 0; g < 6; g++) {
            flag_wait(&gs->flags[(g == 5 ? FL_P + m2 : (g ? FL_H + m2 * 4 + g - 1 : FL_XN + m)) * 32], e * (g == 5 ? 4u : 8u));
            fence_async();
            mbar_arrive(sb + B_DEP + 8 * g);
            if (g == 0) TS(8);
          }
          for (int p = 0; p < 8; p++) {
            asm volatile("cp.async.bulk.prefetch.L2.global [%0], 4096;" ::"l"(gs->dpart + blockIdx.x * 2048 + p * 256) : "memory");
            __nanosleep(PF_SLEEP);
          }
        }
      } else
      if (elect_one()) {
#pragma unroll 1
        for (int r = 0; r < 2; r++) {
          const uint32_t hb = sb + B_HALO + 8 * r;
          if (m) {
            flag_wait(&gs->flags[(FL_HALO + r * 128 + blockIdx.x - 1) * 32], e);
            fence_async();
            mbar_expect_tx(hb, 4096);
            for (int g = 0; g < 2; g++) bulk_load(sb + OFF_X + g * AT_WG + AT_REM + r * 2048, gs->halo + ((r * 128 + blockIdx.x - 1) * 2 + g) * 128, 2048, hb, EVICT_FIRST);
          } else {
            mbar_arrive(hb);
          }
          TS(34 + r);
        }
      }
    }
  } else {
    if (!helper) {
      const int r = threadIdx.x >> 3, ch = threadIdx.x & 7;
      const uint32_t d = sb + ROT * P1_STAGE + r * 128 + ((ch ^ (r & 7)) << 4);
      const uint4* xa = x + (128 * m + 2 * r) * 128 + ch;
      const size_t wo = (size_t)r * (DFF / 8) + 16 * j + ch;
#pragma unroll
      for (int i = 0; i < 12; i++) {
        const uint4* src = i < 4 ? xa + (i & 1) * 64 * 128 + (i >> 1) * 128 : (i < 8 ? wgate : wup) + wo + (i & 1) * 32 * (DFF / 8) + ((i >> 1) & 1) * 8;
        asm volatile("cp.async.cg.shared.global [%0], [%1], 16;" ::"r"(d + i * 4096), "l"(src) : "memory");
      }
    }
    asm volatile("barrier.cluster.arrive.relaxed.aligned;" ::: "memory");
    asm volatile("setmaxnreg.inc.sync.aligned.u32 232;");
    const int wg = warp >> 2, w = warp & 3;
    Cons c;
    c.sb = sb; c.wg = wg; c.zero = warp >> 8;
    c.a0 = ((SM_BASE + wg * 8192) >> 4) | (1u << 16); c.a1 = c.a0 + 4; c.ah = 0x40000040;
    c.rel = mapa(sb, threadIdx.x & 1);
    c.do_rel = (threadIdx.x & 127) < 2;
    constexpr bool t0 = false;
    float acc[128];
    uint32_t pk[64];
    float rs[2];
    const int rho = lane >> 2, q = lane & 3;

    if (helper) {
      asm volatile("barrier.cluster.wait.aligned;" ::: "memory");
      c.a0 = ((SM_BASE + wg * 4096) >> 4) | (1u << 16); c.a1 = c.a0 + 512; c.ah = 0x80000020;
      c.rel = sb;
      uint4* dst = gs->dpart + (blockIdx.x - NMAIN) * 4096 + threadIdx.x;
      auto put = [&](int p) {
#pragma unroll
        for (int i = 4 * p; i < 4 * p + 4; i++) stg128(dst + i * 256, pk[4 * i], pk[4 * i + 1], pk[4 * i + 2], pk[4 * i + 3]);
      };
#pragma unroll 1
      for (int t = 0; t < 16; t++) {
        p1_issue<0, 0>(acc, c, t & 1);
        if (t) put(0);
        p1_issue<1, 1>(acc, c, t & 1); wg_wait<1>(); release(c, B_E1);
        if (t) put(1);
        if (wg == 1) { wg_wait<0>(); release(c, B_E1 + 8); bar_sync(BAR_LAG, 256); }
        p1_issue<2, 1>(acc, c, t & 1); wg_wait<1>(); if (wg == 0) release(c, B_E1 + 8);
        if (t) put(2);
        p1_issue<3, 1>(acc, c, t & 1);
        if (wg == 0) bar_arrive(BAR_LAG, 256);
        if (t) { put(3); bar_arrive(BAR_EV + (~t & 1), 288); dst += 8 * 2048; }
        wg_wait<1>(); release(c, B_E1 + 16);
        wg_wait<0>(); release(c, B_E1 + 24);
#pragma unroll
        for (int i = 0; i < 64; i++) pk[i] = pack2(acc[2 * i], acc[2 * i + 1]);
      }
      put(0); put(1); put(2); put(3);
      bar_arrive(BAR_EV + 1, 288);
      return;
    }
    {
      const int prow = 16 * j + 2 * warp;
      const uint4* xr = x + (size_t)(128 * m + 2 * (prow & 63) + (prow >> 6)) * 128 + lane;
      uint4* xo = gs->xn + (size_t)(128 * m + prow) * 128 + lane;
      float c0[2], mo[4];
      uint32_t st[2];
      uint32_t e;
      asm volatile("" : "+l"(xr), "+l"(xo));
      if (t0) TS(23 + wg * 16);
      asm volatile("cp.async.wait_all;\nfence.proxy.async.shared::cta;" ::: "memory");
      bar_sync(BAR_MMA, 256);
      if (threadIdx.x == 0) TS(39);
      p1_step<0, false>(acc, c);
      asm volatile("barrier.cluster.wait.aligned;" ::: "memory");
      p1_range<1, LN_LD + 1>(acc, c);
      if (t0) TS(24 + wg * 16);
#pragma unroll
      for (int i = 0; i < 8; i++) {
        asm volatile("ld.global.nc.v4.b32 {%0,%1,%2,%3}, [%4];" : "=r"(pk[4 * i]), "=r"(pk[4 * i + 1]), "=r"(pk[4 * i + 2]), "=r"(pk[4 * i + 3]) : "l"(xr + (i >> 2) * 256 + (i & 3) * 32));
      }
      p1_range<LN_LD + 1, LN_KB + 1>(acc, c);
      sched_fence(c.zero);

      pin<16>(pk); ln_moments(pk, c0[0], mo[0], mo[1]); pin<2>(mo);
      p1_step<LN_KB + 1>(acc, c);
      sched_fence(c.zero);
      pin<16>(pk + 16); ln_moments(pk + 16, c0[1], mo[2], mo[3]); ln_reduce(mo[0], mo[1]); pin<4>(mo);
      p1_step<LN_KB + 2>(acc, c);
      mbar_wait(sb + B_EP, 0);
      asm volatile("ld.shared.b32 %0, [%1];" : "=r"(e) : "r"(sb + OFF_EPOCH) : "memory");
      pin<2>(mo); st[0] = ln_finish(c0[0], mo[0], mo[1]); ln_reduce(mo[2], mo[3]); pin<1>(st); pin<2>(mo + 2);
      p1_step<LN_KB + 3>(acc, c);
      sched_fence(c.zero);
      pin<1>(st); pin<2>(mo + 2);
      st[1] = ln_finish(c0[1], mo[2], mo[3]);
      ln_store(pk, st[0], xo);
      if (lane == 0)
        asm volatile("{\n.reg .b64 a, b;\nmov.b64 a, {%1, %3};\nmov.b64 b, {%2, %3};\nst.relaxed.gpu.global.v2.b64 [%0], {a, b};\n}" ::"l"(gs->stats + 128 * m + prow), "r"(st[0]), "r"(st[1]), "r"(e) : "memory");
      p1_step<LN_KB + 4>(acc, c);
      sched_fence(c.zero);
      pin<1>(st + 1); ln_store(pk + 16, st[1], xo + 128);
      bar_arrive(BAR_EV, 288);
      p1_range<LN_KB + 5, G_KB + 1>(acc, c);
      sched_fence(c.zero);
      const unsigned long long* cp = (const unsigned long long*)gs->cspart + j * 4096 + threadIdx.x;
      const unsigned long long* sp = gs->stats + 128 * m + warp * 16 + rho;
      unsigned long long part[18];
      auto gather = [&]() {
#pragma unroll
        for (int i = 0; i < 18; i++) asm volatile("ld.relaxed.gpu.global.b64 %0, [%1];" : "=l"(part[i]) : "l"(i < 16 ? cp + i * 256 : sp + (i - 16) * 8) : "memory");
      };
      gather();
      auto validate = [&]() {
        float csum;
        for (int tries = 0;; tries++) {
          uint32_t bad = 0;
          csum = 0.f;
#pragma unroll
          for (int i = 0; i < 18; i++) { bad |= (uint32_t)(part[i] >> 32) ^ e; if (i < 16) csum += __uint_as_float((uint32_t)part[i]); }
          if (!__any_sync(~0u, bad != 0) || tries > (1 << 20)) break;
          gather();
        }
        const float hi = bf16r(csum), mid = bf16r(csum - hi);
        sts128(sb + OFF_CS + ((threadIdx.x & 62) * 4 + (threadIdx.x >> 6) * 2 + (threadIdx.x & 1)) * 16, make_uint4(pack2(hi, mid), pack2(csum - hi - mid, 0.f), 0, 0));
        asm volatile("fence.proxy.async.shared::cta;" ::: "memory");
        __syncwarp();
        if (lane == 0) mbar_arrive(sb + B_AUX);
      };
      p1_range<G_KB + 1, 14>(acc, c);
      if (wg == 1) validate();
      p1_step<14>(acc, c);
      p1_issue<3, 1>(acc, c, 1);
      if (wg == 0) validate();
      const uint32_t keep = q == 0 ? 0xffffffffu : (q == 1 ? 0xffffu : 0u);
      const uint32_t a0 = (__byte_perm((uint32_t)part[16], 0, 0x1010) ^ 0x80008000u) & keep, a1 = (__byte_perm((uint32_t)part[17], 0, 0x1010) ^ 0x80008000u) & keep;
      mbar_wait(sb + B_AUX, 0);
      wg_fence();
      wgmma256_rs(acc, a0, a1, 0, 0, (SM_BASE + OFF_CS) >> 4);
      wg_commit();
      if (wg == 0) bar_arrive(BAR_LAG, 256);
      rs[0] = rcpf(hi_f((uint32_t)part[16])); rs[1] = rcpf(hi_f((uint32_t)part[17]));
      wg_wait<2>(); release(c, B_E1 + 16);
      wg_wait<0>(); release(c, B_E1 + 24);
#pragma unroll
      for (int i = 0; i < 64; i++) pk[i] = pack2(acc[2 * i], acc[2 * i + 1]);
      if (t0) TS(25 + wg * 16);
    }
    const uint32_t img = warp * 1024 + ((lane ^ (lane >> 3)) << 4);
#pragma unroll 1
    for (int R = 1;; R++) {
      uint8_t* hb = (uint8_t*)gs->h + (size_t)m * 56 * 16384 + img;
      if (R == 2 || R == 3) {
        attn_tile(acc, pk, c, R - 2, warp, m, gs, hb + (16 + j) * 16384, (uint8_t*)gs->o + (m * 16 + j + 8 * (R - 2)) * 16384 + img);
      } else {
        if (R == 5) { c.a0 = ((SM_BASE + wg * 4096) >> 4) | (1u << 16); c.a1 = c.a0 + 512; c.ah = 0x80000020; }
        geglu_tile<0>(acc, pk, c, hb + (2 * j + (R == 1 ? 0 : 16 * R - 40)) * 16384, BAR_EV + (R == 1 ? 1 : R + 1), rs);
        rs[0] = rs[1] = 1.0f;
        if (R == 5) break;
      }
      p1_range<14, 16>(acc, c);
#pragma unroll
      for (int i = 0; i < 64; i++) pk[i] = pack2(acc[2 * i], acc[2 * i + 1]);
      if (t0) TS(25 + R + wg * 16);
    }
    if (t0) TS(30 + wg * 16);
    auto fetch = [&](int p) {
      asm volatile("ld.global.cg.v4.b32 {%0,%1,%2,%3}, [%4];" : "=r"(pk[4 * p]), "=r"(pk[4 * p + 1]), "=r"(pk[4 * p + 2]), "=r"(pk[4 * p + 3]) : "l"(gs->dpart + blockIdx.x * 2048 + p * 256 + threadIdx.x) : "memory");
    };
#pragma unroll 1
    for (int it = 3; it < 5; it++) {
      p1_issue<2, 1>(acc, c, it & 1); wg_wait<1>(); release(c, B_E1 + 8);
      p1_issue<3, 1>(acc, c, it & 1); wg_wait<1>(); release(c, B_E1 + 16);
      p1_issue<0, 1>(acc, c, ~it & 1); wg_wait<1>(); release(c, B_E1 + 24);
      p1_issue<1, 1>(acc, c, ~it & 1); wg_wait<1>(); release(c, B_E1);
    }
    p1_issue<2, 1>(acc, c, 1); wg_wait<1>(); release(c, B_E1 + 8);
    mbar_wait(sb + B_DEP + 40, 0);
    fetch(0); fetch(4);
    p1_issue<3, 1>(acc, c, 1); wg_wait<1>(); release(c, B_E1 + 16);
    fetch(1); fetch(5);
    p1_issue<0, 1>(acc, c, 0); wg_wait<1>(); release(c, B_E1 + 24);
    fetch(2); fetch(6);
    p1_issue<1, 1>(acc, c, 0); wg_wait<1>(); release(c, B_E1);
    fetch(3); fetch(7);
    if (t0) TS(31 + wg * 16);
    {
      float accs[64];
      const uint32_t peer = mapa(sb, rank ^ 1);
      auto send_piece = [&](int p) {
        asm volatile("st.async.weak.shared::cluster.mbarrier::complete_tx::bytes.v4.b32 [%0], {%1,%2,%3,%4}, [%5];" ::"r"(peer + OFF_LAND + p * 4096 + threadIdx.x * 16),
                     "r"(pack2(acc[64 + 8 * p], acc[65 + 8 * p])), "r"(pack2(acc[66 + 8 * p], acc[67 + 8 * p])), "r"(pack2(acc[68 + 8 * p], acc[69 + 8 * p])), "r"(pack2(acc[70 + 8 * p], acc[71 + 8 * p])),
                     "r"(peer + B_EX + 32 * wg + 8 * (p >> 1)) : "memory");
      };
      auto silu_piece = [&](int p) {
        const uint4 r = lds128(sb + OFF_LAND + p * 4096 + threadIdx.x * 16);
        const uint32_t rr[4] = {add2(r.x, pk[4 * p]), add2(r.y, pk[4 * p + 1]), add2(r.z, pk[4 * p + 2]), add2(r.w, pk[4 * p + 3])};
#pragma unroll
        for (int i = 0; i < 4; i++) {
          const float a = acc[8 * p + 2 * i] + lo_f(rr[i]), b = acc[8 * p + 2 * i + 1] + hi_f(rr[i]);
          pk[4 * p + i] = pack2(silu_half(a), silu_half(b));
        }
        pin<4>(pk + 4 * p);
      };
      const uint32_t xa = sb + OFF_XT + (warp * 16 + (lane & 15)) * 128 + (((lane >> 4) ^ (lane & 7)) << 4);
      auto x_piece = [&](int i) { const uint4 v = ldsm((xa ^ ((i & 3) << 5)) + (i >> 2) * 16384); pk[32 + 4 * i] = v.x; pk[33 + 4 * i] = v.y; pk[34 + 4 * i] = v.z; pk[35 + 4 * i] = v.w; };
      p2_step<0>(accs, c);
      p2_step<1>(accs, c); mbar_wait(sb + B_E1 + 8, 0); send_piece(0); send_piece(1);
      p2_step<2>(accs, c); sched_fence(c.zero); send_piece(2); send_piece(3);
      p2_step<3>(accs, c); sched_fence(c.zero); send_piece(4); send_piece(5);
      p2_step<4>(accs, c); sched_fence(c.zero); send_piece(6); send_piece(7);
      p2_step<5>(accs, c); mbar_wait(sb + B_EX + 32 * wg, 0); silu_piece(0);
      p2_step<6>(accs, c); mbar_wait(sb + B_EX + 32 * wg + 8, 0); silu_piece(2);
      p2_step<7>(accs, c); sched_fence(c.zero); silu_piece(3);
      p2_step<8>(accs, c); mbar_wait(sb + B_EX + 32 * wg + 16, 0); silu_piece(4);
      p2_step<9>(accs, c); sched_fence(c.zero); silu_piece(5);
      p2_step<10>(accs, c); mbar_wait(sb + B_EX + 32 * wg + 24, 0); silu_piece(6);
      p2_step<11>(accs, c); sched_fence(c.zero); silu_piece(7);
      p2_step<12>(accs, c); p2_step<13>(accs, c); p2_step<14>(accs, c); p2_step<15>(accs, c);
      if (SEND_MODE >= 2) { sched_fence(c.zero); silu_piece(1); }
      mbar_wait(sb + B_XT, 0);
#pragma unroll
      for (int i = 0; i < 8; i++) x_piece(i);
      sched_fence(c.zero);
      wg_wait<0>();
      if (t0) TS(32 + wg * 16);
#pragma unroll
      for (int i = 0; i < 8; i++) {
        uint32_t v[4];
#pragma unroll
        for (int k = 0; k < 4; k++) v[k] = fma2(pack2(accs[8 * i + 2 * k], accs[1 + 8 * i + 2 * k]), pk[4 * i + k], pk[32 + 4 * i + k]);
        asm volatile("stmatrix.sync.aligned.m8n8.x4.shared.b16 [%0], {%1,%2,%3,%4};" ::"r"((xa ^ ((i & 3) << 5)) + (i >> 2) * 16384), "r"(v[0]), "r"(v[1]), "r"(v[2]), "r"(v[3]) : "memory");
        if (i == 3 || i == 7) {
          asm volatile("fence.proxy.async.shared::cta;" ::: "memory");
          __syncwarp();
          if (elect_one()) tma3d_store(&mp.out, sb + OFF_XT + (i >> 2) * 16384 + warp * 2048, j2 * 128 + (i >> 2) * 64, m2 * 64 + w * 16, wg);
        }
      }
      if (elect_one()) { asm volatile("cp.async.bulk.commit_group;\ncp.async.bulk.wait_group.read 0;" ::: "memory"); }
      if ((threadIdx.x & 127) == 0) { TS(33 + wg * 16); if (wg) { TG(59); unsigned id; asm volatile("mov.u32 %0, %%smid;" : "=r"(id)); TSV(60, id); } }
    }
  }
}

typedef CUresult (*EncodeFn)(CUtensorMap*, CUtensorMapDataType, cuuint32_t, void*, const cuuint64_t*, const cuuint64_t*, const cuuint32_t*, const cuuint32_t*,
                             CUtensorMapInterleave, CUtensorMapSwizzle, CUtensorMapL2promotion, CUtensorMapFloatOOBfill);

void encode(EncodeFn fn, CUtensorMap* tm, const void* p, int rank, const cuuint64_t* dims, const cuuint64_t* strides, const cuuint32_t* box) {
  const cuuint32_t es[5] = {1, 1, 1, 1, 1};
  fn(tm, CU_TENSOR_MAP_DATA_TYPE_BFLOAT16, rank, const_cast<void*>(p), dims, strides, box, es, CU_TENSOR_MAP_INTERLEAVE_NONE, CU_TENSOR_MAP_SWIZZLE_128B,
     PROMO, CU_TENSOR_MAP_FLOAT_OOB_FILL_NONE);
}

}

extern "C" void kernel_launch(void* const* d_in, const int* in_sizes, int n_in, void* d_out, int out_size) {
  (void)in_sizes; (void)n_in; (void)out_size;
  static EncodeFn fn = nullptr;
  static Scratch* gs = nullptr;
  if (!fn) {
    void* p = nullptr;
    cudaDriverEntryPointQueryResult qr;
    cudaGetDriverEntryPoint("cuTensorMapEncodeTiled", &p, cudaEnableDefault, &qr);
    fn = (EncodeFn)p;
    cudaGetSymbolAddress((void**)&gs, g_scratch);
    cudaFuncSetAttribute(fused_kernel, cudaFuncAttributeMaxDynamicSharedMemorySize, SMEM_BYTES);
  }
  const void *x = d_in[0], *wqkv = d_in[1], *wo = d_in[2], *wg = d_in[4], *wu = d_in[5], *wd = d_in[6];
  Maps mp;
  {
    const cuuint64_t dims[3] = {DM, SEQ / 2, 2}, st[2] = {DM * 4, DM * 2};
    const cuuint32_t box_in[3] = {64, 64, 2}, box_out[3] = {64, 16, 1};
    encode(fn, &mp.x, x, 3, dims, st, box_in);
    encode(fn, &mp.out, d_out, 3, dims, st, box_out);
  }
  {
    const cuuint64_t dims[2] = {DM, SEQ}, st[1] = {DM * 2};
    const cuuint32_t box[2] = {64, 128};
    encode(fn, &mp.xn, gs->xn, 2, dims, st, box);
  }
  {
    const cuuint32_t box[2] = {64, 64};
    const cuuint64_t dq[2] = {3 * DM, DM}, sq[1] = {3 * DM * 2}, df[2] = {DFF, DM}, sf[1] = {DFF * 2}, dw[2] = {DM, DM}, sw[1] = {DM * 2};
    encode(fn, &mp.wqkv, wqkv, 2, dq, sq, box);
    encode(fn, &mp.wg, wg, 2, df, sf, box);
    encode(fn, &mp.wu, wu, 2, df, sf, box);
    encode(fn, &mp.wo, wo, 2, dw, sw, box);
  }
  {
    const cuuint32_t box[5] = {64, 2, 4, 4, 2};
    const cuuint64_t st[4] = {DM * 2, 8 * DM * 2, 2 * DM * 2, 32 * DM * 2};
    const cuuint64_t dd[5] = {DM, 2, 4, 4, DFF / 32};
    encode(fn, &mp.wd, wd, 5, dd, st, box);
  }
  fused_kernel<<<NCTA, 384, SMEM_BYTES>>>((const uint4*)x, (const uint4*)wg, (const uint4*)wu, gs, mp);
}
```

```cpp
#include <cuda_runtime.h>
#include <cuda_bf16.h>
#include <cuda.h>
#include <stdint.h>

#define LN_LD 0
#define PROMO CU_TENSOR_MAP_L2_PROMOTION_L2_128B
#define G_KB 12
#define PF_D 4
#define PF_W 1
#define PF_H 1
#define PF_SLEEP 250
#define PF_S 16
#define SEND_MODE 0
#define LAG2 4
#define CS_KB 8
#define LN_KB 4

#define EVICT_FIRST 0x12F0000000000000ull
#define EVICT_NORMAL 0x1000000000000000ull
#define HINT_W EVICT_FIRST
#define HINT_H EVICT_FIRST
#define HINT_LAST EVICT_FIRST

namespace {

constexpr int SEQ = 2048, DM = 1024, DFF = 3584;
constexpr int NMAIN = 128, NCTA = 132;

constexpr uint32_t SM_BASE = 0x400;
constexpr uint32_t P1_BYTES = 49152, P2_BYTES = 32768;
constexpr uint32_t OFF_A = 131072;
__host__ __device__ constexpr uint32_t p2_a(int s) { return s == 0 ? OFF_A + 32768 : s == 1 ? OFF_A + 49152 : s == 2 ? 114688 : s == 3 ? 16384 : 49152; }
__host__ __device__ constexpr uint32_t p2_b(int s) { return s < 3 ? 65536 + s * 16384 : (s - 3) * 32768; }
constexpr uint32_t OFF_LAND = OFF_A;
constexpr uint32_t OFF_X = 196608;
constexpr uint32_t OFF_CS = OFF_X + 14336;
constexpr uint32_t OFF_BAR = 229376;
constexpr uint32_t B_F1 = OFF_BAR, B_E1 = B_F1 + 32, B_F2 = B_E1 + 32, B_E2 = B_F2 + 48;
constexpr uint32_t B_DEP = B_E2 + 48;
constexpr uint32_t B_AUX = B_DEP + 48, B_CS = B_AUX + 8, B_XT = B_CS + 8, B_EX = B_XT + 8, B_HALO = B_EX + 64, B_EP = B_HALO + 16, OFF_EPOCH = B_EP + 8;
constexpr uint32_t SMEM_BYTES = 232448;
constexpr uint32_t AT_V = 0, AT_K = 8192, AT_REM = 11264, AT_WG = 15360;

constexpr int FL_XN = 0, FL_H = 16, FL_P = 80, FL_HALO = 96, FL_N = FL_HALO + 256;
struct __align__(1024) Scratch {
  uint4 h[16 * 56 * 1024];
  uint4 o[16 * 16 * 1024];
  uint4 xn[SEQ * DM / 8];
  uint4 dpart[128 * 8 * 256];
  uint4 halo[2 * 128 * 2 * 128];
  ulonglong2 cspart[8 * 16 * 128];
  unsigned long long stats[SEQ];
  unsigned flags[FL_N * 32];
  unsigned epoch[NCTA * 2];
};
__device__ Scratch g_scratch;
#define TG(i) do {} while (0)
#define TSV(i, v) do {} while (0)
#define TS(i) do {} while (0)

struct Maps { CUtensorMap x, xn, out, wqkv, wg, wu, wd, wo; };

__device__ __forceinline__ void mbar_init(uint32_t bar, uint32_t cnt) { asm volatile("mbarrier.init.shared::cta.b64 [%0], %1;" ::"r"(bar), "r"(cnt)); }
__device__ __forceinline__ void mbar_expect_tx(uint32_t bar, uint32_t bytes) { asm volatile("mbarrier.arrive.expect_tx.shared::cta.b64 _, [%0], %1;" ::"r"(bar), "r"(bytes) : "memory"); }
__device__ __forceinline__ void mbar_arrive(uint32_t bar) { asm volatile("mbarrier.arrive.shared::cta.b64 _, [%0];" ::"r"(bar) : "memory"); }
__device__ __forceinline__ void mbar_arrive_cl(uint32_t bar) { asm volatile("mbarrier.arrive.shared::cluster.b64 _, [%0];" ::"r"(bar) : "memory"); }
__device__ __forceinline__ uint32_t mapa(uint32_t a, uint32_t cta) { uint32_t r; asm("mapa.shared::cluster.u32 %0, %1, %2;" : "=r"(r) : "r"(a), "r"(cta)); return r; }
__device__ __forceinline__ void mbar_wait(uint32_t bar, uint32_t parity) {
  asm volatile("{\n.reg .pred p;\n.reg .u32 n;\nmov.u32 n, 0;\nLAB_WAIT:\nmbarrier.try_wait.parity.shared::cta.b64 p, [%0], %1;\n@p bra LAB_DONE;\n"
               "add.u32 n, n, 1;\nsetp.gt.u32 p, n, 4000000;\n@p trap;\nbra LAB_WAIT;\nLAB_DONE:\n}" ::"r"(bar), "r"(parity) : "memory");
}
__device__ __forceinline__ void flag_wait(const unsigned* f, unsigned target) {
  asm volatile("{\n.reg .pred p;\n.reg .u32 n, v;\nmov.u32 n, 0;\nLAB_WAIT:\nld.relaxed.gpu.global.u32 v, [%0];\nsub.u32 v, v, %1;\nsetp.ge.s32 p, v, 0;\n@p bra LAB_DONE;\n"
               "nanosleep.u32 100;\nadd.u32 n, n, 1;\nsetp.gt.u32 p, n, 4000000;\n@p trap;\nbra LAB_WAIT;\nLAB_DONE:\nfence.acquire.gpu;\n}" ::"l"(f), "r"(target) : "memory");
}
__device__ __forceinline__ void flag_add(unsigned* f) { asm volatile("red.release.gpu.global.add.u32 [%0], 1;" ::"l"(f) : "memory"); }
__device__ __forceinline__ void fence_async() { asm volatile("fence.proxy.async.global;" ::: "memory"); }
__device__ __forceinline__ bool elect_one() { uint32_t p; asm volatile("{\n.reg .pred P;\nelect.sync _|P, 0xffffffff;\nselp.u32 %0, 1, 0, P;\n}" : "=r"(p)); return p; }
__device__ __forceinline__ void bar_sync(int id, int n) { asm volatile("bar.sync %0, %1;" ::"r"(id), "r"(n) : "memory"); }
__device__ __forceinline__ void bar_arrive(int id, int n) { asm volatile("bar.arrive %0, %1;" ::"r"(id), "r"(n) : "memory"); }

__device__ __forceinline__ void tma2d(uint32_t dst, const CUtensorMap* tm, uint32_t bar, int c0, int c1, uint64_t hint) {
  asm volatile("cp.async.bulk.tensor.2d.shared::cluster.global.mbarrier::complete_tx::bytes.L2::cache_hint [%0], [%1, {%3, %4}], [%2], %5;" ::"r"(dst), "l"(tm), "r"(bar), "r"(c0), "r"(c1), "l"(hint) : "memory");
}
__device__ __forceinline__ void tma2d_mc(uint32_t dst, const CUtensorMap* tm, uint32_t bar, int c0, int c1, uint64_t hint) {
  asm volatile("cp.async.bulk.tensor.2d.shared::cluster.global.mbarrier::complete_tx::bytes.multicast::cluster.L2::cache_hint [%0], [%1, {%3, %4}], [%2], %5, %6;" ::"r"(dst), "l"(tm), "r"(bar), "r"(c0), "r"(c1), "h"((uint16_t)3), "l"(hint) : "memory");
}
__device__ __forceinline__ void tma3d(uint32_t dst, const CUtensorMap* tm, uint32_t bar, int c0, int c1, int c2, uint64_t hint) {
  asm volatile("cp.async.bulk.tensor.3d.shared::cluster.global.mbarrier::complete_tx::bytes.L2::cache_hint [%0], [%1, {%3, %4, %5}], [%2], %6;" ::"r"(dst), "l"(tm), "r"(bar), "r"(c0), "r"(c1), "r"(c2), "l"(hint) : "memory");
}
__device__ __forceinline__ void tma5d(uint32_t dst, const CUtensorMap* tm, uint32_t bar, int c0, int c4, uint64_t hint) {
  asm volatile("cp.async.bulk.tensor.5d.shared::cluster.global.mbarrier::complete_tx::bytes.L2::cache_hint [%0], [%1, {%3, %5, %5, %5, %4}], [%2], %6;" ::"r"(dst), "l"(tm), "r"(bar), "r"(c0), "r"(c4), "r"(0), "l"(hint) : "memory");
}
__device__ __forceinline__ void tma5d_prefetch(const CUtensorMap* tm, int c0, int c4) {
  asm volatile("cp.async.bulk.prefetch.tensor.5d.L2.global [%0, {%1, %3, %3, %3, %2}];" ::"l"(tm), "r"(c0), "r"(c4), "r"(0) : "memory");
}
__device__ __forceinline__ void tma3d_store(const CUtensorMap* tm, uint32_t src, int c0, int c1, int c2) {
  asm volatile("cp.async.bulk.tensor.3d.global.shared::cta.bulk_group [%0, {%2, %3, %4}], [%1];" ::"l"(tm), "r"(src), "r"(c0), "r"(c1), "r"(c2) : "memory");
}
__device__ __forceinline__ void bulk_load(uint32_t dst, const void* src, uint32_t bytes, uint32_t bar, uint64_t hint) {
  asm volatile("cp.async.bulk.shared::cluster.global.mbarrier::complete_tx::bytes.L2::cache_hint [%0], [%1], %2, [%3], %4;" ::"r"(dst), "l"(src), "r"(bytes), "r"(bar), "l"(hint) : "memory");
}
__device__ __forceinline__ void bulk_load_mc(uint32_t dst, const void* src, uint32_t bytes, uint32_t bar, uint64_t hint) {
  asm volatile("cp.async.bulk.shared::cluster.global.mbarrier::complete_tx::bytes.multicast::cluster.L2::cache_hint [%0], [%1], %2, [%3], %4, %5;" ::"r"(dst), "l"(src), "r"(bytes), "r"(bar), "h"((uint16_t)3), "l"(hint) : "memory");
}
__device__ __forceinline__ uint4 lds128(uint32_t a) { uint4 v; asm volatile("ld.shared.v4.b32 {%0,%1,%2,%3}, [%4];" : "=r"(v.x), "=r"(v.y), "=r"(v.z), "=r"(v.w) : "r"(a) : "memory"); return v; }
__device__ __forceinline__ void sts128(uint32_t a, uint4 v) { asm volatile("st.shared.v4.b32 [%0], {%1,%2,%3,%4};" ::"r"(a), "r"(v.x), "r"(v.y), "r"(v.z), "r"(v.w) : "memory"); }
__device__ __forceinline__ void stg128(void* p, uint32_t a, uint32_t b, uint32_t c, uint32_t d) { asm volatile("st.global.v4.b32 [%0], {%1,%2,%3,%4};" ::"l"(p), "r"(a), "r"(b), "r"(c), "r"(d) : "memory"); }

__device__ __forceinline__ uint32_t pack2(float lo, float hi) { uint32_t r; asm("cvt.rn.bf16x2.f32 %0, %1, %2;" : "=r"(r) : "f"(hi), "f"(lo)); return r; }
__device__ __forceinline__ float lo_f(uint32_t v) { return __uint_as_float(v << 16); }
__device__ __forceinline__ float hi_f(uint32_t v) { return __uint_as_float(v & 0xffff0000u); }
__device__ __forceinline__ float bf16r(float v) { return lo_f(pack2(v, 0.f)); }
__device__ __forceinline__ uint32_t mul2(uint32_t a, uint32_t b) { uint32_t r; asm("mul.rn.bf16x2 %0, %1, %2;" : "=r"(r) : "r"(a), "r"(b)); return r; }
__device__ __forceinline__ uint32_t add2(uint32_t a, uint32_t b) { uint32_t r; asm("add.rn.bf16x2 %0, %1, %2;" : "=r"(r) : "r"(a), "r"(b)); return r; }
__device__ __forceinline__ uint32_t sub2(uint32_t a, uint32_t b) { uint32_t r; asm("sub.rn.bf16x2 %0, %1, %2;" : "=r"(r) : "r"(a), "r"(b)); return r; }
__device__ __forceinline__ uint32_t fma2(uint32_t a, uint32_t b, uint32_t c) { uint32_t r; asm("fma.rn.bf16x2 %0, %1, %2, %3;" : "=r"(r) : "r"(a), "r"(b), "r"(c)); return r; }
__device__ __forceinline__ uint32_t max2(uint32_t a, uint32_t b) { uint32_t r; asm("max.bf16x2 %0, %1, %2;" : "=r"(r) : "r"(a), "r"(b)); return r; }
__device__ __forceinline__ float ex2f(float x) { float y; asm("ex2.approx.ftz.f32 %0, %1;" : "=f"(y) : "f"(x)); return y; }
__device__ __forceinline__ float rcpf(float x) { float y; asm("rcp.approx.ftz.f32 %0, %1;" : "=f"(y) : "f"(x)); return y; }
__device__ __forceinline__ float gelu2(float g) {
  float z = g * fmaf(g * g, 0.035677408136300125f, 0.7978845608028654f), t;
  asm("tanh.approx.f32 %0, %1;" : "=f"(t) : "f"(z));
  return fmaf(g, t, g);
}

__device__ __forceinline__ float silu_half(float z) { float t; asm("tanh.approx.f32 %0, %1;" : "=f"(t) : "f"(z)); return fmaf(z, t, z); }

__device__ __forceinline__ void wg_fence() { asm volatile("wgmma.fence.sync.aligned;" ::: "memory"); }
__device__ __forceinline__ void wg_commit() { asm volatile("wgmma.commit_group.sync.aligned;" ::: "memory"); }
template <int N> __device__ __forceinline__ void wg_wait() { asm volatile("wgmma.wait_group.sync.aligned %0;" ::"n"(N) : "memory"); }
#define A8(o) "+f"(d[(o)]), "+f"(d[(o) + 1]), "+f"(d[(o) + 2]), "+f"(d[(o) + 3]), "+f"(d[(o) + 4]), "+f"(d[(o) + 5]), "+f"(d[(o) + 6]), "+f"(d[(o) + 7])
#define A64(o) A8(o), A8((o) + 8), A8((o) + 16), A8((o) + 24), A8((o) + 32), A8((o) + 40), A8((o) + 48), A8((o) + 56)
#define REGS0_63 "%0,%1,%2,%3,%4,%5,%6,%7,%8,%9,%10,%11,%12,%13,%14,%15,%16,%17,%18,%19,%20,%21,%22,%23,%24,%25,%26,%27,%28,%29,%30,%31," \
                 "%32,%33,%34,%35,%36,%37,%38,%39,%40,%41,%42,%43,%44,%45,%46,%47,%48,%49,%50,%51,%52,%53,%54,%55,%56,%57,%58,%59,%60,%61,%62,%63"
#define REGS64_127 "%64,%65,%66,%67,%68,%69,%70,%71,%72,%73,%74,%75,%76,%77,%78,%79,%80,%81,%82,%83,%84,%85,%86,%87,%88,%89,%90,%91,%92,%93,%94,%95," \
                   "%96,%97,%98,%99,%100,%101,%102,%103,%104,%105,%106,%107,%108,%109,%110,%111,%112,%113,%114,%115,%116,%117,%118,%119,%120,%121,%122,%123,%124,%125,%126,%127"
template <int ACCUM> __device__ __forceinline__ void wgmma256(float (&d)[128], uint32_t a_lo, uint32_t a_hi, uint32_t b_lo) {
  asm volatile("{\n.reg .pred p;\n.reg .b64 da, db;\nsetp.ne.b32 p, %131, 0;\nmov.b64 da, {%128, %129};\nmov.b64 db, {%130, 0x40000040};\n"
               "wgmma.mma_async.sync.aligned.m64n256k16.f32.bf16.bf16 {" REGS0_63 "," REGS64_127 "}, da, db, p, 1, 1, 0, 1;\n}"
               : A64(0), A64(64) : "r"(a_lo), "r"(a_hi), "r"(b_lo), "n"(ACCUM));
}
__device__ __forceinline__ void wgmma256_rs(float (&d)[128], uint32_t a0, uint32_t a1, uint32_t z0, uint32_t z1, uint32_t b_lo) {
  asm volatile("{\n.reg .b64 db;\nmov.b64 db, {%132, 0x00000008};\n"
               "wgmma.mma_async.sync.aligned.m64n256k16.f32.bf16.bf16 {" REGS0_63 "," REGS64_127 "}, {%128,%129,%130,%131}, db, 1, 1, 1, 0;\n}"
               : A64(0), A64(64) : "r"(a0), "r"(a1), "r"(z0), "r"(z1), "r"(b_lo));
}
template <int ACCUM> __device__ __forceinline__ void wgmma128(float (&d)[64], uint32_t a_lo, uint32_t b_lo) {
  asm volatile("{\n.reg .pred p;\n.reg .b64 da, db;\nsetp.ne.b32 p, %66, 0;\nmov.b64 da, {%64, 0x80000020};\nmov.b64 db, {%65, 0x40000040};\n"
               "wgmma.mma_async.sync.aligned.m64n128k16.f32.bf16.bf16 {" REGS0_63 "}, da, db, p, 1, 1, 0, 1;\n}"
               : A64(0) : "r"(a_lo), "r"(b_lo), "n"(ACCUM));
}
template <int ACCUM> __device__ __forceinline__ void hmma(float (&c)[4], uint32_t a0, uint32_t a1, uint32_t a2, uint32_t a3, uint32_t b0, uint32_t b1) {
  if (ACCUM)
    asm volatile("mma.sync.aligned.m16n8k16.row.col.f32.bf16.bf16.f32 {%0,%1,%2,%3}, {%4,%5,%6,%7}, {%8,%9}, {%0,%1,%2,%3};"
                 : "+f"(c[0]), "+f"(c[1]), "+f"(c[2]), "+f"(c[3]) : "r"(a0), "r"(a1), "r"(a2), "r"(a3), "r"(b0), "r"(b1));
  else
    asm volatile("mma.sync.aligned.m16n8k16.row.col.f32.bf16.bf16.f32 {%0,%1,%2,%3}, {%4,%5,%6,%7}, {%8,%9}, {%10,%10,%10,%10};"
                 : "=f"(c[0]), "=f"(c[1]), "=f"(c[2]), "=f"(c[3]) : "r"(a0), "r"(a1), "r"(a2), "r"(a3), "r"(b0), "r"(b1), "f"(0.f));
}
__device__ __forceinline__ uint32_t movm(uint32_t a) { uint32_t d; asm volatile("movmatrix.sync.aligned.m8n8.trans.b16 %0, %1;" : "=r"(d) : "r"(a)); return d; }
template <int N> __device__ __forceinline__ void pin(uint32_t* r) {
#pragma unroll
  for (int i = 0; i < N; i++) asm volatile("" : "+r"(r[i]));
}
template <int N> __device__ __forceinline__ void pin(float* r) {
#pragma unroll
  for (int i = 0; i < N; i++) asm volatile("" : "+f"(r[i]));
}
__device__ __forceinline__ void sched_fence(uint32_t zero) {
  asm volatile("{\n.reg .pred p;\n.reg .u32 n;\nmov.u32 n, %0;\nLAB_F:\nsetp.eq.u32 p, n, 0;\n@p bra.uni LAB_D;\nnanosleep.u32 n;\nsub.u32 n, n, 1;\nbra.uni LAB_F;\nLAB_D:\n}" ::"r"(zero) : "memory");
}
__device__ __forceinline__ uint4 ldsm(uint32_t a) { uint4 v; asm volatile("ldmatrix.sync.aligned.m8n8.x4.shared.b16 {%0,%1,%2,%3}, [%4];" : "=r"(v.x), "=r"(v.y), "=r"(v.z), "=r"(v.w) : "r"(a) : "memory"); return v; }
__device__ __forceinline__ uint4 ldsm_t(uint32_t a) { uint4 v; asm volatile("ldmatrix.sync.aligned.m8n8.x4.trans.shared.b16 {%0,%1,%2,%3}, [%4];" : "=r"(v.x), "=r"(v.y), "=r"(v.z), "=r"(v.w) : "r"(a) : "memory"); return v; }

constexpr int BAR_LAG = 1, BAR_MMA = 2, BAR_EV = 3;

struct Cons {
  uint32_t sb;
  uint32_t a0, a1, ah;
  uint32_t rel;
  bool do_rel;
  int wg;
  uint32_t zero;
};
#define REL_TS(n) TS(64 + (n))
constexpr uint32_t DB_LO = (SM_BASE >> 4) | ((8192 >> 4) << 16);

template <int ST, int ACCUM, bool WAIT = true> __device__ __forceinline__ void p1_issue(float (&acc)[128], const Cons& c, uint32_t parity) {
  if (WAIT) mbar_wait(c.sb + B_F1 + 8 * ST, parity);
  wg_fence();
  constexpr uint32_t sa = (OFF_A + ST * 16384) >> 4, sbo = DB_LO + ST * 2048;
  wgmma256<ACCUM>(acc, c.a0 + sa, c.ah, sbo);
  wgmma256<1>(acc, c.a0 + sa + 2, c.ah, sbo + 128);
  wgmma256<1>(acc, c.a1 + sa, c.ah, sbo + 256);
  wgmma256<1>(acc, c.a1 + sa + 2, c.ah, sbo + 384);
  wg_commit();
}
__device__ __forceinline__ void release(const Cons& c, uint32_t bar) { if (c.do_rel) mbar_arrive_cl(c.rel + bar); }
template <int KB, bool WAIT = true, int LAG = 2> __device__ __forceinline__ void p1_step(float (&acc)[128], const Cons& c) {
  if (KB == 16 - LAG) { if (c.wg == 1) { wg_wait<0>(); release(c, B_E1 + 8 * ((KB - 1) & 3)); bar_sync(BAR_LAG, 256); } }
  p1_issue<KB & 3, KB != 0, WAIT>(acc, c, (KB >> 2) & 1);
  if (KB == 15) { if (c.wg == 0) bar_arrive(BAR_LAG, 256); }
  if (KB > 0) { wg_wait<1>(); if (KB != 16 - LAG || c.wg == 0) release(c, B_E1 + 8 * ((KB - 1) & 3)); }
  if (KB == 15) { wg_wait<0>(); release(c, B_E1 + 8 * 3); }
}
template <int A, int B> __device__ __forceinline__ void p1_range(float (&acc)[128], const Cons& c) {
  if constexpr (A < B) { p1_step<A>(acc, c); p1_range<A + 1, B>(acc, c); }
}
template <int T> __device__ __forceinline__ void p2_step(float (&acc)[64], const Cons& c) {
  if (T == 16 - LAG2) { if (c.wg == 1) bar_sync(BAR_LAG, 256); }
  mbar_wait(c.sb + B_F2 + 8 * (T % 5), (T / 5) & 1);
  wg_fence();
  constexpr uint32_t sa = p2_a(T % 5) >> 4, sbo = DB_LO + (p2_b(T % 5) >> 4);
  wgmma128<T != 0>(acc, c.a0 + sa, sbo);
  wgmma128<1>(acc, c.a0 + sa + 2, sbo + 128);
  wgmma128<1>(acc, c.a1 + sa, sbo + 256);
  wgmma128<1>(acc, c.a1 + sa + 2, sbo + 384);
  wg_commit();
  if (T == 15) { if (c.wg == 0) bar_arrive(BAR_LAG, 256); }
  if (T <= 11) { wg_wait<1>(); release(c, T ? B_E2 + 8 * ((T + 5 - 1) % 5) : B_E1 + 8); }
}

template <int P> __device__ __forceinline__ void geglu_piece(const uint32_t (&pk)[64], uint8_t* dst, const float (&rs)[2]) {
  constexpr int cg = P >> 1, r = P & 1;
  const float rq = rs[r] * 0.25f;
  uint32_t v[4];
#pragma unroll
  for (int i = 0; i < 4; i++) {
    const uint32_t g = pk[2 * (4 * cg + i) + r];
    v[i] = mul2(pack2(gelu2(lo_f(g) * rs[r]) * rq, gelu2(hi_f(g) * rs[r]) * rq), pk[32 + 2 * (4 * cg + i) + r]);
  }
  stg128(dst + cg * 8192 + r * 512, v[0], v[1], v[2], v[3]);
}
template <int KB> __device__ __forceinline__ void geglu_tile(float (&acc)[128], const uint32_t (&pk)[64], const Cons& c, uint8_t* dst, int ev, const float (&rs)[2]) {
  if constexpr (KB < 14) {
    p1_step<KB>(acc, c);
    if (KB >= 1 && KB <= 8) geglu_piece<(KB - 1) & 7>(pk, dst, rs);
    if (KB == 8) bar_arrive(ev, 288);
    geglu_tile<KB + 1>(acc, pk, c, dst, ev, rs);
  }
}

__device__ __forceinline__ void attn_tile(float (&acc)[128], const uint32_t (&pk)[64], const Cons& c, int round, int warp, int m, Scratch* gs, uint8_t* hdst, uint8_t* odst) {
  const int lane = threadIdx.x & 31, w = warp & 3, rho = lane >> 2, q = lane & 3;
  const uint32_t at = c.sb + OFF_X + c.wg * AT_WG, swz = (lane ^ (lane >> 3)) << 4;
  uint32_t gg[16];
  p1_step<0>(acc, c);
  p1_step<1>(acc, c);
#pragma unroll
  for (int i = 0; i < 4; i++) {
    const int h = i & 1, r = i >> 1;
    sts128(at + AT_V + (2 * w + r) * 1024 + h * 512 + swz, make_uint4(pk[32 + 8 * h + r], pk[34 + 8 * h + r], pk[36 + 8 * h + r], pk[38 + 8 * h + r]));
  }
  if (w < 3) {
#pragma unroll
    for (int i = 0; i < 8; i++) asm volatile("st.shared.b32 [%0], %1;" ::"r"(at + AT_K + w * 1024 + i * 128 + lane * 4), "r"(pk[17 + 2 * i]) : "memory");
  } else {
    uint8_t* g = (uint8_t*)gs->halo + ((round * 128 + blockIdx.x) * 2 + c.wg) * 2048;
#pragma unroll
    for (int i = 0; i < 8; i++) asm volatile("st.global.b32 [%0], %1;" ::"l"(g + i * 128 + lane * 4), "r"(pk[17 + 2 * i]) : "memory");
#pragma unroll
    for (int h = 0; h < 2; h++) stg128(g + 1024 + h * 512 + swz, pk[33 + 8 * h], pk[35 + 8 * h], pk[37 + 8 * h], pk[39 + 8 * h]);
    bar_arrive(BAR_EV + 2 + round, 96);
  }
  __syncwarp();
  if (lane == 0) mbar_arrive(c.sb + B_HALO + 8 * round);
  if (round) {
#pragma unroll
    for (int p = 0; p < 4; p++) asm volatile("ld.global.cg.v4.b32 {%0,%1,%2,%3}, [%4];" : "=r"(gg[4 * p]), "=r"(gg[4 * p + 1]), "=r"(gg[4 * p + 2]), "=r"(gg[4 * p + 3]) : "l"(hdst + (p >> 1) * 8192 + (p & 1) * 512) : "memory");
  }
  auto gu_piece = [&](int p) {
    uint32_t v[4];
#pragma unroll
    for (int i = 0; i < 4; i++) {
      const uint32_t g = pk[48 + 8 * (p >> 1) + 2 * i + (p & 1)];
      v[i] = mul2(round ? gg[4 * p + i] : 0x3e803e80u, round ? g : pack2(gelu2(lo_f(g)), gelu2(hi_f(g))));
    }
    stg128(hdst + (p >> 1) * 8192 + (p & 1) * 512, v[0], v[1], v[2], v[3]);
  };
  p1_step<2>(acc, c);
  p1_step<3>(acc, c); gu_piece(0);
  p1_step<4>(acc, c); gu_piece(1);
  p1_step<5>(acc, c); gu_piece(2);
  p1_step<6>(acc, c); gu_piece(3);
  p1_step<7>(acc, c);
  p1_step<8>(acc, c);
  const bool first = m == 0 && w == 0;
  uint32_t kl[16];
  mbar_wait(c.sb + B_HALO + 8 * round, 0);
  {
    const uint32_t ka = at + lane * 4 + (w ? AT_K + (w - 1) * 1024 : (first ? AT_K : AT_REM + round * 2048));
#pragma unroll
    for (int i = 0; i < 8; i++) {
      asm volatile("ld.shared.b32 %0, [%1];" : "=r"(kl[2 * i]) : "r"(ka + i * 128) : "memory");
      kl[2 * i + 1] = pk[16 + 2 * i] | c.zero;
    }
  }
  float st[4][4];
  pin<16>(kl);
  bar_sync(BAR_MMA, 256);
  mbar_wait(c.sb + B_F1 + 8 * 1, 0);
#pragma unroll
  for (int ks = 0; ks < 2; ks++) {
#pragma unroll
    for (int h = 0; h < 2; h++) {
      const int o = 8 * h + 4 * ks;
      if (ks == 0) { hmma<0>(st[2 * h], kl[o], kl[o + 1], kl[o + 2], kl[o + 3], pk[o], pk[o + 2]); hmma<0>(st[2 * h + 1], pk[16 + o], pk[17 + o], pk[18 + o], pk[19 + o], pk[o + 1], pk[o + 3]); }
      else { hmma<1>(st[2 * h], kl[o], kl[o + 1], kl[o + 2], kl[o + 3], pk[o], pk[o + 2]); hmma<1>(st[2 * h + 1], pk[16 + o], pk[17 + o], pk[18 + o], pk[19 + o], pk[o + 1], pk[o + 3]); }
    }
  }
  sched_fence(c.zero);
  bar_sync(BAR_MMA, 256);
  p1_step<9, false>(acc, c);
  sched_fence(c.zero);
  pin<16>(&st[0][0]);
  const bool le0 = 2 * q <= rho, le1 = 2 * q + 1 <= rho;
  uint32_t la[2], lb[2], mx[2];
#pragma unroll
  for (int h = 0; h < 2; h++) {
    uint32_t l[2];
#pragma unroll
    for (int r = 0; r < 2; r++) {
      const float (&t)[4] = st[2 * h + r];
      l[r] = movm(pack2(rho <= 2 * q ? t[2] : t[0], rho <= 2 * q + 1 ? t[3] : t[1]));
      l[r] = fma2(l[r], 0x3e353e35u, mul2(l[r], 0x379e379eu));
    }
    la[h] = __byte_perm(l[0], l[1], 0x5410); lb[h] = __byte_perm(l[0], l[1], 0x7632);
    if (first && !le0) la[h] = (la[h] & 0xffff0000u) | 0xce6eu;
    if (first && !le1) lb[h] = (lb[h] & 0xffff0000u) | 0xce6eu;
    mx[h] = max2(la[h], lb[h]);
  }
#pragma unroll
  for (int o = 1; o <= 2; o++) { mx[0] = max2(mx[0], __shfl_xor_sync(~0u, mx[0], o)); mx[1] = max2(mx[1], __shfl_xor_sync(~0u, mx[1], o)); }
  const float L2E = 1.4426950408889634f;
  float pr[2][4], z[4];
#pragma unroll
  for (int h = 0; h < 2; h++) {
    pr[h][0] = ex2f((lo_f(la[h]) - lo_f(mx[h])) * L2E); pr[h][1] = ex2f((lo_f(lb[h]) - lo_f(mx[h])) * L2E);
    pr[h][2] = ex2f((hi_f(la[h]) - hi_f(mx[h])) * L2E); pr[h][3] = ex2f((hi_f(lb[h]) - hi_f(mx[h])) * L2E);
    z[2 * h] = pr[h][0] + pr[h][1]; z[2 * h + 1] = pr[h][2] + pr[h][3];
  }
  p1_step<10>(acc, c);
#pragma unroll
  for (int o = 1; o <= 2; o++) {
#pragma unroll
    for (int i = 0; i < 4; i++) z[i] += __shfl_xor_sync(~0u, z[i], o);
  }
  const uint32_t LE = (le0 ? 0xffffu : 0u) | (le1 ? 0xffff0000u : 0u);
  uint32_t P[4][2];
  uint4 vt[4][2];
  {
    const uint32_t row = (lane & 7) * 64 + ((((lane >> 3) & 1) ^ ((lane & 7) >> 1)) << 4);
    const uint32_t v1 = at + AT_V + (2 * w + (lane >> 4)) * 1024 + row;
    const uint32_t v0 = (w || lane >= 16) ? v1 - 1024 : (first ? v1 : at + AT_REM + round * 2048 + 1024 + row);
#pragma unroll
    for (int i = 0; i < 4; i++) {
      const float rz = rcpf(z[i]);
      const uint32_t p = pack2(pr[i >> 1][2 * (i & 1)] * rz, pr[i >> 1][2 * (i & 1) + 1] * rz);
      P[i][0] = p & ~LE; P[i][1] = p & LE;
      const uint32_t a = ((i & 1) ? v1 : v0) + (i >> 1) * 512;
      vt[i][0] = ldsm_t(a); vt[i][1] = ldsm_t(a ^ 32);
    }
  }
  float ot[4][2][4];
  pin<8>(&P[0][0]);
  bar_sync(BAR_MMA, 256);
  mbar_wait(c.sb + B_F1 + 8 * 3, 0);
#pragma unroll
  for (int i = 0; i < 8; i++) { const uint4& v = vt[i >> 1][i & 1]; hmma<0>(ot[i >> 1][i & 1], v.x, v.y, v.z, v.w, P[i >> 1][0], P[i >> 1][1]); }
  sched_fence(c.zero);
  bar_sync(BAR_MMA, 256);
  p1_step<11, false>(acc, c);
  sched_fence(c.zero);
  pin<32>(&ot[0][0][0]);
  auto o_piece = [&](int i) {
    stg128(odst + (i >> 1) * 8192 + (i & 1) * 512, movm(pack2(ot[i][0][0], ot[i][0][1])), movm(pack2(ot[i][0][2], ot[i][0][3])), movm(pack2(ot[i][1][0], ot[i][1][1])), movm(pack2(ot[i][1][2], ot[i][1][3])));
  };
  o_piece(0); o_piece(1);
  p1_step<12>(acc, c);
  o_piece(2); o_piece(3);
  if (round) bar_arrive(BAR_EV + 4, 288);
  p1_step<13>(acc, c);
}

__device__ __forceinline__ void ln_moments(const uint32_t* raw, float& c0, float& s, float& v) {
  c0 = lo_f(__shfl_sync(~0u, raw[0], 0));
  float ss[4] = {0.f, 0.f, 0.f, 0.f}, vv[4] = {0.f, 0.f, 0.f, 0.f};
#pragma unroll
  for (int i = 0; i < 16; i++) {
    const float a = lo_f(raw[i]) - c0, b = hi_f(raw[i]) - c0;
    ss[(2 * i) & 3] += a; ss[(2 * i + 1) & 3] += b;
    vv[(2 * i) & 3] = fmaf(a, a, vv[(2 * i) & 3]); vv[(2 * i + 1) & 3] = fmaf(b, b, vv[(2 * i + 1) & 3]);
  }
  s = (ss[0] + ss[1]) + (ss[2] + ss[3]); v = (vv[0] + vv[1]) + (vv[2] + vv[3]);
}
__device__ __forceinline__ void ln_reduce(float& s, float& v) {
#pragma unroll
  for (int o = 16; o; o >>= 1) { s += __shfl_xor_sync(~0u, s, o); v += __shfl_xor_sync(~0u, v, o); }
}
__device__ __forceinline__ uint32_t ln_finish(float c0, float s, float v) {
  s *= 1.0f / DM;
  float sd;
  asm("sqrt.approx.ftz.f32 %0, %1;" : "=f"(sd) : "f"(bf16r(bf16r(fmaxf(fmaf(v, 1.0f / DM, -s * s), 0.f)) + 1e-5f)));
  return pack2(c0 + s, sd);
}
__device__ __forceinline__ void ln_store(const uint32_t* raw, uint32_t st, uint4* dst) {
  const uint32_t m2 = __byte_perm(st, st, 0x1010);
  const float rinv = rcpf(hi_f(st));
#pragma unroll
  for (int c = 0; c < 4; c++) {
    uint32_t v[4];
#pragma unroll
    for (int i = 0; i < 4; i++) { const uint32_t t = sub2(raw[4 * c + i], m2); v[i] = pack2(lo_f(t) * rinv, hi_f(t) * rinv); }
    stg128(dst + 32 * c, v[0], v[1], v[2], v[3]);
  }
}
__device__ __forceinline__ void col_sums(uint32_t tile, ulonglong2* part, uint32_t tag) {
  const int lane = threadIdx.x & 31;
  float cs[8] = {0, 0, 0, 0, 0, 0, 0, 0};
  uint32_t base = tile + ((lane >> 3) & 1) * 8192 + (lane >> 4) * 4096 + ((lane & 7) << 4);
#pragma unroll 1
  for (int k0 = 0; k0 < 8; k0++, base = (base ^ ((k0 ^ (k0 - 1)) << 4)) + 128) {
    uint4 v[4];
#pragma unroll
    for (int k = 0; k < 4; k++) v[k] = lds128(base + k * 1024);
#pragma unroll
    for (int k = 0; k < 4; k++) {
      cs[0] += lo_f(v[k].x); cs[1] += hi_f(v[k].x); cs[2] += lo_f(v[k].y); cs[3] += hi_f(v[k].y);
      cs[4] += lo_f(v[k].z); cs[5] += hi_f(v[k].z); cs[6] += lo_f(v[k].w); cs[7] += hi_f(v[k].w);
    }
  }
  const bool up = lane >= 16;
#pragma unroll
  for (int i = 0; i < 2; i++) {
    const float a = (up ? cs[4 + 2 * i] : cs[2 * i]) + __shfl_xor_sync(~0u, up ? cs[2 * i] : cs[4 + 2 * i], 16);
    const float b = (up ? cs[5 + 2 * i] : cs[1 + 2 * i]) + __shfl_xor_sync(~0u, up ? cs[1 + 2 * i] : cs[5 + 2 * i], 16);
    asm volatile("{\n.reg .b64 a, b;\nmov.b64 a, {%1, %3};\nmov.b64 b, {%2, %3};\nst.relaxed.gpu.global.v2.b64 [%0], {a, b};\n}"
                 ::"l"(part + 32 * (i + (up ? 2 : 0)) + (lane & 15)), "r"(__float_as_uint(a)), "r"(__float_as_uint(b)), "r"(tag) : "memory");
  }
  asm volatile("fence.proxy.async.shared::cta;" ::: "memory");
}

__global__ void __cluster_dims__(2, 1, 1) __launch_bounds__(384, 1)
fused_kernel(const uint4* __restrict__ x, const uint4* __restrict__ wgate, const uint4* __restrict__ wup, Scratch* gs, const __grid_constant__ Maps mp) {
  extern __shared__ __align__(1024) uint8_t smem_raw[];
  const uint32_t sb = (uint32_t)__cvta_generic_to_shared(smem_raw);
  const unsigned t_start = 0;
  const int warp = __shfl_sync(~0u, threadIdx.x >> 5, 0), lane = threadIdx.x & 31;
  const int m = blockIdx.x & 15, j = blockIdx.x >> 4, rank = blockIdx.x & 1;
  const int m2 = blockIdx.x >> 3, j2 = blockIdx.x & 7;
  const bool helper = blockIdx.x >= NMAIN;
  if (warp >= 8) {
    asm volatile("setmaxnreg.dec.sync.aligned.u32 40;");
    if (warp == 8) {
      if (elect_one()) {
        asm volatile("prefetch.tensormap [%0];\nprefetch.tensormap [%1];\nprefetch.tensormap [%2];" ::"l"(&mp.x), "l"(&mp.wg), "l"(&mp.wu) : "memory");
        for (int s = 0; s < 4; s++) mbar_init(sb + B_F1 + 8 * s, 1);
        if (!helper) mbar_arrive(sb + B_F1);
        asm volatile("fence.mbarrier_init.release.cluster;" ::: "memory");
      }
      __syncwarp();
    } else if (warp == 9) {
      if (elect_one()) {
        if ((sb & 0xffffff) != SM_BASE) asm volatile("trap;");
        for (int s = 0; s < 4; s++) mbar_init(sb + B_E1 + 8 * s, 4);
        for (int s = 0; s < 6; s++) { mbar_init(sb + B_F2 + 8 * s, 1); mbar_init(sb + B_E2 + 8 * s, 4); }
        for (int s = 0; s < 6; s++) mbar_init(sb + B_DEP + 8 * s, 1);
        mbar_init(sb + B_AUX, 8); mbar_init(sb + B_EP, 1); mbar_init(sb + B_XT, 1); mbar_init(sb + B_CS, 1);
        for (int s = 0; s < 8; s++) { mbar_init(sb + B_EX + 8 * s, 1); mbar_expect_tx(sb + B_EX + 8 * s, 4096); }
        mbar_init(sb + B_HALO, 9); mbar_init(sb + B_HALO + 8, 9);
        asm volatile("fence.mbarrier_init.release.cluster;" ::: "memory");
      }
      __syncwarp();
    }
    asm volatile("barrier.cluster.arrive.relaxed.aligned;" ::: "memory");
    if (warp == 8 && !helper) {
      if (elect_one()) {
        TS(0); TG(51);
#pragma unroll 1
        for (int kb = 1; kb < 4; kb++) {
          const uint32_t sa = sb + OFF_A + kb * 16384, sw = sb + kb * 32768, fb = sb + B_F1 + 8 * kb;
          mbar_expect_tx(fb, P1_BYTES);
          tma3d(sa, &mp.x, fb, kb * 64, m * 64, 0, EVICT_NORMAL);
          tma2d(sw, &mp.wg, fb, j * 128, kb * 64, EVICT_NORMAL); tma2d(sw + 16384, &mp.wu, fb, j * 128, kb * 64, EVICT_NORMAL);
          tma2d(sw + 8192, &mp.wg, fb, j * 128 + 64, kb * 64, EVICT_NORMAL); tma2d(sw + 24576, &mp.wu, fb, j * 128 + 64, kb * 64, EVICT_NORMAL);
        }
        TS(7);
      }
      __syncwarp();
    }
    asm volatile("barrier.cluster.wait.aligned;" ::: "memory");
    if (helper) {
      if (warp == 8) {
        unsigned e = 0;
        if (elect_one()) {
#pragma unroll 1
          for (int i = 0; i < 16; i++) {
            const uint32_t fb = sb + B_F1 + 8 * (i >> 2);
            if (!(i & 3)) mbar_expect_tx(fb, P1_BYTES);
            tma5d(sb + i * 8192, &mp.wd, fb, (blockIdx.x - NMAIN) * 256 + (i & 3) * 64, (i >> 2) * 2, HINT_W);
          }
        }
        if (lane == 0) { unsigned* ep = &gs->epoch[blockIdx.x * 2]; e = *ep + 1; *ep = e; }
        e = __shfl_sync(~0u, e, 0);
        if (lane < 16) flag_wait(&gs->flags[(FL_H + lane * 4) * 32], e * 8u);
        __syncwarp();
        if (elect_one()) {
          fence_async();
          TS(0);
#pragma unroll 1
          for (int i = 0; i < 64; i++) {
            const uint32_t fb = sb + B_F1 + 8 * (i & 3);
            if (i >= 4) { mbar_wait(sb + B_E1 + 8 * (i & 3), ~(i >> 2) & 1); mbar_expect_tx(fb, 16384); }
            bulk_load(sb + OFF_A + (i & 3) * 16384, gs->h + ((i >> 2) * 56 + (i & 3)) * 1024, 16384, fb, EVICT_NORMAL);
          }
        }
      } else if (warp == 9) {
#pragma unroll 1
        for (int t = 0; t < 16; t++) {
          bar_sync(BAR_EV + (t & 1), 288);
          if (lane == 0) { flag_add(&gs->flags[(FL_P + t) * 32]); TS(64 + t); }
          __syncwarp();
        }
      }
    } else if (warp == 8) {
      if (elect_one()) {
        uint32_t par = 0;

        auto x_load = [&]() {
          mbar_expect_tx(sb + B_XT, 32768);
          tma3d(sb + OFF_X, &mp.x, sb + B_XT, j2 * 128, m2 * 64, 0, HINT_LAST); tma3d(sb + OFF_X + 16384, &mp.x, sb + B_XT, j2 * 128 + 64, m2 * 64, 0, HINT_LAST);
        };
        auto d_prefetch = [&](int i) {
          if (PF_W == 1 && (m2 >> 2) == (i & 3)) tma5d_prefetch(&mp.wd, (j2 >> 1) * 256 + (m2 & 3) * 64, (2 * i + 4 + rank) * 2);
          if (PF_H == 1 && i < 6) asm volatile("cp.async.bulk.prefetch.L2.global [%0], 4096;" ::"l"(gs->h + (m2 * 56 + 2 * i + 4 + rank) * 1024 + (j2 >> 1) * 256) : "memory");
        };
        for (int R = 0; R < 5; R++) {
          const CUtensorMap *mb0, *mb1;
          int n0, n1;
          if (R == 1 || R == 2) {
            mb0 = &mp.wqkv; n0 = 64 * (j + 8 * (R - 1)) + rank * 2048;
            mb1 = rank ? (R == 1 ? &mp.wg : &mp.wu) : &mp.wqkv; n1 = rank ? 1024 + 64 * j : n0 + 1024;
          } else {
            mb0 = mb1 = rank ? &mp.wu : &mp.wg;
            n0 = 128 * j + (R ? 1024 * R - 1536 : 0); n1 = n0 + 64;
          }
#pragma unroll 1
          for (int kb = R ? 0 : 4; kb < 16; kb++) {
            if (R == 0 && kb == 4) { for (int i = 1; i < 8; i++) asm volatile("prefetch.tensormap [%0];" ::"l"(&mp.x + i) : "memory"); }
            if (R == 0 && kb == (CS_KB)) {
              const uint32_t cb = sb + B_CS, d = sb + OFF_X;
              mbar_expect_tx(cb, 32768);
              tma2d(d, &mp.wg, cb, n0, m * 64, EVICT_NORMAL); tma2d(d + 8192, &mp.wg, cb, n1, m * 64, EVICT_NORMAL);
              tma2d(d + 16384, &mp.wu, cb, n0, m * 64, EVICT_NORMAL); tma2d(d + 24576, &mp.wu, cb, n1, m * 64, EVICT_NORMAL);
            }
            const int st = kb & 3;
            const uint32_t sa = sb + OFF_A + st * 16384, sw = sb + st * 32768, fb = sb + B_F1 + 8 * st;
            mbar_wait(sb + B_E1 + 8 * st, par);
            if (R * 16 + kb >= 4) REL_TS(R * 16 + kb - 4);
            mbar_expect_tx(fb, P1_BYTES);
            tma2d_mc(sw + rank * 16384, mb0, fb, n0, kb * 64, HINT_W);
            tma2d_mc(sw + 8192 + rank * 16384, mb1, fb, n1, kb * 64, HINT_W);
            if (R == 0) {
              tma3d(sa, &mp.x, fb, kb * 64, m * 64, 0, EVICT_NORMAL);
            } else {
              if (R == 1 && kb == 0) { mbar_wait(sb + B_DEP, 0); TS(1); }
              tma2d(sa, &mp.xn, fb, kb * 64, m * 128, R == 4 ? HINT_LAST : EVICT_NORMAL);
            }
            if (R == 4 && kb == 4 + j2) x_load();
            if (R == 4 && kb >= 16 - PF_D) { if (kb == 16 - PF_D) mbar_wait(sb + B_DEP + 8, 0); d_prefetch(kb + PF_D - 16); }
            if (st == 3) par ^= 1;
          }
        }
#pragma unroll 1
        for (int i = 0; i < 26; i++) {
          const int st = i & 3, kb = 2 * i + 4 + rank;
          const uint32_t sa = sb + OFF_A + st * 16384, sw = sb + st * 32768, fb = sb + B_F1 + 8 * st;
          mbar_wait(sb + B_E1 + 8 * st, par);
          REL_TS(76 + i);
          mbar_expect_tx(fb, P1_BYTES);
          tma5d(sw, &mp.wd, fb, j2 * 128, kb * 2, HINT_W); tma5d(sw + 8192, &mp.wd, fb, j2 * 128 + 64, kb * 2, HINT_W);
          tma5d(sw + 16384, &mp.wd, fb, (j2 ^ 1) * 128, kb * 2, HINT_W); tma5d(sw + 24576, &mp.wd, fb, (j2 ^ 1) * 128 + 64, kb * 2, HINT_W);
          if (i == 0 || i == 6 || i == 10 || i == 18) { mbar_wait(sb + B_DEP + 8 * (1 + ((i + 6) >> 3)), 0); TS(2 + ((i + 6) >> 3)); }
          bulk_load(sa, gs->h + (m2 * 56 + kb) * 1024, 16384, fb, HINT_H);
          if (i + PF_D < 26) d_prefetch(i + PF_D);
          if (i >= PF_S && i < PF_S + 8) {
            asm volatile("cp.async.bulk.prefetch.L2.global [%0], 4096;" ::"l"(gs->o + (m2 * 16 + 2 * (i - PF_S)) * 1024 + j2 * 256) : "memory");
            if ((m2 >> 1) == i - PF_S) {
              asm volatile("cp.async.bulk.prefetch.tensor.2d.L2.global [%0, {%1, %2}];" ::"l"(&mp.wo), "r"(j2 * 128), "r"(m2 * 64) : "memory");
              asm volatile("cp.async.bulk.prefetch.tensor.2d.L2.global [%0, {%1, %2}];" ::"l"(&mp.wo), "r"(j2 * 128 + 64), "r"(m2 * 64) : "memory");
            }
          }
          if (st == 3) par ^= 1;
        }
        int st = 0; uint32_t par2 = 1;
#pragma unroll 1
        for (int t = 0; t < 16; t++) {
          const uint32_t sa = sb + p2_a(st), sw = sb + p2_b(st), fb = sb + B_F2 + 8 * st;
          if (t < 5) mbar_wait(sb + B_E1 + 8 * (((2 * t + 1) / 3 + 2) & 3), t < 3); else mbar_wait(sb + B_E2 + 8 * st, par2);
          REL_TS(102 + t);
          mbar_expect_tx(fb, P2_BYTES);
          bulk_load_mc(sa + rank * 8192, gs->o + (m2 * 16 + t) * 1024 + rank * 512, 8192, fb, HINT_H);
          tma2d(sw, &mp.wo, fb, j2 * 128, t * 64, HINT_W); tma2d(sw + 8192, &mp.wo, fb, j2 * 128 + 64, t * 64, HINT_W);
          if (++st == 5) { st = 0; par2 ^= 1; }
        }
      }
    } else if (warp == 9) {
#pragma unroll 1
      for (int e = 0; e < 7; e++) {
        const bool halo = e == 2 || e == 3;
        bar_sync(BAR_EV + e, halo ? 96 : 288);
        if (lane == 0) {
          const int f = e == 0 ? FL_XN + m : (halo ? FL_HALO + (e - 2) * 128 + blockIdx.x : FL_H + m * 4 + (e == 1 ? 0 : e - 3));
          TS(10 + 2 * e); TG(52 + e);
          flag_add(&gs->flags[f * 32]);
          if (e < 6) TS(11 + 2 * e);
        }
        __syncwarp();
      }
    } else {
      unsigned e = 0;
      if (lane == 0) {
        unsigned* ep = &gs->epoch[blockIdx.x * 2 + warp - 10];
        e = *ep + 1; *ep = e;
        if (warp == 10) { asm volatile("st.shared.b32 [%0], %1;" ::"r"(sb + OFF_EPOCH), "r"(e) : "memory"); mbar_arrive(sb + B_EP); }
      }
      e = __shfl_sync(~0u, e, 0);
      mbar_wait(sb + B_CS, 0);
      if (lane == 0 && warp == 11) TS(6);
      col_sums(sb + OFF_X + (warp - 10) * 16384, gs->cspart + (j * 16 + m) * 128 + (warp - 10) * 16, e);
      if (lane == 0 && warp == 11) TS(9);
      if (warp == 10) {
        if (lane == 0) {
#pragma unroll 1
          for (int g = 0; g < 6; g++) {
            flag_wait(&gs->flags[(g == 5 ? FL_P + m2 : (g ? FL_H + m2 * 4 + g - 1 : FL_XN + m)) * 32], e * (g == 5 ? 4u : 8u));
            fence_async();
            mbar_arrive(sb + B_DEP + 8 * g);
            if (g == 0) TS(8);
          }
          for (int p = 0; p < 8; p++) {
            asm volatile("cp.async.bulk.prefetch.L2.global [%0], 4096;" ::"l"(gs->dpart + blockIdx.x * 2048 + p * 256) : "memory");
            __nanosleep(PF_SLEEP);
          }
        }
      } else
      if (elect_one()) {
#pragma unroll 1
        for (int r = 0; r < 2; r++) {
          const uint32_t hb = sb + B_HALO + 8 * r;
          if (m) {
            flag_wait(&gs->flags[(FL_HALO + r * 128 + blockIdx.x - 1) * 32], e);
            fence_async();
            mbar_expect_tx(hb, 4096);
            for (int g = 0; g < 2; g++) bulk_load(sb + OFF_X + g * AT_WG + AT_REM + r * 2048, gs->halo + ((r * 128 + blockIdx.x - 1) * 2 + g) * 128, 2048, hb, EVICT_FIRST);
          } else {
            mbar_arrive(hb);
          }
          TS(34 + r);
        }
      }
    }
  } else {
    if (!helper) {
      const int r = threadIdx.x >> 3, ch = threadIdx.x & 7;
      const uint32_t d = sb + r * 128 + ((ch ^ (r & 7)) << 4);
      const uint4* xa = x + (128 * m + 2 * r) * 128 + ch;
      const size_t wo = (size_t)r * (DFF / 8) + 16 * j + ch;
#pragma unroll
      for (int i = 0; i < 12; i++) {
        const uint4* src = i < 4 ? xa + (i & 1) * 64 * 128 + (i >> 1) * 128 : (i < 8 ? wgate : wup) + wo + (i & 1) * 32 * (DFF / 8) + ((i >> 1) & 1) * 8;
        asm volatile("cp.async.cg.shared.global [%0], [%1], 16;" ::"r"(d + (i < 4 ? OFF_A + i * 4096 : (i - 4) * 4096)), "l"(src) : "memory");
      }
    }
    asm volatile("barrier.cluster.arrive.relaxed.aligned;" ::: "memory");
    asm volatile("setmaxnreg.inc.sync.aligned.u32 232;");
    const int wg = warp >> 2, w = warp & 3;
    Cons c;
    c.sb = sb; c.wg = wg; c.zero = warp >> 8;
    c.a0 = ((SM_BASE + wg * 8192) >> 4) | (1u << 16); c.a1 = c.a0 + 4; c.ah = 0x40000040;
    c.rel = mapa(sb, threadIdx.x & 1);
    c.do_rel = (threadIdx.x & 127) < 2;
    constexpr bool t0 = false;
    float acc[128];
    uint32_t pk[64];
    float rs[2];
    const int rho = lane >> 2, q = lane & 3;

    if (helper) {
      asm volatile("barrier.cluster.wait.aligned;" ::: "memory");
      c.a0 = ((SM_BASE + wg * 4096) >> 4) | (1u << 16); c.a1 = c.a0 + 512; c.ah = 0x80000020;
      c.rel = sb;
      uint4* dst = gs->dpart + (blockIdx.x - NMAIN) * 4096 + threadIdx.x;
      auto put = [&](int p) {
#pragma unroll
        for (int i = 4 * p; i < 4 * p + 4; i++) stg128(dst + i * 256, pk[4 * i], pk[4 * i + 1], pk[4 * i + 2], pk[4 * i + 3]);
      };
#pragma unroll 1
      for (int t = 0; t < 16; t++) {
        p1_issue<0, 0>(acc, c, t & 1);
        if (t) put(0);
        p1_issue<1, 1>(acc, c, t & 1); wg_wait<1>(); release(c, B_E1);
        if (t) put(1);
        if (wg == 1) { wg_wait<0>(); release(c, B_E1 + 8); bar_sync(BAR_LAG, 256); }
        p1_issue<2, 1>(acc, c, t & 1); wg_wait<1>(); if (wg == 0) release(c, B_E1 + 8);
        if (t) put(2);
        p1_issue<3, 1>(acc, c, t & 1);
        if (wg == 0) bar_arrive(BAR_LAG, 256);
        if (t) { put(3); bar_arrive(BAR_EV + (~t & 1), 288); dst += 8 * 2048; }
        wg_wait<1>(); release(c, B_E1 + 16);
        wg_wait<0>(); release(c, B_E1 + 24);
#pragma unroll
        for (int i = 0; i < 64; i++) pk[i] = pack2(acc[2 * i], acc[2 * i + 1]);
      }
      put(0); put(1); put(2); put(3);
      bar_arrive(BAR_EV + 1, 288);
      return;
    }
    {
      const int prow = 16 * j + 2 * warp;
      const uint4* xr = x + (size_t)(128 * m + 2 * (prow & 63) + (prow >> 6)) * 128 + lane;
      uint4* xo = gs->xn + (size_t)(128 * m + prow) * 128 + lane;
      float c0[2], mo[4];
      uint32_t st[2];
      uint32_t e;
      asm volatile("" : "+l"(xr), "+l"(xo));
      if (t0) TS(23 + wg * 16);
      asm volatile("cp.async.wait_all;\nfence.proxy.async.shared::cta;" ::: "memory");
      bar_sync(BAR_MMA, 256);
      if (threadIdx.x == 0) TS(39);
      p1_step<0, false>(acc, c);
      asm volatile("barrier.cluster.wait.aligned;" ::: "memory");
      p1_range<1, LN_LD + 1>(acc, c);
      if (t0) TS(24 + wg * 16);
#pragma unroll
      for (int i = 0; i < 8; i++) {
        asm volatile("ld.global.nc.v4.b32 {%0,%1,%2,%3}, [%4];" : "=r"(pk[4 * i]), "=r"(pk[4 * i + 1]), "=r"(pk[4 * i + 2]), "=r"(pk[4 * i + 3]) : "l"(xr + (i >> 2) * 256 + (i & 3) * 32));
      }
      p1_range<LN_LD + 1, LN_KB + 1>(acc, c);
      sched_fence(c.zero);

      pin<16>(pk); ln_moments(pk, c0[0], mo[0], mo[1]); pin<2>(mo);
      p1_step<LN_KB + 1>(acc, c);
      sched_fence(c.zero);
      pin<16>(pk + 16); ln_moments(pk + 16, c0[1], mo[2], mo[3]); ln_reduce(mo[0], mo[1]); pin<4>(mo);
      p1_step<LN_KB + 2>(acc, c);
      mbar_wait(sb + B_EP, 0);
      asm volatile("ld.shared.b32 %0, [%1];" : "=r"(e) : "r"(sb + OFF_EPOCH) : "memory");
      pin<2>(mo); st[0] = ln_finish(c0[0], mo[0], mo[1]); ln_reduce(mo[2], mo[3]); pin<1>(st); pin<2>(mo + 2);
      p1_step<LN_KB + 3>(acc, c);
      sched_fence(c.zero);
      pin<1>(st); pin<2>(mo + 2);
      st[1] = ln_finish(c0[1], mo[2], mo[3]);
      ln_store(pk, st[0], xo);
      if (lane == 0)
        asm volatile("{\n.reg .b64 a, b;\nmov.b64 a, {%1, %3};\nmov.b64 b, {%2, %3};\nst.relaxed.gpu.global.v2.b64 [%0], {a, b};\n}" ::"l"(gs->stats + 128 * m + prow), "r"(st[0]), "r"(st[1]), "r"(e) : "memory");
      p1_step<LN_KB + 4>(acc, c);
      sched_fence(c.zero);
      pin<1>(st + 1); ln_store(pk + 16, st[1], xo + 128);
      bar_arrive(BAR_EV, 288);
      p1_range<LN_KB + 5, G_KB + 1>(acc, c);
      sched_fence(c.zero);
      const unsigned long long* cp = (const unsigned long long*)gs->cspart + j * 4096 + threadIdx.x;
      const unsigned long long* sp = gs->stats + 128 * m + warp * 16 + rho;
      unsigned long long part[18];
      auto gather = [&]() {
#pragma unroll
        for (int i = 0; i < 18; i++) asm volatile("ld.relaxed.gpu.global.b64 %0, [%1];" : "=l"(part[i]) : "l"(i < 16 ? cp + i * 256 : sp + (i - 16) * 8) : "memory");
      };
      gather();
      auto validate = [&]() {
        float csum;
        for (int tries = 0;; tries++) {
          uint32_t bad = 0;
          csum = 0.f;
#pragma unroll
          for (int i = 0; i < 18; i++) { bad |= (uint32_t)(part[i] >> 32) ^ e; if (i < 16) csum += __uint_as_float((uint32_t)part[i]); }
          if (!__any_sync(~0u, bad != 0) || tries > (1 << 20)) break;
          gather();
        }
        const float hi = bf16r(csum), mid = bf16r(csum - hi);
        sts128(sb + OFF_CS + ((threadIdx.x & 62) * 4 + (threadIdx.x >> 6) * 2 + (threadIdx.x & 1)) * 16, make_uint4(pack2(hi, mid), pack2(csum - hi - mid, 0.f), 0, 0));
        asm volatile("fence.proxy.async.shared::cta;" ::: "memory");
        __syncwarp();
        if (lane == 0) mbar_arrive(sb + B_AUX);
      };
      p1_range<G_KB + 1, 14>(acc, c);
      if (wg == 1) validate();
      p1_step<14>(acc, c);
      p1_issue<3, 1>(acc, c, 1);
      if (wg == 0) validate();
      const uint32_t keep = q == 0 ? 0xffffffffu : (q == 1 ? 0xffffu : 0u);
      const uint32_t a0 = (__byte_perm((uint32_t)part[16], 0, 0x1010) ^ 0x80008000u) & keep, a1 = (__byte_perm((uint32_t)part[17], 0, 0x1010) ^ 0x80008000u) & keep;
      mbar_wait(sb + B_AUX, 0);
      wg_fence();
      wgmma256_rs(acc, a0, a1, 0, 0, (SM_BASE + OFF_CS) >> 4);
      wg_commit();
      if (wg == 0) bar_arrive(BAR_LAG, 256);
      rs[0] = rcpf(hi_f((uint32_t)part[16])); rs[1] = rcpf(hi_f((uint32_t)part[17]));
      wg_wait<2>(); release(c, B_E1 + 16);
      wg_wait<0>(); release(c, B_E1 + 24);
#pragma unroll
      for (int i = 0; i < 64; i++) pk[i] = pack2(acc[2 * i], acc[2 * i + 1]);
      if (t0) TS(25 + wg * 16);
    }
    const uint32_t img = warp * 1024 + ((lane ^ (lane >> 3)) << 4);
#pragma unroll 1
    for (int R = 1;; R++) {
      uint8_t* hb = (uint8_t*)gs->h + (size_t)m * 56 * 16384 + img;
      if (R == 2 || R == 3) {
        attn_tile(acc, pk, c, R - 2, warp, m, gs, hb + (16 + j) * 16384, (uint8_t*)gs->o + (m * 16 + j + 8 * (R - 2)) * 16384 + img);
      } else {
        if (R == 5) { c.a0 = ((SM_BASE + wg * 4096) >> 4) | (1u << 16); c.a1 = c.a0 + 512; c.ah = 0x80000020; }
        geglu_tile<0>(acc, pk, c, hb + (2 * j + (R == 1 ? 0 : 16 * R - 40)) * 16384, BAR_EV + (R == 1 ? 1 : R + 1), rs);
        rs[0] = rs[1] = 1.0f;
        if (R == 5) break;
      }
      p1_range<14, 16>(acc, c);
#pragma unroll
      for (int i = 0; i < 64; i++) pk[i] = pack2(acc[2 * i], acc[2 * i + 1]);
      if (t0) TS(25 + R + wg * 16);
    }
    if (t0) TS(30 + wg * 16);
    auto fetch = [&](int p) {
      asm volatile("ld.global.cg.v4.b32 {%0,%1,%2,%3}, [%4];" : "=r"(pk[4 * p]), "=r"(pk[4 * p + 1]), "=r"(pk[4 * p + 2]), "=r"(pk[4 * p + 3]) : "l"(gs->dpart + blockIdx.x * 2048 + p * 256 + threadIdx.x) : "memory");
    };
#pragma unroll 1
    for (int it = 3; it < 5; it++) {
      p1_issue<2, 1>(acc, c, it & 1); wg_wait<1>(); release(c, B_E1 + 8);
      p1_issue<3, 1>(acc, c, it & 1); wg_wait<1>(); release(c, B_E1 + 16);
      p1_issue<0, 1>(acc, c, ~it & 1); wg_wait<1>(); release(c, B_E1 + 24);
      p1_issue<1, 1>(acc, c, ~it & 1); wg_wait<1>(); release(c, B_E1);
    }
    p1_issue<2, 1>(acc, c, 1); wg_wait<1>(); release(c, B_E1 + 8);
    mbar_wait(sb + B_DEP + 40, 0);
    fetch(0); fetch(4);
    p1_issue<3, 1>(acc, c, 1); wg_wait<1>(); release(c, B_E1 + 16);
    fetch(1); fetch(5);
    p1_issue<0, 1>(acc, c, 0); wg_wait<1>(); release(c, B_E1 + 24);
    fetch(2); fetch(6);
    p1_issue<1, 1>(acc, c, 0); wg_wait<1>(); release(c, B_E1);
    fetch(3); fetch(7);
    if (t0) TS(31 + wg * 16);
    {
      float accs[64];
      const uint32_t peer = mapa(sb, rank ^ 1);
      auto send_piece = [&](int p) {
        asm volatile("st.async.weak.shared::cluster.mbarrier::complete_tx::bytes.v4.b32 [%0], {%1,%2,%3,%4}, [%5];" ::"r"(peer + OFF_LAND + p * 4096 + threadIdx.x * 16),
                     "r"(pack2(acc[64 + 8 * p], acc[65 + 8 * p])), "r"(pack2(acc[66 + 8 * p], acc[67 + 8 * p])), "r"(pack2(acc[68 + 8 * p], acc[69 + 8 * p])), "r"(pack2(acc[70 + 8 * p], acc[71 + 8 * p])),
                     "r"(peer + B_EX + 32 * wg + 8 * (p >> 1)) : "memory");
      };
      auto silu_piece = [&](int p) {
        const uint4 r = lds128(sb + OFF_LAND + p * 4096 + threadIdx.x * 16);
        const uint32_t rr[4] = {add2(r.x, pk[4 * p]), add2(r.y, pk[4 * p + 1]), add2(r.z, pk[4 * p + 2]), add2(r.w, pk[4 * p + 3])};
#pragma unroll
        for (int i = 0; i < 4; i++) {
          const float a = acc[8 * p + 2 * i] + lo_f(rr[i]), b = acc[8 * p + 2 * i + 1] + hi_f(rr[i]);
          pk[4 * p + i] = pack2(silu_half(a), silu_half(b));
        }
        pin<4>(pk + 4 * p);
      };
      const uint32_t xa = sb + OFF_X + (warp * 16 + (lane & 15)) * 128 + (((lane >> 4) ^ (lane & 7)) << 4);
      auto x_piece = [&](int i) { const uint4 v = ldsm((xa ^ ((i & 3) << 5)) + (i >> 2) * 16384); pk[32 + 4 * i] = v.x; pk[33 + 4 * i] = v.y; pk[34 + 4 * i] = v.z; pk[35 + 4 * i] = v.w; };
      p2_step<0>(accs, c);
      p2_step<1>(accs, c);
      mbar_wait(sb + B_E1 + 8, 0);
      send_piece(0); send_piece(1);
      p2_step<2>(accs, c); sched_fence(c.zero); send_piece(2); send_piece(3);
      p2_step<3>(accs, c); sched_fence(c.zero); send_piece(4); send_piece(5);
      p2_step<4>(accs, c); mbar_wait(sb + B_XT, 0); send_piece(6); send_piece(7);
      p2_step<5>(accs, c); mbar_wait(sb + B_EX + 32 * wg, 0); silu_piece(0); x_piece(0);
      p2_step<6>(accs, c); sched_fence(c.zero); silu_piece(1); x_piece(1);
      p2_step<7>(accs, c); mbar_wait(sb + B_EX + 32 * wg + 8, 0); silu_piece(2); x_piece(2);
      p2_step<8>(accs, c); sched_fence(c.zero); silu_piece(3); x_piece(3);
      p2_step<9>(accs, c); mbar_wait(sb + B_EX + 32 * wg + 16, 0); silu_piece(4); x_piece(4);
      p2_step<10>(accs, c); sched_fence(c.zero); silu_piece(5); x_piece(5);
      p2_step<11>(accs, c); mbar_wait(sb + B_EX + 32 * wg + 24, 0); silu_piece(6); x_piece(6); x_piece(7);
      if (wg == 1) silu_piece(7);
      p2_step<12>(accs, c); p2_step<13>(accs, c); p2_step<14>(accs, c); p2_step<15>(accs, c);
      if (wg == 0) silu_piece(7);
      wg_wait<0>();
      if (t0) TS(32 + wg * 16);
#pragma unroll
      for (int i = 0; i < 8; i++) {
        uint32_t v[4];
#pragma unroll
        for (int k = 0; k < 4; k++) v[k] = fma2(pack2(accs[8 * i + 2 * k], accs[1 + 8 * i + 2 * k]), pk[4 * i + k], pk[32 + 4 * i + k]);
        asm volatile("stmatrix.sync.aligned.m8n8.x4.shared.b16 [%0], {%1,%2,%3,%4};" ::"r"((xa ^ ((i & 3) << 5)) + (i >> 2) * 16384), "r"(v[0]), "r"(v[1]), "r"(v[2]), "r"(v[3]) : "memory");
        if (i == 3 || i == 7) {
          asm volatile("fence.proxy.async.shared::cta;" ::: "memory");
          __syncwarp();
          if (elect_one()) tma3d_store(&mp.out, sb + OFF_X + (i >> 2) * 16384 + warp * 2048, j2 * 128 + (i >> 2) * 64, m2 * 64 + w * 16, wg);
        }
      }
      if (elect_one()) { asm volatile("cp.async.bulk.commit_group;\ncp.async.bulk.wait_group.read 0;" ::: "memory"); }
      if ((threadIdx.x & 127) == 0) { TS(33 + wg * 16); if (wg) { TG(59); unsigned id; asm volatile("mov.u32 %0, %%smid;" : "=r"(id)); TSV(60, id); } }
    }
  }
}

typedef CUresult (*EncodeFn)(CUtensorMap*, CUtensorMapDataType, cuuint32_t, void*, const cuuint64_t*, const cuuint64_t*, const cuuint32_t*, const cuuint32_t*,
                             CUtensorMapInterleave, CUtensorMapSwizzle, CUtensorMapL2promotion, CUtensorMapFloatOOBfill);

void encode(EncodeFn fn, CUtensorMap* tm, const void* p, int rank, const cuuint64_t* dims, const cuuint64_t* strides, const cuuint32_t* box) {
  const cuuint32_t es[5] = {1, 1, 1, 1, 1};
  fn(tm, CU_TENSOR_MAP_DATA_TYPE_BFLOAT16, rank, const_cast<void*>(p), dims, strides, box, es, CU_TENSOR_MAP_INTERLEAVE_NONE, CU_TENSOR_MAP_SWIZZLE_128B,
     PROMO, CU_TENSOR_MAP_FLOAT_OOB_FILL_NONE);
}

}

extern "C" void kernel_launch(void* const* d_in, const int* in_sizes, int n_in, void* d_out, int out_size) {
  (void)in_sizes; (void)n_in; (void)out_size;
  static EncodeFn fn = nullptr;
  static Scratch* gs = nullptr;
  if (!fn) {
    void* p = nullptr;
    cudaDriverEntryPointQueryResult qr;
    cudaGetDriverEntryPoint("cuTensorMapEncodeTiled", &p, cudaEnableDefault, &qr);
    fn = (EncodeFn)p;
    cudaGetSymbolAddress((void**)&gs, g_scratch);
    cudaFuncSetAttribute(fused_kernel, cudaFuncAttributeMaxDynamicSharedMemorySize, SMEM_BYTES);
  }
  const void *x = d_in[0], *wqkv = d_in[1], *wo = d_in[2], *wg = d_in[4], *wu = d_in[5], *wd = d_in[6];
  Maps mp;
  {
    const cuuint64_t dims[3] = {DM, SEQ / 2, 2}, st[2] = {DM * 4, DM * 2};
    const cuuint32_t box_in[3] = {64, 64, 2}, box_out[3] = {64, 16, 1};
    encode(fn, &mp.x, x, 3, dims, st, box_in);
    encode(fn, &mp.out, d_out, 3, dims, st, box_out);
  }
  {
    const cuuint64_t dims[2] = {DM, SEQ}, st[1] = {DM * 2};
    const cuuint32_t box[2] = {64, 128};
    encode(fn, &mp.xn, gs->xn, 2, dims, st, box);
  }
  {
    const cuuint32_t box[2] = {64, 64};
    const cuuint64_t dq[2] = {3 * DM, DM}, sq[1] = {3 * DM * 2}, df[2] = {DFF, DM}, sf[1] = {DFF * 2}, dw[2] = {DM, DM}, sw[1] = {DM * 2};
    encode(fn, &mp.wqkv, wqkv, 2, dq, sq, box);
    encode(fn, &mp.wg, wg, 2, df, sf, box);
    encode(fn, &mp.wu, wu, 2, df, sf, box);
    encode(fn, &mp.wo, wo, 2, dw, sw, box);
  }
  {
    const cuuint32_t box[5] = {64, 2, 4, 4, 2};
    const cuuint64_t st[4] = {DM * 2, 8 * DM * 2, 2 * DM * 2, 32 * DM * 2};
    const cuuint64_t dd[5] = {DM, 2, 4, 4, DFF / 32};
    encode(fn, &mp.wd, wd, 5, dd, st, box);
  }
  fused_kernel<<<NCTA, 384, SMEM_BYTES>>>((const uint4*)x, (const uint4*)wg, (const uint4*)wu, gs, mp);
}
```

```cpp
#include <cuda_runtime.h>
#include <cuda_bf16.h>
#include <cuda.h>
#include <stdint.h>

#define LN_LD 0
#define PROMO CU_TENSOR_MAP_L2_PROMOTION_L2_128B
#define G_KB 12
#define PF_D 4
#define PF_W 1
#define PF_H 1
#define PF_SLEEP 250
#define PF_S 16
#define LAG2 4
#define FENCE_SHORT 0
#define CS_KB 8
#define LN_KB 4

#define EVICT_FIRST 0x12F0000000000000ull
#define EVICT_NORMAL 0x1000000000000000ull
#define HINT_W EVICT_FIRST
#define HINT_H EVICT_FIRST
#define HINT_LAST EVICT_FIRST

namespace {

constexpr int SEQ = 2048, DM = 1024, DFF = 3584;
constexpr int NMAIN = 128, NCTA = 132;

constexpr uint32_t SM_BASE = 0x400;
constexpr uint32_t P1_BYTES = 49152, P2_BYTES = 32768;
constexpr uint32_t OFF_A = 131072;
__host__ __device__ constexpr uint32_t p2_a(int s) { return s == 0 ? OFF_A + 32768 : s == 1 ? OFF_A + 49152 : s == 2 ? 114688 : s == 3 ? 16384 : 49152; }
__host__ __device__ constexpr uint32_t p2_b(int s) { return s < 3 ? 65536 + s * 16384 : (s - 3) * 32768; }
constexpr uint32_t OFF_LAND = OFF_A;
constexpr uint32_t OFF_X = 196608;
constexpr uint32_t OFF_CS = OFF_X + 14336;
constexpr uint32_t OFF_BAR = 229376;
constexpr uint32_t B_F1 = OFF_BAR, B_E1 = B_F1 + 32, B_F2 = B_E1 + 32, B_E2 = B_F2 + 48;
constexpr uint32_t B_DEP = B_E2 + 48;
constexpr uint32_t B_AUX = B_DEP + 48, B_CS = B_AUX + 8, B_XT = B_CS + 8, B_EX = B_XT + 8, B_HALO = B_EX + 64, B_EP = B_HALO + 16, B_DONE = B_EP + 8, OFF_EPOCH = B_DONE + 8;
constexpr uint32_t SMEM_BYTES = 232448;
constexpr uint32_t AT_V = 0, AT_K = 8192, AT_REM = 11264, AT_WG = 15360;

constexpr int FL_XN = 0, FL_H = 16, FL_P = 80, FL_HALO = 96, FL_N = FL_HALO + 256;
struct __align__(1024) Scratch {
  uint4 h[16 * 56 * 1024];
  uint4 o[16 * 16 * 1024];
  uint4 xn[SEQ * DM / 8];
  uint4 dpart[128 * 8 * 256];
  uint4 halo[2 * 128 * 2 * 128];
  ulonglong2 cspart[8 * 16 * 128];
  unsigned long long stats[SEQ];
  unsigned flags[FL_N * 32];
  unsigned epoch[NCTA * 2];
};
__device__ Scratch g_scratch;
#define TG(i) do {} while (0)
#define TSV(i, v) do {} while (0)
#define TS(i) do {} while (0)

struct Maps { CUtensorMap x, xn, out, wqkv, wg, wu, wd, wo; };

__device__ __forceinline__ void mbar_init(uint32_t bar, uint32_t cnt) { asm volatile("mbarrier.init.shared::cta.b64 [%0], %1;" ::"r"(bar), "r"(cnt)); }
__device__ __forceinline__ void mbar_expect_tx(uint32_t bar, uint32_t bytes) { asm volatile("mbarrier.arrive.expect_tx.shared::cta.b64 _, [%0], %1;" ::"r"(bar), "r"(bytes) : "memory"); }
__device__ __forceinline__ void mbar_arrive(uint32_t bar) { asm volatile("mbarrier.arrive.shared::cta.b64 _, [%0];" ::"r"(bar) : "memory"); }
__device__ __forceinline__ void mbar_arrive_cl(uint32_t bar) { asm volatile("mbarrier.arrive.shared::cluster.b64 _, [%0];" ::"r"(bar) : "memory"); }
__device__ __forceinline__ uint32_t mapa(uint32_t a, uint32_t cta) { uint32_t r; asm("mapa.shared::cluster.u32 %0, %1, %2;" : "=r"(r) : "r"(a), "r"(cta)); return r; }
__device__ __forceinline__ void mbar_wait(uint32_t bar, uint32_t parity) {
  asm volatile("{\n.reg .pred p;\n.reg .u32 n;\nmov.u32 n, 0;\nLAB_WAIT:\nmbarrier.try_wait.parity.shared::cta.b64 p, [%0], %1;\n@p bra LAB_DONE;\n"
               "add.u32 n, n, 1;\nsetp.gt.u32 p, n, 4000000;\n@p trap;\nbra LAB_WAIT;\nLAB_DONE:\n}" ::"r"(bar), "r"(parity) : "memory");
}
__device__ __forceinline__ void mbar_spin(uint32_t bar, uint32_t parity, uint32_t zero) {
  asm volatile("{\n.reg .pred p, z;\nsetp.ne.u32 z, %2, 0;\nLAB_WAIT:\nmbarrier.try_wait.parity.shared::cta.b64 p, [%0], %1;\n@p bra LAB_DONE;\n@z trap;\nbra LAB_WAIT;\nLAB_DONE:\n}" ::"r"(bar), "r"(parity), "r"(zero) : "memory");
}
__device__ __forceinline__ void flag_wait(const unsigned* f, unsigned target) {
  asm volatile("{\n.reg .pred p;\n.reg .u32 n, v;\nmov.u32 n, 0;\nLAB_WAIT:\nld.relaxed.gpu.global.u32 v, [%0];\nsub.u32 v, v, %1;\nsetp.ge.s32 p, v, 0;\n@p bra LAB_DONE;\n"
               "nanosleep.u32 100;\nadd.u32 n, n, 1;\nsetp.gt.u32 p, n, 4000000;\n@p trap;\nbra LAB_WAIT;\nLAB_DONE:\nfence.acquire.gpu;\n}" ::"l"(f), "r"(target) : "memory");
}
__device__ __forceinline__ void flag_add(unsigned* f) { asm volatile("red.release.gpu.global.add.u32 [%0], 1;" ::"l"(f) : "memory"); }
__device__ __forceinline__ void fence_async() { asm volatile("fence.proxy.async.global;" ::: "memory"); }
__device__ __forceinline__ bool elect_one() { uint32_t p; asm volatile("{\n.reg .pred P;\nelect.sync _|P, 0xffffffff;\nselp.u32 %0, 1, 0, P;\n}" : "=r"(p)); return p; }
__device__ __forceinline__ void bar_sync(int id, int n) { asm volatile("bar.sync %0, %1;" ::"r"(id), "r"(n) : "memory"); }
__device__ __forceinline__ void bar_arrive(int id, int n) { asm volatile("bar.arrive %0, %1;" ::"r"(id), "r"(n) : "memory"); }

__device__ __forceinline__ void tma2d(uint32_t dst, const CUtensorMap* tm, uint32_t bar, int c0, int c1, uint64_t hint) {
  asm volatile("cp.async.bulk.tensor.2d.shared::cluster.global.mbarrier::complete_tx::bytes.L2::cache_hint [%0], [%1, {%3, %4}], [%2], %5;" ::"r"(dst), "l"(tm), "r"(bar), "r"(c0), "r"(c1), "l"(hint) : "memory");
}
__device__ __forceinline__ void tma2d_mc(uint32_t dst, const CUtensorMap* tm, uint32_t bar, int c0, int c1, uint64_t hint) {
  asm volatile("cp.async.bulk.tensor.2d.shared::cluster.global.mbarrier::complete_tx::bytes.multicast::cluster.L2::cache_hint [%0], [%1, {%3, %4}], [%2], %5, %6;" ::"r"(dst), "l"(tm), "r"(bar), "r"(c0), "r"(c1), "h"((uint16_t)3), "l"(hint) : "memory");
}
__device__ __forceinline__ void tma3d(uint32_t dst, const CUtensorMap* tm, uint32_t bar, int c0, int c1, int c2, uint64_t hint) {
  asm volatile("cp.async.bulk.tensor.3d.shared::cluster.global.mbarrier::complete_tx::bytes.L2::cache_hint [%0], [%1, {%3, %4, %5}], [%2], %6;" ::"r"(dst), "l"(tm), "r"(bar), "r"(c0), "r"(c1), "r"(c2), "l"(hint) : "memory");
}
__device__ __forceinline__ void tma5d(uint32_t dst, const CUtensorMap* tm, uint32_t bar, int c0, int c4, uint64_t hint) {
  asm volatile("cp.async.bulk.tensor.5d.shared::cluster.global.mbarrier::complete_tx::bytes.L2::cache_hint [%0], [%1, {%3, %5, %5, %5, %4}], [%2], %6;" ::"r"(dst), "l"(tm), "r"(bar), "r"(c0), "r"(c4), "r"(0), "l"(hint) : "memory");
}
__device__ __forceinline__ void tma5d_prefetch(const CUtensorMap* tm, int c0, int c4) {
  asm volatile("cp.async.bulk.prefetch.tensor.5d.L2.global [%0, {%1, %3, %3, %3, %2}];" ::"l"(tm), "r"(c0), "r"(c4), "r"(0) : "memory");
}
__device__ __forceinline__ void tma3d_store(const CUtensorMap* tm, uint32_t src, int c0, int c1, int c2) {
  asm volatile("cp.async.bulk.tensor.3d.global.shared::cta.bulk_group [%0, {%2, %3, %4}], [%1];" ::"l"(tm), "r"(src), "r"(c0), "r"(c1), "r"(c2) : "memory");
}
__device__ __forceinline__ void bulk_load(uint32_t dst, const void* src, uint32_t bytes, uint32_t bar, uint64_t hint) {
  asm volatile("cp.async.bulk.shared::cluster.global.mbarrier::complete_tx::bytes.L2::cache_hint [%0], [%1], %2, [%3], %4;" ::"r"(dst), "l"(src), "r"(bytes), "r"(bar), "l"(hint) : "memory");
}
__device__ __forceinline__ void bulk_load_mc(uint32_t dst, const void* src, uint32_t bytes, uint32_t bar, uint64_t hint) {
  asm volatile("cp.async.bulk.shared::cluster.global.mbarrier::complete_tx::bytes.multicast::cluster.L2::cache_hint [%0], [%1], %2, [%3], %4, %5;" ::"r"(dst), "l"(src), "r"(bytes), "r"(bar), "h"((uint16_t)3), "l"(hint) : "memory");
}
__device__ __forceinline__ uint4 lds128(uint32_t a) { uint4 v; asm volatile("ld.shared.v4.b32 {%0,%1,%2,%3}, [%4];" : "=r"(v.x), "=r"(v.y), "=r"(v.z), "=r"(v.w) : "r"(a) : "memory"); return v; }
__device__ __forceinline__ void sts128(uint32_t a, uint4 v) { asm volatile("st.shared.v4.b32 [%0], {%1,%2,%3,%4};" ::"r"(a), "r"(v.x), "r"(v.y), "r"(v.z), "r"(v.w) : "memory"); }
__device__ __forceinline__ void stg128(void* p, uint32_t a, uint32_t b, uint32_t c, uint32_t d) { asm volatile("st.global.v4.b32 [%0], {%1,%2,%3,%4};" ::"l"(p), "r"(a), "r"(b), "r"(c), "r"(d) : "memory"); }

__device__ __forceinline__ uint32_t pack2(float lo, float hi) { uint32_t r; asm("cvt.rn.bf16x2.f32 %0, %1, %2;" : "=r"(r) : "f"(hi), "f"(lo)); return r; }
__device__ __forceinline__ float lo_f(uint32_t v) { return __uint_as_float(v << 16); }
__device__ __forceinline__ float hi_f(uint32_t v) { return __uint_as_float(v & 0xffff0000u); }
__device__ __forceinline__ float bf16r(float v) { return lo_f(pack2(v, 0.f)); }
__device__ __forceinline__ uint32_t mul2(uint32_t a, uint32_t b) { uint32_t r; asm("mul.rn.bf16x2 %0, %1, %2;" : "=r"(r) : "r"(a), "r"(b)); return r; }
__device__ __forceinline__ uint32_t add2(uint32_t a, uint32_t b) { uint32_t r; asm("add.rn.bf16x2 %0, %1, %2;" : "=r"(r) : "r"(a), "r"(b)); return r; }
__device__ __forceinline__ uint32_t sub2(uint32_t a, uint32_t b) { uint32_t r; asm("sub.rn.bf16x2 %0, %1, %2;" : "=r"(r) : "r"(a), "r"(b)); return r; }
__device__ __forceinline__ uint32_t fma2(uint32_t a, uint32_t b, uint32_t c) { uint32_t r; asm("fma.rn.bf16x2 %0, %1, %2, %3;" : "=r"(r) : "r"(a), "r"(b), "r"(c)); return r; }
__device__ __forceinline__ uint32_t max2(uint32_t a, uint32_t b) { uint32_t r; asm("max.bf16x2 %0, %1, %2;" : "=r"(r) : "r"(a), "r"(b)); return r; }
__device__ __forceinline__ float ex2f(float x) { float y; asm("ex2.approx.ftz.f32 %0, %1;" : "=f"(y) : "f"(x)); return y; }
__device__ __forceinline__ float rcpf(float x) { float y; asm("rcp.approx.ftz.f32 %0, %1;" : "=f"(y) : "f"(x)); return y; }
__device__ __forceinline__ float gelu2(float g) {
  float z = g * fmaf(g * g, 0.035677408136300125f, 0.7978845608028654f), t;
  asm("tanh.approx.f32 %0, %1;" : "=f"(t) : "f"(z));
  return fmaf(g, t, g);
}

__device__ __forceinline__ float silu_half(float z) { float t; asm("tanh.approx.f32 %0, %1;" : "=f"(t) : "f"(z)); return fmaf(z, t, z); }

__device__ __forceinline__ void wg_fence() { asm volatile("wgmma.fence.sync.aligned;" ::: "memory"); }
__device__ __forceinline__ void wg_commit() { asm volatile("wgmma.commit_group.sync.aligned;" ::: "memory"); }
template <int N> __device__ __forceinline__ void wg_wait() { asm volatile("wgmma.wait_group.sync.aligned %0;" ::"n"(N) : "memory"); }
#define A8(o) "+f"(d[(o)]), "+f"(d[(o) + 1]), "+f"(d[(o) + 2]), "+f"(d[(o) + 3]), "+f"(d[(o) + 4]), "+f"(d[(o) + 5]), "+f"(d[(o) + 6]), "+f"(d[(o) + 7])
#define A64(o) A8(o), A8((o) + 8), A8((o) + 16), A8((o) + 24), A8((o) + 32), A8((o) + 40), A8((o) + 48), A8((o) + 56)
#define REGS0_63 "%0,%1,%2,%3,%4,%5,%6,%7,%8,%9,%10,%11,%12,%13,%14,%15,%16,%17,%18,%19,%20,%21,%22,%23,%24,%25,%26,%27,%28,%29,%30,%31," \
                 "%32,%33,%34,%35,%36,%37,%38,%39,%40,%41,%42,%43,%44,%45,%46,%47,%48,%49,%50,%51,%52,%53,%54,%55,%56,%57,%58,%59,%60,%61,%62,%63"
#define REGS64_127 "%64,%65,%66,%67,%68,%69,%70,%71,%72,%73,%74,%75,%76,%77,%78,%79,%80,%81,%82,%83,%84,%85,%86,%87,%88,%89,%90,%91,%92,%93,%94,%95," \
                   "%96,%97,%98,%99,%100,%101,%102,%103,%104,%105,%106,%107,%108,%109,%110,%111,%112,%113,%114,%115,%116,%117,%118,%119,%120,%121,%122,%123,%124,%125,%126,%127"
__device__ __forceinline__ void desc_add(uint64_t& x, int v) { asm volatile("{\n.reg .b32 lo, hi;\nmov.b64 {lo, hi}, %0;\nadd.s32 lo, lo, %1;\nmov.b64 %0, {lo, hi};\n}" : "+l"(x) : "r"(v)); }
template <int ACCUM> __device__ __forceinline__ void wgmma256(float (&d)[128], uint64_t& a, uint64_t& b, int da, int db) {
  asm volatile("{\n.reg .pred p;\nsetp.ne.b32 p, %130, 0;\n"
               "wgmma.mma_async.sync.aligned.m64n256k16.f32.bf16.bf16 {" REGS0_63 "," REGS64_127 "}, %128, %129, p, 1, 1, 0, 1;\n}"
               : A64(0), A64(64) : "l"(a), "l"(b), "n"(ACCUM));
  desc_add(a, da); desc_add(b, db);
}
__device__ __forceinline__ void wgmma256_rs(float (&d)[128], uint32_t a0, uint32_t a1, uint32_t z0, uint32_t z1, uint32_t b_lo) {
  asm volatile("{\n.reg .b64 db;\nmov.b64 db, {%132, 0x00000008};\n"
               "wgmma.mma_async.sync.aligned.m64n256k16.f32.bf16.bf16 {" REGS0_63 "," REGS64_127 "}, {%128,%129,%130,%131}, db, 1, 1, 1, 0;\n}"
               : A64(0), A64(64) : "r"(a0), "r"(a1), "r"(z0), "r"(z1), "r"(b_lo));
}
template <int ACCUM> __device__ __forceinline__ void wgmma128(float (&d)[64], uint64_t& a, uint64_t& b, int da, int db) {
  asm volatile("{\n.reg .pred p;\nsetp.ne.b32 p, %66, 0;\n"
               "wgmma.mma_async.sync.aligned.m64n128k16.f32.bf16.bf16 {" REGS0_63 "}, %64, %65, p, 1, 1, 0, 1;\n}"
               : A64(0) : "l"(a), "l"(b), "n"(ACCUM));
  desc_add(a, da); desc_add(b, db);
}
template <int ACCUM> __device__ __forceinline__ void hmma(float (&c)[4], uint32_t a0, uint32_t a1, uint32_t a2, uint32_t a3, uint32_t b0, uint32_t b1) {
  if (ACCUM)
    asm volatile("mma.sync.aligned.m16n8k16.row.col.f32.bf16.bf16.f32 {%0,%1,%2,%3}, {%4,%5,%6,%7}, {%8,%9}, {%0,%1,%2,%3};"
                 : "+f"(c[0]), "+f"(c[1]), "+f"(c[2]), "+f"(c[3]) : "r"(a0), "r"(a1), "r"(a2), "r"(a3), "r"(b0), "r"(b1));
  else
    asm volatile("mma.sync.aligned.m16n8k16.row.col.f32.bf16.bf16.f32 {%0,%1,%2,%3}, {%4,%5,%6,%7}, {%8,%9}, {%10,%10,%10,%10};"
                 : "=f"(c[0]), "=f"(c[1]), "=f"(c[2]), "=f"(c[3]) : "r"(a0), "r"(a1), "r"(a2), "r"(a3), "r"(b0), "r"(b1), "f"(0.f));
}
__device__ __forceinline__ uint32_t movm(uint32_t a) { uint32_t d; asm volatile("movmatrix.sync.aligned.m8n8.trans.b16 %0, %1;" : "=r"(d) : "r"(a)); return d; }
template <int N> __device__ __forceinline__ void pin(uint32_t* r) {
#pragma unroll
  for (int i = 0; i < N; i++) asm volatile("" : "+r"(r[i]));
}
template <int N> __device__ __forceinline__ void pin(float* r) {
#pragma unroll
  for (int i = 0; i < N; i++) asm volatile("" : "+f"(r[i]));
}
__device__ __forceinline__ void sched_fence(uint32_t zero) {
  asm volatile(
    "{\n.reg .pred p;\n.reg .u32 n;\nmov.u32 n, %0;\nLAB_F:\nsetp.eq.u32 p, n, 0;\n@p bra.uni LAB_D;\nnanosleep.u32 n;\nsub.u32 n, n, 1;\nbra.uni LAB_F;\nLAB_D:\n}"
     ::"r"(zero) : "memory");
}
__device__ __forceinline__ uint4 ldsm(uint32_t a) { uint4 v; asm volatile("ldmatrix.sync.aligned.m8n8.x4.shared.b16 {%0,%1,%2,%3}, [%4];" : "=r"(v.x), "=r"(v.y), "=r"(v.z), "=r"(v.w) : "r"(a) : "memory"); return v; }
__device__ __forceinline__ uint4 ldsm_t(uint32_t a) { uint4 v; asm volatile("ldmatrix.sync.aligned.m8n8.x4.trans.shared.b16 {%0,%1,%2,%3}, [%4];" : "=r"(v.x), "=r"(v.y), "=r"(v.z), "=r"(v.w) : "r"(a) : "memory"); return v; }

constexpr int BAR_LAG = 1, BAR_MMA = 2, BAR_EV = 3;

struct Cons {
  uint32_t sb;
  mutable uint64_t a, b;
  int k1, k2, k4, k4w, b1;
  uint32_t rel;
  bool do_rel;
  int wg;
  uint32_t zero;
};
#define REL_TS(n) TS(64 + (n))
constexpr uint32_t DB_LO = (SM_BASE >> 4) | ((8192 >> 4) << 16);

template <int ST, int ACCUM, bool WAIT = true> __device__ __forceinline__ void p1_issue(float (&acc)[128], const Cons& c, uint32_t parity) {
  if (WAIT) mbar_spin(c.sb + B_F1 + 8 * ST, parity, c.zero);
  wg_fence();
  wgmma256<ACCUM>(acc, c.a, c.b, c.k1, c.b1);
  wgmma256<1>(acc, c.a, c.b, c.k2, c.b1);
  wgmma256<1>(acc, c.a, c.b, c.k1, c.b1);
  wgmma256<1>(acc, c.a, c.b, ST == 3 ? c.k4w : c.k4, ST == 3 ? -6144 - 384 : 2048 - 384);
  wg_commit();
}
__device__ __forceinline__ void release(const Cons& c, uint32_t bar) { if (c.do_rel) mbar_arrive_cl(c.rel + bar); }
template <int KB, bool WAIT = true, int LAG = 2> __device__ __forceinline__ void p1_step(float (&acc)[128], const Cons& c) {
  if (KB == 16 - LAG) { if (c.wg == 1) { wg_wait<0>(); release(c, B_E1 + 8 * ((KB - 1) & 3)); bar_sync(BAR_LAG, 256); } }
  p1_issue<KB & 3, KB != 0, WAIT>(acc, c, (KB >> 2) & 1);
  if (KB == 15) { if (c.wg == 0) bar_arrive(BAR_LAG, 256); }
  if (KB > 0) { wg_wait<1>(); if (KB != 16 - LAG || c.wg == 0) release(c, B_E1 + 8 * ((KB - 1) & 3)); }
  if (KB == 15) { wg_wait<0>(); release(c, B_E1 + 8 * 3); }
}
template <int A, int B> __device__ __forceinline__ void p1_range(float (&acc)[128], const Cons& c) {
  if constexpr (A < B) { p1_step<A>(acc, c); p1_range<A + 1, B>(acc, c); }
}
template <int T> __device__ __forceinline__ void p2_step(float (&acc)[64], const Cons& c) {
  if (T == 16 - LAG2) { if (c.wg == 1) bar_sync(BAR_LAG, 256); }
  mbar_spin(c.sb + B_F2 + 8 * (T % 5), (T / 5) & 1, c.zero);
  wg_fence();
  wgmma128<T != 0>(acc, c.a, c.b, c.k1, c.b1);
  wgmma128<1>(acc, c.a, c.b, c.k2, c.b1);
  wgmma128<1>(acc, c.a, c.b, c.k1, c.b1);
  wgmma128<1>(acc, c.a, c.b, ((int)p2_a((T + 1) % 5) - (int)p2_a(T % 5)) / 16 - 514, ((int)p2_b((T + 1) % 5) - (int)p2_b(T % 5)) / 16 - 384);
  wg_commit();
  if (T == 15) { if (c.wg == 0) bar_arrive(BAR_LAG, 256); }
  if (T <= 11) { wg_wait<1>(); release(c, T ? B_E2 + 8 * ((T + 5 - 1) % 5) : B_E1 + 8); }
}

template <int P> __device__ __forceinline__ void geglu_piece(const uint32_t (&pk)[64], uint8_t* dst, const float (&rs)[2]) {
  constexpr int cg = P >> 1, r = P & 1;
  const float rq = rs[r] * 0.25f;
  uint32_t v[4];
#pragma unroll
  for (int i = 0; i < 4; i++) {
    const uint32_t g = pk[2 * (4 * cg + i) + r];
    v[i] = mul2(pack2(gelu2(lo_f(g) * rs[r]) * rq, gelu2(hi_f(g) * rs[r]) * rq), pk[32 + 2 * (4 * cg + i) + r]);
  }
  stg128(dst + cg * 8192 + r * 512, v[0], v[1], v[2], v[3]);
}
template <int KB> __device__ __forceinline__ void geglu_tile(float (&acc)[128], const uint32_t (&pk)[64], const Cons& c, uint8_t* dst, int ev, const float (&rs)[2]) {
  if constexpr (KB < 14) {
    p1_step<KB>(acc, c);
    if (KB >= 1 && KB <= 8) geglu_piece<(KB - 1) & 7>(pk, dst, rs);
    if (KB == 8) bar_arrive(ev, 288);
    geglu_tile<KB + 1>(acc, pk, c, dst, ev, rs);
  }
}

__device__ __forceinline__ void attn_tile(float (&acc)[128], const uint32_t (&pk)[64], const Cons& c, int round, int warp, int m, Scratch* gs, uint8_t* hdst, uint8_t* odst) {
  const int lane = threadIdx.x & 31, w = warp & 3, rho = lane >> 2, q = lane & 3;
  const uint32_t at = c.sb + OFF_X + c.wg * AT_WG, swz = (lane ^ (lane >> 3)) << 4;
  uint32_t gg[16];
  p1_step<0>(acc, c);
  p1_step<1>(acc, c);
#pragma unroll
  for (int i = 0; i < 4; i++) {
    const int h = i & 1, r = i >> 1;
    sts128(at + AT_V + (2 * w + r) * 1024 + h * 512 + swz, make_uint4(pk[32 + 8 * h + r], pk[34 + 8 * h + r], pk[36 + 8 * h + r], pk[38 + 8 * h + r]));
  }
  if (w < 3) {
#pragma unroll
    for (int i = 0; i < 8; i++) asm volatile("st.shared.b32 [%0], %1;" ::"r"(at + AT_K + w * 1024 + i * 128 + lane * 4), "r"(pk[17 + 2 * i]) : "memory");
  } else {
    uint8_t* g = (uint8_t*)gs->halo + ((round * 128 + blockIdx.x) * 2 + c.wg) * 2048;
#pragma unroll
    for (int i = 0; i < 8; i++) asm volatile("st.global.b32 [%0], %1;" ::"l"(g + i * 128 + lane * 4), "r"(pk[17 + 2 * i]) : "memory");
#pragma unroll
    for (int h = 0; h < 2; h++) stg128(g + 1024 + h * 512 + swz, pk[33 + 8 * h], pk[35 + 8 * h], pk[37 + 8 * h], pk[39 + 8 * h]);
    bar_arrive(BAR_EV + 2 + round, 96);
  }
  __syncwarp();
  if (lane == 0) mbar_arrive(c.sb + B_HALO + 8 * round);
  if (round) {
#pragma unroll
    for (int p = 0; p < 4; p++) asm volatile("ld.global.cg.v4.b32 {%0,%1,%2,%3}, [%4];" : "=r"(gg[4 * p]), "=r"(gg[4 * p + 1]), "=r"(gg[4 * p + 2]), "=r"(gg[4 * p + 3]) : "l"(hdst + (p >> 1) * 8192 + (p & 1) * 512) : "memory");
  }
  auto gu_piece = [&](int p) {
    uint32_t v[4];
#pragma unroll
    for (int i = 0; i < 4; i++) {
      const uint32_t g = pk[48 + 8 * (p >> 1) + 2 * i + (p & 1)];
      v[i] = mul2(round ? gg[4 * p + i] : 0x3e803e80u, round ? g : pack2(gelu2(lo_f(g)), gelu2(hi_f(g))));
    }
    stg128(hdst + (p >> 1) * 8192 + (p & 1) * 512, v[0], v[1], v[2], v[3]);
  };
  p1_step<2>(acc, c);
  p1_step<3>(acc, c); gu_piece(0);
  p1_step<4>(acc, c); gu_piece(1);
  p1_step<5>(acc, c); gu_piece(2);
  p1_step<6>(acc, c); gu_piece(3);
  p1_step<7>(acc, c);
  p1_step<8>(acc, c);
  const bool first = m == 0 && w == 0;
  uint32_t kl[16];
  mbar_spin(c.sb + B_HALO + 8 * round, 0, c.zero);
  {
    const uint32_t ka = at + lane * 4 + (w ? AT_K + (w - 1) * 1024 : (first ? AT_K : AT_REM + round * 2048));
#pragma unroll
    for (int i = 0; i < 8; i++) {
      asm volatile("ld.shared.b32 %0, [%1];" : "=r"(kl[2 * i]) : "r"(ka + i * 128) : "memory");
      kl[2 * i + 1] = pk[16 + 2 * i] | c.zero;
    }
  }
  float st[4][4];
  pin<16>(kl);
  bar_sync(BAR_MMA, 256);
  mbar_spin(c.sb + B_F1 + 8 * 1, 0, c.zero);
#pragma unroll
  for (int ks = 0; ks < 2; ks++) {
#pragma unroll
    for (int h = 0; h < 2; h++) {
      const int o = 8 * h + 4 * ks;
      if (ks == 0) { hmma<0>(st[2 * h], kl[o], kl[o + 1], kl[o + 2], kl[o + 3], pk[o], pk[o + 2]); hmma<0>(st[2 * h + 1], pk[16 + o], pk[17 + o], pk[18 + o], pk[19 + o], pk[o + 1], pk[o + 3]); }
      else { hmma<1>(st[2 * h], kl[o], kl[o + 1], kl[o + 2], kl[o + 3], pk[o], pk[o + 2]); hmma<1>(st[2 * h + 1], pk[16 + o], pk[17 + o], pk[18 + o], pk[19 + o], pk[o + 1], pk[o + 3]); }
    }
  }
  sched_fence(c.zero);
  bar_sync(BAR_MMA, 256);
  p1_step<9, false>(acc, c);
  sched_fence(c.zero);
  pin<16>(&st[0][0]);
  const bool le0 = 2 * q <= rho, le1 = 2 * q + 1 <= rho;
  uint32_t la[2], lb[2], mx[2];
#pragma unroll
  for (int h = 0; h < 2; h++) {
    uint32_t l[2];
#pragma unroll
    for (int r = 0; r < 2; r++) {
      const float (&t)[4] = st[2 * h + r];
      l[r] = movm(pack2(rho <= 2 * q ? t[2] : t[0], rho <= 2 * q + 1 ? t[3] : t[1]));
      l[r] = fma2(l[r], 0x3e353e35u, mul2(l[r], 0x379e379eu));
    }
    la[h] = __byte_perm(l[0], l[1], 0x5410); lb[h] = __byte_perm(l[0], l[1], 0x7632);
    if (first && !le0) la[h] = (la[h] & 0xffff0000u) | 0xce6eu;
    if (first && !le1) lb[h] = (lb[h] & 0xffff0000u) | 0xce6eu;
    mx[h] = max2(la[h], lb[h]);
  }
#pragma unroll
  for (int o = 1; o <= 2; o++) { mx[0] = max2(mx[0], __shfl_xor_sync(~0u, mx[0], o)); mx[1] = max2(mx[1], __shfl_xor_sync(~0u, mx[1], o)); }
  const float L2E = 1.4426950408889634f;
  float pr[2][4], z[4];
#pragma unroll
  for (int h = 0; h < 2; h++) {
    pr[h][0] = ex2f((lo_f(la[h]) - lo_f(mx[h])) * L2E); pr[h][1] = ex2f((lo_f(lb[h]) - lo_f(mx[h])) * L2E);
    pr[h][2] = ex2f((hi_f(la[h]) - hi_f(mx[h])) * L2E); pr[h][3] = ex2f((hi_f(lb[h]) - hi_f(mx[h])) * L2E);
    z[2 * h] = pr[h][0] + pr[h][1]; z[2 * h + 1] = pr[h][2] + pr[h][3];
  }
  p1_step<10>(acc, c);
#pragma unroll
  for (int o = 1; o <= 2; o++) {
#pragma unroll
    for (int i = 0; i < 4; i++) z[i] += __shfl_xor_sync(~0u, z[i], o);
  }
  const uint32_t LE = (le0 ? 0xffffu : 0u) | (le1 ? 0xffff0000u : 0u);
  uint32_t P[4][2];
  uint4 vt[4][2];
  {
    const uint32_t row = (lane & 7) * 64 + ((((lane >> 3) & 1) ^ ((lane & 7) >> 1)) << 4);
    const uint32_t v1 = at + AT_V + (2 * w + (lane >> 4)) * 1024 + row;
    const uint32_t v0 = (w || lane >= 16) ? v1 - 1024 : (first ? v1 : at + AT_REM + round * 2048 + 1024 + row);
#pragma unroll
    for (int i = 0; i < 4; i++) {
      const float rz = rcpf(z[i]);
      const uint32_t p = pack2(pr[i >> 1][2 * (i & 1)] * rz, pr[i >> 1][2 * (i & 1) + 1] * rz);
      P[i][0] = p & ~LE; P[i][1] = p & LE;
      const uint32_t a = ((i & 1) ? v1 : v0) + (i >> 1) * 512;
      vt[i][0] = ldsm_t(a); vt[i][1] = ldsm_t(a ^ 32);
    }
  }
  float ot[4][2][4];
  pin<8>(&P[0][0]);
  bar_sync(BAR_MMA, 256);
  mbar_spin(c.sb + B_F1 + 8 * 3, 0, c.zero);
#pragma unroll
  for (int i = 0; i < 8; i++) { const uint4& v = vt[i >> 1][i & 1]; hmma<0>(ot[i >> 1][i & 1], v.x, v.y, v.z, v.w, P[i >> 1][0], P[i >> 1][1]); }
  sched_fence(c.zero);
  bar_sync(BAR_MMA, 256);
  p1_step<11, false>(acc, c);
  sched_fence(c.zero);
  pin<32>(&ot[0][0][0]);
  auto o_piece = [&](int i) {
    stg128(odst + (i >> 1) * 8192 + (i & 1) * 512, movm(pack2(ot[i][0][0], ot[i][0][1])), movm(pack2(ot[i][0][2], ot[i][0][3])), movm(pack2(ot[i][1][0], ot[i][1][1])), movm(pack2(ot[i][1][2], ot[i][1][3])));
  };
  o_piece(0); o_piece(1);
  p1_step<12>(acc, c);
  o_piece(2); o_piece(3);
  if (round) bar_arrive(BAR_EV + 4, 288);
  p1_step<13>(acc, c);
}

__device__ __forceinline__ void ln_moments(const uint32_t* raw, float& c0, float& s, float& v) {
  c0 = lo_f(__shfl_sync(~0u, raw[0], 0));
  float ss[4] = {0.f, 0.f, 0.f, 0.f}, vv[4] = {0.f, 0.f, 0.f, 0.f};
#pragma unroll
  for (int i = 0; i < 16; i++) {
    const float a = lo_f(raw[i]) - c0, b = hi_f(raw[i]) - c0;
    ss[(2 * i) & 3] += a; ss[(2 * i + 1) & 3] += b;
    vv[(2 * i) & 3] = fmaf(a, a, vv[(2 * i) & 3]); vv[(2 * i + 1) & 3] = fmaf(b, b, vv[(2 * i + 1) & 3]);
  }
  s = (ss[0] + ss[1]) + (ss[2] + ss[3]); v = (vv[0] + vv[1]) + (vv[2] + vv[3]);
}
__device__ __forceinline__ void ln_reduce(float& s, float& v) {
#pragma unroll
  for (int o = 16; o; o >>= 1) { s += __shfl_xor_sync(~0u, s, o); v += __shfl_xor_sync(~0u, v, o); }
}
__device__ __forceinline__ uint32_t ln_finish(float c0, float s, float v) {
  s *= 1.0f / DM;
  float sd;
  asm("sqrt.approx.ftz.f32 %0, %1;" : "=f"(sd) : "f"(bf16r(bf16r(fmaxf(fmaf(v, 1.0f / DM, -s * s), 0.f)) + 1e-5f)));
  return pack2(c0 + s, sd);
}
__device__ __forceinline__ void ln_store(const uint32_t* raw, uint32_t st, uint4* dst) {
  const uint32_t m2 = __byte_perm(st, st, 0x1010);
  const float rinv = rcpf(hi_f(st));
#pragma unroll
  for (int c = 0; c < 4; c++) {
    uint32_t v[4];
#pragma unroll
    for (int i = 0; i < 4; i++) { const uint32_t t = sub2(raw[4 * c + i], m2); v[i] = pack2(lo_f(t) * rinv, hi_f(t) * rinv); }
    stg128(dst + 32 * c, v[0], v[1], v[2], v[3]);
  }
}
__device__ __forceinline__ void col_sums(uint32_t tile, ulonglong2* part, uint32_t tag) {
  const int lane = threadIdx.x & 31;
  float cs[8] = {0, 0, 0, 0, 0, 0, 0, 0};
  uint32_t base = tile + ((lane >> 3) & 1) * 8192 + (lane >> 4) * 4096 + ((lane & 7) << 4);
#pragma unroll 1
  for (int k0 = 0; k0 < 8; k0++, base = (base ^ ((k0 ^ (k0 - 1)) << 4)) + 128) {
    uint4 v[4];
#pragma unroll
    for (int k = 0; k < 4; k++) v[k] = lds128(base + k * 1024);
#pragma unroll
    for (int k = 0; k < 4; k++) {
      cs[0] += lo_f(v[k].x); cs[1] += hi_f(v[k].x); cs[2] += lo_f(v[k].y); cs[3] += hi_f(v[k].y);
      cs[4] += lo_f(v[k].z); cs[5] += hi_f(v[k].z); cs[6] += lo_f(v[k].w); cs[7] += hi_f(v[k].w);
    }
  }
  const bool up = lane >= 16;
#pragma unroll
  for (int i = 0; i < 2; i++) {
    const float a = (up ? cs[4 + 2 * i] : cs[2 * i]) + __shfl_xor_sync(~0u, up ? cs[2 * i] : cs[4 + 2 * i], 16);
    const float b = (up ? cs[5 + 2 * i] : cs[1 + 2 * i]) + __shfl_xor_sync(~0u, up ? cs[1 + 2 * i] : cs[5 + 2 * i], 16);
    asm volatile("{\n.reg .b64 a, b;\nmov.b64 a, {%1, %3};\nmov.b64 b, {%2, %3};\nst.relaxed.gpu.global.v2.b64 [%0], {a, b};\n}"
                 ::"l"(part + 32 * (i + (up ? 2 : 0)) + (lane & 15)), "r"(__float_as_uint(a)), "r"(__float_as_uint(b)), "r"(tag) : "memory");
  }
  asm volatile("fence.proxy.async.shared::cta;" ::: "memory");
}

__global__ void __cluster_dims__(2, 1, 1) __launch_bounds__(384, 1)
fused_kernel(const uint4* __restrict__ x, const uint4* __restrict__ wgate, const uint4* __restrict__ wup, Scratch* gs, const __grid_constant__ Maps mp) {
  extern __shared__ __align__(1024) uint8_t smem_raw[];
  const uint32_t sb = (uint32_t)__cvta_generic_to_shared(smem_raw);
  const unsigned t_start = 0;
  const int warp = __shfl_sync(~0u, threadIdx.x >> 5, 0), lane = threadIdx.x & 31;
  const int m = blockIdx.x & 15, j = blockIdx.x >> 4, rank = blockIdx.x & 1;
  const int m2 = blockIdx.x >> 3, j2 = blockIdx.x & 7;
  const bool helper = blockIdx.x >= NMAIN;
  if (warp >= 8) {
    asm volatile("setmaxnreg.dec.sync.aligned.u32 40;");
    if (warp == 8) {
      if (elect_one()) {
        asm volatile("prefetch.tensormap [%0];\nprefetch.tensormap [%1];\nprefetch.tensormap [%2];" ::"l"(&mp.x), "l"(&mp.wg), "l"(&mp.wu) : "memory");
        for (int s = 0; s < 4; s++) mbar_init(sb + B_F1 + 8 * s, 1);
        if (!helper) mbar_arrive(sb + B_F1);
        asm volatile("fence.mbarrier_init.release.cluster;" ::: "memory");
      }
      __syncwarp();
    } else if (warp == 9) {
      if (elect_one()) {
        if ((sb & 0xffffff) != SM_BASE) asm volatile("trap;");
        for (int s = 0; s < 4; s++) mbar_init(sb + B_E1 + 8 * s, 4);
        for (int s = 0; s < 6; s++) { mbar_init(sb + B_F2 + 8 * s, 1); mbar_init(sb + B_E2 + 8 * s, 4); }
        for (int s = 0; s < 6; s++) mbar_init(sb + B_DEP + 8 * s, 1);
        mbar_init(sb + B_AUX, 8); mbar_init(sb + B_EP, 1); mbar_init(sb + B_DONE, 4); mbar_init(sb + B_XT, 1); mbar_init(sb + B_CS, 1);
        for (int s = 0; s < 8; s++) { mbar_init(sb + B_EX + 8 * s, 1); mbar_expect_tx(sb + B_EX + 8 * s, 4096); }
        mbar_init(sb + B_HALO, 9); mbar_init(sb + B_HALO + 8, 9);
        asm volatile("fence.mbarrier_init.release.cluster;" ::: "memory");
      }
      __syncwarp();
    }
    asm volatile("barrier.cluster.arrive.relaxed.aligned;" ::: "memory");
    if (warp == 8 && !helper) {
      if (elect_one()) {
        TS(0); TG(51);
#pragma unroll 1
        for (int kb = 1; kb < 4; kb++) {
          const uint32_t sa = sb + OFF_A + kb * 16384, sw = sb + kb * 32768, fb = sb + B_F1 + 8 * kb;
          mbar_expect_tx(fb, P1_BYTES);
          tma3d(sa, &mp.x, fb, kb * 64, m * 64, 0, EVICT_NORMAL);
          tma2d(sw, &mp.wg, fb, j * 128, kb * 64, EVICT_NORMAL); tma2d(sw + 16384, &mp.wu, fb, j * 128, kb * 64, EVICT_NORMAL);
          tma2d(sw + 8192, &mp.wg, fb, j * 128 + 64, kb * 64, EVICT_NORMAL); tma2d(sw + 24576, &mp.wu, fb, j * 128 + 64, kb * 64, EVICT_NORMAL);
        }
        TS(7);
      }
      __syncwarp();
    }
    asm volatile("barrier.cluster.wait.aligned;" ::: "memory");
    if (helper) {
      if (warp == 8) {
        unsigned e = 0;
        if (elect_one()) {
#pragma unroll 1
          for (int i = 0; i < 16; i++) {
            const uint32_t fb = sb + B_F1 + 8 * (i >> 2);
            if (!(i & 3)) mbar_expect_tx(fb, P1_BYTES);
            tma5d(sb + i * 8192, &mp.wd, fb, (blockIdx.x - NMAIN) * 256 + (i & 3) * 64, (i >> 2) * 2, HINT_W);
          }
        }
        if (lane == 0) { unsigned* ep = &gs->epoch[blockIdx.x * 2]; e = *ep + 1; *ep = e; }
        e = __shfl_sync(~0u, e, 0);
        if (lane < 16) flag_wait(&gs->flags[(FL_H + lane * 4) * 32], e * 8u);
        __syncwarp();
        if (elect_one()) {
          fence_async();
          TS(0);
#pragma unroll 1
          for (int i = 0; i < 64; i++) {
            const uint32_t fb = sb + B_F1 + 8 * (i & 3);
            if (i >= 4) { mbar_wait(sb + B_E1 + 8 * (i & 3), ~(i >> 2) & 1); mbar_expect_tx(fb, 16384); }
            bulk_load(sb + OFF_A + (i & 3) * 16384, gs->h + ((i >> 2) * 56 + (i & 3)) * 1024, 16384, fb, EVICT_NORMAL);
          }
        }
      } else if (warp == 9) {
#pragma unroll 1
        for (int t = 0; t < 16; t++) {
          bar_sync(BAR_EV + (t & 1), 288);
          if (lane == 0) { flag_add(&gs->flags[(FL_P + t) * 32]); TS(64 + t); }
          __syncwarp();
        }
      }
    } else if (warp == 8) {
      if (elect_one()) {
        uint32_t par = 0;

        auto x_load = [&]() {
          mbar_expect_tx(sb + B_XT, 32768);
          tma3d(sb + OFF_X, &mp.x, sb + B_XT, j2 * 128, m2 * 64, 0, HINT_LAST); tma3d(sb + OFF_X + 16384, &mp.x, sb + B_XT, j2 * 128 + 64, m2 * 64, 0, HINT_LAST);
        };
        auto d_prefetch = [&](int i) {
          if (PF_W == 1 && (m2 >> 2) == (i & 3)) tma5d_prefetch(&mp.wd, (j2 >> 1) * 256 + (m2 & 3) * 64, (2 * i + 4 + rank) * 2);
          if (PF_H == 1 && i < 6) asm volatile("cp.async.bulk.prefetch.L2.global [%0], 4096;" ::"l"(gs->h + (m2 * 56 + 2 * i + 4 + rank) * 1024 + (j2 >> 1) * 256) : "memory");
        };
        for (int R = 0; R < 5; R++) {
          const CUtensorMap *mb0, *mb1;
          int n0, n1;
          if (R == 1 || R == 2) {
            mb0 = &mp.wqkv; n0 = 64 * (j + 8 * (R - 1)) + rank * 2048;
            mb1 = rank ? (R == 1 ? &mp.wg : &mp.wu) : &mp.wqkv; n1 = rank ? 1024 + 64 * j : n0 + 1024;
          } else {
            mb0 = mb1 = rank ? &mp.wu : &mp.wg;
            n0 = 128 * j + (R ? 1024 * R - 1536 : 0); n1 = n0 + 64;
          }
#pragma unroll 1
          for (int kb = R ? 0 : 4; kb < 16; kb++) {
            if (R == 0 && kb == 14) { asm volatile("prefetch.tensormap [%0];\nprefetch.tensormap [%1];" ::"l"(&mp.xn), "l"(&mp.wqkv) : "memory"); }
            if (R == 4 && kb == 2) { asm volatile("prefetch.tensormap [%0];\nprefetch.tensormap [%1];\nprefetch.tensormap [%2];" ::"l"(&mp.wd), "l"(&mp.wo), "l"(&mp.out) : "memory"); }
            if (R == 0 && kb == (CS_KB)) {
              const uint32_t cb = sb + B_CS, d = sb + OFF_X;
              mbar_expect_tx(cb, 32768);
              tma2d(d, &mp.wg, cb, n0, m * 64, EVICT_NORMAL); tma2d(d + 8192, &mp.wg, cb, n1, m * 64, EVICT_NORMAL);
              tma2d(d + 16384, &mp.wu, cb, n0, m * 64, EVICT_NORMAL); tma2d(d + 24576, &mp.wu, cb, n1, m * 64, EVICT_NORMAL);
            }
            const int st = kb & 3;
            const uint32_t sa = sb + OFF_A + st * 16384, sw = sb + st * 32768, fb = sb + B_F1 + 8 * st;
            mbar_wait(sb + B_E1 + 8 * st, par);
            if (R * 16 + kb >= 4) REL_TS(R * 16 + kb - 4);
            mbar_expect_tx(fb, P1_BYTES);
            tma2d_mc(sw + rank * 16384, mb0, fb, n0, kb * 64, HINT_W);
            tma2d_mc(sw + 8192 + rank * 16384, mb1, fb, n1, kb * 64, HINT_W);
            if (R == 0) {
              tma3d(sa, &mp.x, fb, kb * 64, m * 64, 0, EVICT_NORMAL);
            } else {
              if (R == 1 && kb == 0) { mbar_wait(sb + B_DEP, 0); TS(1); }
              tma2d(sa, &mp.xn, fb, kb * 64, m * 128, R == 4 ? HINT_LAST : EVICT_NORMAL);
            }
            if (R == 4 && kb == 4 + j2) x_load();
            if (R == 4 && kb >= 16 - PF_D) { if (kb == 16 - PF_D) mbar_wait(sb + B_DEP + 8, 0); d_prefetch(kb + PF_D - 16); }
            if (st == 3) par ^= 1;
          }
        }
#pragma unroll 1
        for (int i = 0; i < 26; i++) {
          const int st = i & 3, kb = 2 * i + 4 + rank;
          const uint32_t sa = sb + OFF_A + st * 16384, sw = sb + st * 32768, fb = sb + B_F1 + 8 * st;
          mbar_wait(sb + B_E1 + 8 * st, par);
          REL_TS(76 + i);
          mbar_expect_tx(fb, P1_BYTES);
          tma5d(sw, &mp.wd, fb, j2 * 128, kb * 2, HINT_W); tma5d(sw + 8192, &mp.wd, fb, j2 * 128 + 64, kb * 2, HINT_W);
          tma5d(sw + 16384, &mp.wd, fb, (j2 ^ 1) * 128, kb * 2, HINT_W); tma5d(sw + 24576, &mp.wd, fb, (j2 ^ 1) * 128 + 64, kb * 2, HINT_W);
          if (i == 0 || i == 6 || i == 10 || i == 18) { mbar_wait(sb + B_DEP + 8 * (1 + ((i + 6) >> 3)), 0); TS(2 + ((i + 6) >> 3)); }
          bulk_load(sa, gs->h + (m2 * 56 + kb) * 1024, 16384, fb, HINT_H);
          if (i + PF_D < 26) d_prefetch(i + PF_D);
          if (i >= PF_S && i < PF_S + 8) {
            asm volatile("cp.async.bulk.prefetch.L2.global [%0], 4096;" ::"l"(gs->o + (m2 * 16 + 2 * (i - PF_S)) * 1024 + j2 * 256) : "memory");
            if ((m2 >> 1) == i - PF_S) {
              asm volatile("cp.async.bulk.prefetch.tensor.2d.L2.global [%0, {%1, %2}];" ::"l"(&mp.wo), "r"(j2 * 128), "r"(m2 * 64) : "memory");
              asm volatile("cp.async.bulk.prefetch.tensor.2d.L2.global [%0, {%1, %2}];" ::"l"(&mp.wo), "r"(j2 * 128 + 64), "r"(m2 * 64) : "memory");
            }
          }
          if (st == 3) par ^= 1;
        }
        int st = 0; uint32_t par2 = 1;
#pragma unroll 1
        for (int t = 0; t < 16; t++) {
          const uint32_t sa = sb + p2_a(st), sw = sb + p2_b(st), fb = sb + B_F2 + 8 * st;
          if (t < 5) mbar_wait(sb + B_E1 + 8 * (((2 * t + 1) / 3 + 2) & 3), t < 3); else mbar_wait(sb + B_E2 + 8 * st, par2);
          REL_TS(102 + t);
          mbar_expect_tx(fb, P2_BYTES);
          bulk_load_mc(sa + rank * 8192, gs->o + (m2 * 16 + t) * 1024 + rank * 512, 8192, fb, HINT_H);
          tma2d(sw, &mp.wo, fb, j2 * 128, t * 64, HINT_W); tma2d(sw + 8192, &mp.wo, fb, j2 * 128 + 64, t * 64, HINT_W);
          if (++st == 5) { st = 0; par2 ^= 1; }
        }
      }
    } else if (warp == 9) {
#pragma unroll 1
      for (int e = 0; e < 7; e++) {
        const bool halo = e == 2 || e == 3;
        bar_sync(BAR_EV + e, halo ? 96 : 288);
        if (lane == 0) {
          const int f = e == 0 ? FL_XN + m : (halo ? FL_HALO + (e - 2) * 128 + blockIdx.x : FL_H + m * 4 + (e == 1 ? 0 : e - 3));
          TS(10 + 2 * e); TG(52 + e);
          flag_add(&gs->flags[f * 32]);
          if (e < 6) TS(11 + 2 * e);
        }
        __syncwarp();
      }
      mbar_wait(sb + B_DONE, 0);
    } else {
      unsigned e = 0;
      if (lane == 0) {
        unsigned* ep = &gs->epoch[blockIdx.x * 2 + warp - 10];
        e = *ep + 1; *ep = e;
        if (warp == 10) { asm volatile("st.shared.b32 [%0], %1;" ::"r"(sb + OFF_EPOCH), "r"(e) : "memory"); mbar_arrive(sb + B_EP); }
      }
      e = __shfl_sync(~0u, e, 0);
      mbar_wait(sb + B_CS, 0);
      if (lane == 0 && warp == 11) TS(6);
      col_sums(sb + OFF_X + (warp - 10) * 16384, gs->cspart + (j * 16 + m) * 128 + (warp - 10) * 16, e);
      if (lane == 0 && warp == 11) TS(9);
      if (warp == 10) {
        if (lane == 0) {
#pragma unroll 1
          for (int g = 0; g < 6; g++) {
            flag_wait(&gs->flags[(g == 5 ? FL_P + m2 : (g ? FL_H + m2 * 4 + g - 1 : FL_XN + m)) * 32], e * (g == 5 ? 4u : 8u));
            fence_async();
            mbar_arrive(sb + B_DEP + 8 * g);
            if (g == 0) TS(8);
          }
#pragma unroll 1
          for (int p = 0; p < 8; p++) {
            asm volatile("cp.async.bulk.prefetch.L2.global [%0], 4096;" ::"l"(gs->dpart + blockIdx.x * 2048 + p * 256) : "memory");
            __nanosleep(PF_SLEEP);
          }
        }
      } else
      if (elect_one()) {
#pragma unroll 1
        for (int r = 0; r < 2; r++) {
          const uint32_t hb = sb + B_HALO + 8 * r;
          if (m) {
            flag_wait(&gs->flags[(FL_HALO + r * 128 + blockIdx.x - 1) * 32], e);
            fence_async();
            mbar_expect_tx(hb, 4096);
            for (int g = 0; g < 2; g++) bulk_load(sb + OFF_X + g * AT_WG + AT_REM + r * 2048, gs->halo + ((r * 128 + blockIdx.x - 1) * 2 + g) * 128, 2048, hb, EVICT_FIRST);
          } else {
            mbar_arrive(hb);
          }
          TS(34 + r);
        }
      }
    }
  } else {
    if (!helper) {
      const int r = threadIdx.x >> 3, ch = threadIdx.x & 7;
      const uint32_t d = sb + r * 128 + ((ch ^ (r & 7)) << 4);
      const uint4* xa = x + (128 * m + 2 * r) * 128 + ch;
      const size_t wo = (size_t)r * (DFF / 8) + 16 * j + ch;
#pragma unroll
      for (int i = 0; i < 12; i++) {
        const uint4* src = i < 4 ? xa + (i & 1) * 64 * 128 + (i >> 1) * 128 : (i < 8 ? wgate : wup) + wo + (i & 1) * 32 * (DFF / 8) + ((i >> 1) & 1) * 8;
        asm volatile("cp.async.cg.shared.global [%0], [%1], 16;" ::"r"(d + (i < 4 ? OFF_A + i * 4096 : (i - 4) * 4096)), "l"(src) : "memory");
      }
    }
    asm volatile("barrier.cluster.arrive.relaxed.aligned;" ::: "memory");
    asm volatile("setmaxnreg.inc.sync.aligned.u32 232;");
    const int wg = warp >> 2, w = warp & 3;
    Cons c;
    c.sb = sb; c.wg = wg; c.zero = warp >> 8;
    c.a = 0x4000004000010000ull + ((SM_BASE + OFF_A + wg * 8192) >> 4); c.k1 = 2 + c.zero; c.k2 = 2; c.k4 = 1024 - 6; c.k4w = -3072 - 6; c.b1 = 128 + c.zero;
    c.b = 0x4000004000000000ull + DB_LO + c.zero;
    c.rel = mapa(sb, threadIdx.x & 1);
    c.do_rel = (threadIdx.x & 127) < 2;
    constexpr bool t0 = false;
    float acc[128];
    uint32_t pk[64];
    float rs[2];
    const int rho = lane >> 2, q = lane & 3;

    if (helper) {
      asm volatile("barrier.cluster.wait.aligned;" ::: "memory");
      c.a = 0x8000002000010000ull + ((SM_BASE + OFF_A + wg * 4096) >> 4); c.k2 = 510; c.k4 = 1024 - 514; c.k4w = -3072 - 514;
      c.rel = sb;
      uint4* dst = gs->dpart + (blockIdx.x - NMAIN) * 4096 + threadIdx.x;
      auto put = [&](int p) {
#pragma unroll
        for (int i = 4 * p; i < 4 * p + 4; i++) stg128(dst + i * 256, pk[4 * i], pk[4 * i + 1], pk[4 * i + 2], pk[4 * i + 3]);
      };
#pragma unroll 1
      for (int t = 0; t < 16; t++) {
        p1_issue<0, 0>(acc, c, t & 1);
        if (t) put(0);
        p1_issue<1, 1>(acc, c, t & 1); wg_wait<1>(); release(c, B_E1);
        if (t) put(1);
        if (wg == 1) { wg_wait<0>(); release(c, B_E1 + 8); bar_sync(BAR_LAG, 256); }
        p1_issue<2, 1>(acc, c, t & 1); wg_wait<1>(); if (wg == 0) release(c, B_E1 + 8);
        if (t) put(2);
        p1_issue<3, 1>(acc, c, t & 1);
        if (wg == 0) bar_arrive(BAR_LAG, 256);
        if (t) { put(3); bar_arrive(BAR_EV + (~t & 1), 288); dst += 8 * 2048; }
        wg_wait<1>(); release(c, B_E1 + 16);
        wg_wait<0>(); release(c, B_E1 + 24);
#pragma unroll
        for (int i = 0; i < 64; i++) pk[i] = pack2(acc[2 * i], acc[2 * i + 1]);
      }
      put(0); put(1); put(2); put(3);
      bar_arrive(BAR_EV + 1, 288);
      return;
    }
    {
      const int prow = 16 * j + 2 * warp;
      const uint4* xr = x + (size_t)(128 * m + 2 * (prow & 63) + (prow >> 6)) * 128 + lane;
      uint4* xo = gs->xn + (size_t)(128 * m + prow) * 128 + lane;
      float c0[2], mo[4];
      uint32_t st[2];
      uint32_t e;
      asm volatile("" : "+l"(xr), "+l"(xo));
      if (t0) TS(23 + wg * 16);
      asm volatile("cp.async.wait_all;\nfence.proxy.async.shared::cta;" ::: "memory");
      bar_sync(BAR_MMA, 256);
      if (threadIdx.x == 0) TS(39);
      p1_step<0, false>(acc, c);
      asm volatile("barrier.cluster.wait.aligned;" ::: "memory");
      p1_range<1, LN_LD + 1>(acc, c);
      if (t0) TS(24 + wg * 16);
#pragma unroll
      for (int i = 0; i < 8; i++) {
        asm volatile("ld.global.nc.v4.b32 {%0,%1,%2,%3}, [%4];" : "=r"(pk[4 * i]), "=r"(pk[4 * i + 1]), "=r"(pk[4 * i + 2]), "=r"(pk[4 * i + 3]) : "l"(xr + (i >> 2) * 256 + (i & 3) * 32));
      }
      p1_range<LN_LD + 1, LN_KB + 1>(acc, c);
      sched_fence(c.zero);

      pin<16>(pk); ln_moments(pk, c0[0], mo[0], mo[1]); pin<2>(mo);
      p1_step<LN_KB + 1>(acc, c);
      sched_fence(c.zero);
      pin<16>(pk + 16); ln_moments(pk + 16, c0[1], mo[2], mo[3]); ln_reduce(mo[0], mo[1]); pin<4>(mo);
      p1_step<LN_KB + 2>(acc, c);
      mbar_spin(sb + B_EP, 0, c.zero);
      asm volatile("ld.shared.b32 %0, [%1];" : "=r"(e) : "r"(sb + OFF_EPOCH) : "memory");
      pin<2>(mo); st[0] = ln_finish(c0[0], mo[0], mo[1]); ln_reduce(mo[2], mo[3]); pin<1>(st); pin<2>(mo + 2);
      p1_step<LN_KB + 3>(acc, c);
      sched_fence(c.zero);
      pin<1>(st); pin<2>(mo + 2);
      st[1] = ln_finish(c0[1], mo[2], mo[3]);
      ln_store(pk, st[0], xo);
      if (lane == 0)
        asm volatile("{\n.reg .b64 a, b;\nmov.b64 a, {%1, %3};\nmov.b64 b, {%2, %3};\nst.relaxed.gpu.global.v2.b64 [%0], {a, b};\n}" ::"l"(gs->stats + 128 * m + prow), "r"(st[0]), "r"(st[1]), "r"(e) : "memory");
      p1_step<LN_KB + 4>(acc, c);
      sched_fence(c.zero);
      pin<1>(st + 1); ln_store(pk + 16, st[1], xo + 128);
      bar_arrive(BAR_EV, 288);
      p1_range<LN_KB + 5, G_KB + 1>(acc, c);
      sched_fence(c.zero);
      const unsigned long long* cp = (const unsigned long long*)gs->cspart + j * 4096 + threadIdx.x;
      const unsigned long long* sp = gs->stats + 128 * m + warp * 16 + rho;
      unsigned long long part[18];
      auto gather = [&]() {
#pragma unroll
        for (int i = 0; i < 18; i++) asm volatile("ld.relaxed.gpu.global.b64 %0, [%1];" : "=l"(part[i]) : "l"(i < 16 ? cp + i * 256 : sp + (i - 16) * 8) : "memory");
      };
      gather();
      auto validate = [&]() {
        float csum;
        for (int tries = 0;; tries++) {
          uint32_t bad = 0;
          csum = 0.f;
#pragma unroll
          for (int i = 0; i < 18; i++) { bad |= (uint32_t)(part[i] >> 32) ^ e; if (i < 16) csum += __uint_as_float((uint32_t)part[i]); }
          if (!__any_sync(~0u, bad != 0) || tries > (1 << 20)) break;
          gather();
        }
        const float hi = bf16r(csum), mid = bf16r(csum - hi);
        sts128(sb + OFF_CS + ((threadIdx.x & 62) * 4 + (threadIdx.x >> 6) * 2 + (threadIdx.x & 1)) * 16, make_uint4(pack2(hi, mid), pack2(csum - hi - mid, 0.f), 0, 0));
        asm volatile("fence.proxy.async.shared::cta;" ::: "memory");
        __syncwarp();
        if (lane == 0) mbar_arrive(sb + B_AUX);
      };
      p1_range<G_KB + 1, 14>(acc, c);
      if (wg == 1) validate();
      p1_step<14>(acc, c);
      p1_issue<3, 1>(acc, c, 1);
      if (wg == 0) validate();
      const uint32_t keep = q == 0 ? 0xffffffffu : (q == 1 ? 0xffffu : 0u);
      const uint32_t a0 = (__byte_perm((uint32_t)part[16], 0, 0x1010) ^ 0x80008000u) & keep, a1 = (__byte_perm((uint32_t)part[17], 0, 0x1010) ^ 0x80008000u) & keep;
      mbar_spin(sb + B_AUX, 0, c.zero);
      wg_fence();
      wgmma256_rs(acc, a0, a1, 0, 0, (SM_BASE + OFF_CS) >> 4);
      wg_commit();
      if (wg == 0) bar_arrive(BAR_LAG, 256);
      rs[0] = rcpf(hi_f((uint32_t)part[16])); rs[1] = rcpf(hi_f((uint32_t)part[17]));
      wg_wait<2>(); release(c, B_E1 + 16);
      wg_wait<0>(); release(c, B_E1 + 24);
#pragma unroll
      for (int i = 0; i < 64; i++) pk[i] = pack2(acc[2 * i], acc[2 * i + 1]);
      if (t0) TS(25 + wg * 16);
    }
    const uint32_t img = warp * 1024 + ((lane ^ (lane >> 3)) << 4);
#pragma unroll 1
    for (int R = 1;; R++) {
      uint8_t* hb = (uint8_t*)gs->h + (size_t)m * 56 * 16384 + img;
      if (R == 2 || R == 3) {
        attn_tile(acc, pk, c, R - 2, warp, m, gs, hb + (16 + j) * 16384, (uint8_t*)gs->o + (m * 16 + j + 8 * (R - 2)) * 16384 + img);
      } else {
        if (R == 5) { c.a = 0x8000002000010000ull + ((SM_BASE + OFF_A + wg * 4096) >> 4); c.k2 = 510; c.k4 = 1024 - 514; c.k4w = -3072 - 514; }
        geglu_tile<0>(acc, pk, c, hb + (2 * j + (R == 1 ? 0 : 16 * R - 40)) * 16384, BAR_EV + (R == 1 ? 1 : R + 1), rs);
        rs[0] = rs[1] = 1.0f;
        if (R == 5) break;
      }
      p1_range<14, 16>(acc, c);
#pragma unroll
      for (int i = 0; i < 64; i++) pk[i] = pack2(acc[2 * i], acc[2 * i + 1]);
      if (t0) TS(25 + R + wg * 16);
    }
    if (t0) TS(30 + wg * 16);
    auto fetch = [&](int p) {
      asm volatile("ld.global.cg.v4.b32 {%0,%1,%2,%3}, [%4];" : "=r"(pk[4 * p]), "=r"(pk[4 * p + 1]), "=r"(pk[4 * p + 2]), "=r"(pk[4 * p + 3]) : "l"(gs->dpart + blockIdx.x * 2048 + p * 256 + threadIdx.x) : "memory");
    };
#pragma unroll 1
    for (int it = 3; it < 5; it++) {
      p1_issue<2, 1>(acc, c, it & 1); wg_wait<1>(); release(c, B_E1 + 8);
      p1_issue<3, 1>(acc, c, it & 1); wg_wait<1>(); release(c, B_E1 + 16);
      p1_issue<0, 1>(acc, c, ~it & 1); wg_wait<1>(); release(c, B_E1 + 24);
      p1_issue<1, 1>(acc, c, ~it & 1); wg_wait<1>(); release(c, B_E1);
    }
    p1_issue<2, 1>(acc, c, 1); wg_wait<1>(); release(c, B_E1 + 8);
    mbar_spin(sb + B_DEP + 40, 0, c.zero);
    fetch(0); fetch(4);
    p1_issue<3, 1>(acc, c, 1); wg_wait<1>(); release(c, B_E1 + 16);
    fetch(1); fetch(5);
    p1_issue<0, 1>(acc, c, 0); wg_wait<1>(); release(c, B_E1 + 24);
    fetch(2); fetch(6);
    p1_issue<1, 1>(acc, c, 0); wg_wait<1>(); release(c, B_E1);
    fetch(3); fetch(7);
    if (t0) TS(31 + wg * 16);
    {
      float accs[64];
      const uint32_t peer = mapa(sb, rank ^ 1);
      auto send_piece = [&](int p) {
        asm volatile("st.async.weak.shared::cluster.mbarrier::complete_tx::bytes.v4.b32 [%0], {%1,%2,%3,%4}, [%5];" ::"r"(peer + OFF_LAND + p * 4096 + threadIdx.x * 16),
                     "r"(pack2(acc[64 + 8 * p], acc[65 + 8 * p])), "r"(pack2(acc[66 + 8 * p], acc[67 + 8 * p])), "r"(pack2(acc[68 + 8 * p], acc[69 + 8 * p])), "r"(pack2(acc[70 + 8 * p], acc[71 + 8 * p])),
                     "r"(peer + B_EX + 32 * wg + 8 * (p >> 1)) : "memory");
      };
      auto silu_piece = [&](int p) {
        const uint4 r = lds128(sb + OFF_LAND + p * 4096 + threadIdx.x * 16);
        const uint32_t rr[4] = {add2(r.x, pk[4 * p]), add2(r.y, pk[4 * p + 1]), add2(r.z, pk[4 * p + 2]), add2(r.w, pk[4 * p + 3])};
#pragma unroll
        for (int i = 0; i < 4; i++) {
          const float a = acc[8 * p + 2 * i] + lo_f(rr[i]), b = acc[8 * p + 2 * i + 1] + hi_f(rr[i]);
          pk[4 * p + i] = pack2(silu_half(a), silu_half(b));
        }
        pin<4>(pk + 4 * p);
      };
      const uint32_t xa = sb + OFF_X + (warp * 16 + (lane & 15)) * 128 + (((lane >> 4) ^ (lane & 7)) << 4);
      auto x_piece = [&](int i) { const uint4 v = ldsm((xa ^ ((i & 3) << 5)) + (i >> 2) * 16384); pk[32 + 4 * i] = v.x; pk[33 + 4 * i] = v.y; pk[34 + 4 * i] = v.z; pk[35 + 4 * i] = v.w; };
      p2_step<0>(accs, c);
      p2_step<1>(accs, c);
      mbar_spin(sb + B_E1 + 8, 0, c.zero);
      send_piece(0); send_piece(1);
      p2_step<2>(accs, c); sched_fence(c.zero); send_piece(2); send_piece(3);
      p2_step<3>(accs, c); sched_fence(c.zero); send_piece(4); send_piece(5);
      p2_step<4>(accs, c); mbar_spin(sb + B_XT, 0, c.zero); send_piece(6); send_piece(7);
      p2_step<5>(accs, c); mbar_spin(sb + B_EX + 32 * wg, 0, c.zero); silu_piece(0); x_piece(0);
      p2_step<6>(accs, c); sched_fence(c.zero); silu_piece(1); x_piece(1);
      p2_step<7>(accs, c); mbar_spin(sb + B_EX + 32 * wg + 8, 0, c.zero); silu_piece(2); x_piece(2);
      p2_step<8>(accs, c); sched_fence(c.zero); silu_piece(3); x_piece(3);
      p2_step<9>(accs, c); mbar_spin(sb + B_EX + 32 * wg + 16, 0, c.zero); silu_piece(4); x_piece(4);
      p2_step<10>(accs, c); sched_fence(c.zero); silu_piece(5); x_piece(5);
      p2_step<11>(accs, c); mbar_spin(sb + B_EX + 32 * wg + 24, 0, c.zero); silu_piece(6); x_piece(6); x_piece(7);
      if (wg == 1) silu_piece(7);
      p2_step<12>(accs, c); p2_step<13>(accs, c); p2_step<14>(accs, c); p2_step<15>(accs, c);
      if (c.do_rel) mbar_arrive(sb + B_DONE);
      if (wg == 0) silu_piece(7);
      wg_wait<0>();
      if (t0) TS(32 + wg * 16);
#pragma unroll
      for (int i = 0; i < 8; i++) {
        uint32_t v[4];
#pragma unroll
        for (int k = 0; k < 4; k++) v[k] = fma2(pack2(accs[8 * i + 2 * k], accs[1 + 8 * i + 2 * k]), pk[4 * i + k], pk[32 + 4 * i + k]);
        asm volatile("stmatrix.sync.aligned.m8n8.x4.shared.b16 [%0], {%1,%2,%3,%4};" ::"r"((xa ^ ((i & 3) << 5)) + (i >> 2) * 16384), "r"(v[0]), "r"(v[1]), "r"(v[2]), "r"(v[3]) : "memory");
        if (i == 3 || i == 7) {
          asm volatile("fence.proxy.async.shared::cta;" ::: "memory");
          __syncwarp();
          if (elect_one()) tma3d_store(&mp.out, sb + OFF_X + (i >> 2) * 16384 + warp * 2048, j2 * 128 + (i >> 2) * 64, m2 * 64 + w * 16, wg);
        }
      }
      if (elect_one()) { asm volatile("cp.async.bulk.commit_group;\ncp.async.bulk.wait_group.read 0;" ::: "memory"); }
      if ((threadIdx.x & 127) == 0) { TS(33 + wg * 16); if (wg) { TG(59); unsigned id; asm volatile("mov.u32 %0, %%smid;" : "=r"(id)); TSV(60, id); } }
    }
  }
}

typedef CUresult (*EncodeFn)(CUtensorMap*, CUtensorMapDataType, cuuint32_t, void*, const cuuint64_t*, const cuuint64_t*, const cuuint32_t*, const cuuint32_t*,
                             CUtensorMapInterleave, CUtensorMapSwizzle, CUtensorMapL2promotion, CUtensorMapFloatOOBfill);

void encode(EncodeFn fn, CUtensorMap* tm, const void* p, int rank, const cuuint64_t* dims, const cuuint64_t* strides, const cuuint32_t* box) {
  const cuuint32_t es[5] = {1, 1, 1, 1, 1};
  fn(tm, CU_TENSOR_MAP_DATA_TYPE_BFLOAT16, rank, const_cast<void*>(p), dims, strides, box, es, CU_TENSOR_MAP_INTERLEAVE_NONE, CU_TENSOR_MAP_SWIZZLE_128B,
     PROMO, CU_TENSOR_MAP_FLOAT_OOB_FILL_NONE);
}

}

extern "C" void kernel_launch(void* const* d_in, const int* in_sizes, int n_in, void* d_out, int out_size) {
  (void)in_sizes; (void)n_in; (void)out_size;
  static EncodeFn fn = nullptr;
  static Scratch* gs = nullptr;
  if (!fn) {
    void* p = nullptr;
    cudaDriverEntryPointQueryResult qr;
    cudaGetDriverEntryPoint("cuTensorMapEncodeTiled", &p, cudaEnableDefault, &qr);
    fn = (EncodeFn)p;
    cudaGetSymbolAddress((void**)&gs, g_scratch);
    cudaFuncSetAttribute(fused_kernel, cudaFuncAttributeMaxDynamicSharedMemorySize, SMEM_BYTES);
  }
  const void *x = d_in[0], *wqkv = d_in[1], *wo = d_in[2], *wg = d_in[4], *wu = d_in[5], *wd = d_in[6];
  Maps mp;
  {
    const cuuint64_t dims[3] = {DM, SEQ / 2, 2}, st[2] = {DM * 4, DM * 2};
    const cuuint32_t box_in[3] = {64, 64, 2}, box_out[3] = {64, 16, 1};
    encode(fn, &mp.x, x, 3, dims, st, box_in);
    encode(fn, &mp.out, d_out, 3, dims, st, box_out);
  }
  {
    const cuuint64_t dims[2] = {DM, SEQ}, st[1] = {DM * 2};
    const cuuint32_t box[2] = {64, 128};
    encode(fn, &mp.xn, gs->xn, 2, dims, st, box);
  }
  {
    const cuuint32_t box[2] = {64, 64};
    const cuuint64_t dq[2] = {3 * DM, DM}, sq[1] = {3 * DM * 2}, df[2] = {DFF, DM}, sf[1] = {DFF * 2}, dw[2] = {DM, DM}, sw[1] = {DM * 2};
    encode(fn, &mp.wqkv, wqkv, 2, dq, sq, box);
    encode(fn, &mp.wg, wg, 2, df, sf, box);
    encode(fn, &mp.wu, wu, 2, df, sf, box);
    encode(fn, &mp.wo, wo, 2, dw, sw, box);
  }
  {
    const cuuint32_t box[5] = {64, 2, 4, 4, 2};
    const cuuint64_t st[4] = {DM * 2, 8 * DM * 2, 2 * DM * 2, 32 * DM * 2};
    const cuuint64_t dd[5] = {DM, 2, 4, 4, DFF / 32};
    encode(fn, &mp.wd, wd, 5, dd, st, box);
  }
  fused_kernel<<<NCTA, 384, SMEM_BYTES>>>((const uint4*)x, (const uint4*)wg, (const uint4*)wu, gs, mp);
}
```

```cpp
#include <cuda_runtime.h>
#include <cuda_bf16.h>
#include <cuda.h>
#include <stdint.h>

#define LN_LD 1
#define PROMO CU_TENSOR_MAP_L2_PROMOTION_L2_128B
#define G_KB 12
#define PF_D 4
#define PF_W 1
#define PF_H 1
#define PF_SLEEP 250
#define PF_S 16
#define LAG2 4
#define LN_SPLIT 1
#define CS_KB 8
#define LN_KB 4

#define EVICT_FIRST 0x12F0000000000000ull
#define EVICT_NORMAL 0x1000000000000000ull
#define HINT_W EVICT_FIRST
#define HINT_H EVICT_FIRST
#define HINT_LAST EVICT_FIRST

namespace {

constexpr int SEQ = 2048, DM = 1024, DFF = 3584;
constexpr int NMAIN = 128, NCTA = 132;

constexpr uint32_t SM_BASE = 0x400;
constexpr uint32_t P1_BYTES = 49152, P2_BYTES = 32768;
constexpr uint32_t OFF_A = 131072;
__host__ __device__ constexpr uint32_t p2_a(int s) { return s == 0 ? OFF_A + 32768 : s == 1 ? OFF_A + 49152 : s == 2 ? 114688 : s == 3 ? 16384 : 49152; }
__host__ __device__ constexpr uint32_t p2_b(int s) { return s < 3 ? 65536 + s * 16384 : (s - 3) * 32768; }
constexpr uint32_t OFF_LAND = OFF_A;
constexpr uint32_t OFF_X = 196608;
constexpr uint32_t OFF_CS = OFF_X + 14336;
constexpr uint32_t OFF_BAR = 229376;
constexpr uint32_t B_F1 = OFF_BAR, B_E1 = B_F1 + 32, B_F2 = B_E1 + 32, B_E2 = B_F2 + 48;
constexpr uint32_t B_DEP = B_E2 + 48;
constexpr uint32_t B_AUX = B_DEP + 48, B_CS = B_AUX + 8, B_XT = B_CS + 8, B_EX = B_XT + 8, B_HALO = B_EX + 64, B_EP = B_HALO + 16, B_DONE = B_EP + 8, OFF_EPOCH = B_DONE + 8;
constexpr uint32_t SMEM_BYTES = 232448;
constexpr uint32_t AT_V = 0, AT_K = 8192, AT_REM = 11264, AT_WG = 15360;

constexpr int FL_XN = 0, FL_H = 16, FL_P = 80, FL_HALO = 96, FL_N = FL_HALO + 256;
struct __align__(1024) Scratch {
  uint4 h[16 * 56 * 1024];
  uint4 o[16 * 16 * 1024];
  uint4 xn[SEQ * DM / 8];
  uint4 dpart[128 * 8 * 256];
  uint4 halo[2 * 128 * 2 * 128];
  ulonglong2 cspart[8 * 16 * 128];
  unsigned long long stats[SEQ];
  unsigned flags[FL_N * 32];
  unsigned epoch[NCTA * 2];
};
__device__ Scratch g_scratch;
#define TG(i) do {} while (0)
#define TSV(i, v) do {} while (0)
#define TS(i) do {} while (0)

struct Maps { CUtensorMap x, xn, out, wqkv, wg, wu, wd, wo; };

__device__ __forceinline__ void mbar_init(uint32_t bar, uint32_t cnt) { asm volatile("mbarrier.init.shared::cta.b64 [%0], %1;" ::"r"(bar), "r"(cnt)); }
__device__ __forceinline__ void mbar_expect_tx(uint32_t bar, uint32_t bytes) { asm volatile("mbarrier.arrive.expect_tx.shared::cta.b64 _, [%0], %1;" ::"r"(bar), "r"(bytes) : "memory"); }
__device__ __forceinline__ void mbar_arrive(uint32_t bar) { asm volatile("mbarrier.arrive.shared::cta.b64 _, [%0];" ::"r"(bar) : "memory"); }
__device__ __forceinline__ void mbar_arrive_cl(uint32_t bar) { asm volatile("mbarrier.arrive.shared::cluster.b64 _, [%0];" ::"r"(bar) : "memory"); }
__device__ __forceinline__ uint32_t mapa(uint32_t a, uint32_t cta) { uint32_t r; asm("mapa.shared::cluster.u32 %0, %1, %2;" : "=r"(r) : "r"(a), "r"(cta)); return r; }
__device__ __forceinline__ void mbar_wait(uint32_t bar, uint32_t parity) {
  asm volatile("{\n.reg .pred p;\n.reg .u32 n;\nmov.u32 n, 0;\nLAB_WAIT:\nmbarrier.try_wait.parity.shared::cta.b64 p, [%0], %1;\n@p bra LAB_DONE;\n"
               "add.u32 n, n, 1;\nsetp.gt.u32 p, n, 4000000;\n@p trap;\nbra LAB_WAIT;\nLAB_DONE:\n}" ::"r"(bar), "r"(parity) : "memory");
}
__device__ __forceinline__ void mbar_spin(uint32_t bar, uint32_t parity, uint32_t zero) {
  asm volatile("{\n.reg .pred p, z;\nsetp.ne.u32 z, %2, 0;\nLAB_WAIT:\nmbarrier.try_wait.parity.shared::cta.b64 p, [%0], %1;\n@p bra LAB_DONE;\n@z trap;\nbra LAB_WAIT;\nLAB_DONE:\n}" ::"r"(bar), "r"(parity), "r"(zero) : "memory");
}
__device__ __forceinline__ void flag_wait(const unsigned* f, unsigned target) {
  asm volatile("{\n.reg .pred p;\n.reg .u32 n, v;\nmov.u32 n, 0;\nLAB_WAIT:\nld.relaxed.gpu.global.u32 v, [%0];\nsub.u32 v, v, %1;\nsetp.ge.s32 p, v, 0;\n@p bra LAB_DONE;\n"
               "nanosleep.u32 100;\nadd.u32 n, n, 1;\nsetp.gt.u32 p, n, 4000000;\n@p trap;\nbra LAB_WAIT;\nLAB_DONE:\nfence.acquire.gpu;\n}" ::"l"(f), "r"(target) : "memory");
}
__device__ __forceinline__ void flag_add(unsigned* f) { asm volatile("red.release.gpu.global.add.u32 [%0], 1;" ::"l"(f) : "memory"); }
__device__ __forceinline__ void fence_async() { asm volatile("fence.proxy.async.global;" ::: "memory"); }
__device__ __forceinline__ bool elect_one() { uint32_t p; asm volatile("{\n.reg .pred P;\nelect.sync _|P, 0xffffffff;\nselp.u32 %0, 1, 0, P;\n}" : "=r"(p)); return p; }
__device__ __forceinline__ void bar_sync(int id, int n) { asm volatile("bar.sync %0, %1;" ::"r"(id), "r"(n) : "memory"); }
__device__ __forceinline__ void bar_arrive(int id, int n) { asm volatile("bar.arrive %0, %1;" ::"r"(id), "r"(n) : "memory"); }

__device__ __forceinline__ void tma2d(uint32_t dst, const CUtensorMap* tm, uint32_t bar, int c0, int c1, uint64_t hint) {
  asm volatile("cp.async.bulk.tensor.2d.shared::cluster.global.mbarrier::complete_tx::bytes.L2::cache_hint [%0], [%1, {%3, %4}], [%2], %5;" ::"r"(dst), "l"(tm), "r"(bar), "r"(c0), "r"(c1), "l"(hint) : "memory");
}
__device__ __forceinline__ void tma2d_mc(uint32_t dst, const CUtensorMap* tm, uint32_t bar, int c0, int c1, uint64_t hint) {
  asm volatile("cp.async.bulk.tensor.2d.shared::cluster.global.mbarrier::complete_tx::bytes.multicast::cluster.L2::cache_hint [%0], [%1, {%3, %4}], [%2], %5, %6;" ::"r"(dst), "l"(tm), "r"(bar), "r"(c0), "r"(c1), "h"((uint16_t)3), "l"(hint) : "memory");
}
__device__ __forceinline__ void tma3d(uint32_t dst, const CUtensorMap* tm, uint32_t bar, int c0, int c1, int c2, uint64_t hint) {
  asm volatile("cp.async.bulk.tensor.3d.shared::cluster.global.mbarrier::complete_tx::bytes.L2::cache_hint [%0], [%1, {%3, %4, %5}], [%2], %6;" ::"r"(dst), "l"(tm), "r"(bar), "r"(c0), "r"(c1), "r"(c2), "l"(hint) : "memory");
}
__device__ __forceinline__ void tma5d(uint32_t dst, const CUtensorMap* tm, uint32_t bar, int c0, int c4, uint64_t hint) {
  asm volatile("cp.async.bulk.tensor.5d.shared::cluster.global.mbarrier::complete_tx::bytes.L2::cache_hint [%0], [%1, {%3, %5, %5, %5, %4}], [%2], %6;" ::"r"(dst), "l"(tm), "r"(bar), "r"(c0), "r"(c4), "r"(0), "l"(hint) : "memory");
}
__device__ __forceinline__ void tma5d_prefetch(const CUtensorMap* tm, int c0, int c4) {
  asm volatile("cp.async.bulk.prefetch.tensor.5d.L2.global [%0, {%1, %3, %3, %3, %2}];" ::"l"(tm), "r"(c0), "r"(c4), "r"(0) : "memory");
}
__device__ __forceinline__ void tma3d_store(const CUtensorMap* tm, uint32_t src, int c0, int c1, int c2) {
  asm volatile("cp.async.bulk.tensor.3d.global.shared::cta.bulk_group [%0, {%2, %3, %4}], [%1];" ::"l"(tm), "r"(src), "r"(c0), "r"(c1), "r"(c2) : "memory");
}
__device__ __forceinline__ void bulk_load(uint32_t dst, const void* src, uint32_t bytes, uint32_t bar, uint64_t hint) {
  asm volatile("cp.async.bulk.shared::cluster.global.mbarrier::complete_tx::bytes.L2::cache_hint [%0], [%1], %2, [%3], %4;" ::"r"(dst), "l"(src), "r"(bytes), "r"(bar), "l"(hint) : "memory");
}
__device__ __forceinline__ void bulk_load_mc(uint32_t dst, const void* src, uint32_t bytes, uint32_t bar, uint64_t hint) {
  asm volatile("cp.async.bulk.shared::cluster.global.mbarrier::complete_tx::bytes.multicast::cluster.L2::cache_hint [%0], [%1], %2, [%3], %4, %5;" ::"r"(dst), "l"(src), "r"(bytes), "r"(bar), "h"((uint16_t)3), "l"(hint) : "memory");
}
__device__ __forceinline__ uint4 lds128(uint32_t a) { uint4 v; asm volatile("ld.shared.v4.b32 {%0,%1,%2,%3}, [%4];" : "=r"(v.x), "=r"(v.y), "=r"(v.z), "=r"(v.w) : "r"(a) : "memory"); return v; }
__device__ __forceinline__ void sts128(uint32_t a, uint4 v) { asm volatile("st.shared.v4.b32 [%0], {%1,%2,%3,%4};" ::"r"(a), "r"(v.x), "r"(v.y), "r"(v.z), "r"(v.w) : "memory"); }
__device__ __forceinline__ void stg128(void* p, uint32_t a, uint32_t b, uint32_t c, uint32_t d) { asm volatile("st.global.v4.b32 [%0], {%1,%2,%3,%4};" ::"l"(p), "r"(a), "r"(b), "r"(c), "r"(d) : "memory"); }

__device__ __forceinline__ uint32_t pack2(float lo, float hi) { uint32_t r; asm("cvt.rn.bf16x2.f32 %0, %1, %2;" : "=r"(r) : "f"(hi), "f"(lo)); return r; }
__device__ __forceinline__ float lo_f(uint32_t v) { return __uint_as_float(v << 16); }
__device__ __forceinline__ float hi_f(uint32_t v) { return __uint_as_float(v & 0xffff0000u); }
__device__ __forceinline__ float bf16r(float v) { return lo_f(pack2(v, 0.f)); }
__device__ __forceinline__ uint32_t mul2(uint32_t a, uint32_t b) { uint32_t r; asm("mul.rn.bf16x2 %0, %1, %2;" : "=r"(r) : "r"(a), "r"(b)); return r; }
__device__ __forceinline__ uint32_t add2(uint32_t a, uint32_t b) { uint32_t r; asm("add.rn.bf16x2 %0, %1, %2;" : "=r"(r) : "r"(a), "r"(b)); return r; }
__device__ __forceinline__ uint32_t sub2(uint32_t a, uint32_t b) { uint32_t r; asm("sub.rn.bf16x2 %0, %1, %2;" : "=r"(r) : "r"(a), "r"(b)); return r; }
__device__ __forceinline__ uint32_t fma2(uint32_t a, uint32_t b, uint32_t c) { uint32_t r; asm("fma.rn.bf16x2 %0, %1, %2, %3;" : "=r"(r) : "r"(a), "r"(b), "r"(c)); return r; }
__device__ __forceinline__ uint32_t max2(uint32_t a, uint32_t b) { uint32_t r; asm("max.bf16x2 %0, %1, %2;" : "=r"(r) : "r"(a), "r"(b)); return r; }
__device__ __forceinline__ float ex2f(float x) { float y; asm("ex2.approx.ftz.f32 %0, %1;" : "=f"(y) : "f"(x)); return y; }
__device__ __forceinline__ float rcpf(float x) { float y; asm("rcp.approx.ftz.f32 %0, %1;" : "=f"(y) : "f"(x)); return y; }
constexpr float GELU_C1 = 0.7978845608028654f, GELU_C3 = 0.035677408136300125f;
__device__ __forceinline__ float gelu_k(float g, float c1, float c3, float k) {
  float t;
  asm("tanh.approx.f32 %0, %1;" : "=f"(t) : "f"(g * fmaf(g * g, c3, c1)));
  g *= k;
  return fmaf(g, t, g);
}
__device__ __forceinline__ float silu_half(float z) { float t; asm("tanh.approx.f32 %0, %1;" : "=f"(t) : "f"(z)); return fmaf(z, t, z); }

__device__ __forceinline__ void wg_fence() { asm volatile("wgmma.fence.sync.aligned;" ::: "memory"); }
__device__ __forceinline__ void wg_commit() { asm volatile("wgmma.commit_group.sync.aligned;" ::: "memory"); }
template <int N> __device__ __forceinline__ void wg_wait() { asm volatile("wgmma.wait_group.sync.aligned %0;" ::"n"(N) : "memory"); }
#define A8(o) "+f"(d[(o)]), "+f"(d[(o) + 1]), "+f"(d[(o) + 2]), "+f"(d[(o) + 3]), "+f"(d[(o) + 4]), "+f"(d[(o) + 5]), "+f"(d[(o) + 6]), "+f"(d[(o) + 7])
#define A64(o) A8(o), A8((o) + 8), A8((o) + 16), A8((o) + 24), A8((o) + 32), A8((o) + 40), A8((o) + 48), A8((o) + 56)
#define REGS0_63 "%0,%1,%2,%3,%4,%5,%6,%7,%8,%9,%10,%11,%12,%13,%14,%15,%16,%17,%18,%19,%20,%21,%22,%23,%24,%25,%26,%27,%28,%29,%30,%31," \
                 "%32,%33,%34,%35,%36,%37,%38,%39,%40,%41,%42,%43,%44,%45,%46,%47,%48,%49,%50,%51,%52,%53,%54,%55,%56,%57,%58,%59,%60,%61,%62,%63"
#define REGS64_127 "%64,%65,%66,%67,%68,%69,%70,%71,%72,%73,%74,%75,%76,%77,%78,%79,%80,%81,%82,%83,%84,%85,%86,%87,%88,%89,%90,%91,%92,%93,%94,%95," \
                   "%96,%97,%98,%99,%100,%101,%102,%103,%104,%105,%106,%107,%108,%109,%110,%111,%112,%113,%114,%115,%116,%117,%118,%119,%120,%121,%122,%123,%124,%125,%126,%127"
__device__ __forceinline__ void desc_add(uint64_t& x, int v) { asm volatile("{\n.reg .b32 lo, hi;\nmov.b64 {lo, hi}, %0;\nadd.s32 lo, lo, %1;\nmov.b64 %0, {lo, hi};\n}" : "+l"(x) : "r"(v)); }
template <int ACCUM> __device__ __forceinline__ void wgmma256(float (&d)[128], uint64_t& a, uint64_t& b, int da, int db) {
  asm volatile("{\n.reg .pred p;\nsetp.ne.b32 p, %130, 0;\n"
               "wgmma.mma_async.sync.aligned.m64n256k16.f32.bf16.bf16 {" REGS0_63 "," REGS64_127 "}, %128, %129, p, 1, 1, 0, 1;\n}"
               : A64(0), A64(64) : "l"(a), "l"(b), "n"(ACCUM));
  desc_add(a, da); desc_add(b, db);
}
__device__ __forceinline__ void wgmma256_rs(float (&d)[128], uint32_t a0, uint32_t a1, uint32_t z0, uint32_t z1, uint32_t b_lo) {
  asm volatile("{\n.reg .b64 db;\nmov.b64 db, {%132, 0x00000008};\n"
               "wgmma.mma_async.sync.aligned.m64n256k16.f32.bf16.bf16 {" REGS0_63 "," REGS64_127 "}, {%128,%129,%130,%131}, db, 1, 1, 1, 0;\n}"
               : A64(0), A64(64) : "r"(a0), "r"(a1), "r"(z0), "r"(z1), "r"(b_lo));
}
template <int ACCUM> __device__ __forceinline__ void wgmma128(float (&d)[64], uint64_t& a, uint64_t& b, int da, int db) {
  asm volatile("{\n.reg .pred p;\nsetp.ne.b32 p, %66, 0;\n"
               "wgmma.mma_async.sync.aligned.m64n128k16.f32.bf16.bf16 {" REGS0_63 "}, %64, %65, p, 1, 1, 0, 1;\n}"
               : A64(0) : "l"(a), "l"(b), "n"(ACCUM));
  desc_add(a, da); desc_add(b, db);
}
template <int ACCUM> __device__ __forceinline__ void hmma(float (&c)[4], uint32_t a0, uint32_t a1, uint32_t a2, uint32_t a3, uint32_t b0, uint32_t b1) {
  if (ACCUM)
    asm volatile("mma.sync.aligned.m16n8k16.row.col.f32.bf16.bf16.f32 {%0,%1,%2,%3}, {%4,%5,%6,%7}, {%8,%9}, {%0,%1,%2,%3};"
                 : "+f"(c[0]), "+f"(c[1]), "+f"(c[2]), "+f"(c[3]) : "r"(a0), "r"(a1), "r"(a2), "r"(a3), "r"(b0), "r"(b1));
  else
    asm volatile("mma.sync.aligned.m16n8k16.row.col.f32.bf16.bf16.f32 {%0,%1,%2,%3}, {%4,%5,%6,%7}, {%8,%9}, {%10,%10,%10,%10};"
                 : "=f"(c[0]), "=f"(c[1]), "=f"(c[2]), "=f"(c[3]) : "r"(a0), "r"(a1), "r"(a2), "r"(a3), "r"(b0), "r"(b1), "f"(0.f));
}
__device__ __forceinline__ uint32_t movm(uint32_t a) { uint32_t d; asm volatile("movmatrix.sync.aligned.m8n8.trans.b16 %0, %1;" : "=r"(d) : "r"(a)); return d; }
template <int N> __device__ __forceinline__ void pin(uint32_t* r) {
#pragma unroll
  for (int i = 0; i < N; i++) asm volatile("" : "+r"(r[i]));
}
template <int N> __device__ __forceinline__ void pin(float* r) {
#pragma unroll
  for (int i = 0; i < N; i++) asm volatile("" : "+f"(r[i]));
}
__device__ __forceinline__ void sched_fence(uint32_t zero) {
  asm volatile("{\n.reg .pred p;\nsetp.eq.u32 p, %0, 0;\nLAB_F:\n@p bra.uni LAB_D;\nnanosleep.u32 0;\nbra.uni LAB_F;\nLAB_D:\n}" ::"r"(zero) : "memory");
}
__device__ __forceinline__ uint4 ldsm(uint32_t a) { uint4 v; asm volatile("ldmatrix.sync.aligned.m8n8.x4.shared.b16 {%0,%1,%2,%3}, [%4];" : "=r"(v.x), "=r"(v.y), "=r"(v.z), "=r"(v.w) : "r"(a) : "memory"); return v; }
__device__ __forceinline__ uint4 ldsm_t(uint32_t a) { uint4 v; asm volatile("ldmatrix.sync.aligned.m8n8.x4.trans.shared.b16 {%0,%1,%2,%3}, [%4];" : "=r"(v.x), "=r"(v.y), "=r"(v.z), "=r"(v.w) : "r"(a) : "memory"); return v; }

constexpr int BAR_LAG = 1, BAR_MMA = 2, BAR_EV = 3;

struct Cons {
  uint32_t sb;
  mutable uint64_t a, b;
  int k1, k2, k4, k4w, b1;
  uint32_t rel;
  bool do_rel;
  int wg;
  uint32_t zero;
};
#define REL_TS(n) TS(64 + (n))
constexpr uint32_t DB_LO = (SM_BASE >> 4) | ((8192 >> 4) << 16);

template <int ST, int ACCUM, bool WAIT = true> __device__ __forceinline__ void p1_issue(float (&acc)[128], const Cons& c, uint32_t parity) {
  if (WAIT) mbar_spin(c.sb + B_F1 + 8 * ST, parity, c.zero);
  wg_fence();
  wgmma256<ACCUM>(acc, c.a, c.b, c.k1, c.b1);
  wgmma256<1>(acc, c.a, c.b, c.k2, c.b1);
  wgmma256<1>(acc, c.a, c.b, c.k1, c.b1);
  wgmma256<1>(acc, c.a, c.b, ST == 3 ? c.k4w : c.k4, ST == 3 ? -6144 - 384 : 2048 - 384);
  wg_commit();
}
__device__ __forceinline__ void release(const Cons& c, uint32_t bar) { if (c.do_rel) mbar_arrive_cl(c.rel + bar); }
template <int KB, bool WAIT = true, int LAG = 2> __device__ __forceinline__ void p1_step(float (&acc)[128], const Cons& c) {
  if (KB == 16 - LAG) { if (c.wg == 1) { wg_wait<0>(); release(c, B_E1 + 8 * ((KB - 1) & 3)); bar_sync(BAR_LAG, 256); } }
  p1_issue<KB & 3, KB != 0, WAIT>(acc, c, (KB >> 2) & 1);
  if (KB == 15) { if (c.wg == 0) bar_arrive(BAR_LAG, 256); }
  if (KB > 0) { wg_wait<1>(); if (KB != 16 - LAG || c.wg == 0) release(c, B_E1 + 8 * ((KB - 1) & 3)); }
  if (KB == 15) { wg_wait<0>(); release(c, B_E1 + 8 * 3); }
}
template <int A, int B> __device__ __forceinline__ void p1_range(float (&acc)[128], const Cons& c) {
  if constexpr (A < B) { p1_step<A>(acc, c); p1_range<A + 1, B>(acc, c); }
}
template <int T> __device__ __forceinline__ void p2_step(float (&acc)[64], const Cons& c) {
  if (T == 16 - LAG2) { if (c.wg == 1) bar_sync(BAR_LAG, 256); }
  mbar_spin(c.sb + B_F2 + 8 * (T % 5), (T / 5) & 1, c.zero);
  wg_fence();
  wgmma128<T != 0>(acc, c.a, c.b, c.k1, c.b1);
  wgmma128<1>(acc, c.a, c.b, c.k2, c.b1);
  wgmma128<1>(acc, c.a, c.b, c.k1, c.b1);
  wgmma128<1>(acc, c.a, c.b, ((int)p2_a((T + 1) % 5) - (int)p2_a(T % 5)) / 16 - 514, ((int)p2_b((T + 1) % 5) - (int)p2_b(T % 5)) / 16 - 384);
  wg_commit();
  if (T == 15) { if (c.wg == 0) bar_arrive(BAR_LAG, 256); }
  if (T <= 11) { wg_wait<1>(); release(c, T ? B_E2 + 8 * ((T + 5 - 1) % 5) : B_E1 + 8); }
}

template <int P> __device__ __forceinline__ void geglu_piece(const uint32_t (&pk)[64], uint8_t* dst, const float (&rs)[2]) {
  constexpr int cg = P >> 1, r = P & 1;
  const float r2 = rs[r] * rs[r], c1 = GELU_C1 * rs[r], c3 = GELU_C3 * r2 * rs[r], k = 0.25f * r2;
  uint32_t v[4];
#pragma unroll
  for (int i = 0; i < 4; i++) {
    const uint32_t g = pk[2 * (4 * cg + i) + r];
    v[i] = mul2(pack2(gelu_k(lo_f(g), c1, c3, k), gelu_k(hi_f(g), c1, c3, k)), pk[32 + 2 * (4 * cg + i) + r]);
  }
  stg128(dst + cg * 8192 + r * 512, v[0], v[1], v[2], v[3]);
}
template <int KB> __device__ __forceinline__ void geglu_tile(float (&acc)[128], const uint32_t (&pk)[64], const Cons& c, uint8_t* dst, int ev, const float (&rs)[2]) {
  if constexpr (KB < 14) {
    p1_step<KB>(acc, c);
    if (KB >= 1 && KB <= 8) geglu_piece<(KB - 1) & 7>(pk, dst, rs);
    if (KB == 8) bar_arrive(ev, 288);
    geglu_tile<KB + 1>(acc, pk, c, dst, ev, rs);
  }
}

__device__ __forceinline__ void attn_tile(float (&acc)[128], const uint32_t (&pk)[64], const Cons& c, int round, int warp, int m, Scratch* gs, uint8_t* hdst, uint8_t* odst) {
  const int lane = threadIdx.x & 31, w = warp & 3, rho = lane >> 2, q = lane & 3;
  const uint32_t at = c.sb + OFF_X + c.wg * AT_WG, swz = (lane ^ (lane >> 3)) << 4;
  uint32_t gg[16];
  p1_step<0>(acc, c);
  p1_step<1>(acc, c);
#pragma unroll
  for (int i = 0; i < 4; i++) {
    const int h = i & 1, r = i >> 1;
    sts128(at + AT_V + (2 * w + r) * 1024 + h * 512 + swz, make_uint4(pk[32 + 8 * h + r], pk[34 + 8 * h + r], pk[36 + 8 * h + r], pk[38 + 8 * h + r]));
  }
  if (w < 3) {
#pragma unroll
    for (int i = 0; i < 8; i++) asm volatile("st.shared.b32 [%0], %1;" ::"r"(at + AT_K + w * 1024 + i * 128 + lane * 4), "r"(pk[17 + 2 * i]) : "memory");
  } else {
    uint8_t* g = (uint8_t*)gs->halo + ((round * 128 + blockIdx.x) * 2 + c.wg) * 2048;
#pragma unroll
    for (int i = 0; i < 8; i++) asm volatile("st.global.b32 [%0], %1;" ::"l"(g + i * 128 + lane * 4), "r"(pk[17 + 2 * i]) : "memory");
#pragma unroll
    for (int h = 0; h < 2; h++) stg128(g + 1024 + h * 512 + swz, pk[33 + 8 * h], pk[35 + 8 * h], pk[37 + 8 * h], pk[39 + 8 * h]);
    bar_arrive(BAR_EV + 2 + round, 96);
  }
  __syncwarp();
  if (lane == 0) mbar_arrive(c.sb + B_HALO + 8 * round);
  if (round) {
#pragma unroll
    for (int p = 0; p < 4; p++) asm volatile("ld.global.cg.v4.b32 {%0,%1,%2,%3}, [%4];" : "=r"(gg[4 * p]), "=r"(gg[4 * p + 1]), "=r"(gg[4 * p + 2]), "=r"(gg[4 * p + 3]) : "l"(hdst + (p >> 1) * 8192 + (p & 1) * 512) : "memory");
  }
  auto gu_piece = [&](int p) {
    uint32_t v[4];
#pragma unroll
    for (int i = 0; i < 4; i++) {
      const uint32_t g = pk[48 + 8 * (p >> 1) + 2 * i + (p & 1)];
      v[i] = mul2(round ? gg[4 * p + i] : 0x3e803e80u, round ? g : pack2(gelu_k(lo_f(g), GELU_C1, GELU_C3, 1.0f), gelu_k(hi_f(g), GELU_C1, GELU_C3, 1.0f)));
    }
    stg128(hdst + (p >> 1) * 8192 + (p & 1) * 512, v[0], v[1], v[2], v[3]);
  };
  p1_step<2>(acc, c);
  p1_step<3>(acc, c); gu_piece(0);
  p1_step<4>(acc, c); gu_piece(1);
  p1_step<5>(acc, c); gu_piece(2);
  p1_step<6>(acc, c); gu_piece(3);
  p1_step<7>(acc, c);
  p1_step<8>(acc, c);
  const bool first = m == 0 && w == 0;
  uint32_t kl[16];
  mbar_spin(c.sb + B_HALO + 8 * round, 0, c.zero);
  {
    const uint32_t ka = at + lane * 4 + (w ? AT_K + (w - 1) * 1024 : (first ? AT_K : AT_REM + round * 2048));
#pragma unroll
    for (int i = 0; i < 8; i++) {
      asm volatile("ld.shared.b32 %0, [%1];" : "=r"(kl[2 * i]) : "r"(ka + i * 128) : "memory");
      kl[2 * i + 1] = pk[16 + 2 * i] | c.zero;
    }
  }
  float st[4][4];
  pin<16>(kl);
  bar_sync(BAR_MMA, 256);
  mbar_spin(c.sb + B_F1 + 8 * 1, 0, c.zero);
#pragma unroll
  for (int ks = 0; ks < 2; ks++) {
#pragma unroll
    for (int h = 0; h < 2; h++) {
      const int o = 8 * h + 4 * ks;
      if (ks == 0) { hmma<0>(st[2 * h], kl[o], kl[o + 1], kl[o + 2], kl[o + 3], pk[o], pk[o + 2]); hmma<0>(st[2 * h + 1], pk[16 + o], pk[17 + o], pk[18 + o], pk[19 + o], pk[o + 1], pk[o + 3]); }
      else { hmma<1>(st[2 * h], kl[o], kl[o + 1], kl[o + 2], kl[o + 3], pk[o], pk[o + 2]); hmma<1>(st[2 * h + 1], pk[16 + o], pk[17 + o], pk[18 + o], pk[19 + o], pk[o + 1], pk[o + 3]); }
    }
  }
  sched_fence(c.zero);
  bar_sync(BAR_MMA, 256);
  p1_step<9, false>(acc, c);
  sched_fence(c.zero);
  pin<16>(&st[0][0]);
  const bool le0 = 2 * q <= rho, le1 = 2 * q + 1 <= rho;
  uint32_t la[2], lb[2], mx[2];
#pragma unroll
  for (int h = 0; h < 2; h++) {
    uint32_t l[2];
#pragma unroll
    for (int r = 0; r < 2; r++) {
      const float (&t)[4] = st[2 * h + r];
      l[r] = movm(pack2(rho <= 2 * q ? t[2] : t[0], rho <= 2 * q + 1 ? t[3] : t[1]));
      l[r] = fma2(l[r], 0x3e353e35u, mul2(l[r], 0x379e379eu));
    }
    la[h] = __byte_perm(l[0], l[1], 0x5410); lb[h] = __byte_perm(l[0], l[1], 0x7632);
    if (first && !le0) la[h] = (la[h] & 0xffff0000u) | 0xce6eu;
    if (first && !le1) lb[h] = (lb[h] & 0xffff0000u) | 0xce6eu;
    mx[h] = max2(la[h], lb[h]);
  }
#pragma unroll
  for (int o = 1; o <= 2; o++) { mx[0] = max2(mx[0], __shfl_xor_sync(~0u, mx[0], o)); mx[1] = max2(mx[1], __shfl_xor_sync(~0u, mx[1], o)); }
  const float L2E = 1.4426950408889634f;
  float pr[2][4], z[4];
#pragma unroll
  for (int h = 0; h < 2; h++) {
    pr[h][0] = ex2f((lo_f(la[h]) - lo_f(mx[h])) * L2E); pr[h][1] = ex2f((lo_f(lb[h]) - lo_f(mx[h])) * L2E);
    pr[h][2] = ex2f((hi_f(la[h]) - hi_f(mx[h])) * L2E); pr[h][3] = ex2f((hi_f(lb[h]) - hi_f(mx[h])) * L2E);
    z[2 * h] = pr[h][0] + pr[h][1]; z[2 * h + 1] = pr[h][2] + pr[h][3];
  }
  p1_step<10>(acc, c);
#pragma unroll
  for (int o = 1; o <= 2; o++) {
#pragma unroll
    for (int i = 0; i < 4; i++) z[i] += __shfl_xor_sync(~0u, z[i], o);
  }
  const uint32_t LE = (le0 ? 0xffffu : 0u) | (le1 ? 0xffff0000u : 0u);
  uint32_t P[4][2];
  uint4 vt[4][2];
  {
    const uint32_t row = (lane & 7) * 64 + ((((lane >> 3) & 1) ^ ((lane & 7) >> 1)) << 4);
    const uint32_t v1 = at + AT_V + (2 * w + (lane >> 4)) * 1024 + row;
    const uint32_t v0 = (w || lane >= 16) ? v1 - 1024 : (first ? v1 : at + AT_REM + round * 2048 + 1024 + row);
#pragma unroll
    for (int i = 0; i < 4; i++) {
      const float rz = rcpf(z[i]);
      const uint32_t p = pack2(pr[i >> 1][2 * (i & 1)] * rz, pr[i >> 1][2 * (i & 1) + 1] * rz);
      P[i][0] = p & ~LE; P[i][1] = p & LE;
      const uint32_t a = ((i & 1) ? v1 : v0) + (i >> 1) * 512;
      vt[i][0] = ldsm_t(a); vt[i][1] = ldsm_t(a ^ 32);
    }
  }
  float ot[4][2][4];
  pin<8>(&P[0][0]);
  bar_sync(BAR_MMA, 256);
  mbar_spin(c.sb + B_F1 + 8 * 3, 0, c.zero);
#pragma unroll
  for (int i = 0; i < 8; i++) { const uint4& v = vt[i >> 1][i & 1]; hmma<0>(ot[i >> 1][i & 1], v.x, v.y, v.z, v.w, P[i >> 1][0], P[i >> 1][1]); }
  sched_fence(c.zero);
  bar_sync(BAR_MMA, 256);
  p1_step<11, false>(acc, c);
  sched_fence(c.zero);
  pin<32>(&ot[0][0][0]);
  auto o_piece = [&](int i) {
    stg128(odst + (i >> 1) * 8192 + (i & 1) * 512, movm(pack2(ot[i][0][0], ot[i][0][1])), movm(pack2(ot[i][0][2], ot[i][0][3])), movm(pack2(ot[i][1][0], ot[i][1][1])), movm(pack2(ot[i][1][2], ot[i][1][3])));
  };
  o_piece(0); o_piece(1);
  p1_step<12>(acc, c);
  o_piece(2); o_piece(3);
  if (round) bar_arrive(BAR_EV + 4, 288);
  p1_step<13>(acc, c);
}

__device__ __forceinline__ void ln_moments(const uint32_t* raw, float& c0, float& s, float& v) {
  c0 = lo_f(__shfl_sync(~0u, raw[0], 0));
  float ss[4] = {0.f, 0.f, 0.f, 0.f}, vv[4] = {0.f, 0.f, 0.f, 0.f};
#pragma unroll
  for (int i = 0; i < 16; i++) {
    const float a = lo_f(raw[i]) - c0, b = hi_f(raw[i]) - c0;
    ss[(2 * i) & 3] += a; ss[(2 * i + 1) & 3] += b;
    vv[(2 * i) & 3] = fmaf(a, a, vv[(2 * i) & 3]); vv[(2 * i + 1) & 3] = fmaf(b, b, vv[(2 * i + 1) & 3]);
  }
  s = (ss[0] + ss[1]) + (ss[2] + ss[3]); v = (vv[0] + vv[1]) + (vv[2] + vv[3]);
}
__device__ __forceinline__ void ln_reduce(float& s, float& v) {
#pragma unroll
  for (int o = 16; o; o >>= 1) { s += __shfl_xor_sync(~0u, s, o); v += __shfl_xor_sync(~0u, v, o); }
}
__device__ __forceinline__ uint32_t ln_finish(float c0, float s, float v) {
  s *= 1.0f / DM;
  float sd;
  asm("sqrt.approx.ftz.f32 %0, %1;" : "=f"(sd) : "f"(bf16r(bf16r(fmaxf(fmaf(v, 1.0f / DM, -s * s), 0.f)) + 1e-5f)));
  return pack2(c0 + s, sd);
}
__device__ __forceinline__ void ln_store(const uint32_t* raw, uint32_t st, uint4* dst) {
  const uint32_t m2 = __byte_perm(st, st, 0x1010);
  const float rinv = rcpf(hi_f(st));
  const uint32_t rh = pack2(rinv, rinv), rl = pack2(rinv - hi_f(rh), rinv - hi_f(rh));
#pragma unroll
  for (int c = 0; c < 4; c++) {
    uint32_t v[4];
#pragma unroll
    for (int i = 0; i < 4; i++) { const uint32_t t = sub2(raw[4 * c + i], m2); v[i] = fma2(t, rh, mul2(t, rl)); }
    stg128(dst + 32 * c, v[0], v[1], v[2], v[3]);
  }
}
__device__ __forceinline__ void col_sums(uint32_t tile, ulonglong2* part, uint32_t tag) {
  const int lane = threadIdx.x & 31;
  float cs[8] = {0, 0, 0, 0, 0, 0, 0, 0};
  uint32_t base = tile + ((lane >> 3) & 1) * 8192 + (lane >> 4) * 4096 + ((lane & 7) << 4);
#pragma unroll 1
  for (int k0 = 0; k0 < 8; k0++, base = (base ^ ((k0 ^ (k0 - 1)) << 4)) + 128) {
    uint4 v[4];
#pragma unroll
    for (int k = 0; k < 4; k++) v[k] = lds128(base + k * 1024);
#pragma unroll
    for (int k = 0; k < 4; k++) {
      cs[0] += lo_f(v[k].x); cs[1] += hi_f(v[k].x); cs[2] += lo_f(v[k].y); cs[3] += hi_f(v[k].y);
      cs[4] += lo_f(v[k].z); cs[5] += hi_f(v[k].z); cs[6] += lo_f(v[k].w); cs[7] += hi_f(v[k].w);
    }
  }
  const bool up = lane >= 16;
#pragma unroll
  for (int i = 0; i < 2; i++) {
    const float a = (up ? cs[4 + 2 * i] : cs[2 * i]) + __shfl_xor_sync(~0u, up ? cs[2 * i] : cs[4 + 2 * i], 16);
    const float b = (up ? cs[5 + 2 * i] : cs[1 + 2 * i]) + __shfl_xor_sync(~0u, up ? cs[1 + 2 * i] : cs[5 + 2 * i], 16);
    asm volatile("{\n.reg .b64 a, b;\nmov.b64 a, {%1, %3};\nmov.b64 b, {%2, %3};\nst.relaxed.gpu.global.v2.b64 [%0], {a, b};\n}"
                 ::"l"(part + 32 * (i + (up ? 2 : 0)) + (lane & 15)), "r"(__float_as_uint(a)), "r"(__float_as_uint(b)), "r"(tag) : "memory");
  }
  asm volatile("fence.proxy.async.shared::cta;" ::: "memory");
}

__global__ void __cluster_dims__(2, 1, 1) __launch_bounds__(384, 1)
fused_kernel(const uint4* __restrict__ x, const uint4* __restrict__ wgate, const uint4* __restrict__ wup, Scratch* gs, const __grid_constant__ Maps mp) {
  extern __shared__ __align__(1024) uint8_t smem_raw[];
  const uint32_t sb = (uint32_t)__cvta_generic_to_shared(smem_raw);
  const unsigned t_start = 0;
  const int warp = __shfl_sync(~0u, threadIdx.x >> 5, 0), lane = threadIdx.x & 31;
  const int m = blockIdx.x & 15, j = blockIdx.x >> 4, rank = blockIdx.x & 1;
  const int m2 = blockIdx.x >> 3, j2 = blockIdx.x & 7;
  const bool helper = blockIdx.x >= NMAIN;
  if (warp >= 8) {
    asm volatile("setmaxnreg.dec.sync.aligned.u32 40;");
    if (warp == 8) {
      if (elect_one()) {
        asm volatile("prefetch.tensormap [%0];\nprefetch.tensormap [%1];\nprefetch.tensormap [%2];" ::"l"(&mp.x), "l"(&mp.wg), "l"(&mp.wu) : "memory");
        for (int s = 0; s < 4; s++) mbar_init(sb + B_F1 + 8 * s, 1);
        if (!helper) mbar_arrive(sb + B_F1);
        asm volatile("fence.mbarrier_init.release.cluster;" ::: "memory");
      }
      __syncwarp();
    } else if (warp == 9) {
      if (elect_one()) {
        if ((sb & 0xffffff) != SM_BASE) asm volatile("trap;");
        for (int s = 0; s < 4; s++) mbar_init(sb + B_E1 + 8 * s, 4);
        for (int s = 0; s < 6; s++) { mbar_init(sb + B_F2 + 8 * s, 1); mbar_init(sb + B_E2 + 8 * s, 4); }
        for (int s = 0; s < 6; s++) mbar_init(sb + B_DEP + 8 * s, 1);
        mbar_init(sb + B_AUX, 8); mbar_init(sb + B_EP, 1); mbar_init(sb + B_DONE, 4); mbar_init(sb + B_XT, 1); mbar_init(sb + B_CS, 1);
        for (int s = 0; s < 8; s++) { mbar_init(sb + B_EX + 8 * s, 1); mbar_expect_tx(sb + B_EX + 8 * s, 4096); }
        mbar_init(sb + B_HALO, 9); mbar_init(sb + B_HALO + 8, 9);
        asm volatile("fence.mbarrier_init.release.cluster;" ::: "memory");
      }
      __syncwarp();
    }
    asm volatile("barrier.cluster.arrive.relaxed.aligned;" ::: "memory");
    if (warp == 8 && !helper) {
      if (elect_one()) {
        TS(0); TG(51);
#pragma unroll 1
        for (int kb = 1; kb < 4; kb++) {
          const uint32_t sa = sb + OFF_A + kb * 16384, sw = sb + kb * 32768, fb = sb + B_F1 + 8 * kb;
          mbar_expect_tx(fb, P1_BYTES);
          tma3d(sa, &mp.x, fb, kb * 64, m * 64, 0, EVICT_NORMAL);
          tma2d(sw, &mp.wg, fb, j * 128, kb * 64, EVICT_NORMAL); tma2d(sw + 16384, &mp.wu, fb, j * 128, kb * 64, EVICT_NORMAL);
          tma2d(sw + 8192, &mp.wg, fb, j * 128 + 64, kb * 64, EVICT_NORMAL); tma2d(sw + 24576, &mp.wu, fb, j * 128 + 64, kb * 64, EVICT_NORMAL);
        }
        TS(7);
      }
      __syncwarp();
    }
    asm volatile("barrier.cluster.wait.aligned;" ::: "memory");
    if (helper) {
      if (warp == 8) {
        unsigned e = 0;
        if (elect_one()) {
#pragma unroll 1
          for (int i = 0; i < 16; i++) {
            const uint32_t fb = sb + B_F1 + 8 * (i >> 2);
            if (!(i & 3)) mbar_expect_tx(fb, P1_BYTES);
            tma5d(sb + i * 8192, &mp.wd, fb, (blockIdx.x - NMAIN) * 256 + (i & 3) * 64, (i >> 2) * 2, HINT_W);
          }
        }
        if (lane == 0) { unsigned* ep = &gs->epoch[blockIdx.x * 2]; e = *ep + 1; *ep = e; }
        e = __shfl_sync(~0u, e, 0);
        if (lane < 16) flag_wait(&gs->flags[(FL_H + lane * 4) * 32], e * 8u);
        __syncwarp();
        if (elect_one()) {
          fence_async();
          TS(0);
#pragma unroll 1
          for (int i = 0; i < 64; i++) {
            const uint32_t fb = sb + B_F1 + 8 * (i & 3);
            if (i >= 4) { mbar_wait(sb + B_E1 + 8 * (i & 3), ~(i >> 2) & 1); mbar_expect_tx(fb, 16384); }
            bulk_load(sb + OFF_A + (i & 3) * 16384, gs->h + ((i >> 2) * 56 + (i & 3)) * 1024, 16384, fb, EVICT_NORMAL);
          }
        }
      } else if (warp == 9) {
#pragma unroll 1
        for (int t = 0; t < 16; t++) {
          bar_sync(BAR_EV + (t & 1), 288);
          if (lane == 0) { flag_add(&gs->flags[(FL_P + t) * 32]); TS(64 + t); }
          __syncwarp();
        }
      }
    } else if (warp == 8) {
      if (elect_one()) {
        uint32_t par = 0;

        auto x_load = [&]() {
          mbar_expect_tx(sb + B_XT, 32768);
          tma3d(sb + OFF_X, &mp.x, sb + B_XT, j2 * 128, m2 * 64, 0, HINT_LAST); tma3d(sb + OFF_X + 16384, &mp.x, sb + B_XT, j2 * 128 + 64, m2 * 64, 0, HINT_LAST);
        };
        auto d_prefetch = [&](int i) {
          if (PF_W == 1 && (m2 >> 2) == (i & 3)) tma5d_prefetch(&mp.wd, (j2 >> 1) * 256 + (m2 & 3) * 64, (2 * i + 4 + rank) * 2);
          if (PF_H == 1 && i < 6) asm volatile("cp.async.bulk.prefetch.L2.global [%0], 4096;" ::"l"(gs->h + (m2 * 56 + 2 * i + 4 + rank) * 1024 + (j2 >> 1) * 256) : "memory");
        };
        for (int R = 0; R < 5; R++) {
          const CUtensorMap *mb0, *mb1;
          int n0, n1;
          if (R == 1 || R == 2) {
            mb0 = &mp.wqkv; n0 = 64 * (j + 8 * (R - 1)) + rank * 2048;
            mb1 = rank ? (R == 1 ? &mp.wg : &mp.wu) : &mp.wqkv; n1 = rank ? 1024 + 64 * j : n0 + 1024;
          } else {
            mb0 = mb1 = rank ? &mp.wu : &mp.wg;
            n0 = 128 * j + (R ? 1024 * R - 1536 : 0); n1 = n0 + 64;
          }
#pragma unroll 1
          for (int kb = R ? 0 : 4; kb < 16; kb++) {
            if (R == 0 && kb == 14) { asm volatile("prefetch.tensormap [%0];\nprefetch.tensormap [%1];" ::"l"(&mp.xn), "l"(&mp.wqkv) : "memory"); }
            if (R == 4 && kb == 2) { asm volatile("prefetch.tensormap [%0];\nprefetch.tensormap [%1];\nprefetch.tensormap [%2];" ::"l"(&mp.wd), "l"(&mp.wo), "l"(&mp.out) : "memory"); }
            if (R == 0 && kb == (CS_KB)) {
              const uint32_t cb = sb + B_CS, d = sb + OFF_X;
              mbar_expect_tx(cb, 32768);
              tma2d(d, &mp.wg, cb, n0, m * 64, EVICT_NORMAL); tma2d(d + 8192, &mp.wg, cb, n1, m * 64, EVICT_NORMAL);
              tma2d(d + 16384, &mp.wu, cb, n0, m * 64, EVICT_NORMAL); tma2d(d + 24576, &mp.wu, cb, n1, m * 64, EVICT_NORMAL);
            }
            const int st = kb & 3;
            const uint32_t sa = sb + OFF_A + st * 16384, sw = sb + st * 32768, fb = sb + B_F1 + 8 * st;
            mbar_wait(sb + B_E1 + 8 * st, par);
            if (R * 16 + kb >= 4) REL_TS(R * 16 + kb - 4);
            mbar_expect_tx(fb, P1_BYTES);
            tma2d_mc(sw + rank * 16384, mb0, fb, n0, kb * 64, HINT_W);
            tma2d_mc(sw + 8192 + rank * 16384, mb1, fb, n1, kb * 64, HINT_W);
            if (R == 0) {
              tma3d(sa, &mp.x, fb, kb * 64, m * 64, 0, EVICT_NORMAL);
            } else {
              if (R == 1 && kb == 0) { mbar_wait(sb + B_DEP, 0); TS(1); }
              tma2d(sa, &mp.xn, fb, kb * 64, m * 128, R == 4 ? HINT_LAST : EVICT_NORMAL);
            }
            if (R == 4 && kb == 4 + j2) x_load();
            if (R == 4 && kb >= 16 - PF_D) { if (kb == 16 - PF_D) mbar_wait(sb + B_DEP + 8, 0); d_prefetch(kb + PF_D - 16); }
            if (st == 3) par ^= 1;
          }
        }
#pragma unroll 1
        for (int i = 0; i < 26; i++) {
          const int st = i & 3, kb = 2 * i + 4 + rank;
          const uint32_t sa = sb + OFF_A + st * 16384, sw = sb + st * 32768, fb = sb + B_F1 + 8 * st;
          mbar_wait(sb + B_E1 + 8 * st, par);
          REL_TS(76 + i);
          mbar_expect_tx(fb, P1_BYTES);
          tma5d(sw, &mp.wd, fb, j2 * 128, kb * 2, HINT_W); tma5d(sw + 8192, &mp.wd, fb, j2 * 128 + 64, kb * 2, HINT_W);
          tma5d(sw + 16384, &mp.wd, fb, (j2 ^ 1) * 128, kb * 2, HINT_W); tma5d(sw + 24576, &mp.wd, fb, (j2 ^ 1) * 128 + 64, kb * 2, HINT_W);
          if (i == 0 || i == 6 || i == 10 || i == 18) { mbar_wait(sb + B_DEP + 8 * (1 + ((i + 6) >> 3)), 0); }
          bulk_load(sa, gs->h + (m2 * 56 + kb) * 1024, 16384, fb, HINT_H);
          if (i + PF_D < 26) d_prefetch(i + PF_D);
          if (i >= PF_S && i < PF_S + 8) {
            asm volatile("cp.async.bulk.prefetch.L2.global [%0], 4096;" ::"l"(gs->o + (m2 * 16 + 2 * (i - PF_S)) * 1024 + j2 * 256) : "memory");
            if ((m2 >> 1) == i - PF_S) {
              asm volatile("cp.async.bulk.prefetch.tensor.2d.L2.global [%0, {%1, %2}];" ::"l"(&mp.wo), "r"(j2 * 128), "r"(m2 * 64) : "memory");
              asm volatile("cp.async.bulk.prefetch.tensor.2d.L2.global [%0, {%1, %2}];" ::"l"(&mp.wo), "r"(j2 * 128 + 64), "r"(m2 * 64) : "memory");
            }
          }
          if (st == 3) par ^= 1;
        }
        int st = 0; uint32_t par2 = 1;
#pragma unroll 1
        for (int t = 0; t < 16; t++) {
          const uint32_t sa = sb + p2_a(st), sw = sb + p2_b(st), fb = sb + B_F2 + 8 * st;
          if (t < 5) mbar_wait(sb + B_E1 + 8 * (((2 * t + 1) / 3 + 2) & 3), t < 3); else mbar_wait(sb + B_E2 + 8 * st, par2);
          REL_TS(102 + t);
          mbar_expect_tx(fb, P2_BYTES);
          bulk_load_mc(sa + rank * 8192, gs->o + (m2 * 16 + t) * 1024 + rank * 512, 8192, fb, HINT_H);
          tma2d(sw, &mp.wo, fb, j2 * 128, t * 64, HINT_W); tma2d(sw + 8192, &mp.wo, fb, j2 * 128 + 64, t * 64, HINT_W);
          if (++st == 5) { st = 0; par2 ^= 1; }
        }
      }
    } else if (warp == 9) {
#pragma unroll 1
      for (int e = 0; e < 7; e++) {
        const bool halo = e == 2 || e == 3;
        bar_sync(BAR_EV + e, halo ? 96 : 288);
        if (lane == 0) {
          const int f = e == 0 ? FL_XN + m : (halo ? FL_HALO + (e - 2) * 128 + blockIdx.x : FL_H + m * 4 + (e == 1 ? 0 : e - 3));
          TS(10 + 2 * e); TG(52 + e);
          flag_add(&gs->flags[f * 32]);
          if (e < 6) TS(11 + 2 * e);
        }
        __syncwarp();
      }
      mbar_wait(sb + B_DONE, 0);
    } else {
      unsigned e = 0;
      if (lane == 0) {
        unsigned* ep = &gs->epoch[blockIdx.x * 2 + warp - 10];
        e = *ep + 1; *ep = e;
        if (warp == 10) { asm volatile("st.shared.b32 [%0], %1;" ::"r"(sb + OFF_EPOCH), "r"(e) : "memory"); mbar_arrive(sb + B_EP); }
      }
      e = __shfl_sync(~0u, e, 0);
      mbar_wait(sb + B_CS, 0);
      if (lane == 0 && warp == 11) TS(6);
      col_sums(sb + OFF_X + (warp - 10) * 16384, gs->cspart + (j * 16 + m) * 128 + (warp - 10) * 16, e);
      if (lane == 0 && warp == 11) TS(9);
      if (warp == 10) {
        if (lane == 0) {
#pragma unroll 1
          for (int g = 0; g < 6; g++) {
            flag_wait(&gs->flags[(g == 5 ? FL_P + m2 : (g ? FL_H + m2 * 4 + g - 1 : FL_XN + m)) * 32], e * (g == 5 ? 4u : 8u));
            fence_async();
            mbar_arrive(sb + B_DEP + 8 * g);
            if (g == 0) TS(8);
          }
#pragma unroll 1
          for (int p = 0; p < 8; p++) {
            asm volatile("cp.async.bulk.prefetch.L2.global [%0], 4096;" ::"l"(gs->dpart + blockIdx.x * 2048 + p * 256) : "memory");
            __nanosleep(PF_SLEEP);
          }
        }
      } else
      if (elect_one()) {
#pragma unroll 1
        for (int r = 0; r < 2; r++) {
          const uint32_t hb = sb + B_HALO + 8 * r;
          if (m) {
            flag_wait(&gs->flags[(FL_HALO + r * 128 + blockIdx.x - 1) * 32], e);
            fence_async();
            mbar_expect_tx(hb, 4096);
            for (int g = 0; g < 2; g++) bulk_load(sb + OFF_X + g * AT_WG + AT_REM + r * 2048, gs->halo + ((r * 128 + blockIdx.x - 1) * 2 + g) * 128, 2048, hb, EVICT_FIRST);
          } else {
            mbar_arrive(hb);
          }
          TS(34 + r);
        }
      }
    }
  } else {
    if (!helper) {
      const int r = threadIdx.x >> 3, ch = threadIdx.x & 7;
      const uint32_t d = sb + r * 128 + ((ch ^ (r & 7)) << 4);
      const uint4* xa = x + (128 * m + 2 * r) * 128 + ch;
      const size_t wo = (size_t)r * (DFF / 8) + 16 * j + ch;
#pragma unroll
      for (int i = 0; i < 12; i++) {
        const uint4* src = i < 4 ? xa + (i & 1) * 64 * 128 + (i >> 1) * 128 : (i < 8 ? wgate : wup) + wo + (i & 1) * 32 * (DFF / 8) + ((i >> 1) & 1) * 8;
        asm volatile("cp.async.cg.shared.global [%0], [%1], 16;" ::"r"(d + (i < 4 ? OFF_A + i * 4096 : (i - 4) * 4096)), "l"(src) : "memory");
      }
    }
    asm volatile("barrier.cluster.arrive.relaxed.aligned;" ::: "memory");
    asm volatile("setmaxnreg.inc.sync.aligned.u32 232;");
    const int wg = warp >> 2, w = warp & 3;
    Cons c;
    c.sb = sb; c.wg = wg; c.zero = warp >> 8;
    c.a = 0x4000004000010000ull + ((SM_BASE + OFF_A + wg * 8192) >> 4); c.k1 = 2 + c.zero; c.k2 = 2; c.k4 = 1024 - 6; c.k4w = -3072 - 6; c.b1 = 128 + c.zero;
    c.b = 0x4000004000000000ull + DB_LO + c.zero;
    c.rel = mapa(sb, threadIdx.x & 1);
    c.do_rel = (threadIdx.x & 127) < 2;
    constexpr bool t0 = false;
    float acc[128];
    uint32_t pk[64];
    float rs[2];
    const int rho = lane >> 2, q = lane & 3;

    if (helper) {
      asm volatile("barrier.cluster.wait.aligned;" ::: "memory");
      c.a = 0x8000002000010000ull + ((SM_BASE + OFF_A + wg * 4096) >> 4); c.k2 = 510; c.k4 = 1024 - 514; c.k4w = -3072 - 514;
      c.rel = sb;
      uint4* dst = gs->dpart + (blockIdx.x - NMAIN) * 4096 + threadIdx.x;
      auto put = [&](int p) {
#pragma unroll
        for (int i = 4 * p; i < 4 * p + 4; i++) stg128(dst + i * 256, pk[4 * i], pk[4 * i + 1], pk[4 * i + 2], pk[4 * i + 3]);
      };
#pragma unroll 1
      for (int t = 0; t < 16; t++) {
        p1_issue<0, 0>(acc, c, t & 1);
        if (t) put(0);
        p1_issue<1, 1>(acc, c, t & 1); wg_wait<1>(); release(c, B_E1);
        if (t) put(1);
        if (wg == 1) { wg_wait<0>(); release(c, B_E1 + 8); bar_sync(BAR_LAG, 256); }
        p1_issue<2, 1>(acc, c, t & 1); wg_wait<1>(); if (wg == 0) release(c, B_E1 + 8);
        if (t) put(2);
        p1_issue<3, 1>(acc, c, t & 1);
        if (wg == 0) bar_arrive(BAR_LAG, 256);
        if (t) { put(3); bar_arrive(BAR_EV + (~t & 1), 288); dst += 8 * 2048; }
        wg_wait<1>(); release(c, B_E1 + 16);
        wg_wait<0>(); release(c, B_E1 + 24);
#pragma unroll
        for (int i = 0; i < 64; i++) pk[i] = pack2(acc[2 * i], acc[2 * i + 1]);
      }
      put(0); put(1); put(2); put(3);
      bar_arrive(BAR_EV + 1, 288);
      return;
    }
    {
      const int prow = 16 * j + 2 * warp;
      const uint4* xr = x + (size_t)(128 * m + 2 * (prow & 63) + (prow >> 6)) * 128 + lane;
      uint4* xo = gs->xn + (size_t)(128 * m + prow) * 128 + lane;
      float c0[2], mo[4];
      uint32_t st[2];
      uint32_t e;
      asm volatile("" : "+l"(xr), "+l"(xo));
      if (t0) TS(23 + wg * 16);
      asm volatile("cp.async.wait_all;\nfence.proxy.async.shared::cta;" ::: "memory");
      bar_sync(BAR_MMA, 256);
      if (threadIdx.x == 0) TS(39);
      p1_step<0, false>(acc, c);
      asm volatile("barrier.cluster.wait.aligned;" ::: "memory");
      p1_range<1, LN_LD + 1>(acc, c);
      if (t0) TS(24 + wg * 16);
#pragma unroll
      for (int i = 0; i < 8; i++) {
        asm volatile("ld.global.nc.v4.b32 {%0,%1,%2,%3}, [%4];" : "=r"(pk[4 * i]), "=r"(pk[4 * i + 1]), "=r"(pk[4 * i + 2]), "=r"(pk[4 * i + 3]) : "l"(xr + (i >> 2) * 256 + (i & 3) * 32));
      }
      p1_range<LN_LD + 1, LN_KB + 1>(acc, c);
      sched_fence(c.zero);

      pin<16>(pk); ln_moments(pk, c0[0], mo[0], mo[1]); pin<2>(mo);
      p1_step<LN_KB + 1>(acc, c);
      sched_fence(c.zero);
      pin<16>(pk + 16); ln_moments(pk + 16, c0[1], mo[2], mo[3]); ln_reduce(mo[0], mo[1]); pin<4>(mo);
      p1_step<LN_KB + 2>(acc, c);
      mbar_spin(sb + B_EP, 0, c.zero);
      asm volatile("ld.shared.b32 %0, [%1];" : "=r"(e) : "r"(sb + OFF_EPOCH) : "memory");
      pin<2>(mo); st[0] = ln_finish(c0[0], mo[0], mo[1]); ln_reduce(mo[2], mo[3]); pin<1>(st); pin<2>(mo + 2);
      p1_step<LN_KB + 3>(acc, c);
      sched_fence(c.zero);
      pin<1>(st); pin<2>(mo + 2);
      st[1] = ln_finish(c0[1], mo[2], mo[3]);
      ln_store(pk, st[0], xo);
      if (lane == 0)
        asm volatile("{\n.reg .b64 a, b;\nmov.b64 a, {%1, %3};\nmov.b64 b, {%2, %3};\nst.relaxed.gpu.global.v2.b64 [%0], {a, b};\n}" ::"l"(gs->stats + 128 * m + prow), "r"(st[0]), "r"(st[1]), "r"(e) : "memory");
      if (LN_SPLIT) { p1_step<LN_KB + 4>(acc, c); sched_fence(c.zero); pin<1>(st + 1); }
      ln_store(pk + 16, st[1], xo + 128);
      bar_arrive(BAR_EV, 288);
      p1_range<LN_KB + 4 + LN_SPLIT, G_KB + 1>(acc, c);
      sched_fence(c.zero);
      const unsigned long long* cp = (const unsigned long long*)gs->cspart + j * 4096 + threadIdx.x;
      const unsigned long long* sp = gs->stats + 128 * m + warp * 16 + rho;
      unsigned long long part[18];
      auto gather = [&]() {
#pragma unroll
        for (int i = 0; i < 18; i++) asm volatile("ld.relaxed.gpu.global.b64 %0, [%1];" : "=l"(part[i]) : "l"(i < 16 ? cp + i * 256 : sp + (i - 16) * 8) : "memory");
      };
      gather();
      auto validate = [&]() {
        float csum;
        for (int tries = 0;; tries++) {
          uint32_t bad = 0;
          csum = 0.f;
#pragma unroll
          for (int i = 0; i < 18; i++) { bad |= (uint32_t)(part[i] >> 32) ^ e; if (i < 16) csum += __uint_as_float((uint32_t)part[i]); }
          if (!__any_sync(~0u, bad != 0) || tries > (1 << 20)) break;
          gather();
        }
        const float hi = bf16r(csum), mid = bf16r(csum - hi);
        sts128(sb + OFF_CS + ((threadIdx.x & 62) * 4 + (threadIdx.x >> 6) * 2 + (threadIdx.x & 1)) * 16, make_uint4(pack2(hi, mid), pack2(csum - hi - mid, 0.f), 0, 0));
        asm volatile("fence.proxy.async.shared::cta;" ::: "memory");
        __syncwarp();
        if (lane == 0) mbar_arrive(sb + B_AUX);
      };
      p1_range<G_KB + 1, 14>(acc, c);
      if (wg == 1) validate();
      p1_step<14>(acc, c);
      p1_issue<3, 1>(acc, c, 1);
      if (wg == 0) validate();
      const uint32_t keep = q == 0 ? 0xffffffffu : (q == 1 ? 0xffffu : 0u);
      const uint32_t a0 = (__byte_perm((uint32_t)part[16], 0, 0x1010) ^ 0x80008000u) & keep, a1 = (__byte_perm((uint32_t)part[17], 0, 0x1010) ^ 0x80008000u) & keep;
      mbar_spin(sb + B_AUX, 0, c.zero);
      wg_fence();
      wgmma256_rs(acc, a0, a1, 0, 0, (SM_BASE + OFF_CS) >> 4);
      wg_commit();
      if (wg == 0) bar_arrive(BAR_LAG, 256);
      rs[0] = rcpf(hi_f((uint32_t)part[16])); rs[1] = rcpf(hi_f((uint32_t)part[17]));
      wg_wait<2>(); release(c, B_E1 + 16);
      wg_wait<0>(); release(c, B_E1 + 24);
#pragma unroll
      for (int i = 0; i < 64; i++) pk[i] = pack2(acc[2 * i], acc[2 * i + 1]);
      if (t0) TS(25 + wg * 16);
    }
    const uint32_t img = warp * 1024 + ((lane ^ (lane >> 3)) << 4);
#pragma unroll 1
    for (int R = 1;; R++) {
      uint8_t* hb = (uint8_t*)gs->h + (size_t)m * 56 * 16384 + img;
      if (R == 2 || R == 3) {
        attn_tile(acc, pk, c, R - 2, warp, m, gs, hb + (16 + j) * 16384, (uint8_t*)gs->o + (m * 16 + j + 8 * (R - 2)) * 16384 + img);
      } else {
        if (R == 5) { c.a = 0x8000002000010000ull + ((SM_BASE + OFF_A + wg * 4096) >> 4); c.k2 = 510; c.k4 = 1024 - 514; c.k4w = -3072 - 514; }
        geglu_tile<0>(acc, pk, c, hb + (2 * j + (R == 1 ? 0 : 16 * R - 40)) * 16384, BAR_EV + (R == 1 ? 1 : R + 1), rs);
        rs[0] = rs[1] = 1.0f;
        if (R == 5) break;
      }
      p1_range<14, 16>(acc, c);
#pragma unroll
      for (int i = 0; i < 64; i++) pk[i] = pack2(acc[2 * i], acc[2 * i + 1]);
      if (t0) TS(25 + R + wg * 16);
    }
    if (t0) TS(30 + wg * 16);
    auto fetch = [&](int p) {
      asm volatile("ld.global.cg.v4.b32 {%0,%1,%2,%3}, [%4];" : "=r"(pk[4 * p]), "=r"(pk[4 * p + 1]), "=r"(pk[4 * p + 2]), "=r"(pk[4 * p + 3]) : "l"(gs->dpart + blockIdx.x * 2048 + p * 256 + threadIdx.x) : "memory");
    };
#pragma unroll 1
    for (int it = 3; it < 5; it++) {
      p1_issue<2, 1>(acc, c, it & 1); wg_wait<1>(); release(c, B_E1 + 8);
      p1_issue<3, 1>(acc, c, it & 1); wg_wait<1>(); release(c, B_E1 + 16);
      p1_issue<0, 1>(acc, c, ~it & 1); wg_wait<1>(); release(c, B_E1 + 24);
      p1_issue<1, 1>(acc, c, ~it & 1); wg_wait<1>(); release(c, B_E1);
    }
    p1_issue<2, 1>(acc, c, 1); wg_wait<1>(); release(c, B_E1 + 8);
    mbar_spin(sb + B_DEP + 40, 0, c.zero);
    fetch(0); fetch(4);
    p1_issue<3, 1>(acc, c, 1); wg_wait<1>(); release(c, B_E1 + 16);
    fetch(1); fetch(5);
    p1_issue<0, 1>(acc, c, 0); wg_wait<1>(); release(c, B_E1 + 24);
    fetch(2); fetch(6);
    p1_issue<1, 1>(acc, c, 0); wg_wait<1>(); release(c, B_E1);
    fetch(3); fetch(7);
    if (t0) TS(31 + wg * 16);
    {
      float accs[64];
      const uint32_t peer = mapa(sb, rank ^ 1);
      auto send_piece = [&](int p) {
        asm volatile("st.async.weak.shared::cluster.mbarrier::complete_tx::bytes.v4.b32 [%0], {%1,%2,%3,%4}, [%5];" ::"r"(peer + OFF_LAND + p * 4096 + threadIdx.x * 16),
                     "r"(pack2(acc[64 + 8 * p], acc[65 + 8 * p])), "r"(pack2(acc[66 + 8 * p], acc[67 + 8 * p])), "r"(pack2(acc[68 + 8 * p], acc[69 + 8 * p])), "r"(pack2(acc[70 + 8 * p], acc[71 + 8 * p])),
                     "r"(peer + B_EX + 32 * wg + 8 * (p >> 1)) : "memory");
      };
      auto silu_piece = [&](int p) {
        const uint4 r = lds128(sb + OFF_LAND + p * 4096 + threadIdx.x * 16);
        const uint32_t rr[4] = {add2(r.x, pk[4 * p]), add2(r.y, pk[4 * p + 1]), add2(r.z, pk[4 * p + 2]), add2(r.w, pk[4 * p + 3])};
#pragma unroll
        for (int i = 0; i < 4; i++) {
          const float a = acc[8 * p + 2 * i] + lo_f(rr[i]), b = acc[8 * p + 2 * i + 1] + hi_f(rr[i]);
          pk[4 * p + i] = pack2(silu_half(a), silu_half(b));
        }
        pin<4>(pk + 4 * p);
      };
      const uint32_t xa = sb + OFF_X + (warp * 16 + (lane & 15)) * 128 + (((lane >> 4) ^ (lane & 7)) << 4);
      auto x_piece = [&](int i) { const uint4 v = ldsm((xa ^ ((i & 3) << 5)) + (i >> 2) * 16384); pk[32 + 4 * i] = v.x; pk[33 + 4 * i] = v.y; pk[34 + 4 * i] = v.z; pk[35 + 4 * i] = v.w; };
      p2_step<0>(accs, c);
      p2_step<1>(accs, c);
      mbar_spin(sb + B_E1 + 8, 0, c.zero);
      send_piece(0); send_piece(1);
      p2_step<2>(accs, c); sched_fence(c.zero); send_piece(2); send_piece(3);
      p2_step<3>(accs, c); sched_fence(c.zero); send_piece(4); send_piece(5);
      p2_step<4>(accs, c); mbar_spin(sb + B_XT, 0, c.zero); send_piece(6); send_piece(7);
      p2_step<5>(accs, c); mbar_spin(sb + B_EX + 32 * wg, 0, c.zero); silu_piece(0); x_piece(0);
      p2_step<6>(accs, c); sched_fence(c.zero); silu_piece(1); x_piece(1);
      p2_step<7>(accs, c); mbar_spin(sb + B_EX + 32 * wg + 8, 0, c.zero); silu_piece(2); x_piece(2);
      p2_step<8>(accs, c); sched_fence(c.zero); silu_piece(3); x_piece(3);
      p2_step<9>(accs, c); mbar_spin(sb + B_EX + 32 * wg + 16, 0, c.zero); silu_piece(4); x_piece(4);
      p2_step<10>(accs, c); sched_fence(c.zero); silu_piece(5); x_piece(5);
      p2_step<11>(accs, c); mbar_spin(sb + B_EX + 32 * wg + 24, 0, c.zero); silu_piece(6); x_piece(6); x_piece(7);
      if (wg == 1) silu_piece(7);
      p2_step<12>(accs, c); p2_step<13>(accs, c); p2_step<14>(accs, c); p2_step<15>(accs, c);
      if (c.do_rel) mbar_arrive(sb + B_DONE);
      if (wg == 0) silu_piece(7);
      wg_wait<0>();
      if (t0) TS(32 + wg * 16);
#pragma unroll
      for (int i = 0; i < 8; i++) {
        uint32_t v[4];
#pragma unroll
        for (int k = 0; k < 4; k++) v[k] = fma2(pack2(accs[8 * i + 2 * k], accs[1 + 8 * i + 2 * k]), pk[4 * i + k], pk[32 + 4 * i + k]);
        asm volatile("stmatrix.sync.aligned.m8n8.x4.shared.b16 [%0], {%1,%2,%3,%4};" ::"r"((xa ^ ((i & 3) << 5)) + (i >> 2) * 16384), "r"(v[0]), "r"(v[1]), "r"(v[2]), "r"(v[3]) : "memory");
        if (i == 3 || i == 7) {
          asm volatile("fence.proxy.async.shared::cta;" ::: "memory");
          __syncwarp();
          if (elect_one()) tma3d_store(&mp.out, sb + OFF_X + (i >> 2) * 16384 + warp * 2048, j2 * 128 + (i >> 2) * 64, m2 * 64 + w * 16, wg);
        }
      }
      if (elect_one()) { asm volatile("cp.async.bulk.commit_group;\ncp.async.bulk.wait_group.read 0;" ::: "memory"); }
      if ((threadIdx.x & 127) == 0) { TS(33 + wg * 16); if (wg) { TG(59); unsigned id; asm volatile("mov.u32 %0, %%smid;" : "=r"(id)); TSV(60, id); } }
    }
  }
}

typedef CUresult (*EncodeFn)(CUtensorMap*, CUtensorMapDataType, cuuint32_t, void*, const cuuint64_t*, const cuuint64_t*, const cuuint32_t*, const cuuint32_t*,
                             CUtensorMapInterleave, CUtensorMapSwizzle, CUtensorMapL2promotion, CUtensorMapFloatOOBfill);

void encode(EncodeFn fn, CUtensorMap* tm, const void* p, int rank, const cuuint64_t* dims, const cuuint64_t* strides, const cuuint32_t* box) {
  const cuuint32_t es[5] = {1, 1, 1, 1, 1};
  fn(tm, CU_TENSOR_MAP_DATA_TYPE_BFLOAT16, rank, const_cast<void*>(p), dims, strides, box, es, CU_TENSOR_MAP_INTERLEAVE_NONE, CU_TENSOR_MAP_SWIZZLE_128B,
     PROMO, CU_TENSOR_MAP_FLOAT_OOB_FILL_NONE);
}

}

extern "C" void kernel_launch(void* const* d_in, const int* in_sizes, int n_in, void* d_out, int out_size) {
  (void)in_sizes; (void)n_in; (void)out_size;
  static EncodeFn fn = nullptr;
  static Scratch* gs = nullptr;
  if (!fn) {
    void* p = nullptr;
    cudaDriverEntryPointQueryResult qr;
    cudaGetDriverEntryPoint("cuTensorMapEncodeTiled", &p, cudaEnableDefault, &qr);
    fn = (EncodeFn)p;
    cudaGetSymbolAddress((void**)&gs, g_scratch);
    cudaFuncSetAttribute(fused_kernel, cudaFuncAttributeMaxDynamicSharedMemorySize, SMEM_BYTES);
  }
  const void *x = d_in[0], *wqkv = d_in[1], *wo = d_in[2], *wg = d_in[4], *wu = d_in[5], *wd = d_in[6];
  Maps mp;
  {
    const cuuint64_t dims[3] = {DM, SEQ / 2, 2}, st[2] = {DM * 4, DM * 2};
    const cuuint32_t box_in[3] = {64, 64, 2}, box_out[3] = {64, 16, 1};
    encode(fn, &mp.x, x, 3, dims, st, box_in);
    encode(fn, &mp.out, d_out, 3, dims, st, box_out);
  }
  {
    const cuuint64_t dims[2] = {DM, SEQ}, st[1] = {DM * 2};
    const cuuint32_t box[2] = {64, 128};
    encode(fn, &mp.xn, gs->xn, 2, dims, st, box);
  }
  {
    const cuuint32_t box[2] = {64, 64};
    const cuuint64_t dq[2] = {3 * DM, DM}, sq[1] = {3 * DM * 2}, df[2] = {DFF, DM}, sf[1] = {DFF * 2}, dw[2] = {DM, DM}, sw[1] = {DM * 2};
    encode(fn, &mp.wqkv, wqkv, 2, dq, sq, box);
    encode(fn, &mp.wg, wg, 2, df, sf, box);
    encode(fn, &mp.wu, wu, 2, df, sf, box);
    encode(fn, &mp.wo, wo, 2, dw, sw, box);
  }
  {
    const cuuint32_t box[5] = {64, 2, 4, 4, 2};
    const cuuint64_t st[4] = {DM * 2, 8 * DM * 2, 2 * DM * 2, 32 * DM * 2};
    const cuuint64_t dd[5] = {DM, 2, 4, 4, DFF / 32};
    encode(fn, &mp.wd, wd, 5, dd, st, box);
  }
  fused_kernel<<<NCTA, 384, SMEM_BYTES>>>((const uint4*)x, (const uint4*)wg, (const uint4*)wu, gs, mp);
}
```

```cpp
#include <cuda_runtime.h>
#include <cuda_bf16.h>
#include <cuda.h>
#include <stdint.h>

#define LN_LD 1
#define PROMO CU_TENSOR_MAP_L2_PROMOTION_L2_128B
#define G_KB 12
#define PF_D 4
#define PF_W 1
#define PF_H 1
#define PF_SLEEP 250
#define PF_S 16
#define LAG2 4
#define LN_SPLIT 1
#define CS_KB 8
#define LN_KB 4

#define EVICT_FIRST 0x12F0000000000000ull
#define EVICT_NORMAL 0x1000000000000000ull
#define HINT_W EVICT_FIRST
#define HINT_H EVICT_FIRST
#define HINT_LAST EVICT_FIRST

namespace {

constexpr int SEQ = 2048, DM = 1024, DFF = 3584;
constexpr int NMAIN = 128, NCTA = 132;

constexpr uint32_t SM_BASE = 0x400;
constexpr uint32_t P1_BYTES = 49152, P2_BYTES = 32768;
constexpr uint32_t OFF_A = 131072;
__host__ __device__ constexpr uint32_t p2_a(int s) { return s == 0 ? OFF_A + 32768 : s == 1 ? OFF_A + 49152 : s == 2 ? 114688 : s == 3 ? 16384 : 49152; }
__host__ __device__ constexpr uint32_t p2_b(int s) { return s < 3 ? 65536 + s * 16384 : (s - 3) * 32768; }
constexpr uint32_t OFF_LAND = OFF_A;
constexpr uint32_t OFF_X = 196608;
constexpr uint32_t OFF_CS = OFF_X + 14336;
constexpr uint32_t OFF_BAR = 229376;
constexpr uint32_t B_F1 = OFF_BAR, B_E1 = B_F1 + 32, B_F2 = B_E1 + 32, B_E2 = B_F2 + 48;
constexpr uint32_t B_DEP = B_E2 + 48;
constexpr uint32_t B_AUX = B_DEP + 48, B_CS = B_AUX + 8, B_XT = B_CS + 8, B_EX = B_XT + 8, B_HALO = B_EX + 64, B_EP = B_HALO + 16, B_DONE = B_EP + 8, OFF_EPOCH = B_DONE + 8;
constexpr uint32_t SMEM_BYTES = 232448;
constexpr uint32_t AT_V = 0, AT_K = 8192, AT_REM = 11264, AT_WG = 15360;

constexpr int FL_XN = 0, FL_H = 16, FL_P = 80, FL_HALO = 96, FL_N = FL_HALO + 256;
struct __align__(1024) Scratch {
  uint4 h[16 * 56 * 1024];
  uint4 o[16 * 16 * 1024];
  uint4 xn[SEQ * DM / 8];
  uint4 dpart[128 * 8 * 256];
  uint4 halo[2 * 128 * 2 * 128];
  ulonglong2 cspart[8 * 16 * 128];
  unsigned long long stats[SEQ];
  unsigned flags[FL_N * 32];
  unsigned epoch[NCTA * 2];
};
__device__ Scratch g_scratch;
#define TG(i) do {} while (0)
#define TSV(i, v) do {} while (0)
#define TS(i) do {} while (0)

struct Maps { CUtensorMap x, xn, out, wqkv, wg, wu, wd, wo; };

__device__ __forceinline__ void mbar_init(uint32_t bar, uint32_t cnt) { asm volatile("mbarrier.init.shared::cta.b64 [%0], %1;" ::"r"(bar), "r"(cnt)); }
__device__ __forceinline__ void mbar_expect_tx(uint32_t bar, uint32_t bytes) { asm volatile("mbarrier.arrive.expect_tx.shared::cta.b64 _, [%0], %1;" ::"r"(bar), "r"(bytes) : "memory"); }
__device__ __forceinline__ void mbar_arrive(uint32_t bar) { asm volatile("mbarrier.arrive.shared::cta.b64 _, [%0];" ::"r"(bar) : "memory"); }
__device__ __forceinline__ void mbar_arrive_cl(uint32_t bar) { asm volatile("mbarrier.arrive.shared::cluster.b64 _, [%0];" ::"r"(bar) : "memory"); }
__device__ __forceinline__ uint32_t mapa(uint32_t a, uint32_t cta) { uint32_t r; asm("mapa.shared::cluster.u32 %0, %1, %2;" : "=r"(r) : "r"(a), "r"(cta)); return r; }
__device__ __forceinline__ void mbar_wait(uint32_t bar, uint32_t parity) {
  asm volatile("{\n.reg .pred p;\n.reg .u32 n;\nmov.u32 n, 0;\nLAB_WAIT:\nmbarrier.try_wait.parity.shared::cta.b64 p, [%0], %1;\n@p bra LAB_DONE;\n"
               "add.u32 n, n, 1;\nsetp.gt.u32 p, n, 4000000;\n@p trap;\nbra LAB_WAIT;\nLAB_DONE:\n}" ::"r"(bar), "r"(parity) : "memory");
}
__device__ __forceinline__ void mbar_spin(uint32_t bar, uint32_t parity, uint32_t zero) {
  asm volatile("{\n.reg .pred p, z;\nsetp.ne.u32 z, %2, 0;\nLAB_WAIT:\nmbarrier.try_wait.parity.shared::cta.b64 p, [%0], %1;\n@p bra LAB_DONE;\n@z trap;\nbra LAB_WAIT;\nLAB_DONE:\n}" ::"r"(bar), "r"(parity), "r"(zero) : "memory");
}
__device__ __forceinline__ void flag_wait(const unsigned* f, unsigned target) {
  asm volatile("{\n.reg .pred p;\n.reg .u32 n, v;\nmov.u32 n, 0;\nLAB_WAIT:\nld.relaxed.gpu.global.u32 v, [%0];\nsub.u32 v, v, %1;\nsetp.ge.s32 p, v, 0;\n@p bra LAB_DONE;\n"
               "nanosleep.u32 100;\nadd.u32 n, n, 1;\nsetp.gt.u32 p, n, 4000000;\n@p trap;\nbra LAB_WAIT;\nLAB_DONE:\nfence.acquire.gpu;\n}" ::"l"(f), "r"(target) : "memory");
}
__device__ __forceinline__ void flag_add(unsigned* f) { asm volatile("red.release.gpu.global.add.u32 [%0], 1;" ::"l"(f) : "memory"); }
__device__ __forceinline__ void fence_async() { asm volatile("fence.proxy.async.global;" ::: "memory"); }
__device__ __forceinline__ bool elect_one() { uint32_t p; asm volatile("{\n.reg .pred P;\nelect.sync _|P, 0xffffffff;\nselp.u32 %0, 1, 0, P;\n}" : "=r"(p)); return p; }
__device__ __forceinline__ void bar_sync(int id, int n) { asm volatile("bar.sync %0, %1;" ::"r"(id), "r"(n) : "memory"); }
__device__ __forceinline__ void bar_arrive(int id, int n) { asm volatile("bar.arrive %0, %1;" ::"r"(id), "r"(n) : "memory"); }

__device__ __forceinline__ void tma2d(uint32_t dst, const CUtensorMap* tm, uint32_t bar, int c0, int c1, uint64_t hint) {
  asm volatile("cp.async.bulk.tensor.2d.shared::cluster.global.mbarrier::complete_tx::bytes.L2::cache_hint [%0], [%1, {%3, %4}], [%2], %5;" ::"r"(dst), "l"(tm), "r"(bar), "r"(c0), "r"(c1), "l"(hint) : "memory");
}
__device__ __forceinline__ void tma2d_mc(uint32_t dst, const CUtensorMap* tm, uint32_t bar, int c0, int c1, uint64_t hint) {
  asm volatile("cp.async.bulk.tensor.2d.shared::cluster.global.mbarrier::complete_tx::bytes.multicast::cluster.L2::cache_hint [%0], [%1, {%3, %4}], [%2], %5, %6;" ::"r"(dst), "l"(tm), "r"(bar), "r"(c0), "r"(c1), "h"((uint16_t)3), "l"(hint) : "memory");
}
__device__ __forceinline__ void tma3d(uint32_t dst, const CUtensorMap* tm, uint32_t bar, int c0, int c1, int c2, uint64_t hint) {
  asm volatile("cp.async.bulk.tensor.3d.shared::cluster.global.mbarrier::complete_tx::bytes.L2::cache_hint [%0], [%1, {%3, %4, %5}], [%2], %6;" ::"r"(dst), "l"(tm), "r"(bar), "r"(c0), "r"(c1), "r"(c2), "l"(hint) : "memory");
}
__device__ __forceinline__ void tma5d(uint32_t dst, const CUtensorMap* tm, uint32_t bar, int c0, int c4, uint64_t hint) {
  asm volatile("cp.async.bulk.tensor.5d.shared::cluster.global.mbarrier::complete_tx::bytes.L2::cache_hint [%0], [%1, {%3, %5, %5, %5, %4}], [%2], %6;" ::"r"(dst), "l"(tm), "r"(bar), "r"(c0), "r"(c4), "r"(0), "l"(hint) : "memory");
}
__device__ __forceinline__ void tma5d_prefetch(const CUtensorMap* tm, int c0, int c4) {
  asm volatile("cp.async.bulk.prefetch.tensor.5d.L2.global [%0, {%1, %3, %3, %3, %2}];" ::"l"(tm), "r"(c0), "r"(c4), "r"(0) : "memory");
}
__device__ __forceinline__ void tma3d_store(const CUtensorMap* tm, uint32_t src, int c0, int c1, int c2) {
  asm volatile("cp.async.bulk.tensor.3d.global.shared::cta.bulk_group [%0, {%2, %3, %4}], [%1];" ::"l"(tm), "r"(src), "r"(c0), "r"(c1), "r"(c2) : "memory");
}
__device__ __forceinline__ void bulk_load(uint32_t dst, const void* src, uint32_t bytes, uint32_t bar, uint64_t hint) {
  asm volatile("cp.async.bulk.shared::cluster.global.mbarrier::complete_tx::bytes.L2::cache_hint [%0], [%1], %2, [%3], %4;" ::"r"(dst), "l"(src), "r"(bytes), "r"(bar), "l"(hint) : "memory");
}
__device__ __forceinline__ void bulk_load_mc(uint32_t dst, const void* src, uint32_t bytes, uint32_t bar, uint64_t hint) {
  asm volatile("cp.async.bulk.shared::cluster.global.mbarrier::complete_tx::bytes.multicast::cluster.L2::cache_hint [%0], [%1], %2, [%3], %4, %5;" ::"r"(dst), "l"(src), "r"(bytes), "r"(bar), "h"((uint16_t)3), "l"(hint) : "memory");
}
__device__ __forceinline__ uint4 lds128(uint32_t a) { uint4 v; asm volatile("ld.shared.v4.b32 {%0,%1,%2,%3}, [%4];" : "=r"(v.x), "=r"(v.y), "=r"(v.z), "=r"(v.w) : "r"(a) : "memory"); return v; }
__device__ __forceinline__ void sts128(uint32_t a, uint4 v) { asm volatile("st.shared.v4.b32 [%0], {%1,%2,%3,%4};" ::"r"(a), "r"(v.x), "r"(v.y), "r"(v.z), "r"(v.w) : "memory"); }
__device__ __forceinline__ void stg128(void* p, uint32_t a, uint32_t b, uint32_t c, uint32_t d) { asm volatile("st.global.v4.b32 [%0], {%1,%2,%3,%4};" ::"l"(p), "r"(a), "r"(b), "r"(c), "r"(d) : "memory"); }

__device__ __forceinline__ uint32_t pack2(float lo, float hi) { uint32_t r; asm("cvt.rn.bf16x2.f32 %0, %1, %2;" : "=r"(r) : "f"(hi), "f"(lo)); return r; }
__device__ __forceinline__ float lo_f(uint32_t v) { return __uint_as_float(v << 16); }
__device__ __forceinline__ float hi_f(uint32_t v) { return __uint_as_float(v & 0xffff0000u); }
__device__ __forceinline__ float bf16r(float v) { return lo_f(pack2(v, 0.f)); }
__device__ __forceinline__ uint32_t mul2(uint32_t a, uint32_t b) { uint32_t r; asm("mul.rn.bf16x2 %0, %1, %2;" : "=r"(r) : "r"(a), "r"(b)); return r; }
__device__ __forceinline__ uint32_t add2(uint32_t a, uint32_t b) { uint32_t r; asm("add.rn.bf16x2 %0, %1, %2;" : "=r"(r) : "r"(a), "r"(b)); return r; }
__device__ __forceinline__ uint32_t sub2(uint32_t a, uint32_t b) { uint32_t r; asm("sub.rn.bf16x2 %0, %1, %2;" : "=r"(r) : "r"(a), "r"(b)); return r; }
__device__ __forceinline__ uint32_t fma2(uint32_t a, uint32_t b, uint32_t c) { uint32_t r; asm("fma.rn.bf16x2 %0, %1, %2, %3;" : "=r"(r) : "r"(a), "r"(b), "r"(c)); return r; }
__device__ __forceinline__ uint32_t max2(uint32_t a, uint32_t b) { uint32_t r; asm("max.bf16x2 %0, %1, %2;" : "=r"(r) : "r"(a), "r"(b)); return r; }
__device__ __forceinline__ float ex2f(float x) { float y; asm("ex2.approx.ftz.f32 %0, %1;" : "=f"(y) : "f"(x)); return y; }
__device__ __forceinline__ float rcpf(float x) { float y; asm("rcp.approx.ftz.f32 %0, %1;" : "=f"(y) : "f"(x)); return y; }
constexpr float GELU_C1 = 0.7978845608028654f, GELU_C3 = 0.035677408136300125f;
__device__ __forceinline__ float gelu_k(float g, float c1, float c3, float k) {
  float t;
  asm("tanh.approx.f32 %0, %1;" : "=f"(t) : "f"(g * fmaf(g * g, c3, c1)));
  g *= k;
  return fmaf(g, t, g);
}
__device__ __forceinline__ float silu_half(float z) { float t; asm("tanh.approx.f32 %0, %1;" : "=f"(t) : "f"(z)); return fmaf(z, t, z); }

__device__ __forceinline__ void wg_fence() { asm volatile("wgmma.fence.sync.aligned;" ::: "memory"); }
__device__ __forceinline__ void wg_commit() { asm volatile("wgmma.commit_group.sync.aligned;" ::: "memory"); }
template <int N> __device__ __forceinline__ void wg_wait() { asm volatile("wgmma.wait_group.sync.aligned %0;" ::"n"(N) : "memory"); }
#define A8(o) "+f"(d[(o)]), "+f"(d[(o) + 1]), "+f"(d[(o) + 2]), "+f"(d[(o) + 3]), "+f"(d[(o) + 4]), "+f"(d[(o) + 5]), "+f"(d[(o) + 6]), "+f"(d[(o) + 7])
#define A64(o) A8(o), A8((o) + 8), A8((o) + 16), A8((o) + 24), A8((o) + 32), A8((o) + 40), A8((o) + 48), A8((o) + 56)
#define REGS0_63 "%0,%1,%2,%3,%4,%5,%6,%7,%8,%9,%10,%11,%12,%13,%14,%15,%16,%17,%18,%19,%20,%21,%22,%23,%24,%25,%26,%27,%28,%29,%30,%31," \
                 "%32,%33,%34,%35,%36,%37,%38,%39,%40,%41,%42,%43,%44,%45,%46,%47,%48,%49,%50,%51,%52,%53,%54,%55,%56,%57,%58,%59,%60,%61,%62,%63"
#define REGS64_127 "%64,%65,%66,%67,%68,%69,%70,%71,%72,%73,%74,%75,%76,%77,%78,%79,%80,%81,%82,%83,%84,%85,%86,%87,%88,%89,%90,%91,%92,%93,%94,%95," \
                   "%96,%97,%98,%99,%100,%101,%102,%103,%104,%105,%106,%107,%108,%109,%110,%111,%112,%113,%114,%115,%116,%117,%118,%119,%120,%121,%122,%123,%124,%125,%126,%127"
__device__ __forceinline__ void desc_add(uint64_t& x, int v) { asm volatile("{\n.reg .b32 lo, hi;\nmov.b64 {lo, hi}, %0;\nadd.s32 lo, lo, %1;\nmov.b64 %0, {lo, hi};\n}" : "+l"(x) : "r"(v)); }
template <int ACCUM> __device__ __forceinline__ void wgmma256(float (&d)[128], uint64_t& a, uint64_t& b, int da, int db) {
  asm volatile("{\n.reg .pred p;\nsetp.ne.b32 p, %130, 0;\n"
               "wgmma.mma_async.sync.aligned.m64n256k16.f32.bf16.bf16 {" REGS0_63 "," REGS64_127 "}, %128, %129, p, 1, 1, 0, 1;\n}"
               : A64(0), A64(64) : "l"(a), "l"(b), "n"(ACCUM));
  desc_add(a, da); desc_add(b, db);
}
__device__ __forceinline__ void wgmma256_rs(float (&d)[128], uint32_t a0, uint32_t a1, uint32_t z0, uint32_t z1, uint32_t b_lo) {
  asm volatile("{\n.reg .b64 db;\nmov.b64 db, {%132, 0x00000008};\n"
               "wgmma.mma_async.sync.aligned.m64n256k16.f32.bf16.bf16 {" REGS0_63 "," REGS64_127 "}, {%128,%129,%130,%131}, db, 1, 1, 1, 0;\n}"
               : A64(0), A64(64) : "r"(a0), "r"(a1), "r"(z0), "r"(z1), "r"(b_lo));
}
template <int ACCUM> __device__ __forceinline__ void wgmma128(float (&d)[64], uint64_t& a, uint64_t& b, int da, int db) {
  asm volatile("{\n.reg .pred p;\nsetp.ne.b32 p, %66, 0;\n"
               "wgmma.mma_async.sync.aligned.m64n128k16.f32.bf16.bf16 {" REGS0_63 "}, %64, %65, p, 1, 1, 0, 1;\n}"
               : A64(0) : "l"(a), "l"(b), "n"(ACCUM));
  desc_add(a, da); desc_add(b, db);
}
template <int ACCUM> __device__ __forceinline__ void hmma(float (&c)[4], uint32_t a0, uint32_t a1, uint32_t a2, uint32_t a3, uint32_t b0, uint32_t b1) {
  if (ACCUM)
    asm volatile("mma.sync.aligned.m16n8k16.row.col.f32.bf16.bf16.f32 {%0,%1,%2,%3}, {%4,%5,%6,%7}, {%8,%9}, {%0,%1,%2,%3};"
                 : "+f"(c[0]), "+f"(c[1]), "+f"(c[2]), "+f"(c[3]) : "r"(a0), "r"(a1), "r"(a2), "r"(a3), "r"(b0), "r"(b1));
  else
    asm volatile("mma.sync.aligned.m16n8k16.row.col.f32.bf16.bf16.f32 {%0,%1,%2,%3}, {%4,%5,%6,%7}, {%8,%9}, {%10,%10,%10,%10};"
                 : "=f"(c[0]), "=f"(c[1]), "=f"(c[2]), "=f"(c[3]) : "r"(a0), "r"(a1), "r"(a2), "r"(a3), "r"(b0), "r"(b1), "f"(0.f));
}
__device__ __forceinline__ uint32_t movm(uint32_t a) { uint32_t d; asm volatile("movmatrix.sync.aligned.m8n8.trans.b16 %0, %1;" : "=r"(d) : "r"(a)); return d; }
template <int N> __device__ __forceinline__ void pin(uint32_t* r) {
#pragma unroll
  for (int i = 0; i < N; i++) asm volatile("" : "+r"(r[i]));
}
template <int N> __device__ __forceinline__ void pin(float* r) {
#pragma unroll
  for (int i = 0; i < N; i++) asm volatile("" : "+f"(r[i]));
}
__device__ __forceinline__ void sched_fence(uint32_t zero) {
  asm volatile("{\n.reg .pred p;\nsetp.eq.u32 p, %0, 0;\nLAB_F:\n@p bra.uni LAB_D;\nnanosleep.u32 0;\nbra.uni LAB_F;\nLAB_D:\n}" ::"r"(zero) : "memory");
}
__device__ __forceinline__ uint4 ldsm(uint32_t a) { uint4 v; asm volatile("ldmatrix.sync.aligned.m8n8.x4.shared.b16 {%0,%1,%2,%3}, [%4];" : "=r"(v.x), "=r"(v.y), "=r"(v.z), "=r"(v.w) : "r"(a) : "memory"); return v; }
__device__ __forceinline__ uint4 ldsm_t(uint32_t a) { uint4 v; asm volatile("ldmatrix.sync.aligned.m8n8.x4.trans.shared.b16 {%0,%1,%2,%3}, [%4];" : "=r"(v.x), "=r"(v.y), "=r"(v.z), "=r"(v.w) : "r"(a) : "memory"); return v; }

constexpr int BAR_LAG = 1, BAR_MMA = 2, BAR_EV = 3;

struct Cons {
  uint32_t sb;
  mutable uint64_t a, b;
  int k1, k2, k4, k4w, b1;
  uint32_t rel;
  bool do_rel;
  int wg;
  uint32_t zero;
};
#define REL_TS(n) TS(64 + (n))
constexpr uint32_t DB_LO = (SM_BASE >> 4) | ((8192 >> 4) << 16);

template <int ST, int ACCUM, bool WAIT = true> __device__ __forceinline__ void p1_issue(float (&acc)[128], const Cons& c, uint32_t parity) {
  if (WAIT) mbar_spin(c.sb + B_F1 + 8 * ST, parity, c.zero);
  wg_fence();
  wgmma256<ACCUM>(acc, c.a, c.b, c.k1, c.b1);
  wgmma256<1>(acc, c.a, c.b, c.k2, c.b1);
  wgmma256<1>(acc, c.a, c.b, c.k1, c.b1);
  wgmma256<1>(acc, c.a, c.b, ST == 3 ? c.k4w : c.k4, ST == 3 ? -6144 - 384 : 2048 - 384);
  wg_commit();
}
__device__ __forceinline__ void release(const Cons& c, uint32_t bar) { if (c.do_rel) mbar_arrive_cl(c.rel + bar); }
template <int KB, bool WAIT = true, int LAG = 2> __device__ __forceinline__ void p1_step(float (&acc)[128], const Cons& c) {
  if (KB == 16 - LAG) { if (c.wg == 1) { wg_wait<0>(); release(c, B_E1 + 8 * ((KB - 1) & 3)); bar_sync(BAR_LAG, 256); } }
  p1_issue<KB & 3, KB != 0, WAIT>(acc, c, (KB >> 2) & 1);
  if (KB == 15) { if (c.wg == 0) bar_arrive(BAR_LAG, 256); }
  if (KB > 0) { wg_wait<1>(); if (KB != 16 - LAG || c.wg == 0) release(c, B_E1 + 8 * ((KB - 1) & 3)); }
  if (KB == 15) { wg_wait<0>(); release(c, B_E1 + 8 * 3); }
}
template <int A, int B> __device__ __forceinline__ void p1_range(float (&acc)[128], const Cons& c) {
  if constexpr (A < B) { p1_step<A>(acc, c); p1_range<A + 1, B>(acc, c); }
}
template <int T> __device__ __forceinline__ void p2_step(float (&acc)[64], const Cons& c) {
  if (T == 16 - LAG2) { if (c.wg == 1) bar_sync(BAR_LAG, 256); }
  mbar_spin(c.sb + B_F2 + 8 * (T % 5), (T / 5) & 1, c.zero);
  wg_fence();
  wgmma128<T != 0>(acc, c.a, c.b, c.k1, c.b1);
  wgmma128<1>(acc, c.a, c.b, c.k2, c.b1);
  wgmma128<1>(acc, c.a, c.b, c.k1, c.b1);
  wgmma128<1>(acc, c.a, c.b, ((int)p2_a((T + 1) % 5) - (int)p2_a(T % 5)) / 16 - 514, ((int)p2_b((T + 1) % 5) - (int)p2_b(T % 5)) / 16 - 384);
  wg_commit();
  if (T == 15) { if (c.wg == 0) bar_arrive(BAR_LAG, 256); }
  if (T <= 11) { wg_wait<1>(); release(c, T ? B_E2 + 8 * ((T + 5 - 1) % 5) : B_E1 + 8); }
}

template <int P> __device__ __forceinline__ void geglu_piece(const uint32_t (&pk)[64], uint8_t* dst, const float (&rs)[2]) {
  constexpr int cg = P >> 1, r = P & 1;
  const float r2 = rs[r] * rs[r], c1 = GELU_C1 * rs[r], c3 = GELU_C3 * r2 * rs[r], k = 0.25f * r2;
  uint32_t v[4];
#pragma unroll
  for (int i = 0; i < 4; i++) {
    const uint32_t g = pk[2 * (4 * cg + i) + r];
    v[i] = mul2(pack2(gelu_k(lo_f(g), c1, c3, k), gelu_k(hi_f(g), c1, c3, k)), pk[32 + 2 * (4 * cg + i) + r]);
  }
  stg128(dst + cg * 8192 + r * 512, v[0], v[1], v[2], v[3]);
}
template <int KB> __device__ __forceinline__ void geglu_tile(float (&acc)[128], const uint32_t (&pk)[64], const Cons& c, uint8_t* dst, int ev, const float (&rs)[2]) {
  if constexpr (KB < 14) {
    p1_step<KB>(acc, c);
    if (KB >= 1 && KB <= 8) geglu_piece<(KB - 1) & 7>(pk, dst, rs);
    if (KB == 8) bar_arrive(ev, 288);
    geglu_tile<KB + 1>(acc, pk, c, dst, ev, rs);
  }
}

__device__ __forceinline__ void attn_tile(float (&acc)[128], const uint32_t (&pk)[64], const Cons& c, int round, int warp, int m, Scratch* gs, uint8_t* hdst, uint8_t* odst) {
  const int lane = threadIdx.x & 31, w = warp & 3, rho = lane >> 2, q = lane & 3;
  const uint32_t at = c.sb + OFF_X + c.wg * AT_WG, swz = (lane ^ (lane >> 3)) << 4;
  uint32_t gg[16];
  p1_step<0>(acc, c);
  p1_step<1>(acc, c);
#pragma unroll
  for (int i = 0; i < 4; i++) {
    const int h = i & 1, r = i >> 1;
    sts128(at + AT_V + (2 * w + r) * 1024 + h * 512 + swz, make_uint4(pk[32 + 8 * h + r], pk[34 + 8 * h + r], pk[36 + 8 * h + r], pk[38 + 8 * h + r]));
  }
  if (w < 3) {
#pragma unroll
    for (int i = 0; i < 8; i++) asm volatile("st.shared.b32 [%0], %1;" ::"r"(at + AT_K + w * 1024 + i * 128 + lane * 4), "r"(pk[17 + 2 * i]) : "memory");
  } else {
    uint8_t* g = (uint8_t*)gs->halo + ((round * 128 + blockIdx.x) * 2 + c.wg) * 2048;
#pragma unroll
    for (int i = 0; i < 8; i++) asm volatile("st.global.b32 [%0], %1;" ::"l"(g + i * 128 + lane * 4), "r"(pk[17 + 2 * i]) : "memory");
#pragma unroll
    for (int h = 0; h < 2; h++) stg128(g + 1024 + h * 512 + swz, pk[33 + 8 * h], pk[35 + 8 * h], pk[37 + 8 * h], pk[39 + 8 * h]);
    bar_arrive(BAR_EV + 2 + round, 96);
  }
  __syncwarp();
  if (lane == 0) mbar_arrive(c.sb + B_HALO + 8 * round);
  if (round) {
#pragma unroll
    for (int p = 0; p < 4; p++) asm volatile("ld.global.cg.v4.b32 {%0,%1,%2,%3}, [%4];" : "=r"(gg[4 * p]), "=r"(gg[4 * p + 1]), "=r"(gg[4 * p + 2]), "=r"(gg[4 * p + 3]) : "l"(hdst + (p >> 1) * 8192 + (p & 1) * 512) : "memory");
  }
  auto gu_piece = [&](int p) {
    uint32_t v[4];
#pragma unroll
    for (int i = 0; i < 4; i++) {
      const uint32_t g = pk[48 + 8 * (p >> 1) + 2 * i + (p & 1)];
      v[i] = mul2(round ? gg[4 * p + i] : 0x3e803e80u, round ? g : pack2(gelu_k(lo_f(g), GELU_C1, GELU_C3, 1.0f), gelu_k(hi_f(g), GELU_C1, GELU_C3, 1.0f)));
    }
    stg128(hdst + (p >> 1) * 8192 + (p & 1) * 512, v[0], v[1], v[2], v[3]);
  };
  p1_step<2>(acc, c);
  p1_step<3>(acc, c); gu_piece(0);
  p1_step<4>(acc, c); gu_piece(1);
  p1_step<5>(acc, c); gu_piece(2);
  p1_step<6>(acc, c); gu_piece(3);
  p1_step<7>(acc, c);
  p1_step<8>(acc, c);
  const bool first = m == 0 && w == 0;
  uint32_t kl[16];
  mbar_spin(c.sb + B_HALO + 8 * round, 0, c.zero);
  {
    const uint32_t ka = at + lane * 4 + (w ? AT_K + (w - 1) * 1024 : (first ? AT_K : AT_REM + round * 2048));
#pragma unroll
    for (int i = 0; i < 8; i++) {
      asm volatile("ld.shared.b32 %0, [%1];" : "=r"(kl[2 * i]) : "r"(ka + i * 128) : "memory");
      kl[2 * i + 1] = pk[16 + 2 * i] | c.zero;
    }
  }
  float st[4][4];
  pin<16>(kl);
  bar_sync(BAR_MMA, 256);
  mbar_spin(c.sb + B_F1 + 8 * 1, 0, c.zero);
#pragma unroll
  for (int ks = 0; ks < 2; ks++) {
#pragma unroll
    for (int h = 0; h < 2; h++) {
      const int o = 8 * h + 4 * ks;
      if (ks == 0) { hmma<0>(st[2 * h], kl[o], kl[o + 1], kl[o + 2], kl[o + 3], pk[o], pk[o + 2]); hmma<0>(st[2 * h + 1], pk[16 + o], pk[17 + o], pk[18 + o], pk[19 + o], pk[o + 1], pk[o + 3]); }
      else { hmma<1>(st[2 * h], kl[o], kl[o + 1], kl[o + 2], kl[o + 3], pk[o], pk[o + 2]); hmma<1>(st[2 * h + 1], pk[16 + o], pk[17 + o], pk[18 + o], pk[19 + o], pk[o + 1], pk[o + 3]); }
    }
  }
  sched_fence(c.zero);
  bar_sync(BAR_MMA, 256);
  p1_step<9, false>(acc, c);
  sched_fence(c.zero);
  pin<16>(&st[0][0]);
  const bool le0 = 2 * q <= rho, le1 = 2 * q + 1 <= rho;
  uint32_t la[2], lb[2], mx[2];
#pragma unroll
  for (int h = 0; h < 2; h++) {
    uint32_t l[2];
#pragma unroll
    for (int r = 0; r < 2; r++) {
      const float (&t)[4] = st[2 * h + r];
      l[r] = movm(pack2(rho <= 2 * q ? t[2] : t[0], rho <= 2 * q + 1 ? t[3] : t[1]));
      l[r] = fma2(l[r], 0x3e353e35u, mul2(l[r], 0x379e379eu));
    }
    la[h] = __byte_perm(l[0], l[1], 0x5410); lb[h] = __byte_perm(l[0], l[1], 0x7632);
    if (first && !le0) la[h] = (la[h] & 0xffff0000u) | 0xce6eu;
    if (first && !le1) lb[h] = (lb[h] & 0xffff0000u) | 0xce6eu;
    mx[h] = max2(la[h], lb[h]);
  }
#pragma unroll
  for (int o = 1; o <= 2; o++) { mx[0] = max2(mx[0], __shfl_xor_sync(~0u, mx[0], o)); mx[1] = max2(mx[1], __shfl_xor_sync(~0u, mx[1], o)); }
  const float L2E = 1.4426950408889634f;
  float pr[2][4], z[4];
#pragma unroll
  for (int h = 0; h < 2; h++) {
    pr[h][0] = ex2f((lo_f(la[h]) - lo_f(mx[h])) * L2E); pr[h][1] = ex2f((lo_f(lb[h]) - lo_f(mx[h])) * L2E);
    pr[h][2] = ex2f((hi_f(la[h]) - hi_f(mx[h])) * L2E); pr[h][3] = ex2f((hi_f(lb[h]) - hi_f(mx[h])) * L2E);
    z[2 * h] = pr[h][0] + pr[h][1]; z[2 * h + 1] = pr[h][2] + pr[h][3];
  }
  p1_step<10>(acc, c);
#pragma unroll
  for (int o = 1; o <= 2; o++) {
#pragma unroll
    for (int i = 0; i < 4; i++) z[i] += __shfl_xor_sync(~0u, z[i], o);
  }
  const uint32_t LE = (le0 ? 0xffffu : 0u) | (le1 ? 0xffff0000u : 0u);
  uint32_t P[4][2];
  uint4 vt[4][2];
  {
    const uint32_t row = (lane & 7) * 64 + ((((lane >> 3) & 1) ^ ((lane & 7) >> 1)) << 4);
    const uint32_t v1 = at + AT_V + (2 * w + (lane >> 4)) * 1024 + row;
    const uint32_t v0 = (w || lane >= 16) ? v1 - 1024 : (first ? v1 : at + AT_REM + round * 2048 + 1024 + row);
#pragma unroll
    for (int i = 0; i < 4; i++) {
      const float rz = rcpf(z[i]);
      const uint32_t p = pack2(pr[i >> 1][2 * (i & 1)] * rz, pr[i >> 1][2 * (i & 1) + 1] * rz);
      P[i][0] = p & ~LE; P[i][1] = p & LE;
      const uint32_t a = ((i & 1) ? v1 : v0) + (i >> 1) * 512;
      vt[i][0] = ldsm_t(a); vt[i][1] = ldsm_t(a ^ 32);
    }
  }
  float ot[4][2][4];
  pin<8>(&P[0][0]);
  bar_sync(BAR_MMA, 256);
  mbar_spin(c.sb + B_F1 + 8 * 3, 0, c.zero);
#pragma unroll
  for (int i = 0; i < 8; i++) { const uint4& v = vt[i >> 1][i & 1]; hmma<0>(ot[i >> 1][i & 1], v.x, v.y, v.z, v.w, P[i >> 1][0], P[i >> 1][1]); }
  sched_fence(c.zero);
  bar_sync(BAR_MMA, 256);
  p1_step<11, false>(acc, c);
  sched_fence(c.zero);
  pin<32>(&ot[0][0][0]);
  auto o_piece = [&](int i) {
    stg128(odst + (i >> 1) * 8192 + (i & 1) * 512, movm(pack2(ot[i][0][0], ot[i][0][1])), movm(pack2(ot[i][0][2], ot[i][0][3])), movm(pack2(ot[i][1][0], ot[i][1][1])), movm(pack2(ot[i][1][2], ot[i][1][3])));
  };
  o_piece(0); o_piece(1);
  p1_step<12>(acc, c);
  o_piece(2); o_piece(3);
  if (round) bar_arrive(BAR_EV + 4, 288);
  p1_step<13>(acc, c);
}

__device__ __forceinline__ void ln_moments(const uint32_t* raw, float& c0, float& s, float& v) {
  c0 = lo_f(__shfl_sync(~0u, raw[0], 0));
  float ss[4] = {0.f, 0.f, 0.f, 0.f}, vv[4] = {0.f, 0.f, 0.f, 0.f};
#pragma unroll
  for (int i = 0; i < 16; i++) {
    const float a = lo_f(raw[i]) - c0, b = hi_f(raw[i]) - c0;
    ss[(2 * i) & 3] += a; ss[(2 * i + 1) & 3] += b;
    vv[(2 * i) & 3] = fmaf(a, a, vv[(2 * i) & 3]); vv[(2 * i + 1) & 3] = fmaf(b, b, vv[(2 * i + 1) & 3]);
  }
  s = (ss[0] + ss[1]) + (ss[2] + ss[3]); v = (vv[0] + vv[1]) + (vv[2] + vv[3]);
}
__device__ __forceinline__ void ln_reduce(float& s, float& v) {
#pragma unroll
  for (int o = 16; o; o >>= 1) { s += __shfl_xor_sync(~0u, s, o); v += __shfl_xor_sync(~0u, v, o); }
}
__device__ __forceinline__ uint32_t ln_finish(float c0, float s, float v) {
  s *= 1.0f / DM;
  float sd;
  asm("sqrt.approx.ftz.f32 %0, %1;" : "=f"(sd) : "f"(bf16r(bf16r(fmaxf(fmaf(v, 1.0f / DM, -s * s), 0.f)) + 1e-5f)));
  return pack2(c0 + s, sd);
}
__device__ __forceinline__ void ln_store(const uint32_t* raw, uint32_t st, uint4* dst) {
  const uint32_t m2 = __byte_perm(st, st, 0x1010);
  const float rinv = rcpf(hi_f(st));
  const uint32_t rh = pack2(rinv, rinv), rl = pack2(rinv - hi_f(rh), rinv - hi_f(rh));
#pragma unroll
  for (int c = 0; c < 4; c++) {
    uint32_t v[4];
#pragma unroll
    for (int i = 0; i < 4; i++) { const uint32_t t = sub2(raw[4 * c + i], m2); v[i] = fma2(t, rh, mul2(t, rl)); }
    stg128(dst + 32 * c, v[0], v[1], v[2], v[3]);
  }
}
__device__ __forceinline__ void col_sums(uint32_t tile, ulonglong2* part, uint32_t tag) {
  const int lane = threadIdx.x & 31;
  float cs[8] = {0, 0, 0, 0, 0, 0, 0, 0};
  uint32_t base = tile + ((lane >> 3) & 1) * 8192 + (lane >> 4) * 4096 + ((lane & 7) << 4);
#pragma unroll 1
  for (int k0 = 0; k0 < 8; k0++, base = (base ^ ((k0 ^ (k0 - 1)) << 4)) + 128) {
    uint4 v[4];
#pragma unroll
    for (int k = 0; k < 4; k++) v[k] = lds128(base + k * 1024);
#pragma unroll
    for (int k = 0; k < 4; k++) {
      cs[0] += lo_f(v[k].x); cs[1] += hi_f(v[k].x); cs[2] += lo_f(v[k].y); cs[3] += hi_f(v[k].y);
      cs[4] += lo_f(v[k].z); cs[5] += hi_f(v[k].z); cs[6] += lo_f(v[k].w); cs[7] += hi_f(v[k].w);
    }
  }
  const bool up = lane >= 16;
#pragma unroll
  for (int i = 0; i < 2; i++) {
    const float a = (up ? cs[4 + 2 * i] : cs[2 * i]) + __shfl_xor_sync(~0u, up ? cs[2 * i] : cs[4 + 2 * i], 16);
    const float b = (up ? cs[5 + 2 * i] : cs[1 + 2 * i]) + __shfl_xor_sync(~0u, up ? cs[1 + 2 * i] : cs[5 + 2 * i], 16);
    asm volatile("{\n.reg .b64 a, b;\nmov.b64 a, {%1, %3};\nmov.b64 b, {%2, %3};\nst.relaxed.gpu.global.v2.b64 [%0], {a, b};\n}"
                 ::"l"(part + 32 * (i + (up ? 2 : 0)) + (lane & 15)), "r"(__float_as_uint(a)), "r"(__float_as_uint(b)), "r"(tag) : "memory");
  }
  asm volatile("fence.proxy.async.shared::cta;" ::: "memory");
}

__global__ void __cluster_dims__(2, 1, 1) __launch_bounds__(384, 1)
fused_kernel(const uint4* __restrict__ x, const uint4* __restrict__ wgate, const uint4* __restrict__ wup, Scratch* gs, const __grid_constant__ Maps mp) {
  extern __shared__ __align__(1024) uint8_t smem_raw[];
  const uint32_t sb = (uint32_t)__cvta_generic_to_shared(smem_raw);
  const unsigned t_start = 0;
  if (threadIdx.x < 256 && blockIdx.x < NMAIN) {
    const uint32_t r = threadIdx.x >> 3, ch = threadIdx.x & 7;
    const uint32_t d = sb + r * 128 + ((ch ^ (r & 7)) << 4);
    const uint8_t* xa = (const uint8_t*)x + ((blockIdx.x & 15) * 262144 + r * 4096 + ch * 16);
    const uint32_t wo = r * (DFF * 2) + (blockIdx.x >> 4) * 256 + ch * 16;
    const uint8_t *wa = (const uint8_t*)wgate + wo, *wb = (const uint8_t*)wup + wo;
#pragma unroll
    for (int i = 0; i < 12; i++) {
      const int h = i >= 8;
      const uint8_t* src = (i >> 2) == 1 ? xa + (i & 1) * 131072 + ((i >> 1) & 1) * 2048 : ((i & 2) ? wb : wa) + h * 32 * (DFF * 2) + (i & 1) * 128;
      asm volatile("cp.async.cg.shared.global [%0], [%1], 16;" ::"r"(d + ((i >> 2) == 1 ? OFF_A + (i & 3) * 4096 : (i & 3) * 8192 + h * 4096)), "l"(src) : "memory");
    }
    if (threadIdx.x == 0) TS(23);
  }
  const int warp = __shfl_sync(~0u, threadIdx.x >> 5, 0), lane = threadIdx.x & 31;
  const int m = blockIdx.x & 15, j = blockIdx.x >> 4, rank = blockIdx.x & 1;
  const int m2 = blockIdx.x >> 3, j2 = blockIdx.x & 7;
  const bool helper = blockIdx.x >= NMAIN;
  if (warp >= 8) {
    asm volatile("setmaxnreg.dec.sync.aligned.u32 40;");
    if (warp == 8) {
      if (elect_one()) {
        asm volatile("prefetch.tensormap [%0];\nprefetch.tensormap [%1];\nprefetch.tensormap [%2];" ::"l"(&mp.x), "l"(&mp.wg), "l"(&mp.wu) : "memory");
        for (int s = 0; s < 4; s++) mbar_init(sb + B_F1 + 8 * s, 1);
        if (!helper) mbar_arrive(sb + B_F1);
        asm volatile("fence.mbarrier_init.release.cluster;" ::: "memory");
      }
      __syncwarp();
    } else if (warp == 9) {
      if (elect_one()) {
        if ((sb & 0xffffff) != SM_BASE) asm volatile("trap;");
        for (int s = 0; s < 4; s++) mbar_init(sb + B_E1 + 8 * s, 4);
        for (int s = 0; s < 6; s++) { mbar_init(sb + B_F2 + 8 * s, 1); mbar_init(sb + B_E2 + 8 * s, 4); }
        for (int s = 0; s < 6; s++) mbar_init(sb + B_DEP + 8 * s, 1);
        mbar_init(sb + B_AUX, 8); mbar_init(sb + B_EP, 1); mbar_init(sb + B_DONE, 4); mbar_init(sb + B_XT, 1); mbar_init(sb + B_CS, 1);
        for (int s = 0; s < 8; s++) { mbar_init(sb + B_EX + 8 * s, 1); mbar_expect_tx(sb + B_EX + 8 * s, 4096); }
        mbar_init(sb + B_HALO, 9); mbar_init(sb + B_HALO + 8, 9);
        asm volatile("fence.mbarrier_init.release.cluster;" ::: "memory");
      }
      __syncwarp();
    }
    asm volatile("barrier.cluster.arrive.relaxed.aligned;" ::: "memory");
    if (warp == 8 && !helper) {
      if (elect_one()) {
        TS(0); TG(51);
#pragma unroll 1
        for (int kb = 1; kb < 4; kb++) {
          const uint32_t sa = sb + OFF_A + kb * 16384, sw = sb + kb * 32768, fb = sb + B_F1 + 8 * kb;
          mbar_expect_tx(fb, P1_BYTES);
          tma3d(sa, &mp.x, fb, kb * 64, m * 64, 0, EVICT_NORMAL);
          tma2d(sw, &mp.wg, fb, j * 128, kb * 64, EVICT_NORMAL); tma2d(sw + 16384, &mp.wu, fb, j * 128, kb * 64, EVICT_NORMAL);
          tma2d(sw + 8192, &mp.wg, fb, j * 128 + 64, kb * 64, EVICT_NORMAL); tma2d(sw + 24576, &mp.wu, fb, j * 128 + 64, kb * 64, EVICT_NORMAL);
        }
        TS(7);
      }
      __syncwarp();
    }
    asm volatile("barrier.cluster.wait.aligned;" ::: "memory");
    if (helper) {
      if (warp == 8) {
        unsigned e = 0;
        if (elect_one()) {
#pragma unroll 1
          for (int i = 0; i < 16; i++) {
            const uint32_t fb = sb + B_F1 + 8 * (i >> 2);
            if (!(i & 3)) mbar_expect_tx(fb, P1_BYTES);
            tma5d(sb + i * 8192, &mp.wd, fb, (blockIdx.x - NMAIN) * 256 + (i & 3) * 64, (i >> 2) * 2, HINT_W);
          }
        }
        if (lane == 0) { unsigned* ep = &gs->epoch[blockIdx.x * 2]; e = *ep + 1; *ep = e; }
        e = __shfl_sync(~0u, e, 0);
        if (lane < 16) flag_wait(&gs->flags[(FL_H + lane * 4) * 32], e * 8u);
        __syncwarp();
        if (elect_one()) {
          fence_async();
          TS(0);
#pragma unroll 1
          for (int i = 0; i < 64; i++) {
            const uint32_t fb = sb + B_F1 + 8 * (i & 3);
            if (i >= 4) { mbar_wait(sb + B_E1 + 8 * (i & 3), ~(i >> 2) & 1); mbar_expect_tx(fb, 16384); }
            bulk_load(sb + OFF_A + (i & 3) * 16384, gs->h + ((i >> 2) * 56 + (i & 3)) * 1024, 16384, fb, EVICT_NORMAL);
          }
        }
      } else if (warp == 9) {
#pragma unroll 1
        for (int t = 0; t < 16; t++) {
          bar_sync(BAR_EV + (t & 1), 288);
          if (lane == 0) { flag_add(&gs->flags[(FL_P + t) * 32]); TS(64 + t); }
          __syncwarp();
        }
      }
    } else if (warp == 8) {
      if (elect_one()) {
        uint32_t par = 0;

        auto x_load = [&]() {
          mbar_expect_tx(sb + B_XT, 32768);
          tma3d(sb + OFF_X, &mp.x, sb + B_XT, j2 * 128, m2 * 64, 0, HINT_LAST); tma3d(sb + OFF_X + 16384, &mp.x, sb + B_XT, j2 * 128 + 64, m2 * 64, 0, HINT_LAST);
        };
        auto d_prefetch = [&](int i) {
          if (PF_W == 1 && (m2 >> 2) == (i & 3)) tma5d_prefetch(&mp.wd, (j2 >> 1) * 256 + (m2 & 3) * 64, (2 * i + 4 + rank) * 2);
          if (PF_H == 1 && i < 6) asm volatile("cp.async.bulk.prefetch.L2.global [%0], 4096;" ::"l"(gs->h + (m2 * 56 + 2 * i + 4 + rank) * 1024 + (j2 >> 1) * 256) : "memory");
        };
        for (int R = 0; R < 5; R++) {
          const CUtensorMap *mb0, *mb1;
          int n0, n1;
          if (R == 1 || R == 2) {
            mb0 = &mp.wqkv; n0 = 64 * (j + 8 * (R - 1)) + rank * 2048;
            mb1 = rank ? (R == 1 ? &mp.wg : &mp.wu) : &mp.wqkv; n1 = rank ? 1024 + 64 * j : n0 + 1024;
          } else {
            mb0 = mb1 = rank ? &mp.wu : &mp.wg;
            n0 = 128 * j + (R ? 1024 * R - 1536 : 0); n1 = n0 + 64;
          }
#pragma unroll 1
          for (int kb = R ? 0 : 4; kb < 16; kb++) {
            if (R == 0 && kb == 14) { asm volatile("prefetch.tensormap [%0];\nprefetch.tensormap [%1];" ::"l"(&mp.xn), "l"(&mp.wqkv) : "memory"); }
            if (R == 4 && kb == 2) { asm volatile("prefetch.tensormap [%0];\nprefetch.tensormap [%1];\nprefetch.tensormap [%2];" ::"l"(&mp.wd), "l"(&mp.wo), "l"(&mp.out) : "memory"); }
            if (R == 0 && kb == (CS_KB)) {
              const uint32_t cb = sb + B_CS, d = sb + OFF_X;
              mbar_expect_tx(cb, 32768);
              tma2d(d, &mp.wg, cb, n0, m * 64, EVICT_NORMAL); tma2d(d + 8192, &mp.wg, cb, n1, m * 64, EVICT_NORMAL);
              tma2d(d + 16384, &mp.wu, cb, n0, m * 64, EVICT_NORMAL); tma2d(d + 24576, &mp.wu, cb, n1, m * 64, EVICT_NORMAL);
            }
            const int st = kb & 3;
            const uint32_t sa = sb + OFF_A + st * 16384, sw = sb + st * 32768, fb = sb + B_F1 + 8 * st;
            mbar_wait(sb + B_E1 + 8 * st, par);
            if (R * 16 + kb >= 4) REL_TS(R * 16 + kb - 4);
            mbar_expect_tx(fb, P1_BYTES);
            tma2d_mc(sw + rank * 16384, mb0, fb, n0, kb * 64, HINT_W);
            tma2d_mc(sw + 8192 + rank * 16384, mb1, fb, n1, kb * 64, HINT_W);
            if (R == 0) {
              tma3d(sa, &mp.x, fb, kb * 64, m * 64, 0, EVICT_NORMAL);
            } else {
              if (R == 1 && kb == 0) { mbar_wait(sb + B_DEP, 0); TS(1); }
              tma2d(sa, &mp.xn, fb, kb * 64, m * 128, R == 4 ? HINT_LAST : EVICT_NORMAL);
            }
            if (R == 4 && kb == 4 + j2) x_load();
            if (R == 4 && kb >= 16 - PF_D) { if (kb == 16 - PF_D) mbar_wait(sb + B_DEP + 8, 0); d_prefetch(kb + PF_D - 16); }
            if (st == 3) par ^= 1;
          }
        }
#pragma unroll 1
        for (int i = 0; i < 26; i++) {
          const int st = i & 3, kb = 2 * i + 4 + rank;
          const uint32_t sa = sb + OFF_A + st * 16384, sw = sb + st * 32768, fb = sb + B_F1 + 8 * st;
          mbar_wait(sb + B_E1 + 8 * st, par);
          REL_TS(76 + i);
          mbar_expect_tx(fb, P1_BYTES);
          tma5d(sw, &mp.wd, fb, j2 * 128, kb * 2, HINT_W); tma5d(sw + 8192, &mp.wd, fb, j2 * 128 + 64, kb * 2, HINT_W);
          tma5d(sw + 16384, &mp.wd, fb, (j2 ^ 1) * 128, kb * 2, HINT_W); tma5d(sw + 24576, &mp.wd, fb, (j2 ^ 1) * 128 + 64, kb * 2, HINT_W);
          if (i == 0 || i == 6 || i == 10 || i == 18) { mbar_wait(sb + B_DEP + 8 * (1 + ((i + 6) >> 3)), 0); }
          bulk_load(sa, gs->h + (m2 * 56 + kb) * 1024, 16384, fb, HINT_H);
          if (i + PF_D < 26) d_prefetch(i + PF_D);
          if (i >= PF_S && i < PF_S + 8) {
            asm volatile("cp.async.bulk.prefetch.L2.global [%0], 4096;" ::"l"(gs->o + (m2 * 16 + 2 * (i - PF_S)) * 1024 + j2 * 256) : "memory");
            if ((m2 >> 1) == i - PF_S) {
              asm volatile("cp.async.bulk.prefetch.tensor.2d.L2.global [%0, {%1, %2}];" ::"l"(&mp.wo), "r"(j2 * 128), "r"(m2 * 64) : "memory");
              asm volatile("cp.async.bulk.prefetch.tensor.2d.L2.global [%0, {%1, %2}];" ::"l"(&mp.wo), "r"(j2 * 128 + 64), "r"(m2 * 64) : "memory");
            }
          }
          if (st == 3) par ^= 1;
        }
        int st = 0; uint32_t par2 = 1;
#pragma unroll 1
        for (int t = 0; t < 16; t++) {
          const uint32_t sa = sb + p2_a(st), sw = sb + p2_b(st), fb = sb + B_F2 + 8 * st;
          if (t < 5) mbar_wait(sb + B_E1 + 8 * (((2 * t + 1) / 3 + 2) & 3), t < 3); else mbar_wait(sb + B_E2 + 8 * st, par2);
          REL_TS(102 + t);
          mbar_expect_tx(fb, P2_BYTES);
          bulk_load_mc(sa + rank * 8192, gs->o + (m2 * 16 + t) * 1024 + rank * 512, 8192, fb, HINT_H);
          tma2d(sw, &mp.wo, fb, j2 * 128, t * 64, HINT_W); tma2d(sw + 8192, &mp.wo, fb, j2 * 128 + 64, t * 64, HINT_W);
          if (++st == 5) { st = 0; par2 ^= 1; }
        }
      }
    } else if (warp == 9) {
#pragma unroll 1
      for (int e = 0; e < 7; e++) {
        const bool halo = e == 2 || e == 3;
        bar_sync(BAR_EV + e, halo ? 96 : 288);
        if (lane == 0) {
          const int f = e == 0 ? FL_XN + m : (halo ? FL_HALO + (e - 2) * 128 + blockIdx.x : FL_H + m * 4 + (e == 1 ? 0 : e - 3));
          TS(10 + 2 * e); TG(52 + e);
          flag_add(&gs->flags[f * 32]);
          if (e < 6) TS(11 + 2 * e);
        }
        __syncwarp();
      }
      mbar_wait(sb + B_DONE, 0);
    } else {
      unsigned e = 0;
      if (lane == 0) {
        unsigned* ep = &gs->epoch[blockIdx.x * 2 + warp - 10];
        e = *ep + 1; *ep = e;
        if (warp == 10) { asm volatile("st.shared.b32 [%0], %1;" ::"r"(sb + OFF_EPOCH), "r"(e) : "memory"); mbar_arrive(sb + B_EP); }
      }
      e = __shfl_sync(~0u, e, 0);
      mbar_wait(sb + B_CS, 0);
      if (lane == 0 && warp == 11) TS(6);
      col_sums(sb + OFF_X + (warp - 10) * 16384, gs->cspart + (j * 16 + m) * 128 + (warp - 10) * 16, e);
      if (lane == 0 && warp == 11) TS(9);
      if (warp == 10) {
        if (lane == 0) {
#pragma unroll 1
          for (int g = 0; g < 6; g++) {
            flag_wait(&gs->flags[(g == 5 ? FL_P + m2 : (g ? FL_H + m2 * 4 + g - 1 : FL_XN + m)) * 32], e * (g == 5 ? 4u : 8u));
            fence_async();
            mbar_arrive(sb + B_DEP + 8 * g);
            if (g == 0) TS(8);
          }
#pragma unroll 1
          for (int p = 0; p < 8; p++) {
            asm volatile("cp.async.bulk.prefetch.L2.global [%0], 4096;" ::"l"(gs->dpart + blockIdx.x * 2048 + p * 256) : "memory");
            __nanosleep(PF_SLEEP);
          }
        }
      } else
      if (elect_one()) {
#pragma unroll 1
        for (int r = 0; r < 2; r++) {
          const uint32_t hb = sb + B_HALO + 8 * r;
          if (m) {
            flag_wait(&gs->flags[(FL_HALO + r * 128 + blockIdx.x - 1) * 32], e);
            fence_async();
            mbar_expect_tx(hb, 4096);
            for (int g = 0; g < 2; g++) bulk_load(sb + OFF_X + g * AT_WG + AT_REM + r * 2048, gs->halo + ((r * 128 + blockIdx.x - 1) * 2 + g) * 128, 2048, hb, EVICT_FIRST);
          } else {
            mbar_arrive(hb);
          }
          TS(34 + r);
        }
      }
    }
  } else {
    asm volatile("barrier.cluster.arrive.relaxed.aligned;" ::: "memory");
    asm volatile("setmaxnreg.inc.sync.aligned.u32 232;");
    const int wg = warp >> 2, w = warp & 3;
    Cons c;
    c.sb = sb; c.wg = wg; c.zero = warp >> 8;
    c.a = 0x4000004000010000ull + ((SM_BASE + OFF_A + wg * 8192) >> 4); c.k1 = 2 + c.zero; c.k2 = 2; c.k4 = 1024 - 6; c.k4w = -3072 - 6; c.b1 = 128 + c.zero;
    c.b = 0x4000004000000000ull + DB_LO + c.zero;
    c.rel = mapa(sb, threadIdx.x & 1);
    c.do_rel = (threadIdx.x & 127) < 2;
    constexpr bool t0 = false;
    float acc[128];
    uint32_t pk[64];
    float rs[2];
    const int rho = lane >> 2, q = lane & 3;

    if (helper) {
      asm volatile("barrier.cluster.wait.aligned;" ::: "memory");
      c.a = 0x8000002000010000ull + ((SM_BASE + OFF_A + wg * 4096) >> 4); c.k2 = 510; c.k4 = 1024 - 514; c.k4w = -3072 - 514;
      c.rel = sb;
      uint4* dst = gs->dpart + (blockIdx.x - NMAIN) * 4096 + threadIdx.x;
      auto put = [&](int p) {
#pragma unroll
        for (int i = 4 * p; i < 4 * p + 4; i++) stg128(dst + i * 256, pk[4 * i], pk[4 * i + 1], pk[4 * i + 2], pk[4 * i + 3]);
      };
#pragma unroll 1
      for (int t = 0; t < 16; t++) {
        p1_issue<0, 0>(acc, c, t & 1);
        if (t) put(0);
        p1_issue<1, 1>(acc, c, t & 1); wg_wait<1>(); release(c, B_E1);
        if (t) put(1);
        if (wg == 1) { wg_wait<0>(); release(c, B_E1 + 8); bar_sync(BAR_LAG, 256); }
        p1_issue<2, 1>(acc, c, t & 1); wg_wait<1>(); if (wg == 0) release(c, B_E1 + 8);
        if (t) put(2);
        p1_issue<3, 1>(acc, c, t & 1);
        if (wg == 0) bar_arrive(BAR_LAG, 256);
        if (t) { put(3); bar_arrive(BAR_EV + (~t & 1), 288); dst += 8 * 2048; }
        wg_wait<1>(); release(c, B_E1 + 16);
        wg_wait<0>(); release(c, B_E1 + 24);
#pragma unroll
        for (int i = 0; i < 64; i++) pk[i] = pack2(acc[2 * i], acc[2 * i + 1]);
      }
      put(0); put(1); put(2); put(3);
      bar_arrive(BAR_EV + 1, 288);
      return;
    }
    {
      const int prow = 16 * j + 2 * warp;
      const uint4* xr = x + (size_t)(128 * m + 2 * (prow & 63) + (prow >> 6)) * 128 + lane;
      uint4* xo = gs->xn + (size_t)(128 * m + prow) * 128 + lane;
      float c0[2], mo[4];
      uint32_t st[2];
      uint32_t e;
      asm volatile("" : "+l"(xr), "+l"(xo));
      asm volatile("cp.async.wait_all;\nfence.proxy.async.shared::cta;" ::: "memory");
      bar_sync(BAR_MMA, 256);
      if (threadIdx.x == 0) TS(39);
      p1_step<0, false>(acc, c);
      asm volatile("barrier.cluster.wait.aligned;" ::: "memory");
      p1_range<1, LN_LD + 1>(acc, c);
      if (t0) TS(24 + wg * 16);
#pragma unroll
      for (int i = 0; i < 8; i++) {
        asm volatile("ld.global.nc.v4.b32 {%0,%1,%2,%3}, [%4];" : "=r"(pk[4 * i]), "=r"(pk[4 * i + 1]), "=r"(pk[4 * i + 2]), "=r"(pk[4 * i + 3]) : "l"(xr + (i >> 2) * 256 + (i & 3) * 32));
      }
      p1_range<LN_LD + 1, LN_KB + 1>(acc, c);
      sched_fence(c.zero);

      pin<16>(pk); ln_moments(pk, c0[0], mo[0], mo[1]); pin<2>(mo);
      p1_step<LN_KB + 1>(acc, c);
      sched_fence(c.zero);
      pin<16>(pk + 16); ln_moments(pk + 16, c0[1], mo[2], mo[3]); ln_reduce(mo[0], mo[1]); pin<4>(mo);
      p1_step<LN_KB + 2>(acc, c);
      mbar_spin(sb + B_EP, 0, c.zero);
      asm volatile("ld.shared.b32 %0, [%1];" : "=r"(e) : "r"(sb + OFF_EPOCH) : "memory");
      pin<2>(mo); st[0] = ln_finish(c0[0], mo[0], mo[1]); ln_reduce(mo[2], mo[3]); pin<1>(st); pin<2>(mo + 2);
      p1_step<LN_KB + 3>(acc, c);
      sched_fence(c.zero);
      pin<1>(st); pin<2>(mo + 2);
      st[1] = ln_finish(c0[1], mo[2], mo[3]);
      ln_store(pk, st[0], xo);
      if (lane == 0)
        asm volatile("{\n.reg .b64 a, b;\nmov.b64 a, {%1, %3};\nmov.b64 b, {%2, %3};\nst.relaxed.gpu.global.v2.b64 [%0], {a, b};\n}" ::"l"(gs->stats + 128 * m + prow), "r"(st[0]), "r"(st[1]), "r"(e) : "memory");
      if (LN_SPLIT) { p1_step<LN_KB + 4>(acc, c); sched_fence(c.zero); pin<1>(st + 1); }
      ln_store(pk + 16, st[1], xo + 128);
      bar_arrive(BAR_EV, 288);
      p1_range<LN_KB + 4 + LN_SPLIT, G_KB + 1>(acc, c);
      sched_fence(c.zero);
      const unsigned long long* cp = (const unsigned long long*)gs->cspart + j * 4096 + threadIdx.x;
      const unsigned long long* sp = gs->stats + 128 * m + warp * 16 + rho;
      unsigned long long part[18];
      auto gather = [&]() {
#pragma unroll
        for (int i = 0; i < 18; i++) asm volatile("ld.relaxed.gpu.global.b64 %0, [%1];" : "=l"(part[i]) : "l"(i < 16 ? cp + i * 256 : sp + (i - 16) * 8) : "memory");
      };
      gather();
      auto validate = [&]() {
        float csum;
        for (int tries = 0;; tries++) {
          uint32_t bad = 0;
          csum = 0.f;
#pragma unroll
          for (int i = 0; i < 18; i++) { bad |= (uint32_t)(part[i] >> 32) ^ e; if (i < 16) csum += __uint_as_float((uint32_t)part[i]); }
          if (!__any_sync(~0u, bad != 0) || tries > (1 << 20)) break;
          gather();
        }
        const float hi = bf16r(csum), mid = bf16r(csum - hi);
        sts128(sb + OFF_CS + ((threadIdx.x & 62) * 4 + (threadIdx.x >> 6) * 2 + (threadIdx.x & 1)) * 16, make_uint4(pack2(hi, mid), pack2(csum - hi - mid, 0.f), 0, 0));
        asm volatile("fence.proxy.async.shared::cta;" ::: "memory");
        __syncwarp();
        if (lane == 0) mbar_arrive(sb + B_AUX);
      };
      p1_range<G_KB + 1, 14>(acc, c);
      if (wg == 1) validate();
      p1_step<14>(acc, c);
      p1_issue<3, 1>(acc, c, 1);
      if (wg == 0) validate();
      const uint32_t keep = q == 0 ? 0xffffffffu : (q == 1 ? 0xffffu : 0u);
      const uint32_t a0 = (__byte_perm((uint32_t)part[16], 0, 0x1010) ^ 0x80008000u) & keep, a1 = (__byte_perm((uint32_t)part[17], 0, 0x1010) ^ 0x80008000u) & keep;
      mbar_spin(sb + B_AUX, 0, c.zero);
      wg_fence();
      wgmma256_rs(acc, a0, a1, 0, 0, (SM_BASE + OFF_CS) >> 4);
      wg_commit();
      if (wg == 0) bar_arrive(BAR_LAG, 256);
      rs[0] = rcpf(hi_f((uint32_t)part[16])); rs[1] = rcpf(hi_f((uint32_t)part[17]));
      wg_wait<2>(); release(c, B_E1 + 16);
      wg_wait<0>(); release(c, B_E1 + 24);
#pragma unroll
      for (int i = 0; i < 64; i++) pk[i] = pack2(acc[2 * i], acc[2 * i + 1]);
      if (t0) TS(25 + wg * 16);
    }
    const uint32_t img = warp * 1024 + ((lane ^ (lane >> 3)) << 4);
#pragma unroll 1
    for (int R = 1;; R++) {
      uint8_t* hb = (uint8_t*)gs->h + (size_t)m * 56 * 16384 + img;
      if (R == 2 || R == 3) {
        attn_tile(acc, pk, c, R - 2, warp, m, gs, hb + (16 + j) * 16384, (uint8_t*)gs->o + (m * 16 + j + 8 * (R - 2)) * 16384 + img);
      } else {
        if (R == 5) { c.a = 0x8000002000010000ull + ((SM_BASE + OFF_A + wg * 4096) >> 4); c.k2 = 510; c.k4 = 1024 - 514; c.k4w = -3072 - 514; }
        geglu_tile<0>(acc, pk, c, hb + (2 * j + (R == 1 ? 0 : 16 * R - 40)) * 16384, BAR_EV + (R == 1 ? 1 : R + 1), rs);
        rs[0] = rs[1] = 1.0f;
        if (R == 5) break;
      }
      p1_range<14, 16>(acc, c);
#pragma unroll
      for (int i = 0; i < 64; i++) pk[i] = pack2(acc[2 * i], acc[2 * i + 1]);
      if (t0) TS(25 + R + wg * 16);
    }
    if (t0) TS(30 + wg * 16);
    auto fetch = [&](int p) {
      asm volatile("ld.global.cg.v4.b32 {%0,%1,%2,%3}, [%4];" : "=r"(pk[4 * p]), "=r"(pk[4 * p + 1]), "=r"(pk[4 * p + 2]), "=r"(pk[4 * p + 3]) : "l"(gs->dpart + blockIdx.x * 2048 + p * 256 + threadIdx.x) : "memory");
    };
#pragma unroll 1
    for (int it = 3; it < 5; it++) {
      p1_issue<2, 1>(acc, c, it & 1); wg_wait<1>(); release(c, B_E1 + 8);
      p1_issue<3, 1>(acc, c, it & 1); wg_wait<1>(); release(c, B_E1 + 16);
      p1_issue<0, 1>(acc, c, ~it & 1); wg_wait<1>(); release(c, B_E1 + 24);
      p1_issue<1, 1>(acc, c, ~it & 1); wg_wait<1>(); release(c, B_E1);
    }
    p1_issue<2, 1>(acc, c, 1); wg_wait<1>(); release(c, B_E1 + 8);
    mbar_spin(sb + B_DEP + 40, 0, c.zero);
    fetch(0); fetch(4);
    p1_issue<3, 1>(acc, c, 1); wg_wait<1>(); release(c, B_E1 + 16);
    fetch(1); fetch(5);
    p1_issue<0, 1>(acc, c, 0); wg_wait<1>(); release(c, B_E1 + 24);
    fetch(2); fetch(6);
    p1_issue<1, 1>(acc, c, 0); wg_wait<1>(); release(c, B_E1);
    fetch(3); fetch(7);
    if (t0) TS(31 + wg * 16);
    {
      float accs[64];
      const uint32_t peer = mapa(sb, rank ^ 1);
      auto send_piece = [&](int p) {
        asm volatile("st.async.weak.shared::cluster.mbarrier::complete_tx::bytes.v4.b32 [%0], {%1,%2,%3,%4}, [%5];" ::"r"(peer + OFF_LAND + p * 4096 + threadIdx.x * 16),
                     "r"(pack2(acc[64 + 8 * p], acc[65 + 8 * p])), "r"(pack2(acc[66 + 8 * p], acc[67 + 8 * p])), "r"(pack2(acc[68 + 8 * p], acc[69 + 8 * p])), "r"(pack2(acc[70 + 8 * p], acc[71 + 8 * p])),
                     "r"(peer + B_EX + 32 * wg + 8 * (p >> 1)) : "memory");
      };
      auto silu_piece = [&](int p) {
        const uint4 r = lds128(sb + OFF_LAND + p * 4096 + threadIdx.x * 16);
        const uint32_t rr[4] = {add2(r.x, pk[4 * p]), add2(r.y, pk[4 * p + 1]), add2(r.z, pk[4 * p + 2]), add2(r.w, pk[4 * p + 3])};
#pragma unroll
        for (int i = 0; i < 4; i++) {
          const float a = acc[8 * p + 2 * i] + lo_f(rr[i]), b = acc[8 * p + 2 * i + 1] + hi_f(rr[i]);
          pk[4 * p + i] = pack2(silu_half(a), silu_half(b));
        }
        pin<4>(pk + 4 * p);
      };
      const uint32_t xa = sb + OFF_X + (warp * 16 + (lane & 15)) * 128 + (((lane >> 4) ^ (lane & 7)) << 4);
      auto x_piece = [&](int i) { const uint4 v = ldsm((xa ^ ((i & 3) << 5)) + (i >> 2) * 16384); pk[32 + 4 * i] = v.x; pk[33 + 4 * i] = v.y; pk[34 + 4 * i] = v.z; pk[35 + 4 * i] = v.w; };
      p2_step<0>(accs, c);
      p2_step<1>(accs, c);
      mbar_spin(sb + B_E1 + 8, 0, c.zero);
      send_piece(0); send_piece(1);
      p2_step<2>(accs, c); sched_fence(c.zero); send_piece(2); send_piece(3);
      p2_step<3>(accs, c); sched_fence(c.zero); send_piece(4); send_piece(5);
      p2_step<4>(accs, c); mbar_spin(sb + B_XT, 0, c.zero); send_piece(6); send_piece(7);
      p2_step<5>(accs, c); mbar_spin(sb + B_EX + 32 * wg, 0, c.zero); silu_piece(0); x_piece(0);
      p2_step<6>(accs, c); sched_fence(c.zero); silu_piece(1); x_piece(1);
      p2_step<7>(accs, c); mbar_spin(sb + B_EX + 32 * wg + 8, 0, c.zero); silu_piece(2); x_piece(2);
      p2_step<8>(accs, c); sched_fence(c.zero); silu_piece(3); x_piece(3);
      p2_step<9>(accs, c); mbar_spin(sb + B_EX + 32 * wg + 16, 0, c.zero); silu_piece(4); x_piece(4);
      p2_step<10>(accs, c); sched_fence(c.zero); silu_piece(5); x_piece(5);
      p2_step<11>(accs, c); mbar_spin(sb + B_EX + 32 * wg + 24, 0, c.zero); silu_piece(6); x_piece(6); x_piece(7);
      if (wg == 1) silu_piece(7);
      p2_step<12>(accs, c); p2_step<13>(accs, c); p2_step<14>(accs, c); p2_step<15>(accs, c);
      if (c.do_rel) mbar_arrive(sb + B_DONE);
      if (wg == 0) silu_piece(7);
      wg_wait<0>();
#pragma unroll
      for (int i = 0; i < 8; i++) {
        uint32_t v[4];
#pragma unroll
        for (int k = 0; k < 4; k++) v[k] = fma2(pack2(accs[8 * i + 2 * k], accs[1 + 8 * i + 2 * k]), pk[4 * i + k], pk[32 + 4 * i + k]);
        asm volatile("stmatrix.sync.aligned.m8n8.x4.shared.b16 [%0], {%1,%2,%3,%4};" ::"r"((xa ^ ((i & 3) << 5)) + (i >> 2) * 16384), "r"(v[0]), "r"(v[1]), "r"(v[2]), "r"(v[3]) : "memory");
        if (i == 3 || i == 7) {
          asm volatile("fence.proxy.async.shared::cta;" ::: "memory");
          __syncwarp();
          if (elect_one()) tma3d_store(&mp.out, sb + OFF_X + (i >> 2) * 16384 + warp * 2048, j2 * 128 + (i >> 2) * 64, m2 * 64 + w * 16, wg);
        }
      }
      if (elect_one()) { asm volatile("cp.async.bulk.commit_group;\ncp.async.bulk.wait_group.read 0;" ::: "memory"); }
      if ((threadIdx.x & 127) == 0) { TS(33 + wg * 16); if (wg) { TG(59); unsigned id; asm volatile("mov.u32 %0, %%smid;" : "=r"(id)); TSV(60, id); } }
    }
  }
}

typedef CUresult (*EncodeFn)(CUtensorMap*, CUtensorMapDataType, cuuint32_t, void*, const cuuint64_t*, const cuuint64_t*, const cuuint32_t*, const cuuint32_t*,
                             CUtensorMapInterleave, CUtensorMapSwizzle, CUtensorMapL2promotion, CUtensorMapFloatOOBfill);

void encode(EncodeFn fn, CUtensorMap* tm, const void* p, int rank, const cuuint64_t* dims, const cuuint64_t* strides, const cuuint32_t* box) {
  const cuuint32_t es[5] = {1, 1, 1, 1, 1};
  fn(tm, CU_TENSOR_MAP_DATA_TYPE_BFLOAT16, rank, const_cast<void*>(p), dims, strides, box, es, CU_TENSOR_MAP_INTERLEAVE_NONE, CU_TENSOR_MAP_SWIZZLE_128B,
     PROMO, CU_TENSOR_MAP_FLOAT_OOB_FILL_NONE);
}

}

extern "C" void kernel_launch(void* const* d_in, const int* in_sizes, int n_in, void* d_out, int out_size) {
  (void)in_sizes; (void)n_in; (void)out_size;
  static EncodeFn fn = nullptr;
  static Scratch* gs = nullptr;
  if (!fn) {
    void* p = nullptr;
    cudaDriverEntryPointQueryResult qr;
    cudaGetDriverEntryPoint("cuTensorMapEncodeTiled", &p, cudaEnableDefault, &qr);
    fn = (EncodeFn)p;
    cudaGetSymbolAddress((void**)&gs, g_scratch);
    cudaFuncSetAttribute(fused_kernel, cudaFuncAttributeMaxDynamicSharedMemorySize, SMEM_BYTES);
  }
  const void *x = d_in[0], *wqkv = d_in[1], *wo = d_in[2], *wg = d_in[4], *wu = d_in[5], *wd = d_in[6];
  Maps mp;
  {
    const cuuint64_t dims[3] = {DM, SEQ / 2, 2}, st[2] = {DM * 4, DM * 2};
    const cuuint32_t box_in[3] = {64, 64, 2}, box_out[3] = {64, 16, 1};
    encode(fn, &mp.x, x, 3, dims, st, box_in);
    encode(fn, &mp.out, d_out, 3, dims, st, box_out);
  }
  {
    const cuuint64_t dims[2] = {DM, SEQ}, st[1] = {DM * 2};
    const cuuint32_t box[2] = {64, 128};
    encode(fn, &mp.xn, gs->xn, 2, dims, st, box);
  }
  {
    const cuuint32_t box[2] = {64, 64};
    const cuuint64_t dq[2] = {3 * DM, DM}, sq[1] = {3 * DM * 2}, df[2] = {DFF, DM}, sf[1] = {DFF * 2}, dw[2] = {DM, DM}, sw[1] = {DM * 2};
    encode(fn, &mp.wqkv, wqkv, 2, dq, sq, box);
    encode(fn, &mp.wg, wg, 2, df, sf, box);
    encode(fn, &mp.wu, wu, 2, df, sf, box);
    encode(fn, &mp.wo, wo, 2, dw, sw, box);
  }
  {
    const cuuint32_t box[5] = {64, 2, 4, 4, 2};
    const cuuint64_t st[4] = {DM * 2, 8 * DM * 2, 2 * DM * 2, 32 * DM * 2};
    const cuuint64_t dd[5] = {DM, 2, 4, 4, DFF / 32};
    encode(fn, &mp.wd, wd, 5, dd, st, box);
  }
  fused_kernel<<<NCTA, 384, SMEM_BYTES>>>((const uint4*)x, (const uint4*)wg, (const uint4*)wu, gs, mp);
}
```

```cpp
#include <cuda_runtime.h>
#include <cuda_bf16.h>
#include <cuda.h>
#include <stdint.h>

#define PROMO CU_TENSOR_MAP_L2_PROMOTION_L2_128B
#define PF_D 4
#define PF_W 1
#define PF_H 1
#define PF_SLEEP 250
#define PF_S 16
#define LAG2 4
#define CS_KB 8
#define LN_KB 4

#define EVICT_FIRST 0x12F0000000000000ull
#define EVICT_NORMAL 0x1000000000000000ull
#define HINT_W EVICT_FIRST
#define HINT_H EVICT_FIRST
#define HINT_LAST EVICT_FIRST

namespace {

constexpr int SEQ = 2048, DM = 1024, DFF = 3584;
constexpr int NMAIN = 128, NCTA = 132;

constexpr uint32_t SM_BASE = 0x400;
constexpr uint32_t P1_BYTES = 49152, P2_BYTES = 32768;
constexpr uint32_t OFF_A = 131072;
__host__ __device__ constexpr uint32_t p2_a(int s) { return s == 0 ? OFF_A + 32768 : s == 1 ? OFF_A + 49152 : s == 2 ? 114688 : s == 3 ? 16384 : 49152; }
__host__ __device__ constexpr uint32_t p2_b(int s) { return s < 3 ? 65536 + s * 16384 : (s - 3) * 32768; }
constexpr uint32_t OFF_LAND = OFF_A;
constexpr uint32_t OFF_X = 196608;
constexpr uint32_t OFF_CS = OFF_X + 14336;
constexpr uint32_t OFF_BAR = 229376;
constexpr uint32_t B_F1 = OFF_BAR, B_E1 = B_F1 + 32, B_E2 = B_E1 + 32, B_DONE = B_E2 + 40, B_F2 = B_DONE + 8, B_DEP = B_F2 + 40, B_CS = B_DEP + 48,
                   B_XT = B_CS + 8, B_EP = B_XT + 8, B_EX = B_EP + 8, B_AUX = B_EX + 32, B_HALO = B_AUX + 8, OFF_EPOCH = B_HALO + 16;
constexpr uint32_t SMEM_BYTES = 232448;
constexpr uint32_t AT_V = 0, AT_K = 8192, AT_REM = 11264, AT_WG = 15360;

constexpr int FL_XN = 0, FL_H = 16, FL_P = 80, FL_HALO = 96, FL_N = FL_HALO + 256;
struct __align__(1024) Scratch {
  uint4 h[16 * 56 * 1024];
  uint4 o[16 * 16 * 1024];
  uint4 xn[SEQ * DM / 8];
  uint4 dpart[128 * 8 * 256];
  uint4 halo[2 * 128 * 2 * 128];
  ulonglong2 cspart[8 * 16 * 128];
  unsigned long long stats[SEQ];
  unsigned flags[FL_N * 32];
  unsigned epoch[NCTA * 2];
};
__device__ Scratch g_scratch;
#define TG(i) do {} while (0)
#define TSV(i, v) do {} while (0)
#define TS(i) do {} while (0)

struct Maps { CUtensorMap x, xn, out, wqkv, wg, wu, wd, wo; };

__device__ __forceinline__ void mbar_init(uint32_t bar, uint32_t cnt) { asm volatile("mbarrier.init.shared::cta.b64 [%0], %1;" ::"r"(bar), "r"(cnt)); }
__device__ __forceinline__ void mbar_expect_tx(uint32_t bar, uint32_t bytes) { asm volatile("mbarrier.arrive.expect_tx.shared::cta.b64 _, [%0], %1;" ::"r"(bar), "r"(bytes) : "memory"); }
__device__ __forceinline__ void mbar_arrive(uint32_t bar) { asm volatile("mbarrier.arrive.shared::cta.b64 _, [%0];" ::"r"(bar) : "memory"); }
__device__ __forceinline__ void mbar_arrive_cl(uint32_t bar) { asm volatile("mbarrier.arrive.shared::cluster.b64 _, [%0];" ::"r"(bar) : "memory"); }
__device__ __forceinline__ uint32_t mapa(uint32_t a, uint32_t cta) { uint32_t r; asm("mapa.shared::cluster.u32 %0, %1, %2;" : "=r"(r) : "r"(a), "r"(cta)); return r; }
__device__ __forceinline__ void mbar_wait(uint32_t bar, uint32_t parity) {
  asm volatile("{\n.reg .pred p;\n.reg .u32 n;\nmov.u32 n, 0;\nLAB_WAIT:\nmbarrier.try_wait.parity.shared::cta.b64 p, [%0], %1;\n@p bra LAB_DONE;\n"
               "add.u32 n, n, 1;\nsetp.gt.u32 p, n, 4000000;\n@p trap;\nbra LAB_WAIT;\nLAB_DONE:\n}" ::"r"(bar), "r"(parity) : "memory");
}
__device__ __forceinline__ void mbar_spin(uint32_t bar, uint32_t parity, uint32_t zero) {
  asm volatile("{\n.reg .pred p, z;\nsetp.ne.u32 z, %2, 0;\nLAB_WAIT:\nmbarrier.try_wait.parity.shared::cta.b64 p, [%0], %1;\n@p bra LAB_DONE;\n@z trap;\nbra LAB_WAIT;\nLAB_DONE:\n}" ::"r"(bar), "r"(parity), "r"(zero) : "memory");
}
__device__ __forceinline__ void flag_wait(const unsigned* f, unsigned target) {
  asm volatile("{\n.reg .pred p;\n.reg .u32 n, v;\nmov.u32 n, 0;\nLAB_WAIT:\nld.relaxed.gpu.global.u32 v, [%0];\nsub.u32 v, v, %1;\nsetp.ge.s32 p, v, 0;\n@p bra LAB_DONE;\n"
               "nanosleep.u32 100;\nadd.u32 n, n, 1;\nsetp.gt.u32 p, n, 4000000;\n@p trap;\nbra LAB_WAIT;\nLAB_DONE:\nfence.acquire.gpu;\n}" ::"l"(f), "r"(target) : "memory");
}
__device__ __forceinline__ void flag_add(unsigned* f) { asm volatile("red.release.gpu.global.add.u32 [%0], 1;" ::"l"(f) : "memory"); }
__device__ __forceinline__ void fence_async() { asm volatile("fence.proxy.async.global;" ::: "memory"); }
__device__ __forceinline__ bool elect_one() { uint32_t p; asm volatile("{\n.reg .pred P;\nelect.sync _|P, 0xffffffff;\nselp.u32 %0, 1, 0, P;\n}" : "=r"(p)); return p; }
__device__ __forceinline__ void bar_sync(int id, int n) { asm volatile("bar.sync %0, %1;" ::"r"(id), "r"(n) : "memory"); }
__device__ __forceinline__ void bar_arrive(int id, int n) { asm volatile("bar.arrive %0, %1;" ::"r"(id), "r"(n) : "memory"); }

__device__ __forceinline__ void tma2d(uint32_t dst, const CUtensorMap* tm, uint32_t bar, int c0, int c1, uint64_t hint) {
  asm volatile("cp.async.bulk.tensor.2d.shared::cluster.global.mbarrier::complete_tx::bytes.L2::cache_hint [%0], [%1, {%3, %4}], [%2], %5;" ::"r"(dst), "l"(tm), "r"(bar), "r"(c0), "r"(c1), "l"(hint) : "memory");
}
__device__ __forceinline__ void tma2d_mc(uint32_t dst, const CUtensorMap* tm, uint32_t bar, int c0, int c1, uint64_t hint) {
  asm volatile("cp.async.bulk.tensor.2d.shared::cluster.global.mbarrier::complete_tx::bytes.multicast::cluster.L2::cache_hint [%0], [%1, {%3, %4}], [%2], %5, %6;" ::"r"(dst), "l"(tm), "r"(bar), "r"(c0), "r"(c1), "h"((uint16_t)3), "l"(hint) : "memory");
}
__device__ __forceinline__ void tma3d(uint32_t dst, const CUtensorMap* tm, uint32_t bar, int c0, int c1, int c2, uint64_t hint) {
  asm volatile("cp.async.bulk.tensor.3d.shared::cluster.global.mbarrier::complete_tx::bytes.L2::cache_hint [%0], [%1, {%3, %4, %5}], [%2], %6;" ::"r"(dst), "l"(tm), "r"(bar), "r"(c0), "r"(c1), "r"(c2), "l"(hint) : "memory");
}
__device__ __forceinline__ void tma5d(uint32_t dst, const CUtensorMap* tm, uint32_t bar, int c0, int c4, uint64_t hint) {
  asm volatile("cp.async.bulk.tensor.5d.shared::cluster.global.mbarrier::complete_tx::bytes.L2::cache_hint [%0], [%1, {%3, %5, %5, %5, %4}], [%2], %6;" ::"r"(dst), "l"(tm), "r"(bar), "r"(c0), "r"(c4), "r"(0), "l"(hint) : "memory");
}
__device__ __forceinline__ void tma5d_prefetch(const CUtensorMap* tm, int c0, int c4) {
  asm volatile("cp.async.bulk.prefetch.tensor.5d.L2.global [%0, {%1, %3, %3, %3, %2}];" ::"l"(tm), "r"(c0), "r"(c4), "r"(0) : "memory");
}
__device__ __forceinline__ void tma3d_store(const CUtensorMap* tm, uint32_t src, int c0, int c1, int c2) {
  asm volatile("cp.async.bulk.tensor.3d.global.shared::cta.bulk_group [%0, {%2, %3, %4}], [%1];" ::"l"(tm), "r"(src), "r"(c0), "r"(c1), "r"(c2) : "memory");
}
__device__ __forceinline__ void bulk_load(uint32_t dst, const void* src, uint32_t bytes, uint32_t bar, uint64_t hint) {
  asm volatile("cp.async.bulk.shared::cluster.global.mbarrier::complete_tx::bytes.L2::cache_hint [%0], [%1], %2, [%3], %4;" ::"r"(dst), "l"(src), "r"(bytes), "r"(bar), "l"(hint) : "memory");
}
__device__ __forceinline__ void bulk_load_mc(uint32_t dst, const void* src, uint32_t bytes, uint32_t bar, uint64_t hint) {
  asm volatile("cp.async.bulk.shared::cluster.global.mbarrier::complete_tx::bytes.multicast::cluster.L2::cache_hint [%0], [%1], %2, [%3], %4, %5;" ::"r"(dst), "l"(src), "r"(bytes), "r"(bar), "h"((uint16_t)3), "l"(hint) : "memory");
}
__device__ __forceinline__ uint4 lds128(uint32_t a) { uint4 v; asm volatile("ld.shared.v4.b32 {%0,%1,%2,%3}, [%4];" : "=r"(v.x), "=r"(v.y), "=r"(v.z), "=r"(v.w) : "r"(a) : "memory"); return v; }
__device__ __forceinline__ void sts128(uint32_t a, uint4 v) { asm volatile("st.shared.v4.b32 [%0], {%1,%2,%3,%4};" ::"r"(a), "r"(v.x), "r"(v.y), "r"(v.z), "r"(v.w) : "memory"); }
__device__ __forceinline__ void stg128(void* p, uint32_t a, uint32_t b, uint32_t c, uint32_t d) { asm volatile("st.global.v4.b32 [%0], {%1,%2,%3,%4};" ::"l"(p), "r"(a), "r"(b), "r"(c), "r"(d) : "memory"); }

__device__ __forceinline__ uint32_t pack2(float lo, float hi) { uint32_t r; asm("cvt.rn.bf16x2.f32 %0, %1, %2;" : "=r"(r) : "f"(hi), "f"(lo)); return r; }
__device__ __forceinline__ float lo_f(uint32_t v) { return __uint_as_float(v << 16); }
__device__ __forceinline__ float hi_f(uint32_t v) { return __uint_as_float(v & 0xffff0000u); }
__device__ __forceinline__ float bf16r(float v) { return lo_f(pack2(v, 0.f)); }
__device__ __forceinline__ uint32_t mul2(uint32_t a, uint32_t b) { uint32_t r; asm("mul.rn.bf16x2 %0, %1, %2;" : "=r"(r) : "r"(a), "r"(b)); return r; }
__device__ __forceinline__ uint32_t add2(uint32_t a, uint32_t b) { uint32_t r; asm("add.rn.bf16x2 %0, %1, %2;" : "=r"(r) : "r"(a), "r"(b)); return r; }
__device__ __forceinline__ uint32_t sub2(uint32_t a, uint32_t b) { uint32_t r; asm("sub.rn.bf16x2 %0, %1, %2;" : "=r"(r) : "r"(a), "r"(b)); return r; }
__device__ __forceinline__ uint32_t fma2(uint32_t a, uint32_t b, uint32_t c) { uint32_t r; asm("fma.rn.bf16x2 %0, %1, %2, %3;" : "=r"(r) : "r"(a), "r"(b), "r"(c)); return r; }
__device__ __forceinline__ uint32_t max2(uint32_t a, uint32_t b) { uint32_t r; asm("max.bf16x2 %0, %1, %2;" : "=r"(r) : "r"(a), "r"(b)); return r; }
__device__ __forceinline__ float ex2f(float x) { float y; asm("ex2.approx.ftz.f32 %0, %1;" : "=f"(y) : "f"(x)); return y; }
__device__ __forceinline__ float rcpf(float x) { float y; asm("rcp.approx.ftz.f32 %0, %1;" : "=f"(y) : "f"(x)); return y; }
constexpr float GELU_C1 = 0.7978845608028654f, GELU_C3 = 0.035677408136300125f;
__device__ __forceinline__ float gelu_k(float g, float c1, float c3, float k) {
  float t;
  asm("tanh.approx.f32 %0, %1;" : "=f"(t) : "f"(g * fmaf(g * g, c3, c1)));
  g *= k;
  return fmaf(g, t, g);
}
__device__ __forceinline__ float silu_half(float z) { float t; asm("tanh.approx.f32 %0, %1;" : "=f"(t) : "f"(z)); return fmaf(z, t, z); }

__device__ __forceinline__ void wg_fence() { asm volatile("wgmma.fence.sync.aligned;" ::: "memory"); }
__device__ __forceinline__ void wg_commit() { asm volatile("wgmma.commit_group.sync.aligned;" ::: "memory"); }
template <int N> __device__ __forceinline__ void wg_wait() { asm volatile("wgmma.wait_group.sync.aligned %0;" ::"n"(N) : "memory"); }
#define A8(o) "+f"(d[(o)]), "+f"(d[(o) + 1]), "+f"(d[(o) + 2]), "+f"(d[(o) + 3]), "+f"(d[(o) + 4]), "+f"(d[(o) + 5]), "+f"(d[(o) + 6]), "+f"(d[(o) + 7])
#define A64(o) A8(o), A8((o) + 8), A8((o) + 16), A8((o) + 24), A8((o) + 32), A8((o) + 40), A8((o) + 48), A8((o) + 56)
#define REGS0_63 "%0,%1,%2,%3,%4,%5,%6,%7,%8,%9,%10,%11,%12,%13,%14,%15,%16,%17,%18,%19,%20,%21,%22,%23,%24,%25,%26,%27,%28,%29,%30,%31," \
                 "%32,%33,%34,%35,%36,%37,%38,%39,%40,%41,%42,%43,%44,%45,%46,%47,%48,%49,%50,%51,%52,%53,%54,%55,%56,%57,%58,%59,%60,%61,%62,%63"
#define REGS64_127 "%64,%65,%66,%67,%68,%69,%70,%71,%72,%73,%74,%75,%76,%77,%78,%79,%80,%81,%82,%83,%84,%85,%86,%87,%88,%89,%90,%91,%92,%93,%94,%95," \
                   "%96,%97,%98,%99,%100,%101,%102,%103,%104,%105,%106,%107,%108,%109,%110,%111,%112,%113,%114,%115,%116,%117,%118,%119,%120,%121,%122,%123,%124,%125,%126,%127"
__device__ __forceinline__ void desc_add(uint64_t& x, int v) { asm volatile("{\n.reg .b32 lo, hi;\nmov.b64 {lo, hi}, %0;\nadd.s32 lo, lo, %1;\nmov.b64 %0, {lo, hi};\n}" : "+l"(x) : "r"(v)); }
template <int ACCUM> __device__ __forceinline__ void wgmma256(float (&d)[128], uint64_t& a, uint64_t& b, int da, int db) {
  asm volatile("{\n.reg .pred p;\nsetp.ne.b32 p, %130, 0;\n"
               "wgmma.mma_async.sync.aligned.m64n256k16.f32.bf16.bf16 {" REGS0_63 "," REGS64_127 "}, %128, %129, p, 1, 1, 0, 1;\n}"
               : A64(0), A64(64) : "l"(a), "l"(b), "n"(ACCUM));
  desc_add(a, da); desc_add(b, db);
}
__device__ __forceinline__ void wgmma256_rs(float (&d)[128], uint32_t a0, uint32_t a1, uint32_t z0, uint32_t z1, uint32_t b_lo) {
  asm volatile("{\n.reg .b64 db;\nmov.b64 db, {%132, 0x00000008};\n"
               "wgmma.mma_async.sync.aligned.m64n256k16.f32.bf16.bf16 {" REGS0_63 "," REGS64_127 "}, {%128,%129,%130,%131}, db, 1, 1, 1, 0;\n}"
               : A64(0), A64(64) : "r"(a0), "r"(a1), "r"(z0), "r"(z1), "r"(b_lo));
}
template <int ACCUM> __device__ __forceinline__ void wgmma128(float (&d)[64], uint64_t& a, uint64_t& b, int da, int db) {
  asm volatile("{\n.reg .pred p;\nsetp.ne.b32 p, %66, 0;\n"
               "wgmma.mma_async.sync.aligned.m64n128k16.f32.bf16.bf16 {" REGS0_63 "}, %64, %65, p, 1, 1, 0, 1;\n}"
               : A64(0) : "l"(a), "l"(b), "n"(ACCUM));
  desc_add(a, da); desc_add(b, db);
}
template <int ACCUM> __device__ __forceinline__ void hmma(float (&c)[4], uint32_t a0, uint32_t a1, uint32_t a2, uint32_t a3, uint32_t b0, uint32_t b1) {
  if (ACCUM)
    asm volatile("mma.sync.aligned.m16n8k16.row.col.f32.bf16.bf16.f32 {%0,%1,%2,%3}, {%4,%5,%6,%7}, {%8,%9}, {%0,%1,%2,%3};"
                 : "+f"(c[0]), "+f"(c[1]), "+f"(c[2]), "+f"(c[3]) : "r"(a0), "r"(a1), "r"(a2), "r"(a3), "r"(b0), "r"(b1));
  else
    asm volatile("mma.sync.aligned.m16n8k16.row.col.f32.bf16.bf16.f32 {%0,%1,%2,%3}, {%4,%5,%6,%7}, {%8,%9}, {%10,%10,%10,%10};"
                 : "=f"(c[0]), "=f"(c[1]), "=f"(c[2]), "=f"(c[3]) : "r"(a0), "r"(a1), "r"(a2), "r"(a3), "r"(b0), "r"(b1), "f"(0.f));
}
__device__ __forceinline__ uint32_t movm(uint32_t a) { uint32_t d; asm volatile("movmatrix.sync.aligned.m8n8.trans.b16 %0, %1;" : "=r"(d) : "r"(a)); return d; }
__device__ __forceinline__ int lane_here() { int v; asm volatile("mov.u32 %0, %%laneid;" : "=r"(v)); return v; }
template <int N> __device__ __forceinline__ void pin(uint32_t* r) {
#pragma unroll
  for (int i = 0; i < N; i++) asm volatile("" : "+r"(r[i]));
}
template <int N> __device__ __forceinline__ void pin(float* r) {
#pragma unroll
  for (int i = 0; i < N; i++) asm volatile("" : "+f"(r[i]));
}
__device__ __forceinline__ void sched_fence(uint32_t zero) {
  asm volatile("{\n.reg .pred p;\nsetp.eq.u32 p, %0, 0;\nLAB_F:\n@p bra.uni LAB_D;\nnanosleep.u32 0;\nbra.uni LAB_F;\nLAB_D:\n}" ::"r"(zero) : "memory");
}
__device__ __forceinline__ uint4 ldsm(uint32_t a) { uint4 v; asm volatile("ldmatrix.sync.aligned.m8n8.x4.shared.b16 {%0,%1,%2,%3}, [%4];" : "=r"(v.x), "=r"(v.y), "=r"(v.z), "=r"(v.w) : "r"(a) : "memory"); return v; }
__device__ __forceinline__ uint4 ldsm_t(uint32_t a) { uint4 v; asm volatile("ldmatrix.sync.aligned.m8n8.x4.trans.shared.b16 {%0,%1,%2,%3}, [%4];" : "=r"(v.x), "=r"(v.y), "=r"(v.z), "=r"(v.w) : "r"(a) : "memory"); return v; }

constexpr int BAR_LAG = 1, BAR_MMA = 2, BAR_EV = 3;

struct Cons {
  uint32_t sb;
  mutable uint64_t a, b;
  int k1, k2, k4, k4w, b1;
  uint32_t rel;
  bool do_rel;
  int wg;
  uint32_t zero;
};
#define REL_TS(n) TS(64 + (n))
constexpr uint32_t DB_LO = (SM_BASE >> 4) | ((8192 >> 4) << 16);

template <int ST, int ACCUM, bool WAIT = true> __device__ __forceinline__ void p1_issue(float (&acc)[128], const Cons& c, uint32_t parity) {
  if (WAIT) mbar_spin(c.sb + B_F1 + 8 * ST, parity, c.zero);
  wg_fence();
  wgmma256<ACCUM>(acc, c.a, c.b, c.k1, c.b1);
  wgmma256<1>(acc, c.a, c.b, c.k2, c.b1);
  wgmma256<1>(acc, c.a, c.b, c.k1, c.b1);
  wgmma256<1>(acc, c.a, c.b, ST == 3 ? c.k4w : c.k4, ST == 3 ? -6144 - 384 : 2048 - 384);
  wg_commit();
}
__device__ __forceinline__ void release(const Cons& c, uint32_t bar) { if (c.do_rel) mbar_arrive_cl(c.rel + bar); }
template <int KB, bool WAIT = true, int LAG = 2> __device__ __forceinline__ void p1_step(float (&acc)[128], const Cons& c) {
  if (KB == 16 - LAG) { if (c.wg == 1) { wg_wait<0>(); release(c, B_E1 + 8 * ((KB - 1) & 3)); bar_sync(BAR_LAG, 256); } }
  p1_issue<KB & 3, KB != 0, WAIT>(acc, c, (KB >> 2) & 1);
  if (KB == 15) { if (c.wg == 0) bar_arrive(BAR_LAG, 256); }
  if (KB > 0) { wg_wait<1>(); if (KB != 16 - LAG || c.wg == 0) release(c, B_E1 + 8 * ((KB - 1) & 3)); }
  if (KB == 15) { wg_wait<0>(); release(c, B_E1 + 8 * 3); }
}
__device__ __forceinline__ void p1_loop(float (&acc)[128], const Cons& c, int from, int to) {
#pragma unroll 1
  for (int kb = from; kb < to; kb++) {
    const bool wrap = (kb & 3) == 3;
    mbar_spin(c.sb + B_F1 + 8 * (kb & 3), (kb >> 2) & 1, c.zero);
    wg_fence();
    wgmma256<1>(acc, c.a, c.b, c.k1, c.b1);
    wgmma256<1>(acc, c.a, c.b, c.k2, c.b1);
    wgmma256<1>(acc, c.a, c.b, c.k1, c.b1);
    wgmma256<1>(acc, c.a, c.b, wrap ? c.k4w : c.k4, wrap ? -6144 - 384 : 2048 - 384);
    wg_commit();
    wg_wait<1>();
    release(c, B_E1 + 8 * ((kb - 1) & 3));
  }
}
template <int T> __device__ __forceinline__ void p2_step(float (&acc)[64], const Cons& c) {
  if (T == 16 - LAG2) { if (c.wg == 1) bar_sync(BAR_LAG, 256); }
  mbar_spin(c.sb + B_F2 + 8 * (T % 5), (T / 5) & 1, c.zero);
  wg_fence();
  wgmma128<T != 0>(acc, c.a, c.b, c.k1, c.b1);
  wgmma128<1>(acc, c.a, c.b, c.k2, c.b1);
  wgmma128<1>(acc, c.a, c.b, c.k1, c.b1);
  wgmma128<1>(acc, c.a, c.b, ((int)p2_a((T + 1) % 5) - (int)p2_a(T % 5)) / 16 - 514, ((int)p2_b((T + 1) % 5) - (int)p2_b(T % 5)) / 16 - 384);
  wg_commit();
  if (T == 15) { if (c.wg == 0) bar_arrive(BAR_LAG, 256); }
  if (T <= 11) { wg_wait<1>(); release(c, T ? B_E2 + 8 * ((T + 5 - 1) % 5) : B_E1 + 8); }
}

template <int P> __device__ __forceinline__ void geglu_piece(const uint32_t (&pk)[64], uint8_t* dst, const float (&rs)[2]) {
  constexpr int cg = P >> 1, r = P & 1;
  const float r2 = rs[r] * rs[r], c1 = GELU_C1 * rs[r], c3 = GELU_C3 * r2 * rs[r], k = 0.25f * r2;
  uint32_t v[4];
#pragma unroll
  for (int i = 0; i < 4; i++) {
    const uint32_t g = pk[2 * (4 * cg + i) + r];
    v[i] = mul2(pack2(gelu_k(lo_f(g), c1, c3, k), gelu_k(hi_f(g), c1, c3, k)), pk[32 + 2 * (4 * cg + i) + r]);
  }
  stg128(dst + cg * 8192 + r * 512, v[0], v[1], v[2], v[3]);
}
template <int KB> __device__ __forceinline__ void geglu_tile(float (&acc)[128], const uint32_t (&pk)[64], const Cons& c, uint8_t* dst, int ev, const float (&rs)[2]) {
  if constexpr (KB < 9) {
    p1_step<KB>(acc, c);
    if (KB == 0) { const int lane = lane_here(); dst += (lane ^ (lane >> 3)) << 4; }
    if (KB >= 1 && KB <= 8) geglu_piece<(KB - 1) & 7>(pk, dst, rs);
    if (KB == 8) bar_arrive(ev, 288);
    geglu_tile<KB + 1>(acc, pk, c, dst, ev, rs);
  }
}

__device__ __forceinline__ void attn_tile(float (&acc)[128], const uint32_t (&pk)[64], const Cons& c, int round, int warp, int m, Scratch* gs, uint8_t* hdst, uint8_t* odst) {
  const int w = warp & 3;
  const uint32_t at = c.sb + OFF_X + c.wg * AT_WG;
  uint32_t gg[16];
  p1_step<0>(acc, c);
  p1_step<1>(acc, c);
  int lane = lane_here();
  const uint32_t swz = (lane ^ (lane >> 3)) << 4;
  hdst += swz;
#pragma unroll
  for (int i = 0; i < 4; i++) {
    const int h = i & 1, r = i >> 1;
    sts128(at + AT_V + (2 * w + r) * 1024 + h * 512 + swz, make_uint4(pk[32 + 8 * h + r], pk[34 + 8 * h + r], pk[36 + 8 * h + r], pk[38 + 8 * h + r]));
  }
  if (w < 3) {
#pragma unroll
    for (int i = 0; i < 8; i++) asm volatile("st.shared.b32 [%0], %1;" ::"r"(at + AT_K + w * 1024 + i * 128 + lane * 4), "r"(pk[17 + 2 * i]) : "memory");
  } else {
    uint8_t* g = (uint8_t*)gs->halo + ((round * 128 + blockIdx.x) * 2 + c.wg) * 2048;
#pragma unroll
    for (int i = 0; i < 8; i++) asm volatile("st.global.b32 [%0], %1;" ::"l"(g + i * 128 + lane * 4), "r"(pk[17 + 2 * i]) : "memory");
#pragma unroll
    for (int h = 0; h < 2; h++) stg128(g + 1024 + h * 512 + swz, pk[33 + 8 * h], pk[35 + 8 * h], pk[37 + 8 * h], pk[39 + 8 * h]);
    bar_arrive(BAR_EV + 2 + round, 96);
  }
  __syncwarp();
  if (lane == 0) mbar_arrive(c.sb + B_HALO + 8 * round);
  if (round) {
#pragma unroll
    for (int p = 0; p < 4; p++) asm volatile("ld.global.cg.v4.b32 {%0,%1,%2,%3}, [%4];" : "=r"(gg[4 * p]), "=r"(gg[4 * p + 1]), "=r"(gg[4 * p + 2]), "=r"(gg[4 * p + 3]) : "l"(hdst + (p >> 1) * 8192 + (p & 1) * 512) : "memory");
  }
  auto gu_piece = [&](int p) {
    uint32_t v[4];
#pragma unroll
    for (int i = 0; i < 4; i++) {
      const uint32_t g = pk[48 + 8 * (p >> 1) + 2 * i + (p & 1)];
      v[i] = mul2(round ? gg[4 * p + i] : 0x3e803e80u, round ? g : pack2(gelu_k(lo_f(g), GELU_C1, GELU_C3, 1.0f), gelu_k(hi_f(g), GELU_C1, GELU_C3, 1.0f)));
    }
    stg128(hdst + (p >> 1) * 8192 + (p & 1) * 512, v[0], v[1], v[2], v[3]);
  };
  p1_step<2>(acc, c);
  p1_step<3>(acc, c); gu_piece(0);
  p1_step<4>(acc, c); gu_piece(1);
  p1_step<5>(acc, c); gu_piece(2);
  p1_step<6>(acc, c); gu_piece(3);
  p1_loop(acc, c, 7, 9);
  const bool first = m == 0 && w == 0;
  uint32_t kl[16];
  mbar_spin(c.sb + B_HALO + 8 * round, 0, c.zero);
  lane = lane_here();
  {
    const uint32_t ka = at + lane * 4 + (w ? AT_K + (w - 1) * 1024 : (first ? AT_K : AT_REM + round * 2048));
#pragma unroll
    for (int i = 0; i < 8; i++) {
      asm volatile("ld.shared.b32 %0, [%1];" : "=r"(kl[2 * i]) : "r"(ka + i * 128) : "memory");
      kl[2 * i + 1] = pk[16 + 2 * i] | c.zero;
    }
  }
  float st[4][4];
  pin<16>(kl);
  bar_sync(BAR_MMA, 256);
  mbar_spin(c.sb + B_F1 + 8 * 1, 0, c.zero);
#pragma unroll
  for (int ks = 0; ks < 2; ks++) {
#pragma unroll
    for (int h = 0; h < 2; h++) {
      const int o = 8 * h + 4 * ks;
      if (ks == 0) { hmma<0>(st[2 * h], kl[o], kl[o + 1], kl[o + 2], kl[o + 3], pk[o], pk[o + 2]); hmma<0>(st[2 * h + 1], pk[16 + o], pk[17 + o], pk[18 + o], pk[19 + o], pk[o + 1], pk[o + 3]); }
      else { hmma<1>(st[2 * h], kl[o], kl[o + 1], kl[o + 2], kl[o + 3], pk[o], pk[o + 2]); hmma<1>(st[2 * h + 1], pk[16 + o], pk[17 + o], pk[18 + o], pk[19 + o], pk[o + 1], pk[o + 3]); }
    }
  }
  sched_fence(c.zero);
  bar_sync(BAR_MMA, 256);
  p1_step<9, false>(acc, c);
  sched_fence(c.zero);
  pin<16>(&st[0][0]);
  lane = lane_here();
  const int rho = lane >> 2, q = lane & 3;
  const bool le0 = 2 * q <= rho, le1 = 2 * q + 1 <= rho;
  uint32_t la[2], lb[2], mx[2];
#pragma unroll
  for (int h = 0; h < 2; h++) {
    uint32_t l[2];
#pragma unroll
    for (int r = 0; r < 2; r++) {
      const float (&t)[4] = st[2 * h + r];
      l[r] = movm(pack2(rho <= 2 * q ? t[2] : t[0], rho <= 2 * q + 1 ? t[3] : t[1]));
      l[r] = fma2(l[r], 0x3e353e35u, mul2(l[r], 0x379e379eu));
    }
    la[h] = __byte_perm(l[0], l[1], 0x5410); lb[h] = __byte_perm(l[0], l[1], 0x7632);
    if (first && !le0) la[h] = (la[h] & 0xffff0000u) | 0xce6eu;
    if (first && !le1) lb[h] = (lb[h] & 0xffff0000u) | 0xce6eu;
    mx[h] = max2(la[h], lb[h]);
  }
#pragma unroll
  for (int o = 1; o <= 2; o++) { mx[0] = max2(mx[0], __shfl_xor_sync(~0u, mx[0], o)); mx[1] = max2(mx[1], __shfl_xor_sync(~0u, mx[1], o)); }
  const float L2E = 1.4426950408889634f;
  float pr[2][4], z[4];
#pragma unroll
  for (int h = 0; h < 2; h++) {
    pr[h][0] = ex2f((lo_f(la[h]) - lo_f(mx[h])) * L2E); pr[h][1] = ex2f((lo_f(lb[h]) - lo_f(mx[h])) * L2E);
    pr[h][2] = ex2f((hi_f(la[h]) - hi_f(mx[h])) * L2E); pr[h][3] = ex2f((hi_f(lb[h]) - hi_f(mx[h])) * L2E);
    z[2 * h] = pr[h][0] + pr[h][1]; z[2 * h + 1] = pr[h][2] + pr[h][3];
  }
  p1_step<10>(acc, c);
#pragma unroll
  for (int o = 1; o <= 2; o++) {
#pragma unroll
    for (int i = 0; i < 4; i++) z[i] += __shfl_xor_sync(~0u, z[i], o);
  }
  const uint32_t LE = (le0 ? 0xffffu : 0u) | (le1 ? 0xffff0000u : 0u);
  uint32_t P[4][2];
  uint4 vt[4][2];
  {
    const uint32_t row = (lane & 7) * 64 + ((((lane >> 3) & 1) ^ ((lane & 7) >> 1)) << 4);
    const uint32_t v1 = at + AT_V + (2 * w + (lane >> 4)) * 1024 + row;
    const uint32_t v0 = (w || lane >= 16) ? v1 - 1024 : (first ? v1 : at + AT_REM + round * 2048 + 1024 + row);
#pragma unroll
    for (int i = 0; i < 4; i++) {
      const float rz = rcpf(z[i]);
      const uint32_t p = pack2(pr[i >> 1][2 * (i & 1)] * rz, pr[i >> 1][2 * (i & 1) + 1] * rz);
      P[i][0] = p & ~LE; P[i][1] = p & LE;
      const uint32_t a = ((i & 1) ? v1 : v0) + (i >> 1) * 512;
      vt[i][0] = ldsm_t(a); vt[i][1] = ldsm_t(a ^ 32);
    }
  }
  float ot[4][2][4];
  pin<8>(&P[0][0]);
  bar_sync(BAR_MMA, 256);
  mbar_spin(c.sb + B_F1 + 8 * 3, 0, c.zero);
#pragma unroll
  for (int i = 0; i < 8; i++) { const uint4& v = vt[i >> 1][i & 1]; hmma<0>(ot[i >> 1][i & 1], v.x, v.y, v.z, v.w, P[i >> 1][0], P[i >> 1][1]); }
  sched_fence(c.zero);
  bar_sync(BAR_MMA, 256);
  p1_step<11, false>(acc, c);
  sched_fence(c.zero);
  pin<32>(&ot[0][0][0]);
  lane = lane_here();
  odst += (lane ^ (lane >> 3)) << 4;
  auto o_piece = [&](int i) {
    stg128(odst + (i >> 1) * 8192 + (i & 1) * 512, movm(pack2(ot[i][0][0], ot[i][0][1])), movm(pack2(ot[i][0][2], ot[i][0][3])), movm(pack2(ot[i][1][0], ot[i][1][1])), movm(pack2(ot[i][1][2], ot[i][1][3])));
  };
  o_piece(0); o_piece(1);
  p1_step<12>(acc, c);
  o_piece(2); o_piece(3);
  if (round) bar_arrive(BAR_EV + 4, 288);
}

__device__ __forceinline__ void ln_moments(const uint32_t* raw, float& c0, float& s, float& v) {
  c0 = lo_f(__shfl_sync(~0u, raw[0], 0));
  float ss[4] = {0.f, 0.f, 0.f, 0.f}, vv[4] = {0.f, 0.f, 0.f, 0.f};
#pragma unroll
  for (int i = 0; i < 16; i++) {
    const float a = lo_f(raw[i]) - c0, b = hi_f(raw[i]) - c0;
    ss[(2 * i) & 3] += a; ss[(2 * i + 1) & 3] += b;
    vv[(2 * i) & 3] = fmaf(a, a, vv[(2 * i) & 3]); vv[(2 * i + 1) & 3] = fmaf(b, b, vv[(2 * i + 1) & 3]);
  }
  s = (ss[0] + ss[1]) + (ss[2] + ss[3]); v = (vv[0] + vv[1]) + (vv[2] + vv[3]);
}
__device__ __forceinline__ void ln_reduce(float& s, float& v) {
#pragma unroll
  for (int o = 16; o; o >>= 1) { s += __shfl_xor_sync(~0u, s, o); v += __shfl_xor_sync(~0u, v, o); }
}
__device__ __forceinline__ uint32_t ln_finish(float c0, float s, float v) {
  s *= 1.0f / DM;
  float sd;
  asm("sqrt.approx.ftz.f32 %0, %1;" : "=f"(sd) : "f"(bf16r(bf16r(fmaxf(fmaf(v, 1.0f / DM, -s * s), 0.f)) + 1e-5f)));
  return pack2(c0 + s, sd);
}
__device__ __forceinline__ void ln_store(const uint32_t* raw, uint32_t st, uint4* dst) {
  const uint32_t m2 = __byte_perm(st, st, 0x1010);
  const float rinv = rcpf(hi_f(st));
  const uint32_t rh = pack2(rinv, rinv), rl = pack2(rinv - hi_f(rh), rinv - hi_f(rh));
#pragma unroll
  for (int c = 0; c < 4; c++) {
    uint32_t v[4];
#pragma unroll
    for (int i = 0; i < 4; i++) { const uint32_t t = sub2(raw[4 * c + i], m2); v[i] = fma2(t, rh, mul2(t, rl)); }
    stg128(dst + 32 * c, v[0], v[1], v[2], v[3]);
  }
}
__device__ __forceinline__ void col_sums(uint32_t tile, ulonglong2* part, uint32_t tag) {
  const int lane = threadIdx.x & 31;
  float cs[8] = {0, 0, 0, 0, 0, 0, 0, 0};
  uint32_t base = tile + ((lane >> 3) & 1) * 8192 + (lane >> 4) * 4096 + ((lane & 7) << 4);
#pragma unroll 1
  for (int k0 = 0; k0 < 8; k0++, base = (base ^ ((k0 ^ (k0 - 1)) << 4)) + 128) {
    uint4 v[4];
#pragma unroll
    for (int k = 0; k < 4; k++) v[k] = lds128(base + k * 1024);
#pragma unroll
    for (int k = 0; k < 4; k++) {
      cs[0] += lo_f(v[k].x); cs[1] += hi_f(v[k].x); cs[2] += lo_f(v[k].y); cs[3] += hi_f(v[k].y);
      cs[4] += lo_f(v[k].z); cs[5] += hi_f(v[k].z); cs[6] += lo_f(v[k].w); cs[7] += hi_f(v[k].w);
    }
  }
  const bool up = lane >= 16;
#pragma unroll
  for (int i = 0; i < 2; i++) {
    const float a = (up ? cs[4 + 2 * i] : cs[2 * i]) + __shfl_xor_sync(~0u, up ? cs[2 * i] : cs[4 + 2 * i], 16);
    const float b = (up ? cs[5 + 2 * i] : cs[1 + 2 * i]) + __shfl_xor_sync(~0u, up ? cs[1 + 2 * i] : cs[5 + 2 * i], 16);
    asm volatile("{\n.reg .b64 a, b;\nmov.b64 a, {%1, %3};\nmov.b64 b, {%2, %3};\nst.relaxed.gpu.global.v2.b64 [%0], {a, b};\n}"
                 ::"l"(part + 32 * (i + (up ? 2 : 0)) + (lane & 15)), "r"(__float_as_uint(a)), "r"(__float_as_uint(b)), "r"(tag) : "memory");
  }
  asm volatile("fence.proxy.async.shared::cta;" ::: "memory");
}

__global__ void __cluster_dims__(2, 1, 1) __launch_bounds__(384, 1)
fused_kernel(const uint4* __restrict__ x, const uint4* __restrict__ wgate, const uint4* __restrict__ wup, Scratch* gs, const __grid_constant__ Maps mp) {
  extern __shared__ __align__(1024) uint8_t smem_raw[];
  const uint32_t sb = (uint32_t)__cvta_generic_to_shared(smem_raw);
  const unsigned t_start = 0;
  if (threadIdx.x < 256 && blockIdx.x < NMAIN) {
    const uint32_t r = threadIdx.x >> 3, ch = threadIdx.x & 7;
    const uint32_t d = sb + r * 128 + ((ch ^ (r & 7)) << 4);
    const uint8_t* xa = (const uint8_t*)x + ((blockIdx.x & 15) * 262144 + r * 4096 + ch * 16);
    const uint32_t wo = r * (DFF * 2) + (blockIdx.x >> 4) * 256 + ch * 16;
    const uint8_t *wa = (const uint8_t*)wgate + wo, *wb = (const uint8_t*)wup + wo;
#pragma unroll
    for (int i = 0; i < 12; i++) {
      const int h = i >= 8;
      const uint8_t* src = (i >> 2) == 1 ? xa + (i & 1) * 131072 + ((i >> 1) & 1) * 2048 : ((i & 2) ? wb : wa) + h * 32 * (DFF * 2) + (i & 1) * 128;
      asm volatile("cp.async.cg.shared.global [%0], [%1], 16;" ::"r"(d + ((i >> 2) == 1 ? OFF_A + (i & 3) * 4096 : (i & 3) * 8192 + h * 4096)), "l"(src) : "memory");
    }
    if (threadIdx.x == 0) TS(23);
  }
  const int warp = __shfl_sync(~0u, threadIdx.x >> 5, 0), lane = threadIdx.x & 31;
  const int m = blockIdx.x & 15, j = blockIdx.x >> 4, rank = blockIdx.x & 1;
  const int m2 = blockIdx.x >> 3, j2 = blockIdx.x & 7;
  const bool helper = blockIdx.x >= NMAIN;
  if (warp >= 8) {
    asm volatile("setmaxnreg.dec.sync.aligned.u32 40;");
    if (warp == 8) {
      if (elect_one()) {
        asm volatile("prefetch.tensormap [%0];\nprefetch.tensormap [%1];\nprefetch.tensormap [%2];" ::"l"(&mp.x), "l"(&mp.wg), "l"(&mp.wu) : "memory");
        for (int s = 0; s < 4; s++) mbar_init(sb + B_F1 + 8 * s, 1);
        if (!helper) mbar_arrive(sb + B_F1);
        asm volatile("fence.mbarrier_init.release.cluster;" ::: "memory");
      }
      __syncwarp();
    } else if (warp == 9) {
      if (elect_one()) {
        if ((sb & 0xffffff) != SM_BASE) asm volatile("trap;");
        for (uint32_t b = B_E1; b < B_F2; b += 8) mbar_init(sb + b, 4);
        for (uint32_t b = B_F2; b < B_AUX; b += 8) mbar_init(sb + b, 1);
        for (uint32_t b = B_EX; b < B_AUX; b += 8) mbar_expect_tx(sb + b, 8192);
        mbar_init(sb + B_AUX, 8); mbar_init(sb + B_HALO, 9); mbar_init(sb + B_HALO + 8, 9);
        asm volatile("fence.mbarrier_init.release.cluster;" ::: "memory");
      }
      __syncwarp();
    }
    asm volatile("barrier.cluster.arrive.relaxed.aligned;" ::: "memory");
    if (warp == 8 && !helper) {
      if (elect_one()) {
        TS(0); TG(51);
#pragma unroll 1
        for (int kb = 1; kb < 4; kb++) {
          const uint32_t sa = sb + OFF_A + kb * 16384, sw = sb + kb * 32768, fb = sb + B_F1 + 8 * kb;
          mbar_expect_tx(fb, P1_BYTES);
          tma3d(sa, &mp.x, fb, kb * 64, m * 64, 0, EVICT_NORMAL);
          tma2d(sw, &mp.wg, fb, j * 128, kb * 64, EVICT_NORMAL); tma2d(sw + 16384, &mp.wu, fb, j * 128, kb * 64, EVICT_NORMAL);
          tma2d(sw + 8192, &mp.wg, fb, j * 128 + 64, kb * 64, EVICT_NORMAL); tma2d(sw + 24576, &mp.wu, fb, j * 128 + 64, kb * 64, EVICT_NORMAL);
        }
        TS(7);
      }
      __syncwarp();
    }
    asm volatile("barrier.cluster.wait.aligned;" ::: "memory");
    if (helper) {
      if (warp == 8) {
        unsigned e = 0;
        if (elect_one()) {
#pragma unroll 1
          for (int i = 0; i < 16; i++) {
            const uint32_t fb = sb + B_F1 + 8 * (i >> 2);
            if (!(i & 3)) mbar_expect_tx(fb, P1_BYTES);
            tma5d(sb + i * 8192, &mp.wd, fb, (blockIdx.x - NMAIN) * 256 + (i & 3) * 64, (i >> 2) * 2, HINT_W);
          }
        }
        if (lane == 0) { unsigned* ep = &gs->epoch[blockIdx.x * 2]; e = *ep + 1; *ep = e; }
        e = __shfl_sync(~0u, e, 0);
        if (lane < 16) flag_wait(&gs->flags[(FL_H + lane * 4) * 32], e * 8u);
        __syncwarp();
        if (elect_one()) {
          fence_async();
          TS(0);
#pragma unroll 1
          for (int i = 0; i < 64; i++) {
            const uint32_t fb = sb + B_F1 + 8 * (i & 3);
            if (i >= 4) { mbar_wait(sb + B_E1 + 8 * (i & 3), ~(i >> 2) & 1); mbar_expect_tx(fb, 16384); }
            bulk_load(sb + OFF_A + (i & 3) * 16384, gs->h + ((i >> 2) * 56 + (i & 3)) * 1024, 16384, fb, EVICT_NORMAL);
          }
        }
      } else if (warp == 9) {
#pragma unroll 1
        for (int t = 0; t < 16; t++) {
          bar_sync(BAR_EV + (t & 1), 288);
          if (lane == 0) { flag_add(&gs->flags[(FL_P + t) * 32]); TS(64 + t); }
          __syncwarp();
        }
      }
    } else if (warp == 8) {
      if (elect_one()) {
        uint32_t par = 0;

        auto x_load = [&]() {
          mbar_expect_tx(sb + B_XT, 32768);
          tma3d(sb + OFF_X, &mp.x, sb + B_XT, j2 * 128, m2 * 64, 0, HINT_LAST); tma3d(sb + OFF_X + 16384, &mp.x, sb + B_XT, j2 * 128 + 64, m2 * 64, 0, HINT_LAST);
        };
        auto d_prefetch = [&](int i) {
          if (PF_W == 1 && (m2 >> 2) == (i & 3)) tma5d_prefetch(&mp.wd, (j2 >> 1) * 256 + (m2 & 3) * 64, (2 * i + 4 + rank) * 2);
          if (PF_H == 1 && i < 6) asm volatile("cp.async.bulk.prefetch.L2.global [%0], 4096;" ::"l"(gs->h + (m2 * 56 + 2 * i + 4 + rank) * 1024 + (j2 >> 1) * 256) : "memory");
        };
        for (int R = 0; R < 5; R++) {
          const CUtensorMap *mb0, *mb1;
          int n0, n1;
          if (R == 1 || R == 2) {
            mb0 = &mp.wqkv; n0 = 64 * (j + 8 * (R - 1)) + rank * 2048;
            mb1 = rank ? (R == 1 ? &mp.wg : &mp.wu) : &mp.wqkv; n1 = rank ? 1024 + 64 * j : n0 + 1024;
          } else {
            mb0 = mb1 = rank ? &mp.wu : &mp.wg;
            n0 = 128 * j + (R ? 1024 * R - 1536 : 0); n1 = n0 + 64;
          }
#pragma unroll 1
          for (int kb = R ? 0 : 4; kb < 16; kb++) {
            if (R == 0 && kb == 14) { asm volatile("prefetch.tensormap [%0];\nprefetch.tensormap [%1];" ::"l"(&mp.xn), "l"(&mp.wqkv) : "memory"); }
            if (R == 4 && kb == 2) { asm volatile("prefetch.tensormap [%0];\nprefetch.tensormap [%1];\nprefetch.tensormap [%2];" ::"l"(&mp.wd), "l"(&mp.wo), "l"(&mp.out) : "memory"); }
            if (R == 0 && kb == (CS_KB)) {
              const uint32_t cb = sb + B_CS, d = sb + OFF_X;
              mbar_expect_tx(cb, 32768);
              tma2d(d, &mp.wg, cb, n0, m * 64, EVICT_NORMAL); tma2d(d + 8192, &mp.wg, cb, n1, m * 64, EVICT_NORMAL);
              tma2d(d + 16384, &mp.wu, cb, n0, m * 64, EVICT_NORMAL); tma2d(d + 24576, &mp.wu, cb, n1, m * 64, EVICT_NORMAL);
            }
            const int st = kb & 3;
            const uint32_t sa = sb + OFF_A + st * 16384, sw = sb + st * 32768, fb = sb + B_F1 + 8 * st;
            mbar_wait(sb + B_E1 + 8 * st, par);
            if (R * 16 + kb >= 4) REL_TS(R * 16 + kb - 4);
            mbar_expect_tx(fb, P1_BYTES);
            tma2d_mc(sw + rank * 16384, mb0, fb, n0, kb * 64, HINT_W);
            tma2d_mc(sw + 8192 + rank * 16384, mb1, fb, n1, kb * 64, HINT_W);
            if (R == 0) {
              tma3d(sa, &mp.x, fb, kb * 64, m * 64, 0, EVICT_NORMAL);
            } else {
              if (R == 1 && kb == 0) { mbar_wait(sb + B_DEP, 0); TS(1); }
              tma2d(sa, &mp.xn, fb, kb * 64, m * 128, R == 4 ? HINT_LAST : EVICT_NORMAL);
            }
            if (R == 4 && kb == 4 + j2) x_load();
            if (R == 4 && kb >= 16 - PF_D) { if (kb == 16 - PF_D) mbar_wait(sb + B_DEP + 8, 0); d_prefetch(kb + PF_D - 16); }
            if (st == 3) par ^= 1;
          }
        }
#pragma unroll 1
        for (int i = 0; i < 26; i++) {
          const int st = i & 3, kb = 2 * i + 4 + rank;
          const uint32_t sa = sb + OFF_A + st * 16384, sw = sb + st * 32768, fb = sb + B_F1 + 8 * st;
          mbar_wait(sb + B_E1 + 8 * st, par);
          REL_TS(76 + i);
          mbar_expect_tx(fb, P1_BYTES);
          tma5d(sw, &mp.wd, fb, j2 * 128, kb * 2, HINT_W); tma5d(sw + 8192, &mp.wd, fb, j2 * 128 + 64, kb * 2, HINT_W);
          tma5d(sw + 16384, &mp.wd, fb, (j2 ^ 1) * 128, kb * 2, HINT_W); tma5d(sw + 24576, &mp.wd, fb, (j2 ^ 1) * 128 + 64, kb * 2, HINT_W);
          if (i == 0 || i == 6 || i == 10 || i == 18) { mbar_wait(sb + B_DEP + 8 * (1 + ((i + 6) >> 3)), 0); }
          bulk_load(sa, gs->h + (m2 * 56 + kb) * 1024, 16384, fb, HINT_H);
          if (i + PF_D < 26) d_prefetch(i + PF_D);
          if (i >= PF_S && i < PF_S + 8) {
            asm volatile("cp.async.bulk.prefetch.L2.global [%0], 4096;" ::"l"(gs->o + (m2 * 16 + 2 * (i - PF_S)) * 1024 + j2 * 256) : "memory");
            if ((m2 >> 1) == i - PF_S) {
              asm volatile("cp.async.bulk.prefetch.tensor.2d.L2.global [%0, {%1, %2}];" ::"l"(&mp.wo), "r"(j2 * 128), "r"(m2 * 64) : "memory");
              asm volatile("cp.async.bulk.prefetch.tensor.2d.L2.global [%0, {%1, %2}];" ::"l"(&mp.wo), "r"(j2 * 128 + 64), "r"(m2 * 64) : "memory");
            }
          }
          if (st == 3) par ^= 1;
        }
        int st = 0; uint32_t par2 = 1;
#pragma unroll 1
        for (int t = 0; t < 16; t++) {
          const uint32_t sa = sb + p2_a(st), sw = sb + p2_b(st), fb = sb + B_F2 + 8 * st;
          if (t < 5) mbar_wait(sb + B_E1 + 8 * (((2 * t + 1) / 3 + 2) & 3), t < 3); else mbar_wait(sb + B_E2 + 8 * st, par2);
          REL_TS(102 + t);
          mbar_expect_tx(fb, P2_BYTES);
          bulk_load_mc(sa + rank * 8192, gs->o + (m2 * 16 + t) * 1024 + rank * 512, 8192, fb, HINT_H);
          tma2d(sw, &mp.wo, fb, j2 * 128, t * 64, HINT_W); tma2d(sw + 8192, &mp.wo, fb, j2 * 128 + 64, t * 64, HINT_W);
          if (++st == 5) { st = 0; par2 ^= 1; }
        }
      }
    } else if (warp == 9) {
#pragma unroll 1
      for (int e = 0; e < 7; e++) {
        const bool halo = e == 2 || e == 3;
        bar_sync(BAR_EV + e, halo ? 96 : 288);
        if (lane == 0) {
          const int f = e == 0 ? FL_XN + m : (halo ? FL_HALO + (e - 2) * 128 + blockIdx.x : FL_H + m * 4 + (e == 1 ? 0 : e - 3));
          TS(10 + 2 * e); TG(52 + e);
          flag_add(&gs->flags[f * 32]);
          if (e < 6) TS(11 + 2 * e);
        }
        __syncwarp();
      }
      mbar_wait(sb + B_DONE, 0);
    } else {
      unsigned e = 0;
      if (lane == 0) {
        unsigned* ep = &gs->epoch[blockIdx.x * 2 + warp - 10];
        e = *ep + 1; *ep = e;
        if (warp == 10) { asm volatile("st.shared.b32 [%0], %1;" ::"r"(sb + OFF_EPOCH), "r"(e) : "memory"); mbar_arrive(sb + B_EP); }
      }
      e = __shfl_sync(~0u, e, 0);
      mbar_wait(sb + B_CS, 0);
      if (lane == 0 && warp == 11) TS(6);
      col_sums(sb + OFF_X + (warp - 10) * 16384, gs->cspart + (j * 16 + m) * 128 + (warp - 10) * 16, e);
      if (lane == 0 && warp == 11) TS(9);
      if (warp == 10) {
        if (lane == 0) {
#pragma unroll 1
          for (int g = 0; g < 6; g++) {
            flag_wait(&gs->flags[(g == 5 ? FL_P + m2 : (g ? FL_H + m2 * 4 + g - 1 : FL_XN + m)) * 32], e * (g == 5 ? 4u : 8u));
            fence_async();
            mbar_arrive(sb + B_DEP + 8 * g);
            if (g == 0) TS(8);
          }
#pragma unroll 1
          for (int p = 0; p < 8; p++) {
            asm volatile("cp.async.bulk.prefetch.L2.global [%0], 4096;" ::"l"(gs->dpart + blockIdx.x * 2048 + p * 256) : "memory");
            __nanosleep(PF_SLEEP);
          }
        }
      } else
      if (elect_one()) {
#pragma unroll 1
        for (int r = 0; r < 2; r++) {
          const uint32_t hb = sb + B_HALO + 8 * r;
          if (m) {
            flag_wait(&gs->flags[(FL_HALO + r * 128 + blockIdx.x - 1) * 32], e);
            fence_async();
            mbar_expect_tx(hb, 4096);
            for (int g = 0; g < 2; g++) bulk_load(sb + OFF_X + g * AT_WG + AT_REM + r * 2048, gs->halo + ((r * 128 + blockIdx.x - 1) * 2 + g) * 128, 2048, hb, EVICT_FIRST);
          } else {
            mbar_arrive(hb);
          }
          TS(34 + r);
        }
      }
    }
  } else {
    asm volatile("barrier.cluster.arrive.relaxed.aligned;" ::: "memory");
    asm volatile("setmaxnreg.inc.sync.aligned.u32 232;");
    const int wg = warp >> 2, w = warp & 3;
    Cons c;
    c.sb = sb; c.wg = wg; c.zero = warp >> 8;
    c.a = 0x4000004000010000ull + ((SM_BASE + OFF_A + wg * 8192) >> 4); c.k1 = 2 + c.zero; c.k2 = 2; c.k4 = 1024 - 6; c.k4w = -3072 - 6; c.b1 = 128 + c.zero;
    c.b = 0x4000004000000000ull + DB_LO + c.zero;
    c.rel = mapa(sb, threadIdx.x & 1);
    c.do_rel = (threadIdx.x & 127) < 2;
    constexpr bool t0 = false;
    float acc[128];
    uint32_t pk[64];
    float rs[2];
    const int rho = lane >> 2, q = lane & 3;

    if (helper) {
      asm volatile("barrier.cluster.wait.aligned;" ::: "memory");
      c.a = 0x8000002000010000ull + ((SM_BASE + OFF_A + wg * 4096) >> 4); c.k2 = 510; c.k4 = 1024 - 514; c.k4w = -3072 - 514;
      c.rel = sb;
      uint4* dst = gs->dpart + (blockIdx.x - NMAIN) * 4096 + threadIdx.x;
      auto put = [&](int p) {
#pragma unroll
        for (int i = 4 * p; i < 4 * p + 4; i++) stg128(dst + i * 256, pk[4 * i], pk[4 * i + 1], pk[4 * i + 2], pk[4 * i + 3]);
      };
#pragma unroll 1
      for (int t = 0; t < 16; t++) {
        p1_issue<0, 0>(acc, c, t & 1);
        if (t) put(0);
        p1_issue<1, 1>(acc, c, t & 1); wg_wait<1>(); release(c, B_E1);
        if (t) put(1);
        if (wg == 1) { wg_wait<0>(); release(c, B_E1 + 8); bar_sync(BAR_LAG, 256); }
        p1_issue<2, 1>(acc, c, t & 1); wg_wait<1>(); if (wg == 0) release(c, B_E1 + 8);
        if (t) put(2);
        p1_issue<3, 1>(acc, c, t & 1);
        if (wg == 0) bar_arrive(BAR_LAG, 256);
        if (t) { put(3); bar_arrive(BAR_EV + (~t & 1), 288); dst += 8 * 2048; }
        wg_wait<1>(); release(c, B_E1 + 16);
        wg_wait<0>(); release(c, B_E1 + 24);
#pragma unroll
        for (int i = 0; i < 64; i++) pk[i] = pack2(acc[2 * i], acc[2 * i + 1]);
      }
      put(0); put(1); put(2); put(3);
      bar_arrive(BAR_EV + 1, 288);
      return;
    }
    {
      const int prow = 16 * j + 2 * warp;
      const uint4* xr = x + (size_t)(128 * m + 2 * (prow & 63) + (prow >> 6)) * 128 + lane;
      uint4* xo = gs->xn + (size_t)(128 * m + prow) * 128 + lane;
      float c0[2], mo[4];
      uint32_t st[2];
      uint32_t e;
      asm volatile("" : "+l"(xr), "+l"(xo));
      asm volatile("cp.async.wait_all;\nfence.proxy.async.shared::cta;" ::: "memory");
      bar_sync(BAR_MMA, 256);
      if (threadIdx.x == 0) TS(39);
      p1_step<0, false>(acc, c);
      asm volatile("barrier.cluster.wait.aligned;" ::: "memory");
      p1_step<1>(acc, c);
#pragma unroll
      for (int i = 0; i < 8; i++) {
        asm volatile("ld.global.nc.v4.b32 {%0,%1,%2,%3}, [%4];" : "=r"(pk[4 * i]), "=r"(pk[4 * i + 1]), "=r"(pk[4 * i + 2]), "=r"(pk[4 * i + 3]) : "l"(xr + (i >> 2) * 256 + (i & 3) * 32));
      }
      p1_loop(acc, c, 2, LN_KB + 1);
      pin<16>(pk); ln_moments(pk, c0[0], mo[0], mo[1]); pin<2>(mo);
      p1_step<LN_KB + 1>(acc, c);
      sched_fence(c.zero);
      pin<16>(pk + 16); ln_moments(pk + 16, c0[1], mo[2], mo[3]); ln_reduce(mo[0], mo[1]); pin<4>(mo);
      p1_step<LN_KB + 2>(acc, c);
      mbar_spin(sb + B_EP, 0, c.zero);
      asm volatile("ld.shared.b32 %0, [%1];" : "=r"(e) : "r"(sb + OFF_EPOCH) : "memory");
      pin<2>(mo); st[0] = ln_finish(c0[0], mo[0], mo[1]); ln_reduce(mo[2], mo[3]); pin<1>(st); pin<2>(mo + 2);
      p1_step<LN_KB + 3>(acc, c);
      sched_fence(c.zero);
      pin<1>(st); pin<2>(mo + 2);
      st[1] = ln_finish(c0[1], mo[2], mo[3]);
      ln_store(pk, st[0], xo);
      if (lane == 0)
        asm volatile("{\n.reg .b64 a, b;\nmov.b64 a, {%1, %3};\nmov.b64 b, {%2, %3};\nst.relaxed.gpu.global.v2.b64 [%0], {a, b};\n}" ::"l"(gs->stats + 128 * m + prow), "r"(st[0]), "r"(st[1]), "r"(e) : "memory");
      p1_step<LN_KB + 4>(acc, c); sched_fence(c.zero); pin<1>(st + 1);
      ln_store(pk + 16, st[1], xo + 128);
      bar_arrive(BAR_EV, 288);
      p1_loop(acc, c, LN_KB + 5, 13);
      const unsigned long long* cp = (const unsigned long long*)gs->cspart + j * 4096 + threadIdx.x;
      const unsigned long long* sp = gs->stats + 128 * m + warp * 16 + rho;
      unsigned long long part[18];
      auto gather = [&]() {
#pragma unroll
        for (int i = 0; i < 18; i++) asm volatile("ld.relaxed.gpu.global.b64 %0, [%1];" : "=l"(part[i]) : "l"(i < 16 ? cp + i * 256 : sp + (i - 16) * 8) : "memory");
      };
      gather();
      auto validate = [&]() {
        float csum;
        for (int tries = 0;; tries++) {
          uint32_t bad = 0;
          csum = 0.f;
#pragma unroll
          for (int i = 0; i < 18; i++) { bad |= (uint32_t)(part[i] >> 32) ^ e; if (i < 16) csum += __uint_as_float((uint32_t)part[i]); }
          if (!__any_sync(~0u, bad != 0) || tries > (1 << 20)) break;
          gather();
        }
        const float hi = bf16r(csum), mid = bf16r(csum - hi);
        sts128(sb + OFF_CS + ((threadIdx.x & 62) * 4 + (threadIdx.x >> 6) * 2 + (threadIdx.x & 1)) * 16, make_uint4(pack2(hi, mid), pack2(csum - hi - mid, 0.f), 0, 0));
        asm volatile("fence.proxy.async.shared::cta;" ::: "memory");
        __syncwarp();
        if (lane == 0) mbar_arrive(sb + B_AUX);
      };
      p1_step<13>(acc, c);
#pragma unroll 1
      for (int ph = 1; ph >= 0; ph--) {
        if (wg == ph) validate();
        if (ph) { p1_step<14>(acc, c); p1_issue<3, 1>(acc, c, 1); }
      }
      const uint32_t keep = q == 0 ? 0xffffffffu : (q == 1 ? 0xffffu : 0u);
      const uint32_t a0 = (__byte_perm((uint32_t)part[16], 0, 0x1010) ^ 0x80008000u) & keep, a1 = (__byte_perm((uint32_t)part[17], 0, 0x1010) ^ 0x80008000u) & keep;
      mbar_spin(sb + B_AUX, 0, c.zero);
      wg_fence();
      wgmma256_rs(acc, a0, a1, 0, 0, (SM_BASE + OFF_CS) >> 4);
      wg_commit();
      if (wg == 0) bar_arrive(BAR_LAG, 256);
      rs[0] = rcpf(hi_f((uint32_t)part[16])); rs[1] = rcpf(hi_f((uint32_t)part[17]));
      wg_wait<2>(); release(c, B_E1 + 16);
      wg_wait<0>(); release(c, B_E1 + 24);
    }
#pragma unroll 1
    for (int R = 1;; R++) {
#pragma unroll
      for (int i = 0; i < 64; i++) pk[i] = pack2(acc[2 * i], acc[2 * i + 1]);
      if (t0) TS(24 + R + wg * 16);
      uint8_t* hb = (uint8_t*)gs->h + (size_t)m * 56 * 16384 + warp * 1024;
      const bool att = R == 2 || R == 3;
      if (att) {
        attn_tile(acc, pk, c, R - 2, warp, m, gs, hb + (16 + j) * 16384, (uint8_t*)gs->o + (m * 16 + j + 8 * (R - 2)) * 16384 + warp * 1024);
      } else {
        if (R == 5) { c.a = 0x8000002000010000ull + ((SM_BASE + OFF_A + wg * 4096) >> 4); c.k2 = 510; c.k4 = 1024 - 514; c.k4w = -3072 - 514; }
        geglu_tile<0>(acc, pk, c, hb + (2 * j + (R == 1 ? 0 : 16 * R - 40)) * 16384, BAR_EV + (R == 1 ? 1 : R + 1), rs);
        rs[0] = rs[1] = 1.0f;
      }
      p1_loop(acc, c, att ? 13 : 9, R == 5 ? 24 : 14);
      if (R == 5) break;
      p1_step<14>(acc, c); p1_step<15>(acc, c);
    }
    auto fetch = [&](int p) {
      asm volatile("ld.global.cg.v4.b32 {%0,%1,%2,%3}, [%4];" : "=r"(pk[4 * p]), "=r"(pk[4 * p + 1]), "=r"(pk[4 * p + 2]), "=r"(pk[4 * p + 3]) : "l"(gs->dpart + blockIdx.x * 2048 + p * 256 + threadIdx.x) : "memory");
    };
    mbar_spin(sb + B_DEP + 40, 0, c.zero);
    fetch(0); fetch(1); fetch(2);
    p1_step<8>(acc, c);
    fetch(3); fetch(4); fetch(5);
    p1_step<9>(acc, c);
    fetch(6); fetch(7);
    {
      float accs[64];
      const uint32_t peer = mapa(sb, rank ^ 1);
      auto send_piece = [&](int p) {
        asm volatile("st.async.weak.shared::cluster.mbarrier::complete_tx::bytes.v4.b32 [%0], {%1,%2,%3,%4}, [%5];" ::"r"(peer + OFF_LAND + p * 4096 + threadIdx.x * 16),
                     "r"(pack2(acc[64 + 8 * p], acc[65 + 8 * p])), "r"(pack2(acc[66 + 8 * p], acc[67 + 8 * p])), "r"(pack2(acc[68 + 8 * p], acc[69 + 8 * p])), "r"(pack2(acc[70 + 8 * p], acc[71 + 8 * p])),
                     "r"(peer + B_EX + 16 * wg + 8 * (p >> 2)) : "memory");
      };
      auto silu_piece = [&](int p) {
        const uint4 r = lds128(sb + OFF_LAND + p * 4096 + threadIdx.x * 16);
        const uint32_t rr[4] = {add2(r.x, pk[4 * p]), add2(r.y, pk[4 * p + 1]), add2(r.z, pk[4 * p + 2]), add2(r.w, pk[4 * p + 3])};
#pragma unroll
        for (int i = 0; i < 4; i++) {
          const float a = acc[8 * p + 2 * i] + lo_f(rr[i]), b = acc[8 * p + 2 * i + 1] + hi_f(rr[i]);
          pk[4 * p + i] = pack2(silu_half(a), silu_half(b));
        }
        pin<4>(pk + 4 * p);
      };
      const uint32_t xa = sb + OFF_X + (warp * 16 + (lane & 15)) * 128 + (((lane >> 4) ^ (lane & 7)) << 4);
      auto x_piece = [&](int i) { const uint4 v = ldsm((xa ^ ((i & 3) << 5)) + (i >> 2) * 16384); pk[32 + 4 * i] = v.x; pk[33 + 4 * i] = v.y; pk[34 + 4 * i] = v.z; pk[35 + 4 * i] = v.w; };
      p2_step<0>(accs, c);
      p2_step<1>(accs, c);
      mbar_spin(sb + B_E1 + 8, 0, c.zero);
      send_piece(0); send_piece(1);
      p2_step<2>(accs, c); sched_fence(c.zero); send_piece(2); send_piece(3);
      p2_step<3>(accs, c); sched_fence(c.zero); send_piece(4); send_piece(5);
      p2_step<4>(accs, c); mbar_spin(sb + B_XT, 0, c.zero); send_piece(6); send_piece(7);
      p2_step<5>(accs, c); mbar_spin(sb + B_EX + 16 * wg, 0, c.zero); silu_piece(0); x_piece(0);
      p2_step<6>(accs, c); sched_fence(c.zero); silu_piece(1); x_piece(1);
      p2_step<7>(accs, c); sched_fence(c.zero); silu_piece(2); x_piece(2);
      p2_step<8>(accs, c); sched_fence(c.zero); silu_piece(3); x_piece(3);
      p2_step<9>(accs, c); mbar_spin(sb + B_EX + 16 * wg + 8, 0, c.zero); silu_piece(4); x_piece(4);
      p2_step<10>(accs, c); sched_fence(c.zero); silu_piece(5); x_piece(5);
      p2_step<11>(accs, c); sched_fence(c.zero); silu_piece(6); x_piece(6); x_piece(7);
      if (wg == 1) silu_piece(7);
      p2_step<12>(accs, c); p2_step<13>(accs, c); p2_step<14>(accs, c); p2_step<15>(accs, c);
      if (c.do_rel) mbar_arrive(sb + B_DONE);
      if (wg == 0) silu_piece(7);
      wg_wait<0>();
#pragma unroll
      for (int i = 0; i < 8; i++) {
        uint32_t v[4];
#pragma unroll
        for (int k = 0; k < 4; k++) v[k] = fma2(pack2(accs[8 * i + 2 * k], accs[1 + 8 * i + 2 * k]), pk[4 * i + k], pk[32 + 4 * i + k]);
        asm volatile("stmatrix.sync.aligned.m8n8.x4.shared.b16 [%0], {%1,%2,%3,%4};" ::"r"((xa ^ ((i & 3) << 5)) + (i >> 2) * 16384), "r"(v[0]), "r"(v[1]), "r"(v[2]), "r"(v[3]) : "memory");
        if (i == 3 || i == 7) {
          asm volatile("fence.proxy.async.shared::cta;" ::: "memory");
          __syncwarp();
          if (elect_one()) tma3d_store(&mp.out, sb + OFF_X + (i >> 2) * 16384 + warp * 2048, j2 * 128 + (i >> 2) * 64, m2 * 64 + w * 16, wg);
        }
      }
      if (elect_one()) { asm volatile("cp.async.bulk.commit_group;\ncp.async.bulk.wait_group.read 0;" ::: "memory"); }
      if ((threadIdx.x & 127) == 0) { TS(33 + wg * 16); if (wg) { TG(59); unsigned id; asm volatile("mov.u32 %0, %%smid;" : "=r"(id)); TSV(60, id); } }
    }
  }
}

typedef CUresult (*EncodeFn)(CUtensorMap*, CUtensorMapDataType, cuuint32_t, void*, const cuuint64_t*, const cuuint64_t*, const cuuint32_t*, const cuuint32_t*,
                             CUtensorMapInterleave, CUtensorMapSwizzle, CUtensorMapL2promotion, CUtensorMapFloatOOBfill);

void encode(EncodeFn fn, CUtensorMap* tm, const void* p, int rank, const cuuint64_t* dims, const cuuint64_t* strides, const cuuint32_t* box) {
  const cuuint32_t es[5] = {1, 1, 1, 1, 1};
  fn(tm, CU_TENSOR_MAP_DATA_TYPE_BFLOAT16, rank, const_cast<void*>(p), dims, strides, box, es, CU_TENSOR_MAP_INTERLEAVE_NONE, CU_TENSOR_MAP_SWIZZLE_128B,
     PROMO, CU_TENSOR_MAP_FLOAT_OOB_FILL_NONE);
}

}

extern "C" void kernel_launch(void* const* d_in, const int* in_sizes, int n_in, void* d_out, int out_size) {
  (void)in_sizes; (void)n_in; (void)out_size;
  static EncodeFn fn = nullptr;
  static Scratch* gs = nullptr;
  if (!fn) {
    void* p = nullptr;
    cudaDriverEntryPointQueryResult qr;
    cudaGetDriverEntryPoint("cuTensorMapEncodeTiled", &p, cudaEnableDefault, &qr);
    fn = (EncodeFn)p;
    cudaGetSymbolAddress((void**)&gs, g_scratch);
    cudaFuncSetAttribute(fused_kernel, cudaFuncAttributeMaxDynamicSharedMemorySize, SMEM_BYTES);
  }
  const void *x = d_in[0], *wqkv = d_in[1], *wo = d_in[2], *wg = d_in[4], *wu = d_in[5], *wd = d_in[6];
  Maps mp;
  {
    const cuuint64_t dims[3] = {DM, SEQ / 2, 2}, st[2] = {DM * 4, DM * 2};
    const cuuint32_t box_in[3] = {64, 64, 2}, box_out[3] = {64, 16, 1};
    encode(fn, &mp.x, x, 3, dims, st, box_in);
    encode(fn, &mp.out, d_out, 3, dims, st, box_out);
  }
  {
    const cuuint64_t dims[2] = {DM, SEQ}, st[1] = {DM * 2};
    const cuuint32_t box[2] = {64, 128};
    encode(fn, &mp.xn, gs->xn, 2, dims, st, box);
  }
  {
    const cuuint32_t box[2] = {64, 64};
    const cuuint64_t dq[2] = {3 * DM, DM}, sq[1] = {3 * DM * 2}, df[2] = {DFF, DM}, sf[1] = {DFF * 2}, dw[2] = {DM, DM}, sw[1] = {DM * 2};
    encode(fn, &mp.wqkv, wqkv, 2, dq, sq, box);
    encode(fn, &mp.wg, wg, 2, df, sf, box);
    encode(fn, &mp.wu, wu, 2, df, sf, box);
    encode(fn, &mp.wo, wo, 2, dw, sw, box);
  }
  {
    const cuuint32_t box[5] = {64, 2, 4, 4, 2};
    const cuuint64_t st[4] = {DM * 2, 8 * DM * 2, 2 * DM * 2, 32 * DM * 2};
    const cuuint64_t dd[5] = {DM, 2, 4, 4, DFF / 32};
    encode(fn, &mp.wd, wd, 5, dd, st, box);
  }
  fused_kernel<<<NCTA, 384, SMEM_BYTES>>>((const uint4*)x, (const uint4*)wg, (const uint4*)wu, gs, mp);
}
```

```cpp
#include <cuda_runtime.h>
#include <cuda_bf16.h>
#include <cuda.h>
#include <stdint.h>

#define PROMO CU_TENSOR_MAP_L2_PROMOTION_L2_256B
#define PF_D 4
#define PF_W 1
#define PF_H 1
#define PF_SLEEP 250
#define LAG2 4
#define CS_KB 8
#define LN_KB 4

#define EVICT_FIRST 0x12F0000000000000ull
#define EVICT_NORMAL 0x1000000000000000ull
#define HINT_W EVICT_FIRST
#define HINT_H EVICT_FIRST
#define HINT_LAST EVICT_FIRST

namespace {

constexpr int SEQ = 2048, DM = 1024, DFF = 3584;
constexpr int NMAIN = 128, NCTA = 132;

constexpr uint32_t SM_BASE = 0x400;
constexpr uint32_t P1_BYTES = 49152, P2_BYTES = 32768;
constexpr uint32_t OFF_A = 131072;
__host__ __device__ constexpr uint32_t p2_a(int s) { return s == 0 ? OFF_A + 32768 : s == 1 ? OFF_A + 49152 : s == 2 ? 114688 : s == 3 ? 16384 : 49152; }
__host__ __device__ constexpr uint32_t p2_b(int s) { return s < 3 ? 65536 + s * 16384 : (s - 3) * 32768; }
constexpr uint32_t OFF_LAND = OFF_A;
constexpr uint32_t OFF_X = 196608;
constexpr uint32_t OFF_CS = OFF_X + 14336;
constexpr uint32_t OFF_BAR = 229376;
constexpr uint32_t B_F1 = OFF_BAR, B_E1 = B_F1 + 32, B_E2 = B_E1 + 32, B_DONE = B_E2 + 40, B_F2 = B_DONE + 8, B_DEP = B_F2 + 40, B_CS = B_DEP + 48,
                   B_XT = B_CS + 16, B_EP = B_XT + 8, B_EX = B_EP + 8, B_AUX = B_EX + 32, B_HALO = B_AUX + 8, OFF_EPOCH = B_HALO + 16;
constexpr uint32_t SMEM_BYTES = 232448;
constexpr uint32_t AT_V = 0, AT_K = 8192, AT_REM = 11264, AT_WG = 15360;

constexpr int FL_XN = 0, FL_H = 16, FL_P = 80, FL_HALO = 96, FL_N = FL_HALO + 256;
struct __align__(1024) Scratch {
  uint4 h[16 * 56 * 1024];
  uint4 o[16 * 16 * 1024];
  uint4 xn[SEQ * DM / 8];
  uint4 dpart[128 * 8 * 256];
  uint4 halo[2 * 128 * 2 * 128];
  ulonglong2 cspart[8 * 16 * 128];
  unsigned long long stats[SEQ];
  unsigned flags[FL_N * 32];
  unsigned epoch[NCTA * 2];
};
__device__ Scratch g_scratch;
#define TG(i) do {} while (0)
#define TSV(i, v) do {} while (0)
#define TS(i) do {} while (0)

struct Maps { CUtensorMap x, xn, out, wqkv, wg, wu, wd, wo; };

__device__ __forceinline__ void mbar_init(uint32_t bar, uint32_t cnt) { asm volatile("mbarrier.init.shared::cta.b64 [%0], %1;" ::"r"(bar), "r"(cnt)); }
__device__ __forceinline__ void mbar_expect_tx(uint32_t bar, uint32_t bytes) { asm volatile("mbarrier.arrive.expect_tx.shared::cta.b64 _, [%0], %1;" ::"r"(bar), "r"(bytes) : "memory"); }
__device__ __forceinline__ void mbar_arrive(uint32_t bar) { asm volatile("mbarrier.arrive.shared::cta.b64 _, [%0];" ::"r"(bar) : "memory"); }
__device__ __forceinline__ void mbar_arrive_cl(uint32_t bar) { asm volatile("mbarrier.arrive.shared::cluster.b64 _, [%0];" ::"r"(bar) : "memory"); }
__device__ __forceinline__ uint32_t mapa(uint32_t a, uint32_t cta) { uint32_t r; asm("mapa.shared::cluster.u32 %0, %1, %2;" : "=r"(r) : "r"(a), "r"(cta)); return r; }
__device__ __forceinline__ void mbar_wait(uint32_t bar, uint32_t parity) {
  asm volatile("{\n.reg .pred p;\n.reg .u32 n;\nmov.u32 n, 0;\nLAB_WAIT:\nmbarrier.try_wait.parity.shared::cta.b64 p, [%0], %1;\n@p bra LAB_DONE;\n"
               "add.u32 n, n, 1;\nsetp.gt.u32 p, n, 4000000;\n@p trap;\nbra LAB_WAIT;\nLAB_DONE:\n}" ::"r"(bar), "r"(parity) : "memory");
}
__device__ __forceinline__ void mbar_spin(uint32_t bar, uint32_t parity, uint32_t zero) {
  asm volatile("{\n.reg .pred p, z;\nsetp.ne.u32 z, %2, 0;\nLAB_WAIT:\nmbarrier.try_wait.parity.shared::cta.b64 p, [%0], %1;\n@p bra LAB_DONE;\n@z trap;\nbra LAB_WAIT;\nLAB_DONE:\n}" ::"r"(bar), "r"(parity), "r"(zero) : "memory");
}
__device__ __forceinline__ void flag_wait(const unsigned* f, unsigned target) {
  asm volatile("{\n.reg .pred p;\n.reg .u32 n, v;\nmov.u32 n, 0;\nLAB_WAIT:\nld.relaxed.gpu.global.u32 v, [%0];\nsub.u32 v, v, %1;\nsetp.ge.s32 p, v, 0;\n@p bra LAB_DONE;\n"
               "nanosleep.u32 100;\nadd.u32 n, n, 1;\nsetp.gt.u32 p, n, 4000000;\n@p trap;\nbra LAB_WAIT;\nLAB_DONE:\nfence.acquire.gpu;\n}" ::"l"(f), "r"(target) : "memory");
}
__device__ __forceinline__ void flag_add(unsigned* f) { asm volatile("red.release.gpu.global.add.u32 [%0], 1;" ::"l"(f) : "memory"); }
__device__ __forceinline__ void fence_async() { asm volatile("fence.proxy.async.global;" ::: "memory"); }
__device__ __forceinline__ bool elect_one() { uint32_t p; asm volatile("{\n.reg .pred P;\nelect.sync _|P, 0xffffffff;\nselp.u32 %0, 1, 0, P;\n}" : "=r"(p)); return p; }
__device__ __forceinline__ void bar_sync(int id, int n) { asm volatile("bar.sync %0, %1;" ::"r"(id), "r"(n) : "memory"); }
__device__ __forceinline__ void bar_arrive(int id, int n) { asm volatile("bar.arrive %0, %1;" ::"r"(id), "r"(n) : "memory"); }

__device__ __forceinline__ void tma2d(uint32_t dst, const CUtensorMap* tm, uint32_t bar, int c0, int c1, uint64_t hint) {
  asm volatile("cp.async.bulk.tensor.2d.shared::cluster.global.mbarrier::complete_tx::bytes.L2::cache_hint [%0], [%1, {%3, %4}], [%2], %5;" ::"r"(dst), "l"(tm), "r"(bar), "r"(c0), "r"(c1), "l"(hint) : "memory");
}
__device__ __forceinline__ void tma2d_mc(uint32_t dst, const CUtensorMap* tm, uint32_t bar, int c0, int c1, uint64_t hint) {
  asm volatile("cp.async.bulk.tensor.2d.shared::cluster.global.mbarrier::complete_tx::bytes.multicast::cluster.L2::cache_hint [%0], [%1, {%3, %4}], [%2], %5, %6;" ::"r"(dst), "l"(tm), "r"(bar), "r"(c0), "r"(c1), "h"((uint16_t)3), "l"(hint) : "memory");
}
__device__ __forceinline__ void tma3d(uint32_t dst, const CUtensorMap* tm, uint32_t bar, int c0, int c1, int c2, uint64_t hint) {
  asm volatile("cp.async.bulk.tensor.3d.shared::cluster.global.mbarrier::complete_tx::bytes.L2::cache_hint [%0], [%1, {%3, %4, %5}], [%2], %6;" ::"r"(dst), "l"(tm), "r"(bar), "r"(c0), "r"(c1), "r"(c2), "l"(hint) : "memory");
}
__device__ __forceinline__ void tma5d(uint32_t dst, const CUtensorMap* tm, uint32_t bar, int c0, int c4, uint64_t hint) {
  asm volatile("cp.async.bulk.tensor.5d.shared::cluster.global.mbarrier::complete_tx::bytes.L2::cache_hint [%0], [%1, {%3, %5, %5, %5, %4}], [%2], %6;" ::"r"(dst), "l"(tm), "r"(bar), "r"(c0), "r"(c4), "r"(0), "l"(hint) : "memory");
}
__device__ __forceinline__ void tma5d_prefetch(const CUtensorMap* tm, int c0, int c4) {
  asm volatile("cp.async.bulk.prefetch.tensor.5d.L2.global [%0, {%1, %3, %3, %3, %2}];" ::"l"(tm), "r"(c0), "r"(c4), "r"(0) : "memory");
}
__device__ __forceinline__ void tma3d_store(const CUtensorMap* tm, uint32_t src, int c0, int c1, int c2) {
  asm volatile("cp.async.bulk.tensor.3d.global.shared::cta.bulk_group [%0, {%2, %3, %4}], [%1];" ::"l"(tm), "r"(src), "r"(c0), "r"(c1), "r"(c2) : "memory");
}
__device__ __forceinline__ void bulk_load(uint32_t dst, const void* src, uint32_t bytes, uint32_t bar, uint64_t hint) {
  asm volatile("cp.async.bulk.shared::cluster.global.mbarrier::complete_tx::bytes.L2::cache_hint [%0], [%1], %2, [%3], %4;" ::"r"(dst), "l"(src), "r"(bytes), "r"(bar), "l"(hint) : "memory");
}
__device__ __forceinline__ void bulk_load_mc(uint32_t dst, const void* src, uint32_t bytes, uint32_t bar, uint64_t hint) {
  asm volatile("cp.async.bulk.shared::cluster.global.mbarrier::complete_tx::bytes.multicast::cluster.L2::cache_hint [%0], [%1], %2, [%3], %4, %5;" ::"r"(dst), "l"(src), "r"(bytes), "r"(bar), "h"((uint16_t)3), "l"(hint) : "memory");
}
__device__ __forceinline__ uint4 lds128(uint32_t a) { uint4 v; asm volatile("ld.shared.v4.b32 {%0,%1,%2,%3}, [%4];" : "=r"(v.x), "=r"(v.y), "=r"(v.z), "=r"(v.w) : "r"(a) : "memory"); return v; }
__device__ __forceinline__ void sts128(uint32_t a, uint4 v) { asm volatile("st.shared.v4.b32 [%0], {%1,%2,%3,%4};" ::"r"(a), "r"(v.x), "r"(v.y), "r"(v.z), "r"(v.w) : "memory"); }
__device__ __forceinline__ void stg128(void* p, uint32_t a, uint32_t b, uint32_t c, uint32_t d) { asm volatile("st.global.v4.b32 [%0], {%1,%2,%3,%4};" ::"l"(p), "r"(a), "r"(b), "r"(c), "r"(d) : "memory"); }

__device__ __forceinline__ uint32_t pack2(float lo, float hi) { uint32_t r; asm("cvt.rn.bf16x2.f32 %0, %1, %2;" : "=r"(r) : "f"(hi), "f"(lo)); return r; }
__device__ __forceinline__ float lo_f(uint32_t v) { return __uint_as_float(v << 16); }
__device__ __forceinline__ float hi_f(uint32_t v) { return __uint_as_float(v & 0xffff0000u); }
__device__ __forceinline__ float bf16r(float v) { return lo_f(pack2(v, 0.f)); }
__device__ __forceinline__ uint32_t mul2(uint32_t a, uint32_t b) { uint32_t r; asm("mul.rn.bf16x2 %0, %1, %2;" : "=r"(r) : "r"(a), "r"(b)); return r; }
__device__ __forceinline__ uint32_t add2(uint32_t a, uint32_t b) { uint32_t r; asm("add.rn.bf16x2 %0, %1, %2;" : "=r"(r) : "r"(a), "r"(b)); return r; }
__device__ __forceinline__ uint32_t sub2(uint32_t a, uint32_t b) { uint32_t r; asm("sub.rn.bf16x2 %0, %1, %2;" : "=r"(r) : "r"(a), "r"(b)); return r; }
__device__ __forceinline__ uint32_t fma2(uint32_t a, uint32_t b, uint32_t c) { uint32_t r; asm("fma.rn.bf16x2 %0, %1, %2, %3;" : "=r"(r) : "r"(a), "r"(b), "r"(c)); return r; }
__device__ __forceinline__ uint32_t max2(uint32_t a, uint32_t b) { uint32_t r; asm("max.bf16x2 %0, %1, %2;" : "=r"(r) : "r"(a), "r"(b)); return r; }
__device__ __forceinline__ float ex2f(float x) { float y; asm("ex2.approx.ftz.f32 %0, %1;" : "=f"(y) : "f"(x)); return y; }
__device__ __forceinline__ float rcpf(float x) { float y; asm("rcp.approx.ftz.f32 %0, %1;" : "=f"(y) : "f"(x)); return y; }
constexpr float GELU_C1 = 0.7978845608028654f, GELU_C3 = 0.035677408136300125f;
__device__ __forceinline__ float gelu_k(float g, float c1, float c3, float k) {
  float t;
  asm("tanh.approx.f32 %0, %1;" : "=f"(t) : "f"(g * fmaf(g * g, c3, c1)));
  g *= k;
  return fmaf(g, t, g);
}
__device__ __forceinline__ float silu_half(float z) { float t; asm("tanh.approx.f32 %0, %1;" : "=f"(t) : "f"(z)); return fmaf(z, t, z); }

__device__ __forceinline__ void wg_fence() { asm volatile("wgmma.fence.sync.aligned;" ::: "memory"); }
__device__ __forceinline__ void wg_commit() { asm volatile("wgmma.commit_group.sync.aligned;" ::: "memory"); }
template <int N> __device__ __forceinline__ void wg_wait() { asm volatile("wgmma.wait_group.sync.aligned %0;" ::"n"(N) : "memory"); }
#define A8(o) "+f"(d[(o)]), "+f"(d[(o) + 1]), "+f"(d[(o) + 2]), "+f"(d[(o) + 3]), "+f"(d[(o) + 4]), "+f"(d[(o) + 5]), "+f"(d[(o) + 6]), "+f"(d[(o) + 7])
#define A64(o) A8(o), A8((o) + 8), A8((o) + 16), A8((o) + 24), A8((o) + 32), A8((o) + 40), A8((o) + 48), A8((o) + 56)
#define REGS0_63 "%0,%1,%2,%3,%4,%5,%6,%7,%8,%9,%10,%11,%12,%13,%14,%15,%16,%17,%18,%19,%20,%21,%22,%23,%24,%25,%26,%27,%28,%29,%30,%31," \
                 "%32,%33,%34,%35,%36,%37,%38,%39,%40,%41,%42,%43,%44,%45,%46,%47,%48,%49,%50,%51,%52,%53,%54,%55,%56,%57,%58,%59,%60,%61,%62,%63"
#define REGS64_127 "%64,%65,%66,%67,%68,%69,%70,%71,%72,%73,%74,%75,%76,%77,%78,%79,%80,%81,%82,%83,%84,%85,%86,%87,%88,%89,%90,%91,%92,%93,%94,%95," \
                   "%96,%97,%98,%99,%100,%101,%102,%103,%104,%105,%106,%107,%108,%109,%110,%111,%112,%113,%114,%115,%116,%117,%118,%119,%120,%121,%122,%123,%124,%125,%126,%127"
__device__ __forceinline__ void desc_add(uint64_t& x, int v) { asm volatile("{\n.reg .b32 lo, hi;\nmov.b64 {lo, hi}, %0;\nadd.s32 lo, lo, %1;\nmov.b64 %0, {lo, hi};\n}" : "+l"(x) : "r"(v)); }
template <int ACCUM> __device__ __forceinline__ void wgmma256(float (&d)[128], uint64_t& a, uint64_t& b, int da, int db) {
  asm volatile("{\n.reg .pred p;\nsetp.ne.b32 p, %130, 0;\n"
               "wgmma.mma_async.sync.aligned.m64n256k16.f32.bf16.bf16 {" REGS0_63 "," REGS64_127 "}, %128, %129, p, 1, 1, 0, 1;\n}"
               : A64(0), A64(64) : "l"(a), "l"(b), "n"(ACCUM));
  desc_add(a, da); desc_add(b, db);
}
__device__ __forceinline__ void wgmma256_rs(float (&d)[128], uint32_t a0, uint32_t a1, uint32_t z0, uint32_t z1, uint32_t b_lo) {
  asm volatile("{\n.reg .b64 db;\nmov.b64 db, {%132, 0x00000008};\n"
               "wgmma.mma_async.sync.aligned.m64n256k16.f32.bf16.bf16 {" REGS0_63 "," REGS64_127 "}, {%128,%129,%130,%131}, db, 1, 1, 1, 0;\n}"
               : A64(0), A64(64) : "r"(a0), "r"(a1), "r"(z0), "r"(z1), "r"(b_lo));
}
template <int ACCUM> __device__ __forceinline__ void wgmma128(float (&d)[64], uint64_t& a, uint64_t& b, int da, int db) {
  asm volatile("{\n.reg .pred p;\nsetp.ne.b32 p, %66, 0;\n"
               "wgmma.mma_async.sync.aligned.m64n128k16.f32.bf16.bf16 {" REGS0_63 "}, %64, %65, p, 1, 1, 0, 1;\n}"
               : A64(0) : "l"(a), "l"(b), "n"(ACCUM));
  desc_add(a, da); desc_add(b, db);
}
template <int ACCUM> __device__ __forceinline__ void hmma(float (&c)[4], uint32_t a0, uint32_t a1, uint32_t a2, uint32_t a3, uint32_t b0, uint32_t b1) {
  if (ACCUM)
    asm volatile("mma.sync.aligned.m16n8k16.row.col.f32.bf16.bf16.f32 {%0,%1,%2,%3}, {%4,%5,%6,%7}, {%8,%9}, {%0,%1,%2,%3};"
                 : "+f"(c[0]), "+f"(c[1]), "+f"(c[2]), "+f"(c[3]) : "r"(a0), "r"(a1), "r"(a2), "r"(a3), "r"(b0), "r"(b1));
  else
    asm volatile("mma.sync.aligned.m16n8k16.row.col.f32.bf16.bf16.f32 {%0,%1,%2,%3}, {%4,%5,%6,%7}, {%8,%9}, {%10,%10,%10,%10};"
                 : "=f"(c[0]), "=f"(c[1]), "=f"(c[2]), "=f"(c[3]) : "r"(a0), "r"(a1), "r"(a2), "r"(a3), "r"(b0), "r"(b1), "f"(0.f));
}
__device__ __forceinline__ uint32_t movm(uint32_t a) { uint32_t d; asm volatile("movmatrix.sync.aligned.m8n8.trans.b16 %0, %1;" : "=r"(d) : "r"(a)); return d; }
__device__ __forceinline__ int lane_here() { int v; asm volatile("mov.u32 %0, %%laneid;" : "=r"(v)); return v; }
template <int N> __device__ __forceinline__ void pin(uint32_t* r) {
#pragma unroll
  for (int i = 0; i < N; i++) asm volatile("" : "+r"(r[i]));
}
template <int N> __device__ __forceinline__ void pin(float* r) {
#pragma unroll
  for (int i = 0; i < N; i++) asm volatile("" : "+f"(r[i]));
}
__device__ __forceinline__ void sched_fence(uint32_t zero) {
  asm volatile("{\n.reg .pred p;\nsetp.eq.u32 p, %0, 0;\nLAB_F:\n@p bra.uni LAB_D;\nnanosleep.u32 0;\nbra.uni LAB_F;\nLAB_D:\n}" ::"r"(zero) : "memory");
}
__device__ __forceinline__ uint4 ldsm(uint32_t a) { uint4 v; asm volatile("ldmatrix.sync.aligned.m8n8.x4.shared.b16 {%0,%1,%2,%3}, [%4];" : "=r"(v.x), "=r"(v.y), "=r"(v.z), "=r"(v.w) : "r"(a) : "memory"); return v; }
__device__ __forceinline__ uint4 ldsm_t(uint32_t a) { uint4 v; asm volatile("ldmatrix.sync.aligned.m8n8.x4.trans.shared.b16 {%0,%1,%2,%3}, [%4];" : "=r"(v.x), "=r"(v.y), "=r"(v.z), "=r"(v.w) : "r"(a) : "memory"); return v; }

constexpr int BAR_LAG = 1, BAR_MMA = 2, BAR_EV = 3;

struct Cons {
  uint32_t sb;
  mutable uint64_t a, b;
  int k1, k2, k4, k4w, b1;
  uint32_t rel;
  bool do_rel;
  int wg;
  uint32_t zero;
};
#define REL_TS(n) TS(64 + (n))
constexpr uint32_t DB_LO = (SM_BASE >> 4) | ((8192 >> 4) << 16);

template <int ST, int ACCUM, bool WAIT = true> __device__ __forceinline__ void p1_issue(float (&acc)[128], const Cons& c, uint32_t parity) {
  if (WAIT) mbar_spin(c.sb + B_F1 + 8 * ST, parity, c.zero);
  wg_fence();
  wgmma256<ACCUM>(acc, c.a, c.b, c.k1, c.b1);
  wgmma256<1>(acc, c.a, c.b, c.k2, c.b1);
  wgmma256<1>(acc, c.a, c.b, c.k1, c.b1);
  wgmma256<1>(acc, c.a, c.b, ST == 3 ? c.k4w : c.k4, ST == 3 ? -6144 - 384 : 2048 - 384);
  wg_commit();
}
__device__ __forceinline__ void release(const Cons& c, uint32_t bar) { if (c.do_rel) mbar_arrive_cl(c.rel + bar); }
template <int KB, bool WAIT = true, int LAG = 2> __device__ __forceinline__ void p1_step(float (&acc)[128], const Cons& c) {
  if (KB == 16 - LAG) { if (c.wg == 1) { wg_wait<0>(); release(c, B_E1 + 8 * ((KB - 1) & 3)); bar_sync(BAR_LAG, 256); } }
  p1_issue<KB & 3, KB != 0, WAIT>(acc, c, (KB >> 2) & 1);
  if (KB == 15) { if (c.wg == 0) bar_arrive(BAR_LAG, 256); }
  if (KB > 0) { wg_wait<1>(); if (KB != 16 - LAG || c.wg == 0) release(c, B_E1 + 8 * ((KB - 1) & 3)); }
  if (KB == 15) { wg_wait<0>(); release(c, B_E1 + 8 * 3); }
}
__device__ __forceinline__ void p1_loop(float (&acc)[128], const Cons& c, int from, int to) {
#pragma unroll 1
  for (int kb = from; kb < to; kb++) {
    const bool wrap = (kb & 3) == 3;
    mbar_spin(c.sb + B_F1 + 8 * (kb & 3), (kb >> 2) & 1, c.zero);
    wg_fence();
    wgmma256<1>(acc, c.a, c.b, c.k1, c.b1);
    wgmma256<1>(acc, c.a, c.b, c.k2, c.b1);
    wgmma256<1>(acc, c.a, c.b, c.k1, c.b1);
    wgmma256<1>(acc, c.a, c.b, wrap ? c.k4w : c.k4, wrap ? -6144 - 384 : 2048 - 384);
    wg_commit();
    wg_wait<1>();
    release(c, B_E1 + 8 * ((kb - 1) & 3));
  }
}
template <int T> __device__ __forceinline__ void p2_step(float (&acc)[64], const Cons& c) {
  if (T == 16 - LAG2) { if (c.wg == 1) bar_sync(BAR_LAG, 256); }
  mbar_spin(c.sb + B_F2 + 8 * (T % 5), (T / 5) & 1, c.zero);
  wg_fence();
  wgmma128<T != 0>(acc, c.a, c.b, c.k1, c.b1);
  wgmma128<1>(acc, c.a, c.b, c.k2, c.b1);
  wgmma128<1>(acc, c.a, c.b, c.k1, c.b1);
  wgmma128<1>(acc, c.a, c.b, ((int)p2_a((T + 1) % 5) - (int)p2_a(T % 5)) / 16 - 514, ((int)p2_b((T + 1) % 5) - (int)p2_b(T % 5)) / 16 - 384);
  wg_commit();
  if (T == 15) { if (c.wg == 0) bar_arrive(BAR_LAG, 256); }
  if (T <= 11) { wg_wait<1>(); release(c, T ? B_E2 + 8 * ((T + 5 - 1) % 5) : B_E1 + 8); }
}

template <int P> __device__ __forceinline__ void geglu_piece(const uint32_t (&pk)[64], uint8_t* dst, const float (&rs)[2]) {
  constexpr int cg = P >> 1, r = P & 1;
  const float r2 = rs[r] * rs[r], c1 = GELU_C1 * rs[r], c3 = GELU_C3 * r2 * rs[r], k = 0.25f * r2;
  uint32_t v[4];
#pragma unroll
  for (int i = 0; i < 4; i++) {
    const uint32_t g = pk[2 * (4 * cg + i) + r];
    v[i] = mul2(pack2(gelu_k(lo_f(g), c1, c3, k), gelu_k(hi_f(g), c1, c3, k)), pk[32 + 2 * (4 * cg + i) + r]);
  }
  stg128(dst + cg * 8192 + r * 512, v[0], v[1], v[2], v[3]);
}
template <int KB> __device__ __forceinline__ void geglu_tile(float (&acc)[128], const uint32_t (&pk)[64], const Cons& c, uint8_t* dst, int ev, const float (&rs)[2]) {
  if constexpr (KB < 9) {
    p1_step<KB>(acc, c);
    if (KB == 0) { const int lane = lane_here(); dst += (lane ^ (lane >> 3)) << 4; }
    if (KB >= 1 && KB <= 8) geglu_piece<(KB - 1) & 7>(pk, dst, rs);
    if (KB == 8) bar_arrive(ev, 288);
    geglu_tile<KB + 1>(acc, pk, c, dst, ev, rs);
  }
}

__device__ __forceinline__ void attn_tile(float (&acc)[128], const uint32_t (&pk)[64], const Cons& c, int round, int warp, int m, Scratch* gs, uint8_t* hdst, uint8_t* odst) {
  const int w = warp & 3;
  const uint32_t at = c.sb + OFF_X + c.wg * AT_WG;
  uint32_t gg[16];
  p1_step<0>(acc, c);
  p1_step<1>(acc, c);
  int lane = lane_here();
  const uint32_t swz = (lane ^ (lane >> 3)) << 4;
  hdst += swz;
#pragma unroll
  for (int i = 0; i < 4; i++) {
    const int h = i & 1, r = i >> 1;
    sts128(at + AT_V + (2 * w + r) * 1024 + h * 512 + swz, make_uint4(pk[32 + 8 * h + r], pk[34 + 8 * h + r], pk[36 + 8 * h + r], pk[38 + 8 * h + r]));
  }
  if (w < 3) {
#pragma unroll
    for (int i = 0; i < 8; i++) asm volatile("st.shared.b32 [%0], %1;" ::"r"(at + AT_K + w * 1024 + i * 128 + lane * 4), "r"(pk[17 + 2 * i]) : "memory");
  } else {
    uint8_t* g = (uint8_t*)gs->halo + ((round * 128 + blockIdx.x) * 2 + c.wg) * 2048;
#pragma unroll
    for (int i = 0; i < 8; i++) asm volatile("st.global.b32 [%0], %1;" ::"l"(g + i * 128 + lane * 4), "r"(pk[17 + 2 * i]) : "memory");
#pragma unroll
    for (int h = 0; h < 2; h++) stg128(g + 1024 + h * 512 + swz, pk[33 + 8 * h], pk[35 + 8 * h], pk[37 + 8 * h], pk[39 + 8 * h]);
    bar_arrive(BAR_EV + 2 + round, 96);
  }
  __syncwarp();
  if (lane == 0) mbar_arrive(c.sb + B_HALO + 8 * round);
  if (round) {
#pragma unroll
    for (int p = 0; p < 4; p++) asm volatile("ld.global.cg.v4.b32 {%0,%1,%2,%3}, [%4];" : "=r"(gg[4 * p]), "=r"(gg[4 * p + 1]), "=r"(gg[4 * p + 2]), "=r"(gg[4 * p + 3]) : "l"(hdst + (p >> 1) * 8192 + (p & 1) * 512) : "memory");
  }
  auto gu_piece = [&](int p) {
    uint32_t v[4];
#pragma unroll
    for (int i = 0; i < 4; i++) {
      const uint32_t g = pk[48 + 8 * (p >> 1) + 2 * i + (p & 1)];
      v[i] = mul2(round ? gg[4 * p + i] : 0x3e803e80u, round ? g : pack2(gelu_k(lo_f(g), GELU_C1, GELU_C3, 1.0f), gelu_k(hi_f(g), GELU_C1, GELU_C3, 1.0f)));
    }
    stg128(hdst + (p >> 1) * 8192 + (p & 1) * 512, v[0], v[1], v[2], v[3]);
  };
  p1_step<2>(acc, c);
  p1_step<3>(acc, c); gu_piece(0);
  p1_step<4>(acc, c); gu_piece(1);
  p1_step<5>(acc, c); gu_piece(2);
  p1_step<6>(acc, c); gu_piece(3);
  p1_loop(acc, c, 7, 9);
  const bool first = m == 0 && w == 0;
  uint32_t kl[16];
  mbar_spin(c.sb + B_HALO + 8 * round, 0, c.zero);
  lane = lane_here();
  {
    const uint32_t ka = at + lane * 4 + (w ? AT_K + (w - 1) * 1024 : (first ? AT_K : AT_REM + round * 2048));
#pragma unroll
    for (int i = 0; i < 8; i++) {
      asm volatile("ld.shared.b32 %0, [%1];" : "=r"(kl[2 * i]) : "r"(ka + i * 128) : "memory");
      kl[2 * i + 1] = pk[16 + 2 * i] | c.zero;
    }
  }
  float st[4][4];
  pin<16>(kl);
  bar_sync(BAR_MMA, 256);
  mbar_spin(c.sb + B_F1 + 8 * 1, 0, c.zero);
#pragma unroll
  for (int ks = 0; ks < 2; ks++) {
#pragma unroll
    for (int h = 0; h < 2; h++) {
      const int o = 8 * h + 4 * ks;
      if (ks == 0) { hmma<0>(st[2 * h], kl[o], kl[o + 1], kl[o + 2], kl[o + 3], pk[o], pk[o + 2]); hmma<0>(st[2 * h + 1], pk[16 + o], pk[17 + o], pk[18 + o], pk[19 + o], pk[o + 1], pk[o + 3]); }
      else { hmma<1>(st[2 * h], kl[o], kl[o + 1], kl[o + 2], kl[o + 3], pk[o], pk[o + 2]); hmma<1>(st[2 * h + 1], pk[16 + o], pk[17 + o], pk[18 + o], pk[19 + o], pk[o + 1], pk[o + 3]); }
    }
  }
  sched_fence(c.zero);
  bar_sync(BAR_MMA, 256);
  p1_step<9, false>(acc, c);
  sched_fence(c.zero);
  pin<16>(&st[0][0]);
  lane = lane_here();
  const int rho = lane >> 2, q = lane & 3;
  const bool le0 = 2 * q <= rho, le1 = 2 * q + 1 <= rho;
  uint32_t la[2], lb[2], mx[2];
#pragma unroll
  for (int h = 0; h < 2; h++) {
    uint32_t l[2];
#pragma unroll
    for (int r = 0; r < 2; r++) {
      const float (&t)[4] = st[2 * h + r];
      l[r] = movm(pack2(rho <= 2 * q ? t[2] : t[0], rho <= 2 * q + 1 ? t[3] : t[1]));
      l[r] = fma2(l[r], 0x3e353e35u, mul2(l[r], 0x379e379eu));
    }
    la[h] = __byte_perm(l[0], l[1], 0x5410); lb[h] = __byte_perm(l[0], l[1], 0x7632);
    if (first && !le0) la[h] = (la[h] & 0xffff0000u) | 0xce6eu;
    if (first && !le1) lb[h] = (lb[h] & 0xffff0000u) | 0xce6eu;
    mx[h] = max2(la[h], lb[h]);
  }
#pragma unroll
  for (int o = 1; o <= 2; o++) { mx[0] = max2(mx[0], __shfl_xor_sync(~0u, mx[0], o)); mx[1] = max2(mx[1], __shfl_xor_sync(~0u, mx[1], o)); }
  const float L2E = 1.4426950408889634f;
  float pr[2][4], z[4];
#pragma unroll
  for (int h = 0; h < 2; h++) {
    pr[h][0] = ex2f((lo_f(la[h]) - lo_f(mx[h])) * L2E); pr[h][1] = ex2f((lo_f(lb[h]) - lo_f(mx[h])) * L2E);
    pr[h][2] = ex2f((hi_f(la[h]) - hi_f(mx[h])) * L2E); pr[h][3] = ex2f((hi_f(lb[h]) - hi_f(mx[h])) * L2E);
    z[2 * h] = pr[h][0] + pr[h][1]; z[2 * h + 1] = pr[h][2] + pr[h][3];
  }
  p1_step<10>(acc, c);
#pragma unroll
  for (int o = 1; o <= 2; o++) {
#pragma unroll
    for (int i = 0; i < 4; i++) z[i] += __shfl_xor_sync(~0u, z[i], o);
  }
  const uint32_t LE = (le0 ? 0xffffu : 0u) | (le1 ? 0xffff0000u : 0u);
  uint32_t P[4][2];
  uint4 vt[4][2];
  {
    const uint32_t row = (lane & 7) * 64 + ((((lane >> 3) & 1) ^ ((lane & 7) >> 1)) << 4);
    const uint32_t v1 = at + AT_V + (2 * w + (lane >> 4)) * 1024 + row;
    const uint32_t v0 = (w || lane >= 16) ? v1 - 1024 : (first ? v1 : at + AT_REM + round * 2048 + 1024 + row);
#pragma unroll
    for (int i = 0; i < 4; i++) {
      const float rz = rcpf(z[i]);
      const uint32_t p = pack2(pr[i >> 1][2 * (i & 1)] * rz, pr[i >> 1][2 * (i & 1) + 1] * rz);
      P[i][0] = p & ~LE; P[i][1] = p & LE;
      const uint32_t a = ((i & 1) ? v1 : v0) + (i >> 1) * 512;
      vt[i][0] = ldsm_t(a); vt[i][1] = ldsm_t(a ^ 32);
    }
  }
  float ot[4][2][4];
  pin<8>(&P[0][0]);
  bar_sync(BAR_MMA, 256);
  mbar_spin(c.sb + B_F1 + 8 * 3, 0, c.zero);
#pragma unroll
  for (int i = 0; i < 8; i++) { const uint4& v = vt[i >> 1][i & 1]; hmma<0>(ot[i >> 1][i & 1], v.x, v.y, v.z, v.w, P[i >> 1][0], P[i >> 1][1]); }
  sched_fence(c.zero);
  bar_sync(BAR_MMA, 256);
  p1_step<11, false>(acc, c);
  sched_fence(c.zero);
  pin<32>(&ot[0][0][0]);
  lane = lane_here();
  odst += (lane ^ (lane >> 3)) << 4;
  auto o_piece = [&](int i) {
    stg128(odst + (i >> 1) * 8192 + (i & 1) * 512, movm(pack2(ot[i][0][0], ot[i][0][1])), movm(pack2(ot[i][0][2], ot[i][0][3])), movm(pack2(ot[i][1][0], ot[i][1][1])), movm(pack2(ot[i][1][2], ot[i][1][3])));
  };
  o_piece(0); o_piece(1);
  p1_step<12>(acc, c);
  o_piece(2); o_piece(3);
  if (round) bar_arrive(BAR_EV + 4, 288);
}

__device__ __forceinline__ void ln_moments(const uint32_t* raw, float& c0, float& s, float& v) {
  c0 = lo_f(__shfl_sync(~0u, raw[0], 0));
  float ss[4] = {0.f, 0.f, 0.f, 0.f}, vv[4] = {0.f, 0.f, 0.f, 0.f};
#pragma unroll
  for (int i = 0; i < 16; i++) {
    const float a = lo_f(raw[i]) - c0, b = hi_f(raw[i]) - c0;
    ss[(2 * i) & 3] += a; ss[(2 * i + 1) & 3] += b;
    vv[(2 * i) & 3] = fmaf(a, a, vv[(2 * i) & 3]); vv[(2 * i + 1) & 3] = fmaf(b, b, vv[(2 * i + 1) & 3]);
  }
  s = (ss[0] + ss[1]) + (ss[2] + ss[3]); v = (vv[0] + vv[1]) + (vv[2] + vv[3]);
}
__device__ __forceinline__ void ln_reduce(float& s, float& v) {
#pragma unroll
  for (int o = 16; o; o >>= 1) { s += __shfl_xor_sync(~0u, s, o); v += __shfl_xor_sync(~0u, v, o); }
}
__device__ __forceinline__ uint32_t ln_finish(float c0, float s, float v) {
  s *= 1.0f / DM;
  float sd;
  asm("sqrt.approx.ftz.f32 %0, %1;" : "=f"(sd) : "f"(bf16r(bf16r(fmaxf(fmaf(v, 1.0f / DM, -s * s), 0.f)) + 1e-5f)));
  return pack2(c0 + s, sd);
}
__device__ __forceinline__ void ln_store(const uint32_t* raw, uint32_t st, uint4* dst) {
  const uint32_t m2 = __byte_perm(st, st, 0x1010);
  const float rinv = rcpf(hi_f(st));
  const uint32_t rh = pack2(rinv, rinv), rl = pack2(rinv - hi_f(rh), rinv - hi_f(rh));
#pragma unroll
  for (int c = 0; c < 4; c++) {
    uint32_t v[4];
#pragma unroll
    for (int i = 0; i < 4; i++) { const uint32_t t = sub2(raw[4 * c + i], m2); v[i] = fma2(t, rh, mul2(t, rl)); }
    stg128(dst + 32 * c, v[0], v[1], v[2], v[3]);
  }
}
__device__ __forceinline__ void col_sums(uint32_t tile, ulonglong2* part, uint32_t tag) {
  const int lane = threadIdx.x & 31;
  float cs[8] = {0, 0, 0, 0, 0, 0, 0, 0};
  uint32_t base = tile + ((lane >> 3) & 1) * 8192 + (lane >> 4) * 4096 + ((lane & 7) << 4);
#pragma unroll 1
  for (int k0 = 0; k0 < 8; k0++, base = (base ^ ((k0 ^ (k0 - 1)) << 4)) + 128) {
    uint4 v[4];
#pragma unroll
    for (int k = 0; k < 4; k++) v[k] = lds128(base + k * 1024);
#pragma unroll
    for (int k = 0; k < 4; k++) {
      cs[0] += lo_f(v[k].x); cs[1] += hi_f(v[k].x); cs[2] += lo_f(v[k].y); cs[3] += hi_f(v[k].y);
      cs[4] += lo_f(v[k].z); cs[5] += hi_f(v[k].z); cs[6] += lo_f(v[k].w); cs[7] += hi_f(v[k].w);
    }
  }
  const bool up = lane >= 16;
#pragma unroll
  for (int i = 0; i < 2; i++) {
    const float a = (up ? cs[4 + 2 * i] : cs[2 * i]) + __shfl_xor_sync(~0u, up ? cs[2 * i] : cs[4 + 2 * i], 16);
    const float b = (up ? cs[5 + 2 * i] : cs[1 + 2 * i]) + __shfl_xor_sync(~0u, up ? cs[1 + 2 * i] : cs[5 + 2 * i], 16);
    asm volatile("{\n.reg .b64 a, b;\nmov.b64 a, {%1, %3};\nmov.b64 b, {%2, %3};\nst.relaxed.gpu.global.v2.b64 [%0], {a, b};\n}"
                 ::"l"(part + 32 * (i + (up ? 2 : 0)) + (lane & 15)), "r"(__float_as_uint(a)), "r"(__float_as_uint(b)), "r"(tag) : "memory");
  }
  asm volatile("fence.proxy.async.shared::cta;" ::: "memory");
}

__global__ void __cluster_dims__(2, 1, 1) __launch_bounds__(384, 1)
fused_kernel(const uint4* __restrict__ x, const uint4* __restrict__ wgate, const uint4* __restrict__ wup, Scratch* gs, const __grid_constant__ Maps mp) {
  extern __shared__ __align__(1024) uint8_t smem_raw[];
  const uint32_t sb = (uint32_t)__cvta_generic_to_shared(smem_raw);
  const unsigned t_start = 0;
  if (threadIdx.x < 256 && blockIdx.x < NMAIN) {
    const uint32_t r = threadIdx.x >> 3, ch = threadIdx.x & 7;
    const uint32_t d = sb + r * 128 + ((ch ^ (r & 7)) << 4);
    const uint8_t* xa = (const uint8_t*)x + ((blockIdx.x & 15) * 262144 + r * 4096 + ch * 16);
    const uint32_t wo = r * (DFF * 2) + (blockIdx.x >> 4) * 256 + ch * 16;
    const uint8_t *wa = (const uint8_t*)wgate + wo, *wb = (const uint8_t*)wup + wo;
#pragma unroll
    for (int i = 0; i < 12; i++) {
      const int h = i >= 8;
      const uint8_t* src = (i >> 2) == 1 ? xa + (i & 1) * 131072 + ((i >> 1) & 1) * 2048 : ((i & 2) ? wb : wa) + h * 32 * (DFF * 2) + (i & 1) * 128;
      asm volatile("cp.async.cg.shared.global [%0], [%1], 16;" ::"r"(d + ((i >> 2) == 1 ? OFF_A + (i & 3) * 4096 : (i & 3) * 8192 + h * 4096)), "l"(src) : "memory");
    }
    if (threadIdx.x == 0) TS(23);
  }
  const int warp = __shfl_sync(~0u, threadIdx.x >> 5, 0), lane = threadIdx.x & 31;
  const int m = blockIdx.x & 15, j = blockIdx.x >> 4, rank = blockIdx.x & 1;
  const int m2 = blockIdx.x >> 3, j2 = blockIdx.x & 7;
  const bool helper = blockIdx.x >= NMAIN;
  if (warp >= 8) {
    asm volatile("setmaxnreg.dec.sync.aligned.u32 40;");
    if (warp == 8) {
      if (elect_one()) {
        asm volatile("prefetch.tensormap [%0];\nprefetch.tensormap [%1];\nprefetch.tensormap [%2];" ::"l"(&mp.x), "l"(&mp.wg), "l"(&mp.wu) : "memory");
        for (int s = 0; s < 4; s++) mbar_init(sb + B_F1 + 8 * s, 1);
        if (!helper) mbar_arrive(sb + B_F1);
        asm volatile("fence.mbarrier_init.release.cluster;" ::: "memory");
      }
      __syncwarp();
    } else if (warp == 9) {
      if (elect_one()) {
        if ((sb & 0xffffff) != SM_BASE) asm volatile("trap;");
        for (uint32_t b = B_E1; b < B_F2; b += 8) mbar_init(sb + b, 4);
        for (uint32_t b = B_F2; b < B_AUX; b += 8) mbar_init(sb + b, 1);
        for (uint32_t b = B_EX; b < B_AUX; b += 8) mbar_expect_tx(sb + b, 8192);
        mbar_init(sb + B_AUX, 8); mbar_init(sb + B_HALO, 9); mbar_init(sb + B_HALO + 8, 9);
        asm volatile("fence.mbarrier_init.release.cluster;" ::: "memory");
      }
      __syncwarp();
    }
    asm volatile("barrier.cluster.arrive.relaxed.aligned;" ::: "memory");
    if (warp == 8 && !helper) {
      if (elect_one()) {
        TS(0); TG(51);
#pragma unroll 1
        for (int kb = 1; kb < 4; kb++) {
          const uint32_t sa = sb + OFF_A + kb * 16384, sw = sb + kb * 32768, fb = sb + B_F1 + 8 * kb;
          mbar_expect_tx(fb, P1_BYTES);
          tma3d(sa, &mp.x, fb, kb * 64, m * 64, 0, EVICT_NORMAL);
          tma2d(sw, &mp.wg, fb, j * 128, kb * 64, EVICT_NORMAL); tma2d(sw + 16384, &mp.wu, fb, j * 128, kb * 64, EVICT_NORMAL);
          tma2d(sw + 8192, &mp.wg, fb, j * 128 + 64, kb * 64, EVICT_NORMAL); tma2d(sw + 24576, &mp.wu, fb, j * 128 + 64, kb * 64, EVICT_NORMAL);
        }
        TS(7);
      }
      __syncwarp();
    }
    asm volatile("barrier.cluster.wait.aligned;" ::: "memory");
    if (helper) {
      if (warp == 8) {
        unsigned e = 0;
        if (elect_one()) {
#pragma unroll 1
          for (int i = 0; i < 16; i++) {
            const uint32_t fb = sb + B_F1 + 8 * (i >> 2);
            if (!(i & 3)) mbar_expect_tx(fb, P1_BYTES);
            tma5d(sb + i * 8192, &mp.wd, fb, (blockIdx.x - NMAIN) * 256 + (i & 3) * 64, (i >> 2) * 2, HINT_W);
          }
        }
        if (lane == 0) { unsigned* ep = &gs->epoch[blockIdx.x * 2]; e = *ep + 1; *ep = e; }
        e = __shfl_sync(~0u, e, 0);
        if (lane < 16) flag_wait(&gs->flags[(FL_H + lane * 4) * 32], e * 8u);
        __syncwarp();
        if (elect_one()) {
          fence_async();
          TS(0);
#pragma unroll 1
          for (int i = 0; i < 64; i++) {
            const uint32_t fb = sb + B_F1 + 8 * (i & 3);
            if (i >= 4) { mbar_wait(sb + B_E1 + 8 * (i & 3), ~(i >> 2) & 1); mbar_expect_tx(fb, 16384); }
            bulk_load(sb + OFF_A + (i & 3) * 16384, gs->h + ((i >> 2) * 56 + (i & 3)) * 1024, 16384, fb, EVICT_NORMAL);
          }
        }
      } else if (warp == 9) {
#pragma unroll 1
        for (int t = 0; t < 16; t++) {
          bar_sync(BAR_EV + (t & 1), 288);
          if (lane == 0) { flag_add(&gs->flags[(FL_P + t) * 32]); TS(64 + t); }
          __syncwarp();
        }
      }
    } else if (warp == 8) {
      if (elect_one()) {
        uint32_t par = 0;

        auto x_load = [&]() {
          mbar_expect_tx(sb + B_XT, 32768);
          tma3d(sb + OFF_X, &mp.x, sb + B_XT, j2 * 128, m2 * 64, 0, HINT_LAST); tma3d(sb + OFF_X + 16384, &mp.x, sb + B_XT, j2 * 128 + 64, m2 * 64, 0, HINT_LAST);
        };
        auto d_prefetch = [&](int i) {
          if (PF_W == 1 && (m2 >> 2) == (i & 3)) tma5d_prefetch(&mp.wd, (j2 >> 1) * 256 + (m2 & 3) * 64, (2 * i + 4 + rank) * 2);
          if (PF_H == 1 && i < 6) asm volatile("cp.async.bulk.prefetch.L2.global [%0], 4096;" ::"l"(gs->h + (m2 * 56 + 2 * i + 4 + rank) * 1024 + (j2 >> 1) * 256) : "memory");
        };
        for (int R = 0; R < 5; R++) {
          const CUtensorMap *mb0, *mb1;
          int n0, n1;
          if (R == 1 || R == 2) {
            mb0 = &mp.wqkv; n0 = 64 * (j + 8 * (R - 1)) + rank * 2048;
            mb1 = rank ? (R == 1 ? &mp.wg : &mp.wu) : &mp.wqkv; n1 = rank ? 1024 + 64 * j : n0 + 1024;
          } else {
            mb0 = mb1 = rank ? &mp.wu : &mp.wg;
            n0 = 128 * j + (R ? 1024 * R - 1536 : 0); n1 = n0 + 64;
          }
#pragma unroll 1
          for (int kb = R ? 0 : 4; kb < 16; kb++) {
            if (R == 0 && kb == 14) { asm volatile("prefetch.tensormap [%0];\nprefetch.tensormap [%1];" ::"l"(&mp.xn), "l"(&mp.wqkv) : "memory"); }
            if (R == 4 && kb == 2) { asm volatile("prefetch.tensormap [%0];\nprefetch.tensormap [%1];\nprefetch.tensormap [%2];" ::"l"(&mp.wd), "l"(&mp.wo), "l"(&mp.out) : "memory"); }
            if (R == 0 && kb == CS_KB) {
#pragma unroll 1
              for (int h = 0; h < 2; h++) {
                const uint32_t cb = sb + B_CS + 8 * h, d = sb + OFF_X + 16384 * h;
                mbar_expect_tx(cb, 16384);
                tma2d(d, h ? &mp.wu : &mp.wg, cb, n0, m * 64, EVICT_NORMAL); tma2d(d + 8192, h ? &mp.wu : &mp.wg, cb, n1, m * 64, EVICT_NORMAL);
              }
            }
            const int st = kb & 3;
            const uint32_t sa = sb + OFF_A + st * 16384, sw = sb + st * 32768, fb = sb + B_F1 + 8 * st;
            mbar_wait(sb + B_E1 + 8 * st, par);
            if (R * 16 + kb >= 4) REL_TS(R * 16 + kb - 4);
            mbar_expect_tx(fb, P1_BYTES);
            tma2d_mc(sw + rank * 16384, mb0, fb, n0, kb * 64, HINT_W);
            tma2d_mc(sw + 8192 + rank * 16384, mb1, fb, n1, kb * 64, HINT_W);
            if (R == 0) {
              tma3d(sa, &mp.x, fb, kb * 64, m * 64, 0, EVICT_NORMAL);
            } else {
              if (R == 1 && kb == 0) { mbar_wait(sb + B_DEP, 0); TS(1); }
              tma2d(sa, &mp.xn, fb, kb * 64, m * 128, R == 4 ? HINT_LAST : EVICT_NORMAL);
            }
            if (R == 4 && kb == 4 + j2) x_load();
            if (R == 4 && kb >= 16 - PF_D) { if (kb == 16 - PF_D) mbar_wait(sb + B_DEP + 8, 0); d_prefetch(kb + PF_D - 16); }
            if (st == 3) par ^= 1;
          }
        }
#pragma unroll 1
        for (int i = 0; i < 26; i++) {
          const int st = i & 3, kb = 2 * i + 4 + rank;
          const uint32_t sa = sb + OFF_A + st * 16384, sw = sb + st * 32768, fb = sb + B_F1 + 8 * st;
          mbar_wait(sb + B_E1 + 8 * st, par);
          REL_TS(76 + i);
          mbar_expect_tx(fb, P1_BYTES);
          tma5d(sw, &mp.wd, fb, j2 * 128, kb * 2, HINT_W); tma5d(sw + 8192, &mp.wd, fb, j2 * 128 + 64, kb * 2, HINT_W);
          tma5d(sw + 16384, &mp.wd, fb, (j2 ^ 1) * 128, kb * 2, HINT_W); tma5d(sw + 24576, &mp.wd, fb, (j2 ^ 1) * 128 + 64, kb * 2, HINT_W);
          if (i == 0 || i == 6 || i == 10 || i == 18) { mbar_wait(sb + B_DEP + 8 * (1 + ((i + 6) >> 3)), 0); }
          bulk_load(sa, gs->h + (m2 * 56 + kb) * 1024, 16384, fb, HINT_H);
          if (i + PF_D < 26) d_prefetch(i + PF_D);
          if (st == 3) par ^= 1;
        }
        int st = 0; uint32_t par2 = 1;
#pragma unroll 1
        for (int t = 0; t < 16; t++) {
          const uint32_t sa = sb + p2_a(st), sw = sb + p2_b(st), fb = sb + B_F2 + 8 * st;
          if (t < 5) mbar_wait(sb + B_E1 + 8 * (((2 * t + 1) / 3 + 2) & 3), t < 3); else mbar_wait(sb + B_E2 + 8 * st, par2);
          REL_TS(102 + t);
          mbar_expect_tx(fb, P2_BYTES);
          bulk_load_mc(sa + rank * 8192, gs->o + (m2 * 16 + t) * 1024 + rank * 512, 8192, fb, HINT_H);
          tma2d(sw, &mp.wo, fb, j2 * 128, t * 64, HINT_W); tma2d(sw + 8192, &mp.wo, fb, j2 * 128 + 64, t * 64, HINT_W);
          if (++st == 5) { st = 0; par2 ^= 1; }
        }
      }
    } else if (warp == 9) {
#pragma unroll 1
      for (int e = 0; e < 7; e++) {
        const bool halo = e == 2 || e == 3;
        bar_sync(BAR_EV + e, halo ? 96 : 288);
        if (lane == 0) {
          const int f = e == 0 ? FL_XN + m : (halo ? FL_HALO + (e - 2) * 128 + blockIdx.x : FL_H + m * 4 + (e == 1 ? 0 : e - 3));
          TS(10 + 2 * e); TG(52 + e);
          flag_add(&gs->flags[f * 32]);
          if (e < 6) TS(11 + 2 * e);
        }
        __syncwarp();
      }
      mbar_wait(sb + B_DONE, 0);
    } else {
      unsigned e = 0;
      if (lane == 0) {
        unsigned* ep = &gs->epoch[blockIdx.x * 2 + warp - 10];
        e = *ep + 1; *ep = e;
        if (warp == 10) { asm volatile("st.shared.b32 [%0], %1;" ::"r"(sb + OFF_EPOCH), "r"(e) : "memory"); mbar_arrive(sb + B_EP); }
      }
      e = __shfl_sync(~0u, e, 0);
      mbar_wait(sb + B_CS + 8 * (warp - 10), 0);
      if (lane == 0 && warp == 11) TS(6);
      col_sums(sb + OFF_X + (warp - 10) * 16384, gs->cspart + (j * 16 + m) * 128 + (warp - 10) * 16, e);
      if (lane == 0 && warp == 11) TS(9);
      if (warp == 10) {
        if (lane == 0) {
#pragma unroll 1
          for (int g = 0; g < 6; g++) {
            flag_wait(&gs->flags[(g == 5 ? FL_P + m2 : (g ? FL_H + m2 * 4 + g - 1 : FL_XN + m)) * 32], e * (g == 5 ? 4u : 8u));
            fence_async();
            mbar_arrive(sb + B_DEP + 8 * g);
            if (g == 0) TS(8);
          }
#pragma unroll 1
          for (int p = 0; p < 8; p++) {
            asm volatile("cp.async.bulk.prefetch.L2.global [%0], 4096;" ::"l"(gs->dpart + blockIdx.x * 2048 + p * 256) : "memory");
            __nanosleep(PF_SLEEP);
          }
        }
      } else
      if (elect_one()) {
#pragma unroll 1
        for (int r = 0; r < 2; r++) {
          const uint32_t hb = sb + B_HALO + 8 * r;
          if (r) mbar_wait(sb + B_HALO, 0);
          if (m) {
            flag_wait(&gs->flags[(FL_HALO + r * 128 + blockIdx.x - 1) * 32], e);
            fence_async();
            mbar_expect_tx(hb, 4096);
            for (int g = 0; g < 2; g++) bulk_load(sb + OFF_X + g * AT_WG + AT_REM + r * 2048, gs->halo + ((r * 128 + blockIdx.x - 1) * 2 + g) * 128, 2048, hb, EVICT_FIRST);
          } else {
            mbar_arrive(hb);
          }
          TS(34 + r);
        }
      }
    }
  } else {
    asm volatile("barrier.cluster.arrive.relaxed.aligned;" ::: "memory");
    asm volatile("setmaxnreg.inc.sync.aligned.u32 232;");
    const int wg = warp >> 2, w = warp & 3;
    Cons c;
    c.sb = sb; c.wg = wg; c.zero = warp >> 8;
    c.a = 0x4000004000010000ull + ((SM_BASE + OFF_A + wg * 8192) >> 4); c.k1 = 2 + c.zero; c.k2 = 2; c.k4 = 1024 - 6; c.k4w = -3072 - 6; c.b1 = 128 + c.zero;
    c.b = 0x4000004000000000ull + DB_LO + c.zero;
    c.rel = mapa(sb, threadIdx.x & 1);
    c.do_rel = (threadIdx.x & 127) < 2;
    constexpr bool t0 = false;
    float acc[128];
    uint32_t pk[64];
    float rs[2];
    const int rho = lane >> 2, q = lane & 3;

    if (helper) {
      asm volatile("barrier.cluster.wait.aligned;" ::: "memory");
      c.a = 0x8000002000010000ull + ((SM_BASE + OFF_A + wg * 4096) >> 4); c.k2 = 510; c.k4 = 1024 - 514; c.k4w = -3072 - 514;
      c.rel = sb;
      uint4* dst = gs->dpart + (blockIdx.x - NMAIN) * 4096 + threadIdx.x;
      auto put = [&](int p) {
#pragma unroll
        for (int i = 4 * p; i < 4 * p + 4; i++) stg128(dst + i * 256, pk[4 * i], pk[4 * i + 1], pk[4 * i + 2], pk[4 * i + 3]);
      };
#pragma unroll 1
      for (int t = 0; t < 16; t++) {
        p1_issue<0, 0>(acc, c, t & 1);
        if (t) put(0);
        p1_issue<1, 1>(acc, c, t & 1); wg_wait<1>(); release(c, B_E1);
        if (t) put(1);
        if (wg == 1) { wg_wait<0>(); release(c, B_E1 + 8); bar_sync(BAR_LAG, 256); }
        p1_issue<2, 1>(acc, c, t & 1); wg_wait<1>(); if (wg == 0) release(c, B_E1 + 8);
        if (t) put(2);
        p1_issue<3, 1>(acc, c, t & 1);
        if (wg == 0) bar_arrive(BAR_LAG, 256);
        if (t) { put(3); bar_arrive(BAR_EV + (~t & 1), 288); dst += 8 * 2048; }
        wg_wait<1>(); release(c, B_E1 + 16);
        wg_wait<0>(); release(c, B_E1 + 24);
#pragma unroll
        for (int i = 0; i < 64; i++) pk[i] = pack2(acc[2 * i], acc[2 * i + 1]);
      }
      put(0); put(1); put(2); put(3);
      bar_arrive(BAR_EV + 1, 288);
      return;
    }
    {
      const int prow = 16 * j + 2 * warp;
      const uint4* xr = x + (size_t)(128 * m + 2 * (prow & 63) + (prow >> 6)) * 128 + lane;
      uint4* xo = gs->xn + (size_t)(128 * m + prow) * 128 + lane;
      float c0[2], mo[4];
      uint32_t st[2];
      uint32_t e;
      asm volatile("" : "+l"(xr), "+l"(xo));
      asm volatile("cp.async.wait_all;\nfence.proxy.async.shared::cta;" ::: "memory");
      bar_sync(BAR_MMA, 256);
      if (threadIdx.x == 0) TS(39);
      p1_step<0, false>(acc, c);
      asm volatile("barrier.cluster.wait.aligned;" ::: "memory");
      p1_step<1>(acc, c);
#pragma unroll
      for (int i = 0; i < 8; i++)
        asm volatile("ld.global.nc.v4.b32 {%0,%1,%2,%3}, [%4];" : "=r"(pk[4 * i]), "=r"(pk[4 * i + 1]), "=r"(pk[4 * i + 2]), "=r"(pk[4 * i + 3]) : "l"(xr + (i >> 2) * 256 + (i & 3) * 32));
      p1_loop(acc, c, 2, LN_KB + 1);
      pin<16>(pk); ln_moments(pk, c0[0], mo[0], mo[1]); pin<2>(mo);
      p1_step<LN_KB + 1>(acc, c);
      sched_fence(c.zero);
      pin<16>(pk + 16); ln_moments(pk + 16, c0[1], mo[2], mo[3]); ln_reduce(mo[0], mo[1]); pin<4>(mo);
      p1_step<LN_KB + 2>(acc, c);
      mbar_spin(sb + B_EP, 0, c.zero);
      asm volatile("ld.shared.b32 %0, [%1];" : "=r"(e) : "r"(sb + OFF_EPOCH) : "memory");
      pin<2>(mo); st[0] = ln_finish(c0[0], mo[0], mo[1]); ln_reduce(mo[2], mo[3]); pin<1>(st); pin<2>(mo + 2);
      p1_step<LN_KB + 3>(acc, c);
      sched_fence(c.zero);
      pin<1>(st); pin<2>(mo + 2);
      st[1] = ln_finish(c0[1], mo[2], mo[3]);
      ln_store(pk, st[0], xo);
      if (lane == 0)
        asm volatile("{\n.reg .b64 a, b;\nmov.b64 a, {%1, %3};\nmov.b64 b, {%2, %3};\nst.relaxed.gpu.global.v2.b64 [%0], {a, b};\n}" ::"l"(gs->stats + 128 * m + prow), "r"(st[0]), "r"(st[1]), "r"(e) : "memory");
      p1_step<LN_KB + 4>(acc, c); sched_fence(c.zero); pin<1>(st + 1);
      ln_store(pk + 16, st[1], xo + 128);
      bar_arrive(BAR_EV, 288);
      p1_loop(acc, c, LN_KB + 5, 13);
      const unsigned long long* cp = (const unsigned long long*)gs->cspart + j * 4096 + threadIdx.x;
      const unsigned long long* sp = gs->stats + 128 * m + warp * 16 + rho;
      unsigned long long part[18];
      auto gather = [&]() {
#pragma unroll
        for (int i = 0; i < 18; i++) asm volatile("ld.relaxed.gpu.global.b64 %0, [%1];" : "=l"(part[i]) : "l"(i < 16 ? cp + i * 256 : sp + (i - 16) * 8) : "memory");
      };
      gather();
      auto validate = [&]() {
        float csum;
        for (int tries = 0;; tries++) {
          uint32_t bad = 0;
          csum = 0.f;
#pragma unroll
          for (int i = 0; i < 18; i++) { bad |= (uint32_t)(part[i] >> 32) ^ e; if (i < 16) csum += __uint_as_float((uint32_t)part[i]); }
          if (!__any_sync(~0u, bad != 0) || tries > (1 << 20)) break;
          gather();
        }
        const float hi = bf16r(csum), mid = bf16r(csum - hi);
        sts128(sb + OFF_CS + ((threadIdx.x & 62) * 4 + (threadIdx.x >> 6) * 2 + (threadIdx.x & 1)) * 16, make_uint4(pack2(hi, mid), pack2(csum - hi - mid, 0.f), 0, 0));
        asm volatile("fence.proxy.async.shared::cta;" ::: "memory");
        __syncwarp();
        if (lane == 0) mbar_arrive(sb + B_AUX);
      };
      p1_step<13>(acc, c);
#pragma unroll 1
      for (int ph = 1; ph >= 0; ph--) {
        if (wg == ph) validate();
        if (ph) { p1_step<14>(acc, c); p1_issue<3, 1>(acc, c, 1); }
      }
      const uint32_t keep = q == 0 ? 0xffffffffu : (q == 1 ? 0xffffu : 0u);
      const uint32_t a0 = (__byte_perm((uint32_t)part[16], 0, 0x1010) ^ 0x80008000u) & keep, a1 = (__byte_perm((uint32_t)part[17], 0, 0x1010) ^ 0x80008000u) & keep;
      mbar_spin(sb + B_AUX, 0, c.zero);
      wg_fence();
      wgmma256_rs(acc, a0, a1, 0, 0, (SM_BASE + OFF_CS) >> 4);
      wg_commit();
      if (wg == 0) bar_arrive(BAR_LAG, 256);
      rs[0] = rcpf(hi_f((uint32_t)part[16])); rs[1] = rcpf(hi_f((uint32_t)part[17]));
      wg_wait<2>(); release(c, B_E1 + 16);
      wg_wait<0>(); release(c, B_E1 + 24);
    }
#pragma unroll 1
    for (int R = 1;; R++) {
#pragma unroll
      for (int i = 0; i < 64; i++) pk[i] = pack2(acc[2 * i], acc[2 * i + 1]);
      if (t0) TS(24 + R + wg * 16);
      uint8_t* hb = (uint8_t*)gs->h + (size_t)m * 56 * 16384 + warp * 1024;
      const bool att = R == 2 || R == 3;
      if (att) {
        attn_tile(acc, pk, c, R - 2, warp, m, gs, hb + (16 + j) * 16384, (uint8_t*)gs->o + (m * 16 + j + 8 * (R - 2)) * 16384 + warp * 1024);
      } else {
        if (R == 5) { c.a = 0x8000002000010000ull + ((SM_BASE + OFF_A + wg * 4096) >> 4); c.k2 = 510; c.k4 = 1024 - 514; c.k4w = -3072 - 514; }
        geglu_tile<0>(acc, pk, c, hb + (2 * j + (R == 1 ? 0 : 16 * R - 40)) * 16384, BAR_EV + (R == 1 ? 1 : R + 1), rs);
        rs[0] = rs[1] = 1.0f;
      }
      p1_loop(acc, c, att ? 13 : 9, R == 5 ? 24 : 14);
      if (R == 5) break;
      p1_step<14>(acc, c); p1_step<15>(acc, c);
    }
    auto fetch = [&](int p) {
      asm volatile("ld.global.cg.v4.b32 {%0,%1,%2,%3}, [%4];" : "=r"(pk[4 * p]), "=r"(pk[4 * p + 1]), "=r"(pk[4 * p + 2]), "=r"(pk[4 * p + 3]) : "l"(gs->dpart + blockIdx.x * 2048 + p * 256 + threadIdx.x) : "memory");
    };
    mbar_spin(sb + B_DEP + 40, 0, c.zero);
    fetch(0); fetch(1); fetch(2);
    p1_step<8>(acc, c);
    fetch(3); fetch(4); fetch(5);
    p1_step<9>(acc, c);
    fetch(6); fetch(7);
    {
      float accs[64];
      const uint32_t peer = mapa(sb, rank ^ 1);
      auto send_piece = [&](int p) {
        asm volatile("st.async.weak.shared::cluster.mbarrier::complete_tx::bytes.v4.b32 [%0], {%1,%2,%3,%4}, [%5];" ::"r"(peer + OFF_LAND + p * 4096 + threadIdx.x * 16),
                     "r"(pack2(acc[64 + 8 * p], acc[65 + 8 * p])), "r"(pack2(acc[66 + 8 * p], acc[67 + 8 * p])), "r"(pack2(acc[68 + 8 * p], acc[69 + 8 * p])), "r"(pack2(acc[70 + 8 * p], acc[71 + 8 * p])),
                     "r"(peer + B_EX + 16 * wg + 8 * (p >> 2)) : "memory");
      };
      auto silu_piece = [&](int p) {
        const uint4 r = lds128(sb + OFF_LAND + p * 4096 + threadIdx.x * 16);
        const uint32_t rr[4] = {add2(r.x, pk[4 * p]), add2(r.y, pk[4 * p + 1]), add2(r.z, pk[4 * p + 2]), add2(r.w, pk[4 * p + 3])};
#pragma unroll
        for (int i = 0; i < 4; i++) {
          const float a = acc[8 * p + 2 * i] + lo_f(rr[i]), b = acc[8 * p + 2 * i + 1] + hi_f(rr[i]);
          pk[4 * p + i] = pack2(silu_half(a), silu_half(b));
        }
        pin<4>(pk + 4 * p);
      };
      const uint32_t xa = sb + OFF_X + (warp * 16 + (lane & 15)) * 128 + (((lane >> 4) ^ (lane & 7)) << 4);
      auto x_piece = [&](int i) { const uint4 v = ldsm((xa ^ ((i & 3) << 5)) + (i >> 2) * 16384); pk[32 + 4 * i] = v.x; pk[33 + 4 * i] = v.y; pk[34 + 4 * i] = v.z; pk[35 + 4 * i] = v.w; };
      p2_step<0>(accs, c);
      p2_step<1>(accs, c);
      mbar_spin(sb + B_E1 + 8, 0, c.zero);
      send_piece(0); send_piece(1);
      p2_step<2>(accs, c); sched_fence(c.zero); send_piece(2); send_piece(3);
      p2_step<3>(accs, c); sched_fence(c.zero); send_piece(4); send_piece(5);
      p2_step<4>(accs, c); mbar_spin(sb + B_XT, 0, c.zero); send_piece(6); send_piece(7);
      p2_step<5>(accs, c); mbar_spin(sb + B_EX + 16 * wg, 0, c.zero); silu_piece(0); x_piece(0);
      p2_step<6>(accs, c); sched_fence(c.zero); silu_piece(1); x_piece(1);
      p2_step<7>(accs, c); sched_fence(c.zero); silu_piece(2); x_piece(2);
      p2_step<8>(accs, c); sched_fence(c.zero); silu_piece(3); x_piece(3);
      p2_step<9>(accs, c); mbar_spin(sb + B_EX + 16 * wg + 8, 0, c.zero); silu_piece(4); x_piece(4);
      p2_step<10>(accs, c); sched_fence(c.zero); silu_piece(5); x_piece(5);
      p2_step<11>(accs, c); sched_fence(c.zero); silu_piece(6); x_piece(6); x_piece(7);
      if (wg == 1) silu_piece(7);
      p2_step<12>(accs, c); p2_step<13>(accs, c); p2_step<14>(accs, c); p2_step<15>(accs, c);
      if (c.do_rel) mbar_arrive(sb + B_DONE);
      if (wg == 0) silu_piece(7);
      wg_wait<0>();
#pragma unroll
      for (int i = 0; i < 8; i++) {
        uint32_t v[4];
#pragma unroll
        for (int k = 0; k < 4; k++) v[k] = fma2(pack2(accs[8 * i + 2 * k], accs[1 + 8 * i + 2 * k]), pk[4 * i + k], pk[32 + 4 * i + k]);
        asm volatile("stmatrix.sync.aligned.m8n8.x4.shared.b16 [%0], {%1,%2,%3,%4};" ::"r"((xa ^ ((i & 3) << 5)) + (i >> 2) * 16384), "r"(v[0]), "r"(v[1]), "r"(v[2]), "r"(v[3]) : "memory");
        if (i == 3 || i == 7) {
          asm volatile("fence.proxy.async.shared::cta;" ::: "memory");
          __syncwarp();
          if (elect_one()) tma3d_store(&mp.out, sb + OFF_X + (i >> 2) * 16384 + warp * 2048, j2 * 128 + (i >> 2) * 64, m2 * 64 + w * 16, wg);
        }
      }
      if (elect_one()) { asm volatile("cp.async.bulk.commit_group;\ncp.async.bulk.wait_group.read 0;" ::: "memory"); }
      if ((threadIdx.x & 127) == 0) { TS(33 + wg * 16); if (wg) { TG(59); unsigned id; asm volatile("mov.u32 %0, %%smid;" : "=r"(id)); TSV(60, id); } }
    }
  }
}

typedef CUresult (*EncodeFn)(CUtensorMap*, CUtensorMapDataType, cuuint32_t, void*, const cuuint64_t*, const cuuint64_t*, const cuuint32_t*, const cuuint32_t*,
                             CUtensorMapInterleave, CUtensorMapSwizzle, CUtensorMapL2promotion, CUtensorMapFloatOOBfill);

void encode(EncodeFn fn, CUtensorMap* tm, const void* p, int rank, const cuuint64_t* dims, const cuuint64_t* strides, const cuuint32_t* box) {
  const cuuint32_t es[5] = {1, 1, 1, 1, 1};
  fn(tm, CU_TENSOR_MAP_DATA_TYPE_BFLOAT16, rank, const_cast<void*>(p), dims, strides, box, es, CU_TENSOR_MAP_INTERLEAVE_NONE, CU_TENSOR_MAP_SWIZZLE_128B,
     PROMO, CU_TENSOR_MAP_FLOAT_OOB_FILL_NONE);
}

}

extern "C" void kernel_launch(void* const* d_in, const int* in_sizes, int n_in, void* d_out, int out_size) {
  (void)in_sizes; (void)n_in; (void)out_size;
  static EncodeFn fn = nullptr;
  static Scratch* gs = nullptr;
  if (!fn) {
    void* p = nullptr;
    cudaDriverEntryPointQueryResult qr;
    cudaGetDriverEntryPoint("cuTensorMapEncodeTiled", &p, cudaEnableDefault, &qr);
    fn = (EncodeFn)p;
    cudaGetSymbolAddress((void**)&gs, g_scratch);
    cudaFuncSetAttribute(fused_kernel, cudaFuncAttributeMaxDynamicSharedMemorySize, SMEM_BYTES);
  }
  const void *x = d_in[0], *wqkv = d_in[1], *wo = d_in[2], *wg = d_in[4], *wu = d_in[5], *wd = d_in[6];
  Maps mp;
  {
    const cuuint64_t dims[3] = {DM, SEQ / 2, 2}, st[2] = {DM * 4, DM * 2};
    const cuuint32_t box_in[3] = {64, 64, 2}, box_out[3] = {64, 16, 1};
    encode(fn, &mp.x, x, 3, dims, st, box_in);
    encode(fn, &mp.out, d_out, 3, dims, st, box_out);
  }
  {
    const cuuint64_t dims[2] = {DM, SEQ}, st[1] = {DM * 2};
    const cuuint32_t box[2] = {64, 128};
    encode(fn, &mp.xn, gs->xn, 2, dims, st, box);
  }
  {
    const cuuint32_t box[2] = {64, 64};
    const cuuint64_t dq[2] = {3 * DM, DM}, sq[1] = {3 * DM * 2}, df[2] = {DFF, DM}, sf[1] = {DFF * 2}, dw[2] = {DM, DM}, sw[1] = {DM * 2};
    encode(fn, &mp.wqkv, wqkv, 2, dq, sq, box);
    encode(fn, &mp.wg, wg, 2, df, sf, box);
    encode(fn, &mp.wu, wu, 2, df, sf, box);
    encode(fn, &mp.wo, wo, 2, dw, sw, box);
  }
  {
    const cuuint32_t box[5] = {64, 2, 4, 4, 2};
    const cuuint64_t st[4] = {DM * 2, 8 * DM * 2, 2 * DM * 2, 32 * DM * 2};
    const cuuint64_t dd[5] = {DM, 2, 4, 4, DFF / 32};
    encode(fn, &mp.wd, wd, 5, dd, st, box);
  }
  fused_kernel<<<NCTA, 384, SMEM_BYTES>>>((const uint4*)x, (const uint4*)wg, (const uint4*)wu, gs, mp);
}
```

```cpp
#include <cuda_runtime.h>
#include <cuda_bf16.h>
#include <cuda.h>
#include <stdint.h>

#define PROMO CU_TENSOR_MAP_L2_PROMOTION_L2_256B
#define PF_D 4
#define PF_W 1
#define PF_H 1
#define PF_SLEEP 250
#define LAG2 4
#define CS_KB 8
#define LN_KB 4

#define EVICT_FIRST 0x12F0000000000000ull
#define EVICT_NORMAL 0x1000000000000000ull
#define HINT_W EVICT_FIRST
#define HINT_H EVICT_FIRST
#define HINT_LAST EVICT_FIRST

namespace {

constexpr int SEQ = 2048, DM = 1024, DFF = 3584;
constexpr int NMAIN = 128, NCTA = 132;

constexpr uint32_t SM_BASE = 0x400;
constexpr uint32_t P1_BYTES = 49152, P2_BYTES = 32768;
constexpr uint32_t OFF_A = 131072;
__host__ __device__ constexpr uint32_t p2_a(int s) { return s == 0 ? OFF_A + 32768 : s == 1 ? OFF_A + 49152 : s == 2 ? 114688 : s == 3 ? 16384 : 49152; }
__host__ __device__ constexpr uint32_t p2_b(int s) { return s < 3 ? 65536 + s * 16384 : (s - 3) * 32768; }
constexpr uint32_t OFF_LAND = OFF_A;
constexpr uint32_t OFF_X = 196608;
constexpr uint32_t OFF_CS = OFF_X + 14336;
constexpr uint32_t OFF_BAR = 229376;
constexpr uint32_t B_F1 = OFF_BAR, B_E1 = B_F1 + 32, B_E2 = B_E1 + 32, B_DONE = B_E2 + 40, B_F2 = B_DONE + 8, B_DEP = B_F2 + 40, B_CS = B_DEP + 48,
                   B_XT = B_CS + 16, B_EP = B_XT + 8, B_EX = B_EP + 8, B_AUX = B_EX + 32, B_HALO = B_AUX + 8, OFF_EPOCH = B_HALO + 16;
constexpr uint32_t SMEM_BYTES = 232448;
constexpr uint32_t AT_V = 0, AT_K = 8192, AT_REM = 11264, AT_WG = 15360;

constexpr int FL_XN = 0, FL_H = 16, FL_P = 80, FL_HALO = 96, FL_N = FL_HALO + 256;
struct __align__(1024) Scratch {
  uint4 h[16 * 56 * 1024];
  uint4 o[16 * 16 * 1024];
  uint4 xn[SEQ * DM / 8];
  uint4 dpart[128 * 8 * 256];
  uint4 halo[2 * 128 * 2 * 128];
  ulonglong2 cspart[8 * 16 * 128];
  unsigned long long stats[SEQ];
  unsigned flags[FL_N * 32];
  unsigned epoch[NCTA * 2];
};
__device__ Scratch g_scratch;
#define TG(i) do {} while (0)
#define TSV(i, v) do {} while (0)
#define TS(i) do {} while (0)

struct Maps { CUtensorMap x, xn, out, wqkv, wg, wu, wd, wo; };

__device__ __forceinline__ void mbar_init(uint32_t bar, uint32_t cnt) { asm volatile("mbarrier.init.shared::cta.b64 [%0], %1;" ::"r"(bar), "r"(cnt)); }
__device__ __forceinline__ void mbar_expect_tx(uint32_t bar, uint32_t bytes) { asm volatile("mbarrier.arrive.expect_tx.shared::cta.b64 _, [%0], %1;" ::"r"(bar), "r"(bytes) : "memory"); }
__device__ __forceinline__ void mbar_arrive(uint32_t bar) { asm volatile("mbarrier.arrive.shared::cta.b64 _, [%0];" ::"r"(bar) : "memory"); }
__device__ __forceinline__ void mbar_arrive_cl(uint32_t bar) { asm volatile("mbarrier.arrive.shared::cluster.b64 _, [%0];" ::"r"(bar) : "memory"); }
__device__ __forceinline__ uint32_t mapa(uint32_t a, uint32_t cta) { uint32_t r; asm("mapa.shared::cluster.u32 %0, %1, %2;" : "=r"(r) : "r"(a), "r"(cta)); return r; }
__device__ __forceinline__ void mbar_wait(uint32_t bar, uint32_t parity) {
  asm volatile("{\n.reg .pred p;\n.reg .u32 n;\nmov.u32 n, 0;\nLAB_WAIT:\nmbarrier.try_wait.parity.shared::cta.b64 p, [%0], %1;\n@p bra LAB_DONE;\n"
               "add.u32 n, n, 1;\nsetp.gt.u32 p, n, 4000000;\n@p trap;\nbra LAB_WAIT;\nLAB_DONE:\n}" ::"r"(bar), "r"(parity) : "memory");
}
__device__ __forceinline__ void mbar_spin(uint32_t bar, uint32_t parity, uint32_t zero) {
  asm volatile("{\n.reg .pred p, z;\nsetp.ne.u32 z, %2, 0;\nLAB_WAIT:\nmbarrier.try_wait.parity.shared::cta.b64 p, [%0], %1;\n@p bra LAB_DONE;\n@z trap;\nbra LAB_WAIT;\nLAB_DONE:\n}" ::"r"(bar), "r"(parity), "r"(zero) : "memory");
}
__device__ __forceinline__ void flag_wait(const unsigned* f, unsigned target) {
  asm volatile("{\n.reg .pred p;\n.reg .u32 n, v;\nmov.u32 n, 0;\nLAB_WAIT:\nld.relaxed.gpu.global.u32 v, [%0];\nsub.u32 v, v, %1;\nsetp.ge.s32 p, v, 0;\n@p bra LAB_DONE;\n"
               "nanosleep.u32 100;\nadd.u32 n, n, 1;\nsetp.gt.u32 p, n, 4000000;\n@p trap;\nbra LAB_WAIT;\nLAB_DONE:\nfence.acquire.gpu;\n}" ::"l"(f), "r"(target) : "memory");
}
__device__ __forceinline__ void flag_add(unsigned* f) { asm volatile("red.release.gpu.global.add.u32 [%0], 1;" ::"l"(f) : "memory"); }
__device__ __forceinline__ void fence_async() { asm volatile("fence.proxy.async.global;" ::: "memory"); }
__device__ __forceinline__ bool elect_one() { uint32_t p; asm volatile("{\n.reg .pred P;\nelect.sync _|P, 0xffffffff;\nselp.u32 %0, 1, 0, P;\n}" : "=r"(p)); return p; }
__device__ __forceinline__ void bar_sync(int id, int n) { asm volatile("bar.sync %0, %1;" ::"r"(id), "r"(n) : "memory"); }
__device__ __forceinline__ void bar_arrive(int id, int n) { asm volatile("bar.arrive %0, %1;" ::"r"(id), "r"(n) : "memory"); }

__device__ __forceinline__ void tma2d(uint32_t dst, const CUtensorMap* tm, uint32_t bar, int c0, int c1, uint64_t hint) {
  asm volatile("cp.async.bulk.tensor.2d.shared::cluster.global.mbarrier::complete_tx::bytes.L2::cache_hint [%0], [%1, {%3, %4}], [%2], %5;" ::"r"(dst), "l"(tm), "r"(bar), "r"(c0), "r"(c1), "l"(hint) : "memory");
}
__device__ __forceinline__ void tma2d_mc(uint32_t dst, const CUtensorMap* tm, uint32_t bar, int c0, int c1, uint64_t hint) {
  asm volatile("cp.async.bulk.tensor.2d.shared::cluster.global.mbarrier::complete_tx::bytes.multicast::cluster.L2::cache_hint [%0], [%1, {%3, %4}], [%2], %5, %6;" ::"r"(dst), "l"(tm), "r"(bar), "r"(c0), "r"(c1), "h"((uint16_t)3), "l"(hint) : "memory");
}
__device__ __forceinline__ void tma3d(uint32_t dst, const CUtensorMap* tm, uint32_t bar, int c0, int c1, int c2, uint64_t hint) {
  asm volatile("cp.async.bulk.tensor.3d.shared::cluster.global.mbarrier::complete_tx::bytes.L2::cache_hint [%0], [%1, {%3, %4, %5}], [%2], %6;" ::"r"(dst), "l"(tm), "r"(bar), "r"(c0), "r"(c1), "r"(c2), "l"(hint) : "memory");
}
__device__ __forceinline__ void tma5d(uint32_t dst, const CUtensorMap* tm, uint32_t bar, int c0, int c4, uint64_t hint) {
  asm volatile("cp.async.bulk.tensor.5d.shared::cluster.global.mbarrier::complete_tx::bytes.L2::cache_hint [%0], [%1, {%3, %5, %5, %5, %4}], [%2], %6;" ::"r"(dst), "l"(tm), "r"(bar), "r"(c0), "r"(c4), "r"(0), "l"(hint) : "memory");
}
__device__ __forceinline__ void tma5d_prefetch(const CUtensorMap* tm, int c0, int c4) {
  asm volatile("cp.async.bulk.prefetch.tensor.5d.L2.global [%0, {%1, %3, %3, %3, %2}];" ::"l"(tm), "r"(c0), "r"(c4), "r"(0) : "memory");
}
__device__ __forceinline__ void tma3d_store(const CUtensorMap* tm, uint32_t src, int c0, int c1, int c2) {
  asm volatile("cp.async.bulk.tensor.3d.global.shared::cta.bulk_group [%0, {%2, %3, %4}], [%1];" ::"l"(tm), "r"(src), "r"(c0), "r"(c1), "r"(c2) : "memory");
}
__device__ __forceinline__ void bulk_load(uint32_t dst, const void* src, uint32_t bytes, uint32_t bar, uint64_t hint) {
  asm volatile("cp.async.bulk.shared::cluster.global.mbarrier::complete_tx::bytes.L2::cache_hint [%0], [%1], %2, [%3], %4;" ::"r"(dst), "l"(src), "r"(bytes), "r"(bar), "l"(hint) : "memory");
}
__device__ __forceinline__ void bulk_load_mc(uint32_t dst, const void* src, uint32_t bytes, uint32_t bar, uint64_t hint) {
  asm volatile("cp.async.bulk.shared::cluster.global.mbarrier::complete_tx::bytes.multicast::cluster.L2::cache_hint [%0], [%1], %2, [%3], %4, %5;" ::"r"(dst), "l"(src), "r"(bytes), "r"(bar), "h"((uint16_t)3), "l"(hint) : "memory");
}
__device__ __forceinline__ uint4 lds128(uint32_t a) { uint4 v; asm volatile("ld.shared.v4.b32 {%0,%1,%2,%3}, [%4];" : "=r"(v.x), "=r"(v.y), "=r"(v.z), "=r"(v.w) : "r"(a) : "memory"); return v; }
__device__ __forceinline__ void sts128(uint32_t a, uint4 v) { asm volatile("st.shared.v4.b32 [%0], {%1,%2,%3,%4};" ::"r"(a), "r"(v.x), "r"(v.y), "r"(v.z), "r"(v.w) : "memory"); }
__device__ __forceinline__ void stg128(void* p, uint32_t a, uint32_t b, uint32_t c, uint32_t d) { asm volatile("st.global.v4.b32 [%0], {%1,%2,%3,%4};" ::"l"(p), "r"(a), "r"(b), "r"(c), "r"(d) : "memory"); }

__device__ __forceinline__ uint32_t pack2(float lo, float hi) { uint32_t r; asm("cvt.rn.bf16x2.f32 %0, %1, %2;" : "=r"(r) : "f"(hi), "f"(lo)); return r; }
__device__ __forceinline__ float lo_f(uint32_t v) { return __uint_as_float(v << 16); }
__device__ __forceinline__ float hi_f(uint32_t v) { return __uint_as_float(v & 0xffff0000u); }
__device__ __forceinline__ float bf16r(float v) { return lo_f(pack2(v, 0.f)); }
__device__ __forceinline__ uint32_t mul2(uint32_t a, uint32_t b) { uint32_t r; asm("mul.rn.bf16x2 %0, %1, %2;" : "=r"(r) : "r"(a), "r"(b)); return r; }
__device__ __forceinline__ uint32_t add2(uint32_t a, uint32_t b) { uint32_t r; asm("add.rn.bf16x2 %0, %1, %2;" : "=r"(r) : "r"(a), "r"(b)); return r; }
__device__ __forceinline__ uint32_t sub2(uint32_t a, uint32_t b) { uint32_t r; asm("sub.rn.bf16x2 %0, %1, %2;" : "=r"(r) : "r"(a), "r"(b)); return r; }
__device__ __forceinline__ uint32_t fma2(uint32_t a, uint32_t b, uint32_t c) { uint32_t r; asm("fma.rn.bf16x2 %0, %1, %2, %3;" : "=r"(r) : "r"(a), "r"(b), "r"(c)); return r; }
__device__ __forceinline__ uint32_t max2(uint32_t a, uint32_t b) { uint32_t r; asm("max.bf16x2 %0, %1, %2;" : "=r"(r) : "r"(a), "r"(b)); return r; }
__device__ __forceinline__ float ex2f(float x) { float y; asm("ex2.approx.ftz.f32 %0, %1;" : "=f"(y) : "f"(x)); return y; }
__device__ __forceinline__ float rcpf(float x) { float y; asm("rcp.approx.ftz.f32 %0, %1;" : "=f"(y) : "f"(x)); return y; }
constexpr float GELU_C1 = 0.7978845608028654f, GELU_C3 = 0.035677408136300125f;
__device__ __forceinline__ float gelu_k(float g, float c1, float c3, float k) {
  float t;
  asm("tanh.approx.f32 %0, %1;" : "=f"(t) : "f"(g * fmaf(g * g, c3, c1)));
  g *= k;
  return fmaf(g, t, g);
}
__device__ __forceinline__ float silu_half(float z) { float t; asm("tanh.approx.f32 %0, %1;" : "=f"(t) : "f"(z)); return fmaf(z, t, z); }

__device__ __forceinline__ void wg_fence() { asm volatile("wgmma.fence.sync.aligned;" ::: "memory"); }
__device__ __forceinline__ void wg_commit() { asm volatile("wgmma.commit_group.sync.aligned;" ::: "memory"); }
template <int N> __device__ __forceinline__ void wg_wait() { asm volatile("wgmma.wait_group.sync.aligned %0;" ::"n"(N) : "memory"); }
#define A8(o) "+f"(d[(o)]), "+f"(d[(o) + 1]), "+f"(d[(o) + 2]), "+f"(d[(o) + 3]), "+f"(d[(o) + 4]), "+f"(d[(o) + 5]), "+f"(d[(o) + 6]), "+f"(d[(o) + 7])
#define A64(o) A8(o), A8((o) + 8), A8((o) + 16), A8((o) + 24), A8((o) + 32), A8((o) + 40), A8((o) + 48), A8((o) + 56)
#define REGS0_63 "%0,%1,%2,%3,%4,%5,%6,%7,%8,%9,%10,%11,%12,%13,%14,%15,%16,%17,%18,%19,%20,%21,%22,%23,%24,%25,%26,%27,%28,%29,%30,%31," \
                 "%32,%33,%34,%35,%36,%37,%38,%39,%40,%41,%42,%43,%44,%45,%46,%47,%48,%49,%50,%51,%52,%53,%54,%55,%56,%57,%58,%59,%60,%61,%62,%63"
#define REGS64_127 "%64,%65,%66,%67,%68,%69,%70,%71,%72,%73,%74,%75,%76,%77,%78,%79,%80,%81,%82,%83,%84,%85,%86,%87,%88,%89,%90,%91,%92,%93,%94,%95," \
                   "%96,%97,%98,%99,%100,%101,%102,%103,%104,%105,%106,%107,%108,%109,%110,%111,%112,%113,%114,%115,%116,%117,%118,%119,%120,%121,%122,%123,%124,%125,%126,%127"
__device__ __forceinline__ void desc_add(uint64_t& x, int v) { asm volatile("{\n.reg .b32 lo, hi;\nmov.b64 {lo, hi}, %0;\nadd.s32 lo, lo, %1;\nmov.b64 %0, {lo, hi};\n}" : "+l"(x) : "r"(v)); }
template <int ACCUM> __device__ __forceinline__ void wgmma256(float (&d)[128], uint64_t& a, uint64_t& b, int da, int db) {
  asm volatile("{\n.reg .pred p;\nsetp.ne.b32 p, %130, 0;\n"
               "wgmma.mma_async.sync.aligned.m64n256k16.f32.bf16.bf16 {" REGS0_63 "," REGS64_127 "}, %128, %129, p, 1, 1, 0, 1;\n}"
               : A64(0), A64(64) : "l"(a), "l"(b), "n"(ACCUM));
  desc_add(a, da); desc_add(b, db);
}
__device__ __forceinline__ void wgmma256_rs(float (&d)[128], uint32_t a0, uint32_t a1, uint32_t z0, uint32_t z1, uint32_t b_lo) {
  asm volatile("{\n.reg .b64 db;\nmov.b64 db, {%132, 0x00000008};\n"
               "wgmma.mma_async.sync.aligned.m64n256k16.f32.bf16.bf16 {" REGS0_63 "," REGS64_127 "}, {%128,%129,%130,%131}, db, 1, 1, 1, 0;\n}"
               : A64(0), A64(64) : "r"(a0), "r"(a1), "r"(z0), "r"(z1), "r"(b_lo));
}
template <int ACCUM> __device__ __forceinline__ void wgmma128(float (&d)[64], uint64_t& a, uint64_t& b, int da, int db) {
  asm volatile("{\n.reg .pred p;\nsetp.ne.b32 p, %66, 0;\n"
               "wgmma.mma_async.sync.aligned.m64n128k16.f32.bf16.bf16 {" REGS0_63 "}, %64, %65, p, 1, 1, 0, 1;\n}"
               : A64(0) : "l"(a), "l"(b), "n"(ACCUM));
  desc_add(a, da); desc_add(b, db);
}
template <int ACCUM> __device__ __forceinline__ void hmma(float (&c)[4], uint32_t a0, uint32_t a1, uint32_t a2, uint32_t a3, uint32_t b0, uint32_t b1) {
  if (ACCUM)
    asm volatile("mma.sync.aligned.m16n8k16.row.col.f32.bf16.bf16.f32 {%0,%1,%2,%3}, {%4,%5,%6,%7}, {%8,%9}, {%0,%1,%2,%3};"
                 : "+f"(c[0]), "+f"(c[1]), "+f"(c[2]), "+f"(c[3]) : "r"(a0), "r"(a1), "r"(a2), "r"(a3), "r"(b0), "r"(b1));
  else
    asm volatile("mma.sync.aligned.m16n8k16.row.col.f32.bf16.bf16.f32 {%0,%1,%2,%3}, {%4,%5,%6,%7}, {%8,%9}, {%10,%10,%10,%10};"
                 : "=f"(c[0]), "=f"(c[1]), "=f"(c[2]), "=f"(c[3]) : "r"(a0), "r"(a1), "r"(a2), "r"(a3), "r"(b0), "r"(b1), "f"(0.f));
}
__device__ __forceinline__ uint32_t movm(uint32_t a) { uint32_t d; asm volatile("movmatrix.sync.aligned.m8n8.trans.b16 %0, %1;" : "=r"(d) : "r"(a)); return d; }
__device__ __forceinline__ int lane_here() { int v; asm volatile("mov.u32 %0, %%laneid;" : "=r"(v)); return v; }
template <int N> __device__ __forceinline__ void pin(uint32_t* r) {
#pragma unroll
  for (int i = 0; i < N; i++) asm volatile("" : "+r"(r[i]));
}
template <int N> __device__ __forceinline__ void pin(float* r) {
#pragma unroll
  for (int i = 0; i < N; i++) asm volatile("" : "+f"(r[i]));
}
__device__ __forceinline__ void sched_fence(uint32_t zero) {
  asm volatile("{\n.reg .pred p;\nsetp.eq.u32 p, %0, 0;\nLAB_F:\n@p bra.uni LAB_D;\nnanosleep.u32 0;\nbra.uni LAB_F;\nLAB_D:\n}" ::"r"(zero) : "memory");
}
__device__ __forceinline__ uint4 ldsm(uint32_t a) { uint4 v; asm volatile("ldmatrix.sync.aligned.m8n8.x4.shared.b16 {%0,%1,%2,%3}, [%4];" : "=r"(v.x), "=r"(v.y), "=r"(v.z), "=r"(v.w) : "r"(a) : "memory"); return v; }
__device__ __forceinline__ uint4 ldsm_t(uint32_t a) { uint4 v; asm volatile("ldmatrix.sync.aligned.m8n8.x4.trans.shared.b16 {%0,%1,%2,%3}, [%4];" : "=r"(v.x), "=r"(v.y), "=r"(v.z), "=r"(v.w) : "r"(a) : "memory"); return v; }

constexpr int BAR_LAG = 1, BAR_MMA = 2, BAR_EV = 3;

struct Cons {
  uint32_t sb;
  mutable uint64_t a, b;
  int k1, k2, k4, k4w, b1;
  uint32_t rel;
  bool do_rel;
  int wg;
  uint32_t zero;
};
#define REL_TS(n) TS(64 + (n))
constexpr uint32_t DB_LO = (SM_BASE >> 4) | ((8192 >> 4) << 16);

template <int ST, int ACCUM, bool WAIT = true> __device__ __forceinline__ void p1_issue(float (&acc)[128], const Cons& c, uint32_t parity) {
  if (WAIT) mbar_spin(c.sb + B_F1 + 8 * ST, parity, c.zero);
  wg_fence();
  wgmma256<ACCUM>(acc, c.a, c.b, c.k1, c.b1);
  wgmma256<1>(acc, c.a, c.b, c.k2, c.b1);
  wgmma256<1>(acc, c.a, c.b, c.k1, c.b1);
  wgmma256<1>(acc, c.a, c.b, ST == 3 ? c.k4w : c.k4, ST == 3 ? -6144 - 384 : 2048 - 384);
  wg_commit();
}
__device__ __forceinline__ void release(const Cons& c, uint32_t bar) { if (c.do_rel) mbar_arrive_cl(c.rel + bar); }
template <int KB, bool WAIT = true, int LAG = 2> __device__ __forceinline__ void p1_step(float (&acc)[128], const Cons& c) {
  if (KB == 16 - LAG) { if (c.wg == 1) { wg_wait<0>(); release(c, B_E1 + 8 * ((KB - 1) & 3)); bar_sync(BAR_LAG, 256); } }
  p1_issue<KB & 3, KB != 0, WAIT>(acc, c, (KB >> 2) & 1);
  if (KB == 15) { if (c.wg == 0) bar_arrive(BAR_LAG, 256); }
  if (KB > 0) { wg_wait<1>(); if (KB != 16 - LAG || c.wg == 0) release(c, B_E1 + 8 * ((KB - 1) & 3)); }
  if (KB == 15) { wg_wait<0>(); release(c, B_E1 + 8 * 3); }
}
template <class F> __device__ __forceinline__ void p1_loop(float (&acc)[128], const Cons& c, int from, int to, F&& shadow) {
#pragma unroll 1
  for (int kb = from; kb < to; kb++) {
    const bool wrap = (kb & 3) == 3;
    mbar_spin(c.sb + B_F1 + 8 * (kb & 3), (kb >> 2) & 1, c.zero);
    wg_fence();
    wgmma256<1>(acc, c.a, c.b, c.k1, c.b1);
    wgmma256<1>(acc, c.a, c.b, c.k2, c.b1);
    wgmma256<1>(acc, c.a, c.b, c.k1, c.b1);
    wgmma256<1>(acc, c.a, c.b, wrap ? c.k4w : c.k4, wrap ? -6144 - 384 : 2048 - 384);
    wg_commit();
    wg_wait<1>();
    release(c, B_E1 + 8 * ((kb - 1) & 3));
    shadow(kb);
  }
}
template <int T> __device__ __forceinline__ void p2_step(float (&acc)[64], const Cons& c) {
  if (T == 16 - LAG2) { if (c.wg == 1) bar_sync(BAR_LAG, 256); }
  mbar_spin(c.sb + B_F2 + 8 * (T % 5), (T / 5) & 1, c.zero);
  wg_fence();
  wgmma128<T != 0>(acc, c.a, c.b, c.k1, c.b1);
  wgmma128<1>(acc, c.a, c.b, c.k2, c.b1);
  wgmma128<1>(acc, c.a, c.b, c.k1, c.b1);
  wgmma128<1>(acc, c.a, c.b, ((int)p2_a((T + 1) % 5) - (int)p2_a(T % 5)) / 16 - 514, ((int)p2_b((T + 1) % 5) - (int)p2_b(T % 5)) / 16 - 384);
  wg_commit();
  if (T == 15) { if (c.wg == 0) bar_arrive(BAR_LAG, 256); }
  if (T <= 11) { wg_wait<1>(); release(c, T ? B_E2 + 8 * ((T + 5 - 1) % 5) : B_E1 + 8); }
}

template <int P> __device__ __forceinline__ void geglu_piece(uint32_t (&pk)[64], uint8_t* dst, float (&rs)[2]) {
  constexpr int cg = P >> 1, r = P & 1;
  pin<1>(rs + r);
#pragma unroll
  for (int i = 0; i < 4; i++) pin<1>(pk + 2 * (4 * cg + i) + r);
  const float r2 = rs[r] * rs[r], c1 = GELU_C1 * rs[r], c3 = GELU_C3 * r2 * rs[r], k = 0.25f * r2;
  uint32_t v[4];
#pragma unroll
  for (int i = 0; i < 4; i++) {
    const uint32_t g = pk[2 * (4 * cg + i) + r];
    v[i] = mul2(pack2(gelu_k(lo_f(g), c1, c3, k), gelu_k(hi_f(g), c1, c3, k)), pk[32 + 2 * (4 * cg + i) + r]);
  }
  stg128(dst + cg * 8192 + r * 512, v[0], v[1], v[2], v[3]);
}
__device__ __forceinline__ void geglu_tile(float (&acc)[128], uint32_t (&pk)[64], const Cons& c, int to, uint8_t* dst, int ev, float (&rs)[2]) {
  const int lane = lane_here();
  dst += (lane ^ (lane >> 3)) << 4;
  p1_loop(acc, c, 1, to, [&](int kb) {
    if (kb <= 4) {
      if (kb <= 2) { if (kb == 1) geglu_piece<0>(pk, dst, rs); else geglu_piece<1>(pk, dst, rs); }
      else { if (kb == 3) geglu_piece<2>(pk, dst, rs); else geglu_piece<3>(pk, dst, rs); }
    } else if (kb <= 8) {
      if (kb <= 6) { if (kb == 5) geglu_piece<4>(pk, dst, rs); else geglu_piece<5>(pk, dst, rs); }
      else { if (kb == 7) geglu_piece<6>(pk, dst, rs); else { geglu_piece<7>(pk, dst, rs); bar_arrive(ev, 288); } }
    }
  });
}

__device__ __forceinline__ void attn_tile(float (&acc)[128], uint32_t (&pk)[64], const Cons& c, int round, int warp, int m, Scratch* gs, uint8_t* hdst, uint8_t* odst) {
  const int w = warp & 3;
  const uint32_t at = c.sb + OFF_X + c.wg * AT_WG;
  int lane = lane_here();
  hdst += (lane ^ (lane >> 3)) << 4;
  auto scatter = [&]() {
    const int lane = lane_here();
    const uint32_t swz = (lane ^ (lane >> 3)) << 4;
#pragma unroll
    for (int i = 0; i < 4; i++) {
      const int h = i & 1, r = i >> 1;
      sts128(at + AT_V + (2 * w + r) * 1024 + h * 512 + swz, make_uint4(pk[32 + 8 * h + r], pk[34 + 8 * h + r], pk[36 + 8 * h + r], pk[38 + 8 * h + r]));
    }
    if (w < 3) {
#pragma unroll
      for (int i = 0; i < 8; i++) asm volatile("st.shared.b32 [%0], %1;" ::"r"(at + AT_K + w * 1024 + i * 128 + lane * 4), "r"(pk[17 + 2 * i]) : "memory");
    } else {
      uint8_t* g = (uint8_t*)gs->halo + ((round * 128 + blockIdx.x) * 2 + c.wg) * 2048;
#pragma unroll
      for (int i = 0; i < 8; i++) asm volatile("st.global.b32 [%0], %1;" ::"l"(g + i * 128 + lane * 4), "r"(pk[17 + 2 * i]) : "memory");
#pragma unroll
      for (int h = 0; h < 2; h++) stg128(g + 1024 + h * 512 + swz, pk[33 + 8 * h], pk[35 + 8 * h], pk[37 + 8 * h], pk[39 + 8 * h]);
      bar_arrive(BAR_EV + 2 + round, 96);
    }
    __syncwarp();
    if (lane == 0) mbar_arrive(c.sb + B_HALO + 8 * round);
    if (round) {
#pragma unroll
      for (int p = 0; p < 4; p++) {
        const int o = 32 + 8 * (p >> 1) + (p & 1);
        asm volatile("ld.global.cg.v4.b32 {%0,%1,%2,%3}, [%4];" : "=r"(pk[o]), "=r"(pk[o + 2]), "=r"(pk[o + 4]), "=r"(pk[o + 6]) : "l"(hdst + (p >> 1) * 8192 + (p & 1) * 512) : "memory");
      }
    }
  };
  auto gu_piece = [&](int p) {
    uint32_t v[4];
#pragma unroll
    for (int i = 0; i < 4; i++) {
      const int o = 8 * (p >> 1) + 2 * i + (p & 1);
      pin<1>(pk + 48 + o);
      const uint32_t g = pk[48 + o];
      v[i] = mul2(round ? pk[32 + o] : 0x3e803e80u, round ? g : pack2(gelu_k(lo_f(g), GELU_C1, GELU_C3, 1.0f), gelu_k(hi_f(g), GELU_C1, GELU_C3, 1.0f)));
    }
    stg128(hdst + (p >> 1) * 8192 + (p & 1) * 512, v[0], v[1], v[2], v[3]);
  };
  p1_step<1>(acc, c);
  scatter();
  p1_loop(acc, c, 2, 9, [&](int kb) {
    if (kb <= 4) { if (kb == 3) gu_piece(0); else if (kb == 4) gu_piece(1); }
    else if (kb == 5) gu_piece(2); else if (kb == 6) gu_piece(3);
  });
  const bool first = m == 0 && w == 0;
  uint32_t kl[16];
  mbar_spin(c.sb + B_HALO + 8 * round, 0, c.zero);
  lane = lane_here();
  {
    const uint32_t ka = at + lane * 4 + (w ? AT_K + (w - 1) * 1024 : (first ? AT_K : AT_REM + round * 2048));
#pragma unroll
    for (int i = 0; i < 8; i++) {
      asm volatile("ld.shared.b32 %0, [%1];" : "=r"(kl[2 * i]) : "r"(ka + i * 128) : "memory");
      kl[2 * i + 1] = pk[16 + 2 * i] | c.zero;
    }
  }
  float st[4][4];
  pin<16>(kl);
  bar_sync(BAR_MMA, 256);
  mbar_spin(c.sb + B_F1 + 8 * 1, 0, c.zero);
#pragma unroll
  for (int ks = 0; ks < 2; ks++) {
#pragma unroll
    for (int h = 0; h < 2; h++) {
      const int o = 8 * h + 4 * ks;
      if (ks == 0) { hmma<0>(st[2 * h], kl[o], kl[o + 1], kl[o + 2], kl[o + 3], pk[o], pk[o + 2]); hmma<0>(st[2 * h + 1], pk[16 + o], pk[17 + o], pk[18 + o], pk[19 + o], pk[o + 1], pk[o + 3]); }
      else { hmma<1>(st[2 * h], kl[o], kl[o + 1], kl[o + 2], kl[o + 3], pk[o], pk[o + 2]); hmma<1>(st[2 * h + 1], pk[16 + o], pk[17 + o], pk[18 + o], pk[19 + o], pk[o + 1], pk[o + 3]); }
    }
  }
  sched_fence(c.zero);
  bar_sync(BAR_MMA, 256);
  p1_step<9, false>(acc, c);
  sched_fence(c.zero);
  pin<16>(&st[0][0]);
  lane = lane_here();
  const int rho = lane >> 2, q = lane & 3;
  const bool le0 = 2 * q <= rho, le1 = 2 * q + 1 <= rho;
  uint32_t la[2], lb[2], mx[2];
#pragma unroll
  for (int h = 0; h < 2; h++) {
    uint32_t l[2];
#pragma unroll
    for (int r = 0; r < 2; r++) {
      const float (&t)[4] = st[2 * h + r];
      l[r] = movm(pack2(rho <= 2 * q ? t[2] : t[0], rho <= 2 * q + 1 ? t[3] : t[1]));
      l[r] = fma2(l[r], 0x3e353e35u, mul2(l[r], 0x379e379eu));
    }
    la[h] = __byte_perm(l[0], l[1], 0x5410); lb[h] = __byte_perm(l[0], l[1], 0x7632);
    if (first && !le0) la[h] = (la[h] & 0xffff0000u) | 0xce6eu;
    if (first && !le1) lb[h] = (lb[h] & 0xffff0000u) | 0xce6eu;
    mx[h] = max2(la[h], lb[h]);
  }
#pragma unroll
  for (int o = 1; o <= 2; o++) { mx[0] = max2(mx[0], __shfl_xor_sync(~0u, mx[0], o)); mx[1] = max2(mx[1], __shfl_xor_sync(~0u, mx[1], o)); }
  const float L2E = 1.4426950408889634f;
  float pr[2][4], z[4];
#pragma unroll
  for (int h = 0; h < 2; h++) {
    pr[h][0] = ex2f((lo_f(la[h]) - lo_f(mx[h])) * L2E); pr[h][1] = ex2f((lo_f(lb[h]) - lo_f(mx[h])) * L2E);
    pr[h][2] = ex2f((hi_f(la[h]) - hi_f(mx[h])) * L2E); pr[h][3] = ex2f((hi_f(lb[h]) - hi_f(mx[h])) * L2E);
    z[2 * h] = pr[h][0] + pr[h][1]; z[2 * h + 1] = pr[h][2] + pr[h][3];
  }
  p1_step<10>(acc, c);
#pragma unroll
  for (int o = 1; o <= 2; o++) {
#pragma unroll
    for (int i = 0; i < 4; i++) z[i] += __shfl_xor_sync(~0u, z[i], o);
  }
  const uint32_t LE = (le0 ? 0xffffu : 0u) | (le1 ? 0xffff0000u : 0u);
  uint32_t P[4][2];
  uint4 vt[4][2];
  {
    const uint32_t row = (lane & 7) * 64 + ((((lane >> 3) & 1) ^ ((lane & 7) >> 1)) << 4);
    const uint32_t v1 = at + AT_V + (2 * w + (lane >> 4)) * 1024 + row;
    const uint32_t v0 = (w || lane >= 16) ? v1 - 1024 : (first ? v1 : at + AT_REM + round * 2048 + 1024 + row);
#pragma unroll
    for (int i = 0; i < 4; i++) {
      const float rz = rcpf(z[i]);
      const uint32_t p = pack2(pr[i >> 1][2 * (i & 1)] * rz, pr[i >> 1][2 * (i & 1) + 1] * rz);
      P[i][0] = p & ~LE; P[i][1] = p & LE;
      const uint32_t a = ((i & 1) ? v1 : v0) + (i >> 1) * 512;
      vt[i][0] = ldsm_t(a); vt[i][1] = ldsm_t(a ^ 32);
    }
  }
  float ot[4][2][4];
  pin<8>(&P[0][0]);
  bar_sync(BAR_MMA, 256);
  mbar_spin(c.sb + B_F1 + 8 * 3, 0, c.zero);
#pragma unroll
  for (int i = 0; i < 8; i++) { const uint4& v = vt[i >> 1][i & 1]; hmma<0>(ot[i >> 1][i & 1], v.x, v.y, v.z, v.w, P[i >> 1][0], P[i >> 1][1]); }
  sched_fence(c.zero);
  bar_sync(BAR_MMA, 256);
  p1_step<11, false>(acc, c);
  sched_fence(c.zero);
  pin<32>(&ot[0][0][0]);
  lane = lane_here();
  odst += (lane ^ (lane >> 3)) << 4;
  auto o_piece = [&](int i) {
    stg128(odst + (i >> 1) * 8192 + (i & 1) * 512, movm(pack2(ot[i][0][0], ot[i][0][1])), movm(pack2(ot[i][0][2], ot[i][0][3])), movm(pack2(ot[i][1][0], ot[i][1][1])), movm(pack2(ot[i][1][2], ot[i][1][3])));
  };
  o_piece(0); o_piece(1);
  p1_step<12>(acc, c);
  o_piece(2); o_piece(3);
  if (round) bar_arrive(BAR_EV + 4, 288);
  p1_step<13>(acc, c);
}

__device__ __forceinline__ void ln_moments(const uint32_t* raw, float& c0, float& s, float& v) {
  c0 = lo_f(__shfl_sync(~0u, raw[0], 0));
  float ss[4] = {0.f, 0.f, 0.f, 0.f}, vv[4] = {0.f, 0.f, 0.f, 0.f};
#pragma unroll
  for (int i = 0; i < 16; i++) {
    const float a = lo_f(raw[i]) - c0, b = hi_f(raw[i]) - c0;
    ss[(2 * i) & 3] += a; ss[(2 * i + 1) & 3] += b;
    vv[(2 * i) & 3] = fmaf(a, a, vv[(2 * i) & 3]); vv[(2 * i + 1) & 3] = fmaf(b, b, vv[(2 * i + 1) & 3]);
  }
  s = (ss[0] + ss[1]) + (ss[2] + ss[3]); v = (vv[0] + vv[1]) + (vv[2] + vv[3]);
}
__device__ __forceinline__ void ln_reduce(float& s, float& v) {
#pragma unroll
  for (int o = 16; o; o >>= 1) { s += __shfl_xor_sync(~0u, s, o); v += __shfl_xor_sync(~0u, v, o); }
}
__device__ __forceinline__ uint32_t ln_finish(float c0, float s, float v) {
  s *= 1.0f / DM;
  float sd;
  asm("sqrt.approx.ftz.f32 %0, %1;" : "=f"(sd) : "f"(bf16r(bf16r(fmaxf(fmaf(v, 1.0f / DM, -s * s), 0.f)) + 1e-5f)));
  return pack2(c0 + s, sd);
}
__device__ __forceinline__ void ln_store(const uint32_t* raw, uint32_t st, uint4* dst) {
  const uint32_t m2 = __byte_perm(st, st, 0x1010);
  const float rinv = rcpf(hi_f(st));
  const uint32_t rh = pack2(rinv, rinv), rl = pack2(rinv - hi_f(rh), rinv - hi_f(rh));
#pragma unroll
  for (int c = 0; c < 4; c++) {
    uint32_t v[4];
#pragma unroll
    for (int i = 0; i < 4; i++) { const uint32_t t = sub2(raw[4 * c + i], m2); v[i] = fma2(t, rh, mul2(t, rl)); }
    stg128(dst + 32 * c, v[0], v[1], v[2], v[3]);
  }
}
__device__ __forceinline__ void col_sums(uint32_t tile, ulonglong2* part, uint32_t tag) {
  const int lane = threadIdx.x & 31;
  float cs[8] = {0, 0, 0, 0, 0, 0, 0, 0};
  uint32_t base = tile + ((lane >> 3) & 1) * 8192 + (lane >> 4) * 4096 + ((lane & 7) << 4);
#pragma unroll 1
  for (int k0 = 0; k0 < 8; k0++, base = (base ^ ((k0 ^ (k0 - 1)) << 4)) + 128) {
    uint4 v[4];
#pragma unroll
    for (int k = 0; k < 4; k++) v[k] = lds128(base + k * 1024);
#pragma unroll
    for (int k = 0; k < 4; k++) {
      cs[0] += lo_f(v[k].x); cs[1] += hi_f(v[k].x); cs[2] += lo_f(v[k].y); cs[3] += hi_f(v[k].y);
      cs[4] += lo_f(v[k].z); cs[5] += hi_f(v[k].z); cs[6] += lo_f(v[k].w); cs[7] += hi_f(v[k].w);
    }
  }
  const bool up = lane >= 16;
#pragma unroll
  for (int i = 0; i < 2; i++) {
    const float a = (up ? cs[4 + 2 * i] : cs[2 * i]) + __shfl_xor_sync(~0u, up ? cs[2 * i] : cs[4 + 2 * i], 16);
    const float b = (up ? cs[5 + 2 * i] : cs[1 + 2 * i]) + __shfl_xor_sync(~0u, up ? cs[1 + 2 * i] : cs[5 + 2 * i], 16);
    asm volatile("{\n.reg .b64 a, b;\nmov.b64 a, {%1, %3};\nmov.b64 b, {%2, %3};\nst.relaxed.gpu.global.v2.b64 [%0], {a, b};\n}"
                 ::"l"(part + 32 * (i + (up ? 2 : 0)) + (lane & 15)), "r"(__float_as_uint(a)), "r"(__float_as_uint(b)), "r"(tag) : "memory");
  }
  asm volatile("fence.proxy.async.shared::cta;" ::: "memory");
}

__global__ void __cluster_dims__(2, 1, 1) __launch_bounds__(384, 1)
fused_kernel(const uint4* __restrict__ x, const uint4* __restrict__ wgate, const uint4* __restrict__ wup, Scratch* gs, const __grid_constant__ Maps mp) {
  extern __shared__ __align__(1024) uint8_t smem_raw[];
  const uint32_t sb = (uint32_t)__cvta_generic_to_shared(smem_raw);
  const unsigned t_start = 0;
  if (threadIdx.x < 256 && blockIdx.x < NMAIN) {
    const uint32_t r = threadIdx.x >> 3, ch = threadIdx.x & 7;
    const uint32_t d = sb + r * 128 + ((ch ^ (r & 7)) << 4);
    const uint8_t* xa = (const uint8_t*)x + ((blockIdx.x & 15) * 262144 + r * 4096 + ch * 16);
    const uint32_t wo = r * (DFF * 2) + (blockIdx.x >> 4) * 256 + ch * 16;
    const uint8_t *wa = (const uint8_t*)wgate + wo, *wb = (const uint8_t*)wup + wo;
#pragma unroll
    for (int i = 0; i < 12; i++) {
      const int h = i >= 8;
      const uint8_t* src = (i >> 2) == 1 ? xa + (i & 1) * 131072 + ((i >> 1) & 1) * 2048 : ((i & 2) ? wb : wa) + h * 32 * (DFF * 2) + (i & 1) * 128;
      asm volatile("cp.async.cg.shared.global [%0], [%1], 16;" ::"r"(d + ((i >> 2) == 1 ? OFF_A + (i & 3) * 4096 : (i & 3) * 8192 + h * 4096)), "l"(src) : "memory");
    }
    if (threadIdx.x == 0) TS(23);
  }
  const int warp = __shfl_sync(~0u, threadIdx.x >> 5, 0), lane = threadIdx.x & 31;
  const int m = blockIdx.x & 15, j = blockIdx.x >> 4, rank = blockIdx.x & 1;
  const int m2 = blockIdx.x >> 3, j2 = blockIdx.x & 7;
  const bool helper = blockIdx.x >= NMAIN;
  if (warp >= 8) {
    asm volatile("setmaxnreg.dec.sync.aligned.u32 40;");
    if (warp == 8) {
      if (elect_one()) {
        asm volatile("prefetch.tensormap [%0];\nprefetch.tensormap [%1];\nprefetch.tensormap [%2];" ::"l"(&mp.x), "l"(&mp.wg), "l"(&mp.wu) : "memory");
        for (int s = 0; s < 4; s++) mbar_init(sb + B_F1 + 8 * s, 1);
        if (!helper) mbar_arrive(sb + B_F1);
        asm volatile("fence.mbarrier_init.release.cluster;" ::: "memory");
      }
      __syncwarp();
    } else if (warp == 9) {
      if (elect_one()) {
        if ((sb & 0xffffff) != SM_BASE) asm volatile("trap;");
        for (uint32_t b = B_E1; b < B_F2; b += 8) mbar_init(sb + b, 4);
        for (uint32_t b = B_F2; b < B_AUX; b += 8) mbar_init(sb + b, 1);
        for (uint32_t b = B_EX; b < B_AUX; b += 8) mbar_expect_tx(sb + b, 8192);
        mbar_init(sb + B_AUX, 8); mbar_init(sb + B_HALO, 9); mbar_init(sb + B_HALO + 8, 9);
        asm volatile("fence.mbarrier_init.release.cluster;" ::: "memory");
      }
      __syncwarp();
    }
    asm volatile("barrier.cluster.arrive.relaxed.aligned;" ::: "memory");
    if (warp == 8 && !helper) {
      if (elect_one()) {
        TS(0); TG(51);
#pragma unroll 1
        for (int kb = 1; kb < 4; kb++) {
          const uint32_t sa = sb + OFF_A + kb * 16384, sw = sb + kb * 32768, fb = sb + B_F1 + 8 * kb;
          mbar_expect_tx(fb, P1_BYTES);
          tma3d(sa, &mp.x, fb, kb * 64, m * 64, 0, EVICT_NORMAL);
          tma2d(sw, &mp.wg, fb, j * 128, kb * 64, EVICT_NORMAL); tma2d(sw + 16384, &mp.wu, fb, j * 128, kb * 64, EVICT_NORMAL);
          tma2d(sw + 8192, &mp.wg, fb, j * 128 + 64, kb * 64, EVICT_NORMAL); tma2d(sw + 24576, &mp.wu, fb, j * 128 + 64, kb * 64, EVICT_NORMAL);
        }
        TS(7);
      }
      __syncwarp();
    }
    asm volatile("barrier.cluster.wait.aligned;" ::: "memory");
    if (helper) {
      if (warp == 8) {
        unsigned e = 0;
        if (elect_one()) {
#pragma unroll 1
          for (int i = 0; i < 16; i++) {
            const uint32_t fb = sb + B_F1 + 8 * (i >> 2);
            if (!(i & 3)) mbar_expect_tx(fb, P1_BYTES);
            tma5d(sb + i * 8192, &mp.wd, fb, (blockIdx.x - NMAIN) * 256 + (i & 3) * 64, (i >> 2) * 2, HINT_W);
          }
        }
        if (lane == 0) { unsigned* ep = &gs->epoch[blockIdx.x * 2]; e = *ep + 1; *ep = e; }
        e = __shfl_sync(~0u, e, 0);
        if (lane < 16) flag_wait(&gs->flags[(FL_H + lane * 4) * 32], e * 8u);
        __syncwarp();
        if (elect_one()) {
          fence_async();
          TS(0);
#pragma unroll 1
          for (int i = 0; i < 64; i++) {
            const uint32_t fb = sb + B_F1 + 8 * (i & 3);
            if (i >= 4) { mbar_wait(sb + B_E1 + 8 * (i & 3), ~(i >> 2) & 1); mbar_expect_tx(fb, 16384); }
            bulk_load(sb + OFF_A + (i & 3) * 16384, gs->h + ((i >> 2) * 56 + (i & 3)) * 1024, 16384, fb, EVICT_NORMAL);
          }
        }
      } else if (warp == 9) {
#pragma unroll 1
        for (int t = 0; t < 16; t++) {
          bar_sync(BAR_EV + (t & 1), 288);
          if (lane == 0) { flag_add(&gs->flags[(FL_P + t) * 32]); TS(64 + t); }
          __syncwarp();
        }
      }
    } else if (warp == 8) {
      if (elect_one()) {
        uint32_t par = 0;

        auto x_load = [&]() {
          mbar_expect_tx(sb + B_XT, 32768);
          tma3d(sb + OFF_X, &mp.x, sb + B_XT, j2 * 128, m2 * 64, 0, HINT_LAST); tma3d(sb + OFF_X + 16384, &mp.x, sb + B_XT, j2 * 128 + 64, m2 * 64, 0, HINT_LAST);
        };
        auto d_prefetch = [&](int i) {
          if (PF_W == 1 && (m2 >> 2) == (i & 3)) tma5d_prefetch(&mp.wd, (j2 >> 1) * 256 + (m2 & 3) * 64, (2 * i + 4 + rank) * 2);
          if (PF_H == 1 && i < 6) asm volatile("cp.async.bulk.prefetch.L2.global [%0], 4096;" ::"l"(gs->h + (m2 * 56 + 2 * i + 4 + rank) * 1024 + (j2 >> 1) * 256) : "memory");
        };
        for (int R = 0; R < 5; R++) {
          const CUtensorMap *mb0, *mb1;
          int n0, n1;
          if (R == 1 || R == 2) {
            mb0 = &mp.wqkv; n0 = 64 * (j + 8 * (R - 1)) + rank * 2048;
            mb1 = rank ? (R == 1 ? &mp.wg : &mp.wu) : &mp.wqkv; n1 = rank ? 1024 + 64 * j : n0 + 1024;
          } else {
            mb0 = mb1 = rank ? &mp.wu : &mp.wg;
            n0 = 128 * j + (R ? 1024 * R - 1536 : 0); n1 = n0 + 64;
          }
#pragma unroll 1
          for (int kb = R ? 0 : 4; kb < 16; kb++) {
            if (R == 0 && kb == 14) { asm volatile("prefetch.tensormap [%0];\nprefetch.tensormap [%1];" ::"l"(&mp.xn), "l"(&mp.wqkv) : "memory"); }
            if (R == 4 && kb == 2) { asm volatile("prefetch.tensormap [%0];\nprefetch.tensormap [%1];\nprefetch.tensormap [%2];" ::"l"(&mp.wd), "l"(&mp.wo), "l"(&mp.out) : "memory"); }
            if (R == 0 && kb == CS_KB) {
#pragma unroll 1
              for (int h = 0; h < 2; h++) {
                const uint32_t cb = sb + B_CS + 8 * h, d = sb + OFF_X + 16384 * h;
                mbar_expect_tx(cb, 16384);
                tma2d(d, h ? &mp.wu : &mp.wg, cb, n0, m * 64, EVICT_NORMAL); tma2d(d + 8192, h ? &mp.wu : &mp.wg, cb, n1, m * 64, EVICT_NORMAL);
              }
            }
            const int st = kb & 3;
            const uint32_t sa = sb + OFF_A + st * 16384, sw = sb + st * 32768, fb = sb + B_F1 + 8 * st;
            mbar_wait(sb + B_E1 + 8 * st, par);
            if (R * 16 + kb >= 4) REL_TS(R * 16 + kb - 4);
            mbar_expect_tx(fb, P1_BYTES);
            tma2d_mc(sw + rank * 16384, mb0, fb, n0, kb * 64, HINT_W);
            tma2d_mc(sw + 8192 + rank * 16384, mb1, fb, n1, kb * 64, HINT_W);
            if (R == 0) {
              tma3d(sa, &mp.x, fb, kb * 64, m * 64, 0, EVICT_NORMAL);
            } else {
              if (R == 1 && kb == 0) { mbar_wait(sb + B_DEP, 0); TS(1); }
              tma2d(sa, &mp.xn, fb, kb * 64, m * 128, R == 4 ? HINT_LAST : EVICT_NORMAL);
            }
            if (R == 4 && kb == 4 + j2) x_load();
            if (R == 4 && kb >= 16 - PF_D) { if (kb == 16 - PF_D) mbar_wait(sb + B_DEP + 8, 0); d_prefetch(kb + PF_D - 16); }
            if (st == 3) par ^= 1;
          }
        }
#pragma unroll 1
        for (int i = 0; i < 26; i++) {
          const int st = i & 3, kb = 2 * i + 4 + rank;
          const uint32_t sa = sb + OFF_A + st * 16384, sw = sb + st * 32768, fb = sb + B_F1 + 8 * st;
          mbar_wait(sb + B_E1 + 8 * st, par);
          REL_TS(76 + i);
          mbar_expect_tx(fb, P1_BYTES);
          tma5d(sw, &mp.wd, fb, j2 * 128, kb * 2, HINT_W); tma5d(sw + 8192, &mp.wd, fb, j2 * 128 + 64, kb * 2, HINT_W);
          tma5d(sw + 16384, &mp.wd, fb, (j2 ^ 1) * 128, kb * 2, HINT_W); tma5d(sw + 24576, &mp.wd, fb, (j2 ^ 1) * 128 + 64, kb * 2, HINT_W);
          if (i == 0 || i == 6 || i == 10 || i == 18) { mbar_wait(sb + B_DEP + 8 * (1 + ((i + 6) >> 3)), 0); }
          bulk_load(sa, gs->h + (m2 * 56 + kb) * 1024, 16384, fb, HINT_H);
          if (i + PF_D < 26) d_prefetch(i + PF_D);
          if (st == 3) par ^= 1;
        }
        int st = 0; uint32_t par2 = 1;
#pragma unroll 1
        for (int t = 0; t < 16; t++) {
          const uint32_t sa = sb + p2_a(st), sw = sb + p2_b(st), fb = sb + B_F2 + 8 * st;
          if (t < 5) mbar_wait(sb + B_E1 + 8 * (((2 * t + 1) / 3 + 2) & 3), t < 3); else mbar_wait(sb + B_E2 + 8 * st, par2);
          REL_TS(102 + t);
          mbar_expect_tx(fb, P2_BYTES);
          bulk_load_mc(sa + rank * 8192, gs->o + (m2 * 16 + t) * 1024 + rank * 512, 8192, fb, HINT_H);
          tma2d(sw, &mp.wo, fb, j2 * 128, t * 64, HINT_W); tma2d(sw + 8192, &mp.wo, fb, j2 * 128 + 64, t * 64, HINT_W);
          if (++st == 5) { st = 0; par2 ^= 1; }
        }
      }
    } else if (warp == 9) {
#pragma unroll 1
      for (int e = 0; e < 7; e++) {
        const bool halo = e == 2 || e == 3;
        bar_sync(BAR_EV + e, halo ? 96 : 288);
        if (lane == 0) {
          const int f = e == 0 ? FL_XN + m : (halo ? FL_HALO + (e - 2) * 128 + blockIdx.x : FL_H + m * 4 + (e == 1 ? 0 : e - 3));
          TS(10 + 2 * e); TG(52 + e);
          flag_add(&gs->flags[f * 32]);
          if (e < 6) TS(11 + 2 * e);
        }
        __syncwarp();
      }
      mbar_wait(sb + B_DONE, 0);
    } else {
      unsigned e = 0;
      if (lane == 0) {
        unsigned* ep = &gs->epoch[blockIdx.x * 2 + warp - 10];
        e = *ep + 1; *ep = e;
        if (warp == 10) { asm volatile("st.shared.b32 [%0], %1;" ::"r"(sb + OFF_EPOCH), "r"(e) : "memory"); mbar_arrive(sb + B_EP); }
      }
      e = __shfl_sync(~0u, e, 0);
      mbar_wait(sb + B_CS + 8 * (warp - 10), 0);
      if (lane == 0 && warp == 11) TS(6);
      col_sums(sb + OFF_X + (warp - 10) * 16384, gs->cspart + (j * 16 + m) * 128 + (warp - 10) * 16, e);
      if (lane == 0 && warp == 11) TS(9);
      if (warp == 10) {
        if (lane == 0) {
#pragma unroll 1
          for (int g = 0; g < 6; g++) {
            flag_wait(&gs->flags[(g == 5 ? FL_P + m2 : (g ? FL_H + m2 * 4 + g - 1 : FL_XN + m)) * 32], e * (g == 5 ? 4u : 8u));
            fence_async();
            mbar_arrive(sb + B_DEP + 8 * g);
            if (g == 0) TS(8);
          }
#pragma unroll 1
          for (int p = 0; p < 8; p++) {
            asm volatile("cp.async.bulk.prefetch.L2.global [%0], 4096;" ::"l"(gs->dpart + blockIdx.x * 2048 + p * 256) : "memory");
            __nanosleep(PF_SLEEP);
          }
        }
      } else
      if (elect_one()) {
#pragma unroll 1
        for (int r = 0; r < 2; r++) {
          const uint32_t hb = sb + B_HALO + 8 * r;
          if (r) mbar_wait(sb + B_HALO, 0);
          if (m) {
            flag_wait(&gs->flags[(FL_HALO + r * 128 + blockIdx.x - 1) * 32], e);
            fence_async();
            mbar_expect_tx(hb, 4096);
            for (int g = 0; g < 2; g++) bulk_load(sb + OFF_X + g * AT_WG + AT_REM + r * 2048, gs->halo + ((r * 128 + blockIdx.x - 1) * 2 + g) * 128, 2048, hb, EVICT_FIRST);
          } else {
            mbar_arrive(hb);
          }
          TS(34 + r);
        }
      }
    }
  } else {
    asm volatile("barrier.cluster.arrive.relaxed.aligned;" ::: "memory");
    asm volatile("setmaxnreg.inc.sync.aligned.u32 232;");
    const int wg = warp >> 2, w = warp & 3;
    Cons c;
    c.sb = sb; c.wg = wg; c.zero = warp >> 8;
    c.a = 0x4000004000010000ull + ((SM_BASE + OFF_A + wg * 8192) >> 4); c.k1 = 2 + c.zero; c.k2 = 2; c.k4 = 1024 - 6; c.k4w = -3072 - 6; c.b1 = 128 + c.zero;
    c.b = 0x4000004000000000ull + DB_LO + c.zero;
    c.rel = mapa(sb, threadIdx.x & 1);
    c.do_rel = (threadIdx.x & 127) < 2;
    constexpr bool t0 = false;
    float acc[128];
    uint32_t pk[64];
    float rs[2];
    const int q = lane & 3;

    if (helper) {
      asm volatile("barrier.cluster.wait.aligned;" ::: "memory");
      c.a = 0x8000002000010000ull + ((SM_BASE + OFF_A + wg * 4096) >> 4); c.k2 = 510; c.k4 = 1024 - 514; c.k4w = -3072 - 514;
      c.rel = sb;
      uint4* dst = gs->dpart + (blockIdx.x - NMAIN) * 4096 + threadIdx.x;
      auto put = [&](int p) {
#pragma unroll
        for (int i = 4 * p; i < 4 * p + 4; i++) stg128(dst + i * 256, pk[4 * i], pk[4 * i + 1], pk[4 * i + 2], pk[4 * i + 3]);
      };
#pragma unroll 1
      for (int t = 0; t < 16; t++) {
        p1_issue<0, 0>(acc, c, t & 1);
        if (t) put(0);
        p1_issue<1, 1>(acc, c, t & 1); wg_wait<1>(); release(c, B_E1);
        if (t) put(1);
        if (wg == 1) { wg_wait<0>(); release(c, B_E1 + 8); bar_sync(BAR_LAG, 256); }
        p1_issue<2, 1>(acc, c, t & 1); wg_wait<1>(); if (wg == 0) release(c, B_E1 + 8);
        if (t) put(2);
        p1_issue<3, 1>(acc, c, t & 1);
        if (wg == 0) bar_arrive(BAR_LAG, 256);
        if (t) { put(3); bar_arrive(BAR_EV + (~t & 1), 288); dst += 8 * 2048; }
        wg_wait<1>(); release(c, B_E1 + 16);
        wg_wait<0>(); release(c, B_E1 + 24);
#pragma unroll
        for (int i = 0; i < 64; i++) pk[i] = pack2(acc[2 * i], acc[2 * i + 1]);
      }
      put(0); put(1); put(2); put(3);
      bar_arrive(BAR_EV + 1, 288);
      return;
    }
    {
      const int prow = 16 * j + 2 * warp;
      const uint4* xr = x + (size_t)(128 * m + 2 * (prow & 63) + (prow >> 6)) * 128 + lane;
      uint4* xo = gs->xn + (size_t)(128 * m + prow) * 128 + lane;
      float c0[2], mo[4];
      uint32_t st[2];
      uint32_t e;
      asm volatile("" : "+l"(xr), "+l"(xo));
      asm volatile("cp.async.wait_all;\nfence.proxy.async.shared::cta;" ::: "memory");
      bar_sync(BAR_MMA, 256);
      if (threadIdx.x == 0) TS(39);
      p1_step<0, false>(acc, c);
      asm volatile("barrier.cluster.wait.aligned;" ::: "memory");
      unsigned long long part[18];
      auto gather = [&]() {
        const int lane = lane_here();
        const unsigned long long* cp = (const unsigned long long*)gs->cspart + j * 4096 + warp * 32 + lane;
        const unsigned long long* sp = gs->stats + 128 * m + warp * 16 + (lane >> 2);
#pragma unroll
        for (int i = 0; i < 18; i++) asm volatile("ld.relaxed.gpu.global.b64 %0, [%1];" : "=l"(part[i]) : "l"(i < 16 ? cp + i * 256 : sp + (i - 16) * 8) : "memory");
      };
      p1_step<1>(acc, c);
#pragma unroll
      for (int i = 0; i < 8; i++)
        asm volatile("ld.global.nc.v4.b32 {%0,%1,%2,%3}, [%4];" : "=r"(pk[4 * i]), "=r"(pk[4 * i + 1]), "=r"(pk[4 * i + 2]), "=r"(pk[4 * i + 3]) : "l"(xr + (i >> 2) * 256 + (i & 3) * 32));
      p1_loop(acc, c, 2, 13, [&](int kb) {
        if (kb <= LN_KB + 1) {
          if (kb == LN_KB) {
            pin<16>(pk);
            ln_moments(pk, c0[0], mo[0], mo[1]);
          } else if (kb == LN_KB + 1) {
            pin<16>(pk + 16);
            ln_moments(pk + 16, c0[1], mo[2], mo[3]); ln_reduce(mo[0], mo[1]);
          }
        } else if (kb <= LN_KB + 3) {
          if (kb == LN_KB + 2) {
            mbar_spin(sb + B_EP, 0, c.zero);
            asm volatile("ld.shared.b32 %0, [%1];" : "=r"(e) : "r"(sb + OFF_EPOCH) : "memory");
            st[0] = ln_finish(c0[0], mo[0], mo[1]); ln_reduce(mo[2], mo[3]);
          } else {
            st[1] = ln_finish(c0[1], mo[2], mo[3]);
            ln_store(pk, st[0], xo);
            if (lane == 0)
              asm volatile("{\n.reg .b64 a, b;\nmov.b64 a, {%1, %3};\nmov.b64 b, {%2, %3};\nst.relaxed.gpu.global.v2.b64 [%0], {a, b};\n}" ::"l"(gs->stats + 128 * m + prow), "r"(st[0]), "r"(st[1]), "r"(e) : "memory");
          }
        } else if (kb == LN_KB + 4) {
          ln_store(pk + 16, st[1], xo + 128);
          bar_arrive(BAR_EV, 288);
        }
      });
      gather();
      p1_step<13>(acc, c);
      auto validate = [&]() {
        float csum;
        for (int tries = 0;; tries++) {
          uint32_t bad = 0;
          csum = 0.f;
#pragma unroll
          for (int i = 0; i < 18; i++) { bad |= (uint32_t)(part[i] >> 32) ^ e; if (i < 16) csum += __uint_as_float((uint32_t)part[i]); }
          if (!__any_sync(~0u, bad != 0) || tries > (1 << 20)) break;
          gather();
        }
        const float hi = bf16r(csum), mid = bf16r(csum - hi);
        sts128(sb + OFF_CS + ((threadIdx.x & 62) * 4 + (threadIdx.x >> 6) * 2 + (threadIdx.x & 1)) * 16, make_uint4(pack2(hi, mid), pack2(csum - hi - mid, 0.f), 0, 0));
        asm volatile("fence.proxy.async.shared::cta;" ::: "memory");
        __syncwarp();
        if (lane == 0) mbar_arrive(sb + B_AUX);
      };
#pragma unroll 1
      for (int ph = 1; ph >= 0; ph--) {
        if (wg == ph) validate();
        if (ph) { p1_step<14>(acc, c); p1_issue<3, 1>(acc, c, 1); }
      }
      const uint32_t keep = q == 0 ? 0xffffffffu : (q == 1 ? 0xffffu : 0u);
      const uint32_t a0 = (__byte_perm((uint32_t)part[16], 0, 0x1010) ^ 0x80008000u) & keep, a1 = (__byte_perm((uint32_t)part[17], 0, 0x1010) ^ 0x80008000u) & keep;
      mbar_spin(sb + B_AUX, 0, c.zero);
      wg_fence();
      wgmma256_rs(acc, a0, a1, 0, 0, (SM_BASE + OFF_CS) >> 4);
      wg_commit();
      if (wg == 0) bar_arrive(BAR_LAG, 256);
      rs[0] = rcpf(hi_f((uint32_t)part[16])); rs[1] = rcpf(hi_f((uint32_t)part[17]));
      wg_wait<2>(); release(c, B_E1 + 16);
      wg_wait<0>(); release(c, B_E1 + 24);
    }
#pragma unroll 1
    for (int R = 1;; R++) {
#pragma unroll
      for (int i = 0; i < 64; i++) pk[i] = pack2(acc[2 * i], acc[2 * i + 1]);
      if (t0) TS(24 + R + wg * 16);
      uint8_t* hb = (uint8_t*)gs->h + (size_t)m * 56 * 16384 + warp * 1024;
      if (R == 5) { c.a = 0x8000002000010000ull + ((SM_BASE + OFF_A + wg * 4096) >> 4); c.k2 = 510; c.k4 = 1024 - 514; c.k4w = -3072 - 514; }
      p1_step<0>(acc, c);
      if (R == 2 || R == 3) {
        attn_tile(acc, pk, c, R - 2, warp, m, gs, hb + (16 + j) * 16384, (uint8_t*)gs->o + (m * 16 + j + 8 * (R - 2)) * 16384 + warp * 1024);
      } else {
        geglu_tile(acc, pk, c, R == 5 ? 24 : 14, hb + (2 * j + (R == 1 ? 0 : 16 * R - 40)) * 16384, BAR_EV + (R == 1 ? 1 : R + 1), rs);
        rs[0] = rs[1] = 1.0f;
        if (R == 5) break;
      }
      p1_step<14>(acc, c); p1_step<15>(acc, c);
    }
    auto fetch = [&](int p) {
      asm volatile("ld.global.cg.v4.b32 {%0,%1,%2,%3}, [%4];" : "=r"(pk[4 * p]), "=r"(pk[4 * p + 1]), "=r"(pk[4 * p + 2]), "=r"(pk[4 * p + 3]) : "l"(gs->dpart + blockIdx.x * 2048 + p * 256 + threadIdx.x) : "memory");
    };
    mbar_spin(sb + B_DEP + 40, 0, c.zero);
    fetch(0); fetch(1); fetch(2);
    p1_step<8>(acc, c);
    fetch(3); fetch(4); fetch(5);
    p1_step<9>(acc, c);
    fetch(6); fetch(7);
    {
      float accs[64];
      const uint32_t peer = mapa(sb, rank ^ 1);
      auto send_piece = [&](int p) {
        asm volatile("st.async.weak.shared::cluster.mbarrier::complete_tx::bytes.v4.b32 [%0], {%1,%2,%3,%4}, [%5];" ::"r"(peer + OFF_LAND + p * 4096 + threadIdx.x * 16),
                     "r"(pack2(acc[64 + 8 * p], acc[65 + 8 * p])), "r"(pack2(acc[66 + 8 * p], acc[67 + 8 * p])), "r"(pack2(acc[68 + 8 * p], acc[69 + 8 * p])), "r"(pack2(acc[70 + 8 * p], acc[71 + 8 * p])),
                     "r"(peer + B_EX + 16 * wg + 8 * (p >> 2)) : "memory");
      };
      auto silu_piece = [&](int p) {
        const uint4 r = lds128(sb + OFF_LAND + p * 4096 + threadIdx.x * 16);
        const uint32_t rr[4] = {add2(r.x, pk[4 * p]), add2(r.y, pk[4 * p + 1]), add2(r.z, pk[4 * p + 2]), add2(r.w, pk[4 * p + 3])};
#pragma unroll
        for (int i = 0; i < 4; i++) {
          const float a = acc[8 * p + 2 * i] + lo_f(rr[i]), b = acc[8 * p + 2 * i + 1] + hi_f(rr[i]);
          pk[4 * p + i] = pack2(silu_half(a), silu_half(b));
        }
        pin<4>(pk + 4 * p);
      };
      const uint32_t xa = sb + OFF_X + (warp * 16 + (lane & 15)) * 128 + (((lane >> 4) ^ (lane & 7)) << 4);
      auto x_piece = [&](int i) { const uint4 v = ldsm((xa ^ ((i & 3) << 5)) + (i >> 2) * 16384); pk[32 + 4 * i] = v.x; pk[33 + 4 * i] = v.y; pk[34 + 4 * i] = v.z; pk[35 + 4 * i] = v.w; };
      p2_step<0>(accs, c);
      p2_step<1>(accs, c);
      mbar_spin(sb + B_E1 + 8, 0, c.zero);
      send_piece(0); send_piece(1);
      p2_step<2>(accs, c); sched_fence(c.zero); send_piece(2); send_piece(3);
      p2_step<3>(accs, c); sched_fence(c.zero); send_piece(4); send_piece(5);
      p2_step<4>(accs, c); mbar_spin(sb + B_XT, 0, c.zero); send_piece(6); send_piece(7);
      p2_step<5>(accs, c); mbar_spin(sb + B_EX + 16 * wg, 0, c.zero); silu_piece(0); x_piece(0);
      p2_step<6>(accs, c); sched_fence(c.zero); silu_piece(1); x_piece(1);
      p2_step<7>(accs, c); sched_fence(c.zero); silu_piece(2); x_piece(2);
      p2_step<8>(accs, c); sched_fence(c.zero); silu_piece(3); x_piece(3);
      p2_step<9>(accs, c); mbar_spin(sb + B_EX + 16 * wg + 8, 0, c.zero); silu_piece(4); x_piece(4);
      p2_step<10>(accs, c); sched_fence(c.zero); silu_piece(5); x_piece(5);
      p2_step<11>(accs, c); sched_fence(c.zero); silu_piece(6); x_piece(6); x_piece(7);
      if (wg == 1) silu_piece(7);
      p2_step<12>(accs, c); p2_step<13>(accs, c); p2_step<14>(accs, c); p2_step<15>(accs, c);
      if (c.do_rel) mbar_arrive(sb + B_DONE);
      if (wg == 0) silu_piece(7);
      wg_wait<0>();
#pragma unroll
      for (int i = 0; i < 8; i++) {
        uint32_t v[4];
#pragma unroll
        for (int k = 0; k < 4; k++) v[k] = fma2(pack2(accs[8 * i + 2 * k], accs[1 + 8 * i + 2 * k]), pk[4 * i + k], pk[32 + 4 * i + k]);
        asm volatile("stmatrix.sync.aligned.m8n8.x4.shared.b16 [%0], {%1,%2,%3,%4};" ::"r"((xa ^ ((i & 3) << 5)) + (i >> 2) * 16384), "r"(v[0]), "r"(v[1]), "r"(v[2]), "r"(v[3]) : "memory");
        if (i == 3 || i == 7) {
          asm volatile("fence.proxy.async.shared::cta;" ::: "memory");
          __syncwarp();
          if (elect_one()) tma3d_store(&mp.out, sb + OFF_X + (i >> 2) * 16384 + warp * 2048, j2 * 128 + (i >> 2) * 64, m2 * 64 + w * 16, wg);
        }
      }
      if (elect_one()) { asm volatile("cp.async.bulk.commit_group;\ncp.async.bulk.wait_group.read 0;" ::: "memory"); }
      if ((threadIdx.x & 127) == 0) { TS(33 + wg * 16); if (wg) { TG(59); unsigned id; asm volatile("mov.u32 %0, %%smid;" : "=r"(id)); TSV(60, id); } }
    }
  }
}

typedef CUresult (*EncodeFn)(CUtensorMap*, CUtensorMapDataType, cuuint32_t, void*, const cuuint64_t*, const cuuint64_t*, const cuuint32_t*, const cuuint32_t*,
                             CUtensorMapInterleave, CUtensorMapSwizzle, CUtensorMapL2promotion, CUtensorMapFloatOOBfill);

void encode(EncodeFn fn, CUtensorMap* tm, const void* p, int rank, const cuuint64_t* dims, const cuuint64_t* strides, const cuuint32_t* box) {
  const cuuint32_t es[5] = {1, 1, 1, 1, 1};
  fn(tm, CU_TENSOR_MAP_DATA_TYPE_BFLOAT16, rank, const_cast<void*>(p), dims, strides, box, es, CU_TENSOR_MAP_INTERLEAVE_NONE, CU_TENSOR_MAP_SWIZZLE_128B,
     PROMO, CU_TENSOR_MAP_FLOAT_OOB_FILL_NONE);
}

}

extern "C" void kernel_launch(void* const* d_in, const int* in_sizes, int n_in, void* d_out, int out_size) {
  (void)in_sizes; (void)n_in; (void)out_size;
  static EncodeFn fn = nullptr;
  static Scratch* gs = nullptr;
  if (!fn) {
    void* p = nullptr;
    cudaDriverEntryPointQueryResult qr;
    cudaGetDriverEntryPoint("cuTensorMapEncodeTiled", &p, cudaEnableDefault, &qr);
    fn = (EncodeFn)p;
    cudaGetSymbolAddress((void**)&gs, g_scratch);
    cudaFuncSetAttribute(fused_kernel, cudaFuncAttributeMaxDynamicSharedMemorySize, SMEM_BYTES);
  }
  const void *x = d_in[0], *wqkv = d_in[1], *wo = d_in[2], *wg = d_in[4], *wu = d_in[5], *wd = d_in[6];
  Maps mp;
  {
    const cuuint64_t dims[3] = {DM, SEQ / 2, 2}, st[2] = {DM * 4, DM * 2};
    const cuuint32_t box_in[3] = {64, 64, 2}, box_out[3] = {64, 16, 1};
    encode(fn, &mp.x, x, 3, dims, st, box_in);
    encode(fn, &mp.out, d_out, 3, dims, st, box_out);
  }
  {
    const cuuint64_t dims[2] = {DM, SEQ}, st[1] = {DM * 2};
    const cuuint32_t box[2] = {64, 128};
    encode(fn, &mp.xn, gs->xn, 2, dims, st, box);
  }
  {
    const cuuint32_t box[2] = {64, 64};
    const cuuint64_t dq[2] = {3 * DM, DM}, sq[1] = {3 * DM * 2}, df[2] = {DFF, DM}, sf[1] = {DFF * 2}, dw[2] = {DM, DM}, sw[1] = {DM * 2};
    encode(fn, &mp.wqkv, wqkv, 2, dq, sq, box);
    encode(fn, &mp.wg, wg, 2, df, sf, box);
    encode(fn, &mp.wu, wu, 2, df, sf, box);
    encode(fn, &mp.wo, wo, 2, dw, sw, box);
  }
  {
    const cuuint32_t box[5] = {64, 2, 4, 4, 2};
    const cuuint64_t st[4] = {DM * 2, 8 * DM * 2, 2 * DM * 2, 32 * DM * 2};
    const cuuint64_t dd[5] = {DM, 2, 4, 4, DFF / 32};
    encode(fn, &mp.wd, wd, 5, dd, st, box);
  }
  fused_kernel<<<NCTA, 384, SMEM_BYTES>>>((const uint4*)x, (const uint4*)wg, (const uint4*)wu, gs, mp);
}
```

```cpp
#include <cuda_runtime.h>
#include <cuda_bf16.h>
#include <cuda.h>
#include <stdint.h>

#define PROMO CU_TENSOR_MAP_L2_PROMOTION_L2_256B
#define PF_D 4
#define PF_W 1
#define PF_H 1
#define PF_SLEEP 250
#define LAG2 4
#define CS_KB 8
#define LN_KB 4

#define EVICT_FIRST 0x12F0000000000000ull
#define EVICT_NORMAL 0x1000000000000000ull
#define HINT_W EVICT_FIRST
#define HINT_H EVICT_FIRST
#define HINT_LAST EVICT_FIRST

namespace {

constexpr int SEQ = 2048, DM = 1024, DFF = 3584;
constexpr int NMAIN = 128, NCTA = 132;

constexpr uint32_t SM_BASE = 0x400;
constexpr uint32_t P1_BYTES = 49152, P2_BYTES = 32768;
constexpr uint32_t OFF_A = 131072;
__host__ __device__ constexpr uint32_t p2_a(int s) { return s == 0 ? OFF_A + 32768 : s == 1 ? OFF_A + 49152 : s == 2 ? 114688 : s == 3 ? 16384 : 49152; }
__host__ __device__ constexpr uint32_t p2_b(int s) { return s < 3 ? 65536 + s * 16384 : (s - 3) * 32768; }
constexpr uint32_t OFF_LAND = OFF_A;
constexpr uint32_t OFF_X = 196608;
constexpr uint32_t OFF_CS = OFF_X + 14336;
constexpr uint32_t OFF_BAR = 229376;
constexpr uint32_t B_F1 = OFF_BAR, B_E1 = B_F1 + 32, B_E2 = B_E1 + 32, B_DONE = B_E2 + 40, B_F2 = B_DONE + 8, B_DEP = B_F2 + 40, B_CS = B_DEP + 48,
                   B_XT = B_CS + 16, B_EP = B_XT + 8, B_EX = B_EP + 8, B_AUX = B_EX + 32, B_HALO = B_AUX + 8, OFF_EPOCH = B_HALO + 16;
constexpr uint32_t SMEM_BYTES = 232448;
constexpr uint32_t AT_V = 0, AT_K = 8192, AT_REM = 11264, AT_WG = 15360;

constexpr int FL_XN = 0, FL_H = 16, FL_P = 80, FL_HALO = 96, FL_N = FL_HALO + 256;
struct __align__(1024) Scratch {
  uint4 h[16 * 56 * 1024];
  uint4 o[16 * 16 * 1024];
  uint4 xn[SEQ * DM / 8];
  uint4 dpart[128 * 8 * 256];
  uint4 halo[2 * 128 * 2 * 128];
  ulonglong2 cspart[8 * 16 * 128];
  unsigned long long stats[SEQ];
  unsigned flags[FL_N * 32];
  unsigned epoch[NCTA * 2];
};
__device__ Scratch g_scratch;
#define TG(i) do {} while (0)
#define TSV(i, v) do {} while (0)
#define TS(i) do {} while (0)

struct Maps { CUtensorMap x, xn, out, wqkv, wg, wu, wd, wo; };

__device__ __forceinline__ void mbar_init(uint32_t bar, uint32_t cnt) { asm volatile("mbarrier.init.shared::cta.b64 [%0], %1;" ::"r"(bar), "r"(cnt)); }
__device__ __forceinline__ void mbar_expect_tx(uint32_t bar, uint32_t bytes) { asm volatile("mbarrier.arrive.expect_tx.shared::cta.b64 _, [%0], %1;" ::"r"(bar), "r"(bytes) : "memory"); }
__device__ __forceinline__ void mbar_arrive(uint32_t bar) { asm volatile("mbarrier.arrive.shared::cta.b64 _, [%0];" ::"r"(bar) : "memory"); }
__device__ __forceinline__ void mbar_arrive_cl(uint32_t bar) { asm volatile("mbarrier.arrive.shared::cluster.b64 _, [%0];" ::"r"(bar) : "memory"); }
__device__ __forceinline__ uint32_t mapa(uint32_t a, uint32_t cta) { uint32_t r; asm("mapa.shared::cluster.u32 %0, %1, %2;" : "=r"(r) : "r"(a), "r"(cta)); return r; }
__device__ __forceinline__ void mbar_wait(uint32_t bar, uint32_t parity) {
  asm volatile("{\n.reg .pred p;\n.reg .u32 n;\nmov.u32 n, 0;\nLAB_WAIT:\nmbarrier.try_wait.parity.shared::cta.b64 p, [%0], %1;\n@p bra LAB_DONE;\n"
               "add.u32 n, n, 1;\nsetp.gt.u32 p, n, 4000000;\n@p trap;\nbra LAB_WAIT;\nLAB_DONE:\n}" ::"r"(bar), "r"(parity) : "memory");
}
__device__ __forceinline__ void mbar_spin(uint32_t bar, uint32_t parity, uint32_t zero) {
  asm volatile("{\n.reg .pred p, z;\nsetp.ne.u32 z, %2, 0;\nLAB_WAIT:\nmbarrier.try_wait.parity.shared::cta.b64 p, [%0], %1;\n@p bra LAB_DONE;\n@z trap;\nbra LAB_WAIT;\nLAB_DONE:\n}" ::"r"(bar), "r"(parity), "r"(zero) : "memory");
}
__device__ __forceinline__ void flag_wait(const unsigned* f, unsigned target) {
  asm volatile("{\n.reg .pred p;\n.reg .u32 n, v;\nmov.u32 n, 0;\nLAB_WAIT:\nld.relaxed.gpu.global.u32 v, [%0];\nsub.u32 v, v, %1;\nsetp.ge.s32 p, v, 0;\n@p bra LAB_DONE;\n"
               "nanosleep.u32 100;\nadd.u32 n, n, 1;\nsetp.gt.u32 p, n, 4000000;\n@p trap;\nbra LAB_WAIT;\nLAB_DONE:\nfence.acquire.gpu;\n}" ::"l"(f), "r"(target) : "memory");
}
__device__ __forceinline__ void flag_add(unsigned* f) { asm volatile("red.release.gpu.global.add.u32 [%0], 1;" ::"l"(f) : "memory"); }
__device__ __forceinline__ void fence_async() { asm volatile("fence.proxy.async.global;" ::: "memory"); }
__device__ __forceinline__ bool elect_one() { uint32_t p; asm volatile("{\n.reg .pred P;\nelect.sync _|P, 0xffffffff;\nselp.u32 %0, 1, 0, P;\n}" : "=r"(p)); return p; }
__device__ __forceinline__ void bar_sync(int id, int n) { asm volatile("bar.sync %0, %1;" ::"r"(id), "r"(n) : "memory"); }
__device__ __forceinline__ void bar_arrive(int id, int n) { asm volatile("bar.arrive %0, %1;" ::"r"(id), "r"(n) : "memory"); }

__device__ __forceinline__ void tma2d(uint32_t dst, const CUtensorMap* tm, uint32_t bar, int c0, int c1, uint64_t hint) {
  asm volatile("cp.async.bulk.tensor.2d.shared::cluster.global.mbarrier::complete_tx::bytes.L2::cache_hint [%0], [%1, {%3, %4}], [%2], %5;" ::"r"(dst), "l"(tm), "r"(bar), "r"(c0), "r"(c1), "l"(hint) : "memory");
}
__device__ __forceinline__ void tma2d_mc(uint32_t dst, const CUtensorMap* tm, uint32_t bar, int c0, int c1, uint64_t hint) {
  asm volatile("cp.async.bulk.tensor.2d.shared::cluster.global.mbarrier::complete_tx::bytes.multicast::cluster.L2::cache_hint [%0], [%1, {%3, %4}], [%2], %5, %6;" ::"r"(dst), "l"(tm), "r"(bar), "r"(c0), "r"(c1), "h"((uint16_t)3), "l"(hint) : "memory");
}
__device__ __forceinline__ void tma3d(uint32_t dst, const CUtensorMap* tm, uint32_t bar, int c0, int c1, int c2, uint64_t hint) {
  asm volatile("cp.async.bulk.tensor.3d.shared::cluster.global.mbarrier::complete_tx::bytes.L2::cache_hint [%0], [%1, {%3, %4, %5}], [%2], %6;" ::"r"(dst), "l"(tm), "r"(bar), "r"(c0), "r"(c1), "r"(c2), "l"(hint) : "memory");
}
__device__ __forceinline__ void tma5d(uint32_t dst, const CUtensorMap* tm, uint32_t bar, int c0, int c4, uint64_t hint) {
  asm volatile("cp.async.bulk.tensor.5d.shared::cluster.global.mbarrier::complete_tx::bytes.L2::cache_hint [%0], [%1, {%3, %5, %5, %5, %4}], [%2], %6;" ::"r"(dst), "l"(tm), "r"(bar), "r"(c0), "r"(c4), "r"(0), "l"(hint) : "memory");
}
__device__ __forceinline__ void tma5d_prefetch(const CUtensorMap* tm, int c0, int c4) {
  asm volatile("cp.async.bulk.prefetch.tensor.5d.L2.global [%0, {%1, %3, %3, %3, %2}];" ::"l"(tm), "r"(c0), "r"(c4), "r"(0) : "memory");
}
__device__ __forceinline__ void tma3d_store(const CUtensorMap* tm, uint32_t src, int c0, int c1, int c2) {
  asm volatile("cp.async.bulk.tensor.3d.global.shared::cta.bulk_group [%0, {%2, %3, %4}], [%1];" ::"l"(tm), "r"(src), "r"(c0), "r"(c1), "r"(c2) : "memory");
}
__device__ __forceinline__ void bulk_load(uint32_t dst, const void* src, uint32_t bytes, uint32_t bar, uint64_t hint) {
  asm volatile("cp.async.bulk.shared::cluster.global.mbarrier::complete_tx::bytes.L2::cache_hint [%0], [%1], %2, [%3], %4;" ::"r"(dst), "l"(src), "r"(bytes), "r"(bar), "l"(hint) : "memory");
}
__device__ __forceinline__ void bulk_load_mc(uint32_t dst, const void* src, uint32_t bytes, uint32_t bar, uint64_t hint) {
  asm volatile("cp.async.bulk.shared::cluster.global.mbarrier::complete_tx::bytes.multicast::cluster.L2::cache_hint [%0], [%1], %2, [%3], %4, %5;" ::"r"(dst), "l"(src), "r"(bytes), "r"(bar), "h"((uint16_t)3), "l"(hint) : "memory");
}
__device__ __forceinline__ uint4 lds128(uint32_t a) { uint4 v; asm volatile("ld.shared.v4.b32 {%0,%1,%2,%3}, [%4];" : "=r"(v.x), "=r"(v.y), "=r"(v.z), "=r"(v.w) : "r"(a) : "memory"); return v; }
__device__ __forceinline__ void sts128(uint32_t a, uint4 v) { asm volatile("st.shared.v4.b32 [%0], {%1,%2,%3,%4};" ::"r"(a), "r"(v.x), "r"(v.y), "r"(v.z), "r"(v.w) : "memory"); }
__device__ __forceinline__ void stg128(void* p, uint32_t a, uint32_t b, uint32_t c, uint32_t d) { asm volatile("st.global.v4.b32 [%0], {%1,%2,%3,%4};" ::"l"(p), "r"(a), "r"(b), "r"(c), "r"(d) : "memory"); }

__device__ __forceinline__ uint32_t pack2(float lo, float hi) { uint32_t r; asm("cvt.rn.bf16x2.f32 %0, %1, %2;" : "=r"(r) : "f"(hi), "f"(lo)); return r; }
__device__ __forceinline__ float lo_f(uint32_t v) { return __uint_as_float(v << 16); }
__device__ __forceinline__ float hi_f(uint32_t v) { return __uint_as_float(v & 0xffff0000u); }
__device__ __forceinline__ float bf16r(float v) { return lo_f(pack2(v, 0.f)); }
__device__ __forceinline__ uint32_t mul2(uint32_t a, uint32_t b) { uint32_t r; asm("mul.rn.bf16x2 %0, %1, %2;" : "=r"(r) : "r"(a), "r"(b)); return r; }
__device__ __forceinline__ uint32_t add2(uint32_t a, uint32_t b) { uint32_t r; asm("add.rn.bf16x2 %0, %1, %2;" : "=r"(r) : "r"(a), "r"(b)); return r; }
__device__ __forceinline__ uint32_t sub2(uint32_t a, uint32_t b) { uint32_t r; asm("sub.rn.bf16x2 %0, %1, %2;" : "=r"(r) : "r"(a), "r"(b)); return r; }
__device__ __forceinline__ uint32_t fma2(uint32_t a, uint32_t b, uint32_t c) { uint32_t r; asm("fma.rn.bf16x2 %0, %1, %2, %3;" : "=r"(r) : "r"(a), "r"(b), "r"(c)); return r; }
__device__ __forceinline__ uint32_t max2(uint32_t a, uint32_t b) { uint32_t r; asm("max.bf16x2 %0, %1, %2;" : "=r"(r) : "r"(a), "r"(b)); return r; }
__device__ __forceinline__ float ex2f(float x) { float y; asm("ex2.approx.ftz.f32 %0, %1;" : "=f"(y) : "f"(x)); return y; }
__device__ __forceinline__ float rcpf(float x) { float y; asm("rcp.approx.ftz.f32 %0, %1;" : "=f"(y) : "f"(x)); return y; }
constexpr float GELU_C1 = 0.7978845608028654f, GELU_C3 = 0.035677408136300125f;
__device__ __forceinline__ float gelu_k(float g, float c1, float c3, float k) {
  float t;
  asm("tanh.approx.f32 %0, %1;" : "=f"(t) : "f"(g * fmaf(g * g, c3, c1)));
  g *= k;
  return fmaf(g, t, g);
}
__device__ __forceinline__ float silu_half(float z) { float t; asm("tanh.approx.f32 %0, %1;" : "=f"(t) : "f"(z)); return fmaf(z, t, z); }

__device__ __forceinline__ void wg_fence() { asm volatile("wgmma.fence.sync.aligned;" ::: "memory"); }
__device__ __forceinline__ void wg_commit() { asm volatile("wgmma.commit_group.sync.aligned;" ::: "memory"); }
template <int N> __device__ __forceinline__ void wg_wait() { asm volatile("wgmma.wait_group.sync.aligned %0;" ::"n"(N) : "memory"); }
#define A8(o) "+f"(d[(o)]), "+f"(d[(o) + 1]), "+f"(d[(o) + 2]), "+f"(d[(o) + 3]), "+f"(d[(o) + 4]), "+f"(d[(o) + 5]), "+f"(d[(o) + 6]), "+f"(d[(o) + 7])
#define A64(o) A8(o), A8((o) + 8), A8((o) + 16), A8((o) + 24), A8((o) + 32), A8((o) + 40), A8((o) + 48), A8((o) + 56)
#define REGS0_63 "%0,%1,%2,%3,%4,%5,%6,%7,%8,%9,%10,%11,%12,%13,%14,%15,%16,%17,%18,%19,%20,%21,%22,%23,%24,%25,%26,%27,%28,%29,%30,%31," \
                 "%32,%33,%34,%35,%36,%37,%38,%39,%40,%41,%42,%43,%44,%45,%46,%47,%48,%49,%50,%51,%52,%53,%54,%55,%56,%57,%58,%59,%60,%61,%62,%63"
#define REGS64_127 "%64,%65,%66,%67,%68,%69,%70,%71,%72,%73,%74,%75,%76,%77,%78,%79,%80,%81,%82,%83,%84,%85,%86,%87,%88,%89,%90,%91,%92,%93,%94,%95," \
                   "%96,%97,%98,%99,%100,%101,%102,%103,%104,%105,%106,%107,%108,%109,%110,%111,%112,%113,%114,%115,%116,%117,%118,%119,%120,%121,%122,%123,%124,%125,%126,%127"
__device__ __forceinline__ void desc_add(uint64_t& x, int v) { asm volatile("{\n.reg .b32 lo, hi;\nmov.b64 {lo, hi}, %0;\nadd.s32 lo, lo, %1;\nmov.b64 %0, {lo, hi};\n}" : "+l"(x) : "r"(v)); }
template <int ACCUM> __device__ __forceinline__ void wgmma256(float (&d)[128], uint64_t& a, uint64_t& b, int da, int db) {
  asm volatile("{\n.reg .pred p;\nsetp.ne.b32 p, %130, 0;\n"
               "wgmma.mma_async.sync.aligned.m64n256k16.f32.bf16.bf16 {" REGS0_63 "," REGS64_127 "}, %128, %129, p, 1, 1, 0, 1;\n}"
               : A64(0), A64(64) : "l"(a), "l"(b), "n"(ACCUM));
  desc_add(a, da); desc_add(b, db);
}
__device__ __forceinline__ void wgmma256_rs(float (&d)[128], uint32_t a0, uint32_t a1, uint32_t z0, uint32_t z1, uint32_t b_lo) {
  asm volatile("{\n.reg .b64 db;\nmov.b64 db, {%132, 0x00000008};\n"
               "wgmma.mma_async.sync.aligned.m64n256k16.f32.bf16.bf16 {" REGS0_63 "," REGS64_127 "}, {%128,%129,%130,%131}, db, 1, 1, 1, 0;\n}"
               : A64(0), A64(64) : "r"(a0), "r"(a1), "r"(z0), "r"(z1), "r"(b_lo));
}
template <int ACCUM> __device__ __forceinline__ void wgmma128(float (&d)[64], uint64_t& a, uint64_t& b, int da, int db) {
  asm volatile("{\n.reg .pred p;\nsetp.ne.b32 p, %66, 0;\n"
               "wgmma.mma_async.sync.aligned.m64n128k16.f32.bf16.bf16 {" REGS0_63 "}, %64, %65, p, 1, 1, 0, 1;\n}"
               : A64(0) : "l"(a), "l"(b), "n"(ACCUM));
  desc_add(a, da); desc_add(b, db);
}
template <int ACCUM> __device__ __forceinline__ void hmma(float (&c)[4], uint32_t a0, uint32_t a1, uint32_t a2, uint32_t a3, uint32_t b0, uint32_t b1) {
  if (ACCUM)
    asm volatile("mma.sync.aligned.m16n8k16.row.col.f32.bf16.bf16.f32 {%0,%1,%2,%3}, {%4,%5,%6,%7}, {%8,%9}, {%0,%1,%2,%3};"
                 : "+f"(c[0]), "+f"(c[1]), "+f"(c[2]), "+f"(c[3]) : "r"(a0), "r"(a1), "r"(a2), "r"(a3), "r"(b0), "r"(b1));
  else
    asm volatile("mma.sync.aligned.m16n8k16.row.col.f32.bf16.bf16.f32 {%0,%1,%2,%3}, {%4,%5,%6,%7}, {%8,%9}, {%10,%10,%10,%10};"
                 : "=f"(c[0]), "=f"(c[1]), "=f"(c[2]), "=f"(c[3]) : "r"(a0), "r"(a1), "r"(a2), "r"(a3), "r"(b0), "r"(b1), "f"(0.f));
}
__device__ __forceinline__ uint32_t movm(uint32_t a) { uint32_t d; asm volatile("movmatrix.sync.aligned.m8n8.trans.b16 %0, %1;" : "=r"(d) : "r"(a)); return d; }
__device__ __forceinline__ int lane_here() { int v; asm volatile("mov.u32 %0, %%laneid;" : "=r"(v)); return v; }
template <int N> __device__ __forceinline__ void pin(uint32_t* r) {
#pragma unroll
  for (int i = 0; i < N; i++) asm volatile("" : "+r"(r[i]));
}
template <int N> __device__ __forceinline__ void pin(float* r) {
#pragma unroll
  for (int i = 0; i < N; i++) asm volatile("" : "+f"(r[i]));
}
__device__ __forceinline__ void sched_fence(uint32_t zero) {
  asm volatile("{\n.reg .pred p;\nsetp.eq.u32 p, %0, 0;\nLAB_F:\n@p bra.uni LAB_D;\nnanosleep.u32 0;\nbra.uni LAB_F;\nLAB_D:\n}" ::"r"(zero) : "memory");
}
__device__ __forceinline__ uint4 ldsm(uint32_t a) { uint4 v; asm volatile("ldmatrix.sync.aligned.m8n8.x4.shared.b16 {%0,%1,%2,%3}, [%4];" : "=r"(v.x), "=r"(v.y), "=r"(v.z), "=r"(v.w) : "r"(a) : "memory"); return v; }
__device__ __forceinline__ uint4 ldsm_t(uint32_t a) { uint4 v; asm volatile("ldmatrix.sync.aligned.m8n8.x4.trans.shared.b16 {%0,%1,%2,%3}, [%4];" : "=r"(v.x), "=r"(v.y), "=r"(v.z), "=r"(v.w) : "r"(a) : "memory"); return v; }

constexpr int BAR_LAG = 1, BAR_MMA = 2, BAR_EV = 3;

struct Cons {
  uint32_t sb;
  mutable uint64_t a, b;
  int k1, k2, k4, k4w, b1;
  uint32_t rel;
  bool do_rel;
  int wg;
  uint32_t zero;
};
#define REL_TS(n) TS(64 + (n))
constexpr uint32_t DB_LO = (SM_BASE >> 4) | ((8192 >> 4) << 16);

template <int ST, int ACCUM, bool WAIT = true> __device__ __forceinline__ void p1_issue(float (&acc)[128], const Cons& c, uint32_t parity) {
  if (WAIT) mbar_spin(c.sb + B_F1 + 8 * ST, parity, c.zero);
  wg_fence();
  wgmma256<ACCUM>(acc, c.a, c.b, c.k1, c.b1);
  wgmma256<1>(acc, c.a, c.b, c.k2, c.b1);
  wgmma256<1>(acc, c.a, c.b, c.k1, c.b1);
  wgmma256<1>(acc, c.a, c.b, ST == 3 ? c.k4w : c.k4, ST == 3 ? -6144 - 384 : 2048 - 384);
  wg_commit();
}
__device__ __forceinline__ void release(const Cons& c, uint32_t bar) { if (c.do_rel) mbar_arrive_cl(c.rel + bar); }
template <int KB, bool WAIT = true, int LAG = 2> __device__ __forceinline__ void p1_step(float (&acc)[128], const Cons& c) {
  if (KB == 16 - LAG) { if (c.wg == 1) { wg_wait<0>(); release(c, B_E1 + 8 * ((KB - 1) & 3)); bar_sync(BAR_LAG, 256); } }
  p1_issue<KB & 3, KB != 0, WAIT>(acc, c, (KB >> 2) & 1);
  if (KB == 15) { if (c.wg == 0) bar_arrive(BAR_LAG, 256); }
  if (KB > 0) { wg_wait<1>(); if (KB != 16 - LAG || c.wg == 0) release(c, B_E1 + 8 * ((KB - 1) & 3)); }
  if (KB == 15) { wg_wait<0>(); release(c, B_E1 + 8 * 3); }
}
template <class F> __device__ __forceinline__ void p1_loop(float (&acc)[128], const Cons& c, int from, int to, F&& shadow) {
#pragma unroll 1
  for (int kb = from; kb < to; kb++) {
    const bool wrap = (kb & 3) == 3;
    mbar_spin(c.sb + B_F1 + 8 * (kb & 3), (kb >> 2) & 1, c.zero);
    wg_fence();
    wgmma256<1>(acc, c.a, c.b, c.k1, c.b1);
    wgmma256<1>(acc, c.a, c.b, c.k2, c.b1);
    wgmma256<1>(acc, c.a, c.b, c.k1, c.b1);
    wgmma256<1>(acc, c.a, c.b, wrap ? c.k4w : c.k4, wrap ? -6144 - 384 : 2048 - 384);
    wg_commit();
    wg_wait<1>();
    release(c, B_E1 + 8 * ((kb - 1) & 3));
    shadow(kb);
  }
}
template <int T> __device__ __forceinline__ void p2_step(float (&acc)[64], const Cons& c) {
  if (T == 16 - LAG2) { if (c.wg == 1) bar_sync(BAR_LAG, 256); }
  mbar_spin(c.sb + B_F2 + 8 * (T % 5), (T / 5) & 1, c.zero);
  wg_fence();
  wgmma128<T != 0>(acc, c.a, c.b, c.k1, c.b1);
  wgmma128<1>(acc, c.a, c.b, c.k2, c.b1);
  wgmma128<1>(acc, c.a, c.b, c.k1, c.b1);
  wgmma128<1>(acc, c.a, c.b, ((int)p2_a((T + 1) % 5) - (int)p2_a(T % 5)) / 16 - 514, ((int)p2_b((T + 1) % 5) - (int)p2_b(T % 5)) / 16 - 384);
  wg_commit();
  if (T == 15) { if (c.wg == 0) bar_arrive(BAR_LAG, 256); }
  if (T <= 11) { wg_wait<1>(); release(c, T ? B_E2 + 8 * ((T + 5 - 1) % 5) : B_E1 + 8); }
}

template <int P> __device__ __forceinline__ void geglu_piece(uint32_t (&pk)[64], uint8_t* dst, float (&rs)[2]) {
  constexpr int cg = P >> 1, r = P & 1;
  pin<1>(rs + r);
#pragma unroll
  for (int i = 0; i < 4; i++) pin<1>(pk + 2 * (4 * cg + i) + r);
  const float r2 = rs[r] * rs[r], c1 = GELU_C1 * rs[r], c3 = GELU_C3 * r2 * rs[r], k = 0.25f * r2;
  uint32_t v[4];
#pragma unroll
  for (int i = 0; i < 4; i++) {
    const uint32_t g = pk[2 * (4 * cg + i) + r];
    v[i] = mul2(pack2(gelu_k(lo_f(g), c1, c3, k), gelu_k(hi_f(g), c1, c3, k)), pk[32 + 2 * (4 * cg + i) + r]);
  }
  stg128(dst + cg * 8192 + r * 512, v[0], v[1], v[2], v[3]);
}
__device__ __forceinline__ void geglu_tile(float (&acc)[128], uint32_t (&pk)[64], const Cons& c, int to, uint8_t* dst, int ev, float (&rs)[2]) {
  const int lane = lane_here();
  dst += (lane ^ (lane >> 3)) << 4;
  p1_loop(acc, c, 1, to, [&](int kb) {
    if (kb <= 4) {
      if (kb <= 2) { if (kb == 1) geglu_piece<0>(pk, dst, rs); else geglu_piece<1>(pk, dst, rs); }
      else { if (kb == 3) geglu_piece<2>(pk, dst, rs); else geglu_piece<3>(pk, dst, rs); }
    } else if (kb <= 8) {
      if (kb <= 6) { if (kb == 5) geglu_piece<4>(pk, dst, rs); else geglu_piece<5>(pk, dst, rs); }
      else { if (kb == 7) geglu_piece<6>(pk, dst, rs); else { geglu_piece<7>(pk, dst, rs); bar_arrive(ev, 288); } }
    }
  });
}

__device__ __forceinline__ void attn_tile(float (&acc)[128], uint32_t (&pk)[64], const Cons& c, int round, int warp, int m, Scratch* gs, uint8_t* hdst, uint8_t* odst) {
  const int w = warp & 3;
  const uint32_t at = c.sb + OFF_X + c.wg * AT_WG;
  int lane = lane_here();
  hdst += (lane ^ (lane >> 3)) << 4;
  auto scatter = [&]() {
    const int lane = lane_here();
    const uint32_t swz = (lane ^ (lane >> 3)) << 4;
#pragma unroll
    for (int i = 0; i < 4; i++) {
      const int h = i & 1, r = i >> 1;
      sts128(at + AT_V + (2 * w + r) * 1024 + h * 512 + swz, make_uint4(pk[32 + 8 * h + r], pk[34 + 8 * h + r], pk[36 + 8 * h + r], pk[38 + 8 * h + r]));
    }
    if (w < 3) {
#pragma unroll
      for (int i = 0; i < 8; i++) asm volatile("st.shared.b32 [%0], %1;" ::"r"(at + AT_K + w * 1024 + i * 128 + lane * 4), "r"(pk[17 + 2 * i]) : "memory");
    } else {
      uint8_t* g = (uint8_t*)gs->halo + ((round * 128 + blockIdx.x) * 2 + c.wg) * 2048;
#pragma unroll
      for (int i = 0; i < 8; i++) asm volatile("st.global.b32 [%0], %1;" ::"l"(g + i * 128 + lane * 4), "r"(pk[17 + 2 * i]) : "memory");
#pragma unroll
      for (int h = 0; h < 2; h++) stg128(g + 1024 + h * 512 + swz, pk[33 + 8 * h], pk[35 + 8 * h], pk[37 + 8 * h], pk[39 + 8 * h]);
      bar_arrive(BAR_EV + 2 + round, 96);
    }
    __syncwarp();
    if (lane == 0) mbar_arrive(c.sb + B_HALO + 8 * round);
    if (round) {
#pragma unroll
      for (int p = 0; p < 4; p++) {
        const int o = 32 + 8 * (p >> 1) + (p & 1);
        asm volatile("ld.global.cg.v4.b32 {%0,%1,%2,%3}, [%4];" : "=r"(pk[o]), "=r"(pk[o + 2]), "=r"(pk[o + 4]), "=r"(pk[o + 6]) : "l"(hdst + (p >> 1) * 8192 + (p & 1) * 512) : "memory");
      }
    }
  };
  auto gu_piece = [&](int p) {
    uint32_t v[4];
#pragma unroll
    for (int i = 0; i < 4; i++) {
      const int o = 8 * (p >> 1) + 2 * i + (p & 1);
      pin<1>(pk + 48 + o);
      const uint32_t g = pk[48 + o];
      v[i] = mul2(round ? pk[32 + o] : 0x3e803e80u, round ? g : pack2(gelu_k(lo_f(g), GELU_C1, GELU_C3, 1.0f), gelu_k(hi_f(g), GELU_C1, GELU_C3, 1.0f)));
    }
    stg128(hdst + (p >> 1) * 8192 + (p & 1) * 512, v[0], v[1], v[2], v[3]);
  };
  p1_step<1>(acc, c);
  scatter();
  p1_loop(acc, c, 2, 9, [&](int kb) {
    if (kb <= 4) { if (kb == 3) gu_piece(0); else if (kb == 4) gu_piece(1); }
    else if (kb == 5) gu_piece(2); else if (kb == 6) gu_piece(3);
  });
  const bool first = m == 0 && w == 0;
  uint32_t kl[16];
  mbar_spin(c.sb + B_HALO + 8 * round, 0, c.zero);
  lane = lane_here();
  {
    const uint32_t ka = at + lane * 4 + (w ? AT_K + (w - 1) * 1024 : (first ? AT_K : AT_REM + round * 2048));
#pragma unroll
    for (int i = 0; i < 8; i++) {
      asm volatile("ld.shared.b32 %0, [%1];" : "=r"(kl[2 * i]) : "r"(ka + i * 128) : "memory");
      kl[2 * i + 1] = pk[16 + 2 * i] | c.zero;
    }
  }
  float st[4][4];
  pin<16>(kl);
  bar_sync(BAR_MMA, 256);
  mbar_spin(c.sb + B_F1 + 8 * 1, 0, c.zero);
#pragma unroll
  for (int ks = 0; ks < 2; ks++) {
#pragma unroll
    for (int h = 0; h < 2; h++) {
      const int o = 8 * h + 4 * ks;
      if (ks == 0) { hmma<0>(st[2 * h], kl[o], kl[o + 1], kl[o + 2], kl[o + 3], pk[o], pk[o + 2]); hmma<0>(st[2 * h + 1], pk[16 + o], pk[17 + o], pk[18 + o], pk[19 + o], pk[o + 1], pk[o + 3]); }
      else { hmma<1>(st[2 * h], kl[o], kl[o + 1], kl[o + 2], kl[o + 3], pk[o], pk[o + 2]); hmma<1>(st[2 * h + 1], pk[16 + o], pk[17 + o], pk[18 + o], pk[19 + o], pk[o + 1], pk[o + 3]); }
    }
  }
  sched_fence(c.zero);
  bar_sync(BAR_MMA, 256);
  p1_step<9, false>(acc, c);
  sched_fence(c.zero);
  pin<16>(&st[0][0]);
  lane = lane_here();
  const int rho = lane >> 2, q = lane & 3;
  const bool le0 = 2 * q <= rho, le1 = 2 * q + 1 <= rho;
  uint32_t la[2], lb[2], mx[2];
#pragma unroll
  for (int h = 0; h < 2; h++) {
    uint32_t l[2];
#pragma unroll
    for (int r = 0; r < 2; r++) {
      const float (&t)[4] = st[2 * h + r];
      l[r] = movm(pack2(rho <= 2 * q ? t[2] : t[0], rho <= 2 * q + 1 ? t[3] : t[1]));
      l[r] = fma2(l[r], 0x3e353e35u, mul2(l[r], 0x379e379eu));
    }
    la[h] = __byte_perm(l[0], l[1], 0x5410); lb[h] = __byte_perm(l[0], l[1], 0x7632);
    if (first && !le0) la[h] = (la[h] & 0xffff0000u) | 0xce6eu;
    if (first && !le1) lb[h] = (lb[h] & 0xffff0000u) | 0xce6eu;
    mx[h] = max2(la[h], lb[h]);
  }
#pragma unroll
  for (int o = 1; o <= 2; o++) { mx[0] = max2(mx[0], __shfl_xor_sync(~0u, mx[0], o)); mx[1] = max2(mx[1], __shfl_xor_sync(~0u, mx[1], o)); }
  const float L2E = 1.4426950408889634f;
  float pr[2][4], z[4];
#pragma unroll
  for (int h = 0; h < 2; h++) {
    pr[h][0] = ex2f((lo_f(la[h]) - lo_f(mx[h])) * L2E); pr[h][1] = ex2f((lo_f(lb[h]) - lo_f(mx[h])) * L2E);
    pr[h][2] = ex2f((hi_f(la[h]) - hi_f(mx[h])) * L2E); pr[h][3] = ex2f((hi_f(lb[h]) - hi_f(mx[h])) * L2E);
    z[2 * h] = pr[h][0] + pr[h][1]; z[2 * h + 1] = pr[h][2] + pr[h][3];
  }
  p1_step<10>(acc, c);
#pragma unroll
  for (int o = 1; o <= 2; o++) {
#pragma unroll
    for (int i = 0; i < 4; i++) z[i] += __shfl_xor_sync(~0u, z[i], o);
  }
  const uint32_t LE = (le0 ? 0xffffu : 0u) | (le1 ? 0xffff0000u : 0u);
  uint32_t P[4][2];
  uint4 vt[4][2];
  {
    const uint32_t row = (lane & 7) * 64 + ((((lane >> 3) & 1) ^ ((lane & 7) >> 1)) << 4);
    const uint32_t v1 = at + AT_V + (2 * w + (lane >> 4)) * 1024 + row;
    const uint32_t v0 = (w || lane >= 16) ? v1 - 1024 : (first ? v1 : at + AT_REM + round * 2048 + 1024 + row);
#pragma unroll
    for (int i = 0; i < 4; i++) {
      const float rz = rcpf(z[i]);
      const uint32_t p = pack2(pr[i >> 1][2 * (i & 1)] * rz, pr[i >> 1][2 * (i & 1) + 1] * rz);
      P[i][0] = p & ~LE; P[i][1] = p & LE;
      const uint32_t a = ((i & 1) ? v1 : v0) + (i >> 1) * 512;
      vt[i][0] = ldsm_t(a); vt[i][1] = ldsm_t(a ^ 32);
    }
  }
  float ot[4][2][4];
  pin<8>(&P[0][0]);
  bar_sync(BAR_MMA, 256);
  mbar_spin(c.sb + B_F1 + 8 * 3, 0, c.zero);
#pragma unroll
  for (int i = 0; i < 8; i++) { const uint4& v = vt[i >> 1][i & 1]; hmma<0>(ot[i >> 1][i & 1], v.x, v.y, v.z, v.w, P[i >> 1][0], P[i >> 1][1]); }
  sched_fence(c.zero);
  bar_sync(BAR_MMA, 256);
  p1_step<11, false>(acc, c);
  sched_fence(c.zero);
  pin<32>(&ot[0][0][0]);
  lane = lane_here();
  odst += (lane ^ (lane >> 3)) << 4;
  auto o_piece = [&](int i) {
    stg128(odst + (i >> 1) * 8192 + (i & 1) * 512, movm(pack2(ot[i][0][0], ot[i][0][1])), movm(pack2(ot[i][0][2], ot[i][0][3])), movm(pack2(ot[i][1][0], ot[i][1][1])), movm(pack2(ot[i][1][2], ot[i][1][3])));
  };
  o_piece(0); o_piece(1);
  p1_step<12>(acc, c);
  o_piece(2); o_piece(3);
  if (round) bar_arrive(BAR_EV + 4, 288);
  p1_step<13>(acc, c);
}

__device__ __forceinline__ void ln_moments(const uint32_t* raw, float& c0, float& s, float& v) {
  c0 = lo_f(__shfl_sync(~0u, raw[0], 0));
  float ss[4] = {0.f, 0.f, 0.f, 0.f}, vv[4] = {0.f, 0.f, 0.f, 0.f};
#pragma unroll
  for (int i = 0; i < 16; i++) {
    const float a = lo_f(raw[i]) - c0, b = hi_f(raw[i]) - c0;
    ss[(2 * i) & 3] += a; ss[(2 * i + 1) & 3] += b;
    vv[(2 * i) & 3] = fmaf(a, a, vv[(2 * i) & 3]); vv[(2 * i + 1) & 3] = fmaf(b, b, vv[(2 * i + 1) & 3]);
  }
  s = (ss[0] + ss[1]) + (ss[2] + ss[3]); v = (vv[0] + vv[1]) + (vv[2] + vv[3]);
}
__device__ __forceinline__ void ln_reduce(float& s, float& v) {
#pragma unroll
  for (int o = 16; o; o >>= 1) { s += __shfl_xor_sync(~0u, s, o); v += __shfl_xor_sync(~0u, v, o); }
}
__device__ __forceinline__ uint32_t ln_finish(float c0, float s, float v) {
  s *= 1.0f / DM;
  float sd;
  asm("sqrt.approx.ftz.f32 %0, %1;" : "=f"(sd) : "f"(bf16r(bf16r(fmaxf(fmaf(v, 1.0f / DM, -s * s), 0.f)) + 1e-5f)));
  return pack2(c0 + s, sd);
}
__device__ __forceinline__ void ln_store(const uint32_t* raw, uint32_t st, uint4* dst) {
  const uint32_t m2 = __byte_perm(st, st, 0x1010);
  const float rinv = rcpf(hi_f(st));
  const uint32_t rh = pack2(rinv, rinv), rl = pack2(rinv - hi_f(rh), rinv - hi_f(rh));
#pragma unroll
  for (int c = 0; c < 4; c++) {
    uint32_t v[4];
#pragma unroll
    for (int i = 0; i < 4; i++) { const uint32_t t = sub2(raw[4 * c + i], m2); v[i] = fma2(t, rh, mul2(t, rl)); }
    stg128(dst + 32 * c, v[0], v[1], v[2], v[3]);
  }
}
__device__ __forceinline__ void col_sums(uint32_t tile, ulonglong2* part, uint32_t tag) {
  const int lane = threadIdx.x & 31;
  float cs[8] = {0, 0, 0, 0, 0, 0, 0, 0};
  uint32_t base = tile + ((lane >> 3) & 1) * 8192 + (lane >> 4) * 4096 + ((lane & 7) << 4);
#pragma unroll 1
  for (int k0 = 0; k0 < 8; k0++, base = (base ^ ((k0 ^ (k0 - 1)) << 4)) + 128) {
    uint4 v[4];
#pragma unroll
    for (int k = 0; k < 4; k++) v[k] = lds128(base + k * 1024);
#pragma unroll
    for (int k = 0; k < 4; k++) {
      cs[0] += lo_f(v[k].x); cs[1] += hi_f(v[k].x); cs[2] += lo_f(v[k].y); cs[3] += hi_f(v[k].y);
      cs[4] += lo_f(v[k].z); cs[5] += hi_f(v[k].z); cs[6] += lo_f(v[k].w); cs[7] += hi_f(v[k].w);
    }
  }
  const bool up = lane >= 16;
#pragma unroll
  for (int i = 0; i < 2; i++) {
    const float a = (up ? cs[4 + 2 * i] : cs[2 * i]) + __shfl_xor_sync(~0u, up ? cs[2 * i] : cs[4 + 2 * i], 16);
    const float b = (up ? cs[5 + 2 * i] : cs[1 + 2 * i]) + __shfl_xor_sync(~0u, up ? cs[1 + 2 * i] : cs[5 + 2 * i], 16);
    asm volatile("{\n.reg .b64 a, b;\nmov.b64 a, {%1, %3};\nmov.b64 b, {%2, %3};\nst.relaxed.gpu.global.v2.b64 [%0], {a, b};\n}"
                 ::"l"(part + 32 * (i + (up ? 2 : 0)) + (lane & 15)), "r"(__float_as_uint(a)), "r"(__float_as_uint(b)), "r"(tag) : "memory");
  }
  asm volatile("fence.proxy.async.shared::cta;" ::: "memory");
}

__global__ void __cluster_dims__(2, 1, 1) __launch_bounds__(384, 1)
fused_kernel(const uint4* __restrict__ x, const uint4* __restrict__ wgate, const uint4* __restrict__ wup, Scratch* gs, const __grid_constant__ Maps mp) {
  extern __shared__ __align__(1024) uint8_t smem_raw[];
  const uint32_t sb = (uint32_t)__cvta_generic_to_shared(smem_raw);
  if (threadIdx.x == 352) TS(63);
  if (threadIdx.x < 256 && blockIdx.x < NMAIN) {
    const uint32_t r = threadIdx.x >> 3, ch = threadIdx.x & 7;
    const uint32_t d = sb + r * 128 + ((ch ^ (r & 7)) << 4);
    const uint8_t* xa = (const uint8_t*)x + ((blockIdx.x & 15) * 262144 + r * 4096 + ch * 16);
    const uint32_t wo = r * (DFF * 2) + (blockIdx.x >> 4) * 256 + ch * 16;
    const uint8_t *wa = (const uint8_t*)wgate + wo, *wb = (const uint8_t*)wup + wo;
#pragma unroll
    for (int i = 0; i < 12; i++) {
      const int h = i >= 8;
      const uint8_t* src = (i >> 2) == 1 ? xa + (i & 1) * 131072 + ((i >> 1) & 1) * 2048 : ((i & 2) ? wb : wa) + h * 32 * (DFF * 2) + (i & 1) * 128;
      asm volatile("cp.async.cg.shared.global [%0], [%1], 16;" ::"r"(d + ((i >> 2) == 1 ? OFF_A + (i & 3) * 4096 : (i & 3) * 8192 + h * 4096)), "l"(src) : "memory");
    }
    if (threadIdx.x == 0) TS(23);
  }
  const int warp = __shfl_sync(~0u, threadIdx.x >> 5, 0), lane = threadIdx.x & 31;
  const int m = blockIdx.x & 15, j = blockIdx.x >> 4, rank = blockIdx.x & 1;
  const int m2 = blockIdx.x >> 3, j2 = blockIdx.x & 7;
  const bool helper = blockIdx.x >= NMAIN;
  if (warp >= 8) {
    asm volatile("setmaxnreg.dec.sync.aligned.u32 40;");
    if (warp == 8) {
      if (elect_one()) {
        asm volatile("prefetch.tensormap [%0];\nprefetch.tensormap [%1];\nprefetch.tensormap [%2];" ::"l"(&mp.x), "l"(&mp.wg), "l"(&mp.wu) : "memory");
        for (int s = 0; s < 4; s++) mbar_init(sb + B_F1 + 8 * s, 1);
        if (!helper) mbar_arrive(sb + B_F1);
        asm volatile("fence.mbarrier_init.release.cluster;" ::: "memory");
      }
      __syncwarp();
    } else if (warp == 9) {
      if (elect_one()) {
        if ((sb & 0xffffff) != SM_BASE) asm volatile("trap;");
        for (uint32_t b = B_E1; b < B_F2; b += 8) mbar_init(sb + b, 4);
        for (uint32_t b = B_F2; b < B_AUX; b += 8) mbar_init(sb + b, 1);
        for (uint32_t b = B_EX; b < B_AUX; b += 8) mbar_expect_tx(sb + b, 8192);
        mbar_init(sb + B_AUX, 8); mbar_init(sb + B_HALO, 9); mbar_init(sb + B_HALO + 8, 9);
        asm volatile("fence.mbarrier_init.release.cluster;" ::: "memory");
      }
      __syncwarp();
    }
    asm volatile("barrier.cluster.arrive.relaxed.aligned;" ::: "memory");
    if (warp == 8 && !helper) {
      if (elect_one()) {
        TS(0); TG(51);
#pragma unroll 1
        for (int kb = 1; kb < 4; kb++) {
          const uint32_t sa = sb + OFF_A + kb * 16384, sw = sb + kb * 32768, fb = sb + B_F1 + 8 * kb;
          mbar_expect_tx(fb, P1_BYTES);
          tma3d(sa, &mp.x, fb, kb * 64, m * 64, 0, EVICT_NORMAL);
          tma2d(sw, &mp.wg, fb, j * 128, kb * 64, EVICT_NORMAL); tma2d(sw + 16384, &mp.wu, fb, j * 128, kb * 64, EVICT_NORMAL);
          tma2d(sw + 8192, &mp.wg, fb, j * 128 + 64, kb * 64, EVICT_NORMAL); tma2d(sw + 24576, &mp.wu, fb, j * 128 + 64, kb * 64, EVICT_NORMAL);
        }
        TS(7);
      }
      __syncwarp();
    }
    asm volatile("barrier.cluster.wait.aligned;" ::: "memory");
    if (helper) {
      if (warp == 8) {
        unsigned e = 0;
        if (elect_one()) {
#pragma unroll 1
          for (int i = 0; i < 16; i++) {
            const uint32_t fb = sb + B_F1 + 8 * (i >> 2);
            if (!(i & 3)) mbar_expect_tx(fb, P1_BYTES);
            tma5d(sb + i * 8192, &mp.wd, fb, (blockIdx.x - NMAIN) * 256 + (i & 3) * 64, (i >> 2) * 2, HINT_W);
          }
        }
        if (lane == 0) { unsigned* ep = &gs->epoch[blockIdx.x * 2]; e = *ep + 1; *ep = e; }
        e = __shfl_sync(~0u, e, 0);
        if (lane < 16) flag_wait(&gs->flags[(FL_H + lane * 4) * 32], e * 8u);
        __syncwarp();
        if (elect_one()) {
          fence_async();
          TS(0);
#pragma unroll 1
          for (int i = 0; i < 64; i++) {
            const uint32_t fb = sb + B_F1 + 8 * (i & 3);
            if (i >= 4) { mbar_wait(sb + B_E1 + 8 * (i & 3), ~(i >> 2) & 1); mbar_expect_tx(fb, 16384); }
            bulk_load(sb + OFF_A + (i & 3) * 16384, gs->h + ((i >> 2) * 56 + (i & 3)) * 1024, 16384, fb, EVICT_NORMAL);
          }
        }
      } else if (warp == 9) {
#pragma unroll 1
        for (int t = 0; t < 16; t++) {
          bar_sync(BAR_EV + (t & 1), 288);
          if (lane == 0) { flag_add(&gs->flags[(FL_P + t) * 32]); TS(64 + t); }
          __syncwarp();
        }
      }
    } else if (warp == 8) {
      if (elect_one()) {
        uint32_t par = 0;

        auto x_load = [&]() {
          mbar_expect_tx(sb + B_XT, 32768);
          tma3d(sb + OFF_X, &mp.x, sb + B_XT, j2 * 128, m2 * 64, 0, HINT_LAST); tma3d(sb + OFF_X + 16384, &mp.x, sb + B_XT, j2 * 128 + 64, m2 * 64, 0, HINT_LAST);
        };
        auto d_prefetch = [&](int i) {
          if (PF_W == 1 && (m2 >> 2) == (i & 3)) tma5d_prefetch(&mp.wd, (j2 >> 1) * 256 + (m2 & 3) * 64, (2 * i + 4 + rank) * 2);
          if (PF_H == 1 && i < 6) asm volatile("cp.async.bulk.prefetch.L2.global [%0], 4096;" ::"l"(gs->h + (m2 * 56 + 2 * i + 4 + rank) * 1024 + (j2 >> 1) * 256) : "memory");
        };
        for (int R = 0; R < 5; R++) {
          const CUtensorMap *mb0, *mb1;
          int n0, n1;
          if (R == 1 || R == 2) {
            mb0 = &mp.wqkv; n0 = 64 * (j + 8 * (R - 1)) + rank * 2048;
            mb1 = rank ? (R == 1 ? &mp.wg : &mp.wu) : &mp.wqkv; n1 = rank ? 1024 + 64 * j : n0 + 1024;
          } else {
            mb0 = mb1 = rank ? &mp.wu : &mp.wg;
            n0 = 128 * j + (R ? 1024 * R - 1536 : 0); n1 = n0 + 64;
          }
#pragma unroll 1
          for (int kb = R ? 0 : 4; kb < 16; kb++) {
            if (R == 0 && kb == 14) { asm volatile("prefetch.tensormap [%0];\nprefetch.tensormap [%1];" ::"l"(&mp.xn), "l"(&mp.wqkv) : "memory"); }
            if (R == 4 && kb == 2) { asm volatile("prefetch.tensormap [%0];\nprefetch.tensormap [%1];\nprefetch.tensormap [%2];" ::"l"(&mp.wd), "l"(&mp.wo), "l"(&mp.out) : "memory"); }
            if (R == 0 && kb == CS_KB) {
#pragma unroll 1
              for (int h = 0; h < 2; h++) {
                const uint32_t cb = sb + B_CS + 8 * h, d = sb + OFF_X + 16384 * h;
                mbar_expect_tx(cb, 16384);
                tma2d(d, h ? &mp.wu : &mp.wg, cb, n0, m * 64, EVICT_NORMAL); tma2d(d + 8192, h ? &mp.wu : &mp.wg, cb, n1, m * 64, EVICT_NORMAL);
              }
            }
            const int st = kb & 3;
            const uint32_t sa = sb + OFF_A + st * 16384, sw = sb + st * 32768, fb = sb + B_F1 + 8 * st;
            mbar_wait(sb + B_E1 + 8 * st, par);
            if (R * 16 + kb >= 4) REL_TS(R * 16 + kb - 4);
            mbar_expect_tx(fb, P1_BYTES);
            tma2d_mc(sw + rank * 16384, mb0, fb, n0, kb * 64, HINT_W);
            tma2d_mc(sw + 8192 + rank * 16384, mb1, fb, n1, kb * 64, HINT_W);
            if (R == 0) {
              tma3d(sa, &mp.x, fb, kb * 64, m * 64, 0, EVICT_NORMAL);
            } else {
              if (R == 1 && kb == 0) { mbar_wait(sb + B_DEP, 0); TS(1); }
              tma2d(sa, &mp.xn, fb, kb * 64, m * 128, R == 4 ? HINT_LAST : EVICT_NORMAL);
            }
            if (R == 4 && kb == 4 + j2) x_load();
            if (R == 4 && kb >= 16 - PF_D) { if (kb == 16 - PF_D) mbar_wait(sb + B_DEP + 8, 0); d_prefetch(kb + PF_D - 16); }
            if (st == 3) par ^= 1;
          }
        }
#pragma unroll 1
        for (int i = 0; i < 26; i++) {
          const int st = i & 3, kb = 2 * i + 4 + rank;
          const uint32_t sa = sb + OFF_A + st * 16384, sw = sb + st * 32768, fb = sb + B_F1 + 8 * st;
          mbar_wait(sb + B_E1 + 8 * st, par);
          REL_TS(76 + i);
          mbar_expect_tx(fb, P1_BYTES);
          tma5d(sw, &mp.wd, fb, j2 * 128, kb * 2, HINT_W); tma5d(sw + 8192, &mp.wd, fb, j2 * 128 + 64, kb * 2, HINT_W);
          tma5d(sw + 16384, &mp.wd, fb, (j2 ^ 1) * 128, kb * 2, HINT_W); tma5d(sw + 24576, &mp.wd, fb, (j2 ^ 1) * 128 + 64, kb * 2, HINT_W);
          if (i == 0 || i == 6 || i == 10 || i == 18) { mbar_wait(sb + B_DEP + 8 * (1 + ((i + 6) >> 3)), 0); }
          bulk_load(sa, gs->h + (m2 * 56 + kb) * 1024, 16384, fb, HINT_H);
          if (i + PF_D < 26) d_prefetch(i + PF_D);
          if (st == 3) par ^= 1;
        }
        int st = 0; uint32_t par2 = 1;
#pragma unroll 1
        for (int t = 0; t < 16; t++) {
          const uint32_t sa = sb + p2_a(st), sw = sb + p2_b(st), fb = sb + B_F2 + 8 * st;
          if (t < 5) mbar_wait(sb + B_E1 + 8 * (((2 * t + 1) / 3 + 2) & 3), t < 3); else mbar_wait(sb + B_E2 + 8 * st, par2);
          REL_TS(102 + t);
          mbar_expect_tx(fb, P2_BYTES);
          bulk_load_mc(sa + rank * 8192, gs->o + (m2 * 16 + t) * 1024 + rank * 512, 8192, fb, HINT_H);
          tma2d(sw, &mp.wo, fb, j2 * 128, t * 64, HINT_W); tma2d(sw + 8192, &mp.wo, fb, j2 * 128 + 64, t * 64, HINT_W);
          if (++st == 5) { st = 0; par2 ^= 1; }
        }
      }
    } else if (warp == 9) {
#pragma unroll 1
      for (int e = 0; e < 7; e++) {
        const bool halo = e == 2 || e == 3;
        bar_sync(BAR_EV + e, halo ? 96 : 288);
        if (lane == 0) {
          const int f = e == 0 ? FL_XN + m : (halo ? FL_HALO + (e - 2) * 128 + blockIdx.x : FL_H + m * 4 + (e == 1 ? 0 : e - 3));
          TS(10 + 2 * e); TG(52 + e);
          flag_add(&gs->flags[f * 32]);
          if (e < 6) TS(11 + 2 * e);
        }
        __syncwarp();
      }
      mbar_wait(sb + B_DONE, 0);
    } else {
      unsigned e = 0;
      if (lane == 0) {
        unsigned* ep = &gs->epoch[blockIdx.x * 2 + warp - 10];
        e = *ep + 1; *ep = e;
        if (warp == 10) { asm volatile("st.shared.b32 [%0], %1;" ::"r"(sb + OFF_EPOCH), "r"(e) : "memory"); mbar_arrive(sb + B_EP); }
      }
      e = __shfl_sync(~0u, e, 0);
      mbar_wait(sb + B_CS + 8 * (warp - 10), 0);
      if (lane == 0 && warp == 11) TS(6);
      col_sums(sb + OFF_X + (warp - 10) * 16384, gs->cspart + (j * 16 + m) * 128 + (warp - 10) * 16, e);
      if (lane == 0 && warp == 11) TS(9);
      if (warp == 10) {
        if (lane == 0) {
#pragma unroll 1
          for (int g = 0; g < 6; g++) {
            flag_wait(&gs->flags[(g == 5 ? FL_P + m2 : (g ? FL_H + m2 * 4 + g - 1 : FL_XN + m)) * 32], e * (g == 5 ? 4u : 8u));
            fence_async();
            mbar_arrive(sb + B_DEP + 8 * g);
            if (g == 0) TS(8);
          }
#pragma unroll 1
          for (int p = 0; p < 8; p++) {
            asm volatile("cp.async.bulk.prefetch.L2.global [%0], 4096;" ::"l"(gs->dpart + blockIdx.x * 2048 + p * 256) : "memory");
            __nanosleep(PF_SLEEP);
          }
        }
      } else
      if (elect_one()) {
#pragma unroll 1
        for (int r = 0; r < 2; r++) {
          const uint32_t hb = sb + B_HALO + 8 * r;
          if (r) mbar_wait(sb + B_HALO, 0);
          if (m) {
            flag_wait(&gs->flags[(FL_HALO + r * 128 + blockIdx.x - 1) * 32], e);
            fence_async();
            mbar_expect_tx(hb, 4096);
            for (int g = 0; g < 2; g++) bulk_load(sb + OFF_X + g * AT_WG + AT_REM + r * 2048, gs->halo + ((r * 128 + blockIdx.x - 1) * 2 + g) * 128, 2048, hb, EVICT_FIRST);
          } else {
            mbar_arrive(hb);
          }
          TS(34 + r);
        }
      }
    }
  } else {
    asm volatile("barrier.cluster.arrive.relaxed.aligned;" ::: "memory");
    asm volatile("setmaxnreg.inc.sync.aligned.u32 232;");
    const int wg = warp >> 2, w = warp & 3;
    Cons c;
    c.sb = sb; c.wg = wg; c.zero = warp >> 8;
    c.a = 0x4000004000010000ull + ((SM_BASE + OFF_A + wg * 8192) >> 4); c.k1 = 2 + c.zero; c.k2 = 2; c.k4 = 1024 - 6; c.k4w = -3072 - 6; c.b1 = 128 + c.zero;
    c.b = 0x4000004000000000ull + DB_LO + c.zero;
    c.rel = mapa(sb, threadIdx.x & 1);
    c.do_rel = (threadIdx.x & 127) < 2;
    constexpr bool t0 = false;
    float acc[128];
    uint32_t pk[64];
    float rs[2];
    const int q = lane & 3;

    if (helper) {
      asm volatile("barrier.cluster.wait.aligned;" ::: "memory");
      c.a = 0x8000002000010000ull + ((SM_BASE + OFF_A + wg * 4096) >> 4); c.k2 = 510; c.k4 = 1024 - 514; c.k4w = -3072 - 514;
      c.rel = sb;
      uint4* dst = gs->dpart + (blockIdx.x - NMAIN) * 4096 + threadIdx.x;
      auto put = [&](int p) {
#pragma unroll
        for (int i = 4 * p; i < 4 * p + 4; i++) stg128(dst + i * 256, pk[4 * i], pk[4 * i + 1], pk[4 * i + 2], pk[4 * i + 3]);
      };
#pragma unroll 1
      for (int t = 0; t < 16; t++) {
        p1_issue<0, 0>(acc, c, t & 1);
        if (t) put(0);
        p1_issue<1, 1>(acc, c, t & 1); wg_wait<1>(); release(c, B_E1);
        if (t) put(1);
        if (wg == 1) { wg_wait<0>(); release(c, B_E1 + 8); bar_sync(BAR_LAG, 256); }
        p1_issue<2, 1>(acc, c, t & 1); wg_wait<1>(); if (wg == 0) release(c, B_E1 + 8);
        if (t) put(2);
        p1_issue<3, 1>(acc, c, t & 1);
        if (wg == 0) bar_arrive(BAR_LAG, 256);
        if (t) { put(3); bar_arrive(BAR_EV + (~t & 1), 288); dst += 8 * 2048; }
        wg_wait<1>(); release(c, B_E1 + 16);
        wg_wait<0>(); release(c, B_E1 + 24);
#pragma unroll
        for (int i = 0; i < 64; i++) pk[i] = pack2(acc[2 * i], acc[2 * i + 1]);
      }
      put(0); put(1); put(2); put(3);
      bar_arrive(BAR_EV + 1, 288);
      return;
    }
    {
      const int prow = 16 * j + 2 * warp;
      const uint4* xr = x + (size_t)(128 * m + 2 * (prow & 63) + (prow >> 6)) * 128 + lane;
      uint4* xo = gs->xn + (size_t)(128 * m + prow) * 128 + lane;
      float c0[2], mo[4];
      uint32_t st[2];
      uint32_t e;
      asm volatile("" : "+l"(xr), "+l"(xo));
      asm volatile("cp.async.wait_all;\nfence.proxy.async.shared::cta;" ::: "memory");
      bar_sync(BAR_MMA, 256);
      if (threadIdx.x == 0) TS(39);
      p1_step<0, false>(acc, c);
      asm volatile("barrier.cluster.wait.aligned;" ::: "memory");
      unsigned long long part[18];
      auto gather = [&]() {
        const int lane = lane_here();
        const unsigned long long* cp = (const unsigned long long*)gs->cspart + j * 4096 + warp * 32 + lane;
        const unsigned long long* sp = gs->stats + 128 * m + warp * 16 + (lane >> 2);
#pragma unroll
        for (int i = 0; i < 18; i++) asm volatile("ld.relaxed.gpu.global.b64 %0, [%1];" : "=l"(part[i]) : "l"(i < 16 ? cp + i * 256 : sp + (i - 16) * 8) : "memory");
      };
      p1_step<1>(acc, c);
#pragma unroll
      for (int i = 0; i < 8; i++)
        asm volatile("ld.global.nc.v4.b32 {%0,%1,%2,%3}, [%4];" : "=r"(pk[4 * i]), "=r"(pk[4 * i + 1]), "=r"(pk[4 * i + 2]), "=r"(pk[4 * i + 3]) : "l"(xr + (i >> 2) * 256 + (i & 3) * 32));
      p1_loop(acc, c, 2, LN_KB + 1, [](int) {});
      pin<16>(pk); ln_moments(pk, c0[0], mo[0], mo[1]); pin<2>(mo);
      p1_step<LN_KB + 1>(acc, c);
      sched_fence(c.zero);
      pin<16>(pk + 16); ln_moments(pk + 16, c0[1], mo[2], mo[3]); ln_reduce(mo[0], mo[1]); pin<4>(mo);
      p1_step<LN_KB + 2>(acc, c);
      mbar_spin(sb + B_EP, 0, c.zero);
      asm volatile("ld.shared.b32 %0, [%1];" : "=r"(e) : "r"(sb + OFF_EPOCH) : "memory");
      pin<2>(mo); st[0] = ln_finish(c0[0], mo[0], mo[1]); ln_reduce(mo[2], mo[3]); pin<1>(st); pin<2>(mo + 2);
      p1_step<LN_KB + 3>(acc, c);
      sched_fence(c.zero);
      pin<1>(st); pin<2>(mo + 2);
      st[1] = ln_finish(c0[1], mo[2], mo[3]);
      ln_store(pk, st[0], xo);
      if (lane == 0)
        asm volatile("{\n.reg .b64 a, b;\nmov.b64 a, {%1, %3};\nmov.b64 b, {%2, %3};\nst.relaxed.gpu.global.v2.b64 [%0], {a, b};\n}" ::"l"(gs->stats + 128 * m + prow), "r"(st[0]), "r"(st[1]), "r"(e) : "memory");
      p1_step<LN_KB + 4>(acc, c);
      sched_fence(c.zero);
      pin<1>(st + 1);
      ln_store(pk + 16, st[1], xo + 128);
      bar_arrive(BAR_EV, 288);
      p1_loop(acc, c, LN_KB + 5, 13, [](int) {});
      gather();
      p1_step<13>(acc, c);
      auto validate = [&]() {
        float csum;
        for (int tries = 0;; tries++) {
          uint32_t bad = 0;
          csum = 0.f;
#pragma unroll
          for (int i = 0; i < 18; i++) { bad |= (uint32_t)(part[i] >> 32) ^ e; if (i < 16) csum += __uint_as_float((uint32_t)part[i]); }
          if (!__any_sync(~0u, bad != 0) || tries > (1 << 20)) break;
          gather();
        }
        const float hi = bf16r(csum), mid = bf16r(csum - hi);
        sts128(sb + OFF_CS + ((threadIdx.x & 62) * 4 + (threadIdx.x >> 6) * 2 + (threadIdx.x & 1)) * 16, make_uint4(pack2(hi, mid), pack2(csum - hi - mid, 0.f), 0, 0));
        asm volatile("fence.proxy.async.shared::cta;" ::: "memory");
        __syncwarp();
        if (lane == 0) mbar_arrive(sb + B_AUX);
      };
#pragma unroll 1
      for (int ph = 1; ph >= 0; ph--) {
        if (wg == ph) validate();
        if (ph) { p1_step<14>(acc, c); p1_issue<3, 1>(acc, c, 1); }
      }
      const uint32_t keep = q == 0 ? 0xffffffffu : (q == 1 ? 0xffffu : 0u);
      const uint32_t a0 = (__byte_perm((uint32_t)part[16], 0, 0x1010) ^ 0x80008000u) & keep, a1 = (__byte_perm((uint32_t)part[17], 0, 0x1010) ^ 0x80008000u) & keep;
      mbar_spin(sb + B_AUX, 0, c.zero);
      wg_fence();
      wgmma256_rs(acc, a0, a1, 0, 0, (SM_BASE + OFF_CS) >> 4);
      wg_commit();
      if (wg == 0) bar_arrive(BAR_LAG, 256);
      rs[0] = rcpf(hi_f((uint32_t)part[16])); rs[1] = rcpf(hi_f((uint32_t)part[17]));
      wg_wait<2>(); release(c, B_E1 + 16);
      wg_wait<0>(); release(c, B_E1 + 24);
    }
#pragma unroll 1
    for (int R = 1;; R++) {
#pragma unroll
      for (int i = 0; i < 64; i++) pk[i] = pack2(acc[2 * i], acc[2 * i + 1]);
      if (t0) TS(24 + R + wg * 16);
      uint8_t* hb = (uint8_t*)gs->h + (size_t)m * 56 * 16384 + warp * 1024;
      if (R == 5) { c.a = 0x8000002000010000ull + ((SM_BASE + OFF_A + wg * 4096) >> 4); c.k2 = 510; c.k4 = 1024 - 514; c.k4w = -3072 - 514; }
      p1_step<0>(acc, c);
      if (R == 2 || R == 3) {
        attn_tile(acc, pk, c, R - 2, warp, m, gs, hb + (16 + j) * 16384, (uint8_t*)gs->o + (m * 16 + j + 8 * (R - 2)) * 16384 + warp * 1024);
      } else {
        geglu_tile(acc, pk, c, R == 5 ? 24 : 14, hb + (2 * j + (R == 1 ? 0 : 16 * R - 40)) * 16384, BAR_EV + (R == 1 ? 1 : R + 1), rs);
        rs[0] = rs[1] = 1.0f;
        if (R == 5) break;
      }
      p1_step<14>(acc, c); p1_step<15>(acc, c);
    }
    auto fetch = [&](int p) {
      asm volatile("ld.global.cg.v4.b32 {%0,%1,%2,%3}, [%4];" : "=r"(pk[4 * p]), "=r"(pk[4 * p + 1]), "=r"(pk[4 * p + 2]), "=r"(pk[4 * p + 3]) : "l"(gs->dpart + blockIdx.x * 2048 + p * 256 + threadIdx.x) : "memory");
    };
    mbar_spin(sb + B_DEP + 40, 0, c.zero);
    fetch(0); fetch(1); fetch(2);
    p1_step<8>(acc, c);
    fetch(3); fetch(4); fetch(5);
    p1_step<9>(acc, c);
    fetch(6); fetch(7);
    {
      float accs[64];
      const uint32_t peer = mapa(sb, rank ^ 1);
      auto send_piece = [&](int p) {
        asm volatile("st.async.weak.shared::cluster.mbarrier::complete_tx::bytes.v4.b32 [%0], {%1,%2,%3,%4}, [%5];" ::"r"(peer + OFF_LAND + p * 4096 + threadIdx.x * 16),
                     "r"(pack2(acc[64 + 8 * p], acc[65 + 8 * p])), "r"(pack2(acc[66 + 8 * p], acc[67 + 8 * p])), "r"(pack2(acc[68 + 8 * p], acc[69 + 8 * p])), "r"(pack2(acc[70 + 8 * p], acc[71 + 8 * p])),
                     "r"(peer + B_EX + 16 * wg + 8 * (p >> 2)) : "memory");
      };
      auto silu_piece = [&](int p) {
        const uint4 r = lds128(sb + OFF_LAND + p * 4096 + threadIdx.x * 16);
        const uint32_t rr[4] = {add2(r.x, pk[4 * p]), add2(r.y, pk[4 * p + 1]), add2(r.z, pk[4 * p + 2]), add2(r.w, pk[4 * p + 3])};
#pragma unroll
        for (int i = 0; i < 4; i++) {
          const float a = acc[8 * p + 2 * i] + lo_f(rr[i]), b = acc[8 * p + 2 * i + 1] + hi_f(rr[i]);
          pk[4 * p + i] = pack2(silu_half(a), silu_half(b));
        }
        pin<4>(pk + 4 * p);
      };
      const uint32_t xa = sb + OFF_X + (warp * 16 + (lane & 15)) * 128 + (((lane >> 4) ^ (lane & 7)) << 4);
      auto x_piece = [&](int i) { const uint4 v = ldsm((xa ^ ((i & 3) << 5)) + (i >> 2) * 16384); pk[32 + 4 * i] = v.x; pk[33 + 4 * i] = v.y; pk[34 + 4 * i] = v.z; pk[35 + 4 * i] = v.w; };
      p2_step<0>(accs, c);
      p2_step<1>(accs, c);
      mbar_spin(sb + B_E1 + 8, 0, c.zero);
      send_piece(0); send_piece(1);
      p2_step<2>(accs, c); sched_fence(c.zero); send_piece(2); send_piece(3);
      p2_step<3>(accs, c); sched_fence(c.zero); send_piece(4); send_piece(5);
      p2_step<4>(accs, c); mbar_spin(sb + B_XT, 0, c.zero); send_piece(6); send_piece(7);
      p2_step<5>(accs, c); mbar_spin(sb + B_EX + 16 * wg, 0, c.zero); silu_piece(0); x_piece(0);
      p2_step<6>(accs, c); sched_fence(c.zero); silu_piece(1); x_piece(1);
      p2_step<7>(accs, c); sched_fence(c.zero); silu_piece(2); x_piece(2);
      p2_step<8>(accs, c); sched_fence(c.zero); silu_piece(3); x_piece(3);
      p2_step<9>(accs, c); mbar_spin(sb + B_EX + 16 * wg + 8, 0, c.zero); silu_piece(4); x_piece(4);
      p2_step<10>(accs, c); sched_fence(c.zero); silu_piece(5); x_piece(5);
      p2_step<11>(accs, c); sched_fence(c.zero); silu_piece(6); x_piece(6); x_piece(7);
      if (wg == 1) silu_piece(7);
      p2_step<12>(accs, c); p2_step<13>(accs, c); p2_step<14>(accs, c); p2_step<15>(accs, c);
      if (c.do_rel) mbar_arrive(sb + B_DONE);
      if (wg == 0) silu_piece(7);
      wg_wait<0>();
#pragma unroll
      for (int i = 0; i < 8; i++) {
        uint32_t v[4];
#pragma unroll
        for (int k = 0; k < 4; k++) v[k] = fma2(pack2(accs[8 * i + 2 * k], accs[1 + 8 * i + 2 * k]), pk[4 * i + k], pk[32 + 4 * i + k]);
        asm volatile("stmatrix.sync.aligned.m8n8.x4.shared.b16 [%0], {%1,%2,%3,%4};" ::"r"((xa ^ ((i & 3) << 5)) + (i >> 2) * 16384), "r"(v[0]), "r"(v[1]), "r"(v[2]), "r"(v[3]) : "memory");
        if (i == 3 || i == 7) {
          asm volatile("fence.proxy.async.shared::cta;" ::: "memory");
          __syncwarp();
          if (elect_one()) tma3d_store(&mp.out, sb + OFF_X + (i >> 2) * 16384 + warp * 2048, j2 * 128 + (i >> 2) * 64, m2 * 64 + w * 16, wg);
        }
      }
      if (elect_one()) { asm volatile("cp.async.bulk.commit_group;\ncp.async.bulk.wait_group.read 0;" ::: "memory"); }
      if ((threadIdx.x & 127) == 0) { TS(33 + wg * 16); if (wg) { TG(59); unsigned id; asm volatile("mov.u32 %0, %%smid;" : "=r"(id)); TSV(60, id); } }
    }
  }
}

typedef CUresult (*EncodeFn)(CUtensorMap*, CUtensorMapDataType, cuuint32_t, void*, const cuuint64_t*, const cuuint64_t*, const cuuint32_t*, const cuuint32_t*,
                             CUtensorMapInterleave, CUtensorMapSwizzle, CUtensorMapL2promotion, CUtensorMapFloatOOBfill);

void encode(EncodeFn fn, CUtensorMap* tm, const void* p, int rank, const cuuint64_t* dims, const cuuint64_t* strides, const cuuint32_t* box) {
  const cuuint32_t es[5] = {1, 1, 1, 1, 1};
  fn(tm, CU_TENSOR_MAP_DATA_TYPE_BFLOAT16, rank, const_cast<void*>(p), dims, strides, box, es, CU_TENSOR_MAP_INTERLEAVE_NONE, CU_TENSOR_MAP_SWIZZLE_128B,
     PROMO, CU_TENSOR_MAP_FLOAT_OOB_FILL_NONE);
}

}

extern "C" void kernel_launch(void* const* d_in, const int* in_sizes, int n_in, void* d_out, int out_size) {
  (void)in_sizes; (void)n_in; (void)out_size;
  static EncodeFn fn = nullptr;
  static Scratch* gs = nullptr;
  if (!fn) {
    void* p = nullptr;
    cudaDriverEntryPointQueryResult qr;
    cudaGetDriverEntryPoint("cuTensorMapEncodeTiled", &p, cudaEnableDefault, &qr);
    fn = (EncodeFn)p;
    cudaGetSymbolAddress((void**)&gs, g_scratch);
    cudaFuncSetAttribute(fused_kernel, cudaFuncAttributeMaxDynamicSharedMemorySize, SMEM_BYTES);
  }
  const void *x = d_in[0], *wqkv = d_in[1], *wo = d_in[2], *wg = d_in[4], *wu = d_in[5], *wd = d_in[6];
  Maps mp;
  {
    const cuuint64_t dims[3] = {DM, SEQ / 2, 2}, st[2] = {DM * 4, DM * 2};
    const cuuint32_t box_in[3] = {64, 64, 2}, box_out[3] = {64, 16, 1};
    encode(fn, &mp.x, x, 3, dims, st, box_in);
    encode(fn, &mp.out, d_out, 3, dims, st, box_out);
  }
  {
    const cuuint64_t dims[2] = {DM, SEQ}, st[1] = {DM * 2};
    const cuuint32_t box[2] = {64, 128};
    encode(fn, &mp.xn, gs->xn, 2, dims, st, box);
  }
  {
    const cuuint32_t box[2] = {64, 64};
    const cuuint64_t dq[2] = {3 * DM, DM}, sq[1] = {3 * DM * 2}, df[2] = {DFF, DM}, sf[1] = {DFF * 2}, dw[2] = {DM, DM}, sw[1] = {DM * 2};
    encode(fn, &mp.wqkv, wqkv, 2, dq, sq, box);
    encode(fn, &mp.wg, wg, 2, df, sf, box);
    encode(fn, &mp.wu, wu, 2, df, sf, box);
    encode(fn, &mp.wo, wo, 2, dw, sw, box);
  }
  {
    const cuuint32_t box[5] = {64, 2, 4, 4, 2};
    const cuuint64_t st[4] = {DM * 2, 8 * DM * 2, 2 * DM * 2, 32 * DM * 2};
    const cuuint64_t dd[5] = {DM, 2, 4, 4, DFF / 32};
    encode(fn, &mp.wd, wd, 5, dd, st, box);
  }
  fused_kernel<<<NCTA, 384, SMEM_BYTES>>>((const uint4*)x, (const uint4*)wg, (const uint4*)wu, gs, mp);
}
```

```cpp
#include <cuda_runtime.h>
#include <cuda_bf16.h>
#include <cuda.h>
#include <stdint.h>

#define PROMO CU_TENSOR_MAP_L2_PROMOTION_L2_128B
#define PF_D 6
#define LAG2 4
#define POLL_NS "200"
#define CS_KB 8
#define LN_KB 4

#define EVICT_FIRST 0x12F0000000000000ull
#define EVICT_NORMAL 0x1000000000000000ull
#define HINT_W EVICT_FIRST
#define HINT_H EVICT_FIRST
#define HINT_LAST EVICT_FIRST

namespace {

constexpr int SEQ = 2048, DM = 1024, DFF = 3584;
constexpr int NMAIN = 128, NCTA = 132;

constexpr uint32_t SM_BASE = 0x400;
constexpr uint32_t P1_BYTES = 49152, P2_BYTES = 32768;
constexpr uint32_t OFF_A = 131072;
__host__ __device__ constexpr uint32_t p2_a(int s) { return s == 0 ? OFF_A + 32768 : s == 1 ? OFF_A + 49152 : s == 2 ? 114688 : s == 3 ? 16384 : 49152; }
__host__ __device__ constexpr uint32_t p2_b(int s) { return s < 3 ? 65536 + s * 16384 : (s - 3) * 32768; }
constexpr uint32_t OFF_LAND = OFF_A;
constexpr uint32_t OFF_X = 196608;
constexpr uint32_t OFF_CS = OFF_X + 14336;
constexpr uint32_t OFF_BAR = 229376;
constexpr uint32_t B_F1 = OFF_BAR, B_E1 = B_F1 + 32, B_E2 = B_E1 + 32, B_DONE = B_E2 + 40, B_F2 = B_DONE + 8, B_DEP = B_F2 + 40, B_CS = B_DEP + 48,
                   B_XT = B_CS + 16, B_EP = B_XT + 8, B_EX = B_EP + 8, B_AUX = B_EX + 32, B_HALO = B_AUX + 8, OFF_EPOCH = B_HALO + 16;
constexpr uint32_t SMEM_BYTES = 232448;
constexpr uint32_t AT_V = 0, AT_K = 8192, AT_REM = 11264, AT_WG = 15360;

constexpr int FL_XN = 0, FL_H = 16, FL_P = 80, FL_HALO = 96, FL_N = FL_HALO + 256;
struct __align__(1024) Scratch {
  uint4 h[16 * 56 * 1024];
  uint4 o[16 * 16 * 1024];
  uint4 xn[SEQ * DM / 8];
  uint4 dpart[128 * 8 * 256];
  uint4 halo[2 * 128 * 2 * 128];
  ulonglong2 cspart[8 * 16 * 128];
  unsigned long long stats[SEQ];
  unsigned flags[FL_N * 32];
  unsigned epoch[NCTA * 2];
};
__device__ Scratch g_scratch;
#define TG(i) do {} while (0)
#define TSV(i, v) do {} while (0)
#define TS(i) do {} while (0)

struct Maps { CUtensorMap x, xn, out, wqkv, wg, wu, wd, wo; };

__device__ __forceinline__ void mbar_init(uint32_t bar, uint32_t cnt) { asm volatile("mbarrier.init.shared::cta.b64 [%0], %1;" ::"r"(bar), "r"(cnt)); }
__device__ __forceinline__ void mbar_expect_tx(uint32_t bar, uint32_t bytes) { asm volatile("mbarrier.arrive.expect_tx.shared::cta.b64 _, [%0], %1;" ::"r"(bar), "r"(bytes) : "memory"); }
__device__ __forceinline__ void mbar_arrive(uint32_t bar) { asm volatile("mbarrier.arrive.shared::cta.b64 _, [%0];" ::"r"(bar) : "memory"); }
__device__ __forceinline__ void mbar_arrive_cl(uint32_t bar) { asm volatile("mbarrier.arrive.shared::cluster.b64 _, [%0];" ::"r"(bar) : "memory"); }
__device__ __forceinline__ uint32_t mapa(uint32_t a, uint32_t cta) { uint32_t r; asm("mapa.shared::cluster.u32 %0, %1, %2;" : "=r"(r) : "r"(a), "r"(cta)); return r; }
__device__ __forceinline__ void mbar_wait(uint32_t bar, uint32_t parity) {
  asm volatile("{\n.reg .pred p;\n.reg .u32 n;\nmov.u32 n, 0;\nLAB_WAIT:\nmbarrier.try_wait.parity.shared::cta.b64 p, [%0], %1;\n@p bra LAB_DONE;\n"
               "add.u32 n, n, 1;\nsetp.gt.u32 p, n, 4000000;\n@p trap;\nbra LAB_WAIT;\nLAB_DONE:\n}" ::"r"(bar), "r"(parity) : "memory");
}
__device__ __forceinline__ void mbar_spin(uint32_t bar, uint32_t parity, uint32_t zero) {
  asm volatile("{\n.reg .pred p, z;\nsetp.ne.u32 z, %2, 0;\nLAB_WAIT:\nmbarrier.try_wait.parity.shared::cta.b64 p, [%0], %1;\n@p bra LAB_DONE;\n@z trap;\nbra LAB_WAIT;\nLAB_DONE:\n}" ::"r"(bar), "r"(parity), "r"(zero) : "memory");
}
__device__ __forceinline__ void flag_wait(const unsigned* f, unsigned target) {
  asm volatile("{\n.reg .pred p;\n.reg .u32 n, v;\nmov.u32 n, 0;\nLAB_WAIT:\nld.relaxed.gpu.global.u32 v, [%0];\nsub.u32 v, v, %1;\nsetp.ge.s32 p, v, 0;\n@p bra LAB_DONE;\n"
               "nanosleep.u32 " POLL_NS ";\nadd.u32 n, n, 1;\nsetp.gt.u32 p, n, 4000000;\n@p trap;\nbra LAB_WAIT;\nLAB_DONE:\nfence.acquire.gpu;\n}" ::"l"(f), "r"(target) : "memory");
}
__device__ __forceinline__ void flag_add(unsigned* f) { asm volatile("red.release.gpu.global.add.u32 [%0], 1;" ::"l"(f) : "memory"); }
__device__ __forceinline__ void fence_async() { asm volatile("fence.proxy.async.global;" ::: "memory"); }
__device__ __forceinline__ bool elect_one() { uint32_t p; asm volatile("{\n.reg .pred P;\nelect.sync _|P, 0xffffffff;\nselp.u32 %0, 1, 0, P;\n}" : "=r"(p)); return p; }
__device__ __forceinline__ void bar_sync(int id, int n) { asm volatile("bar.sync %0, %1;" ::"r"(id), "r"(n) : "memory"); }
__device__ __forceinline__ void bar_arrive(int id, int n) { asm volatile("bar.arrive %0, %1;" ::"r"(id), "r"(n) : "memory"); }

__device__ __forceinline__ void tma2d(uint32_t dst, const CUtensorMap* tm, uint32_t bar, int c0, int c1, uint64_t hint) {
  asm volatile("cp.async.bulk.tensor.2d.shared::cluster.global.mbarrier::complete_tx::bytes.L2::cache_hint [%0], [%1, {%3, %4}], [%2], %5;" ::"r"(dst), "l"(tm), "r"(bar), "r"(c0), "r"(c1), "l"(hint) : "memory");
}
__device__ __forceinline__ void tma2d_mc(uint32_t dst, const CUtensorMap* tm, uint32_t bar, int c0, int c1, uint64_t hint) {
  asm volatile("cp.async.bulk.tensor.2d.shared::cluster.global.mbarrier::complete_tx::bytes.multicast::cluster.L2::cache_hint [%0], [%1, {%3, %4}], [%2], %5, %6;" ::"r"(dst), "l"(tm), "r"(bar), "r"(c0), "r"(c1), "h"((uint16_t)3), "l"(hint) : "memory");
}
__device__ __forceinline__ void tma3d(uint32_t dst, const CUtensorMap* tm, uint32_t bar, int c0, int c1, int c2, uint64_t hint) {
  asm volatile("cp.async.bulk.tensor.3d.shared::cluster.global.mbarrier::complete_tx::bytes.L2::cache_hint [%0], [%1, {%3, %4, %5}], [%2], %6;" ::"r"(dst), "l"(tm), "r"(bar), "r"(c0), "r"(c1), "r"(c2), "l"(hint) : "memory");
}
__device__ __forceinline__ void tma5d(uint32_t dst, const CUtensorMap* tm, uint32_t bar, int c0, int c4, uint64_t hint) {
  asm volatile("cp.async.bulk.tensor.5d.shared::cluster.global.mbarrier::complete_tx::bytes.L2::cache_hint [%0], [%1, {%3, %5, %5, %5, %4}], [%2], %6;" ::"r"(dst), "l"(tm), "r"(bar), "r"(c0), "r"(c4), "r"(0), "l"(hint) : "memory");
}
__device__ __forceinline__ void tma5d_prefetch(const CUtensorMap* tm, int c0, int c4) {
  asm volatile("cp.async.bulk.prefetch.tensor.5d.L2.global [%0, {%1, %3, %3, %3, %2}];" ::"l"(tm), "r"(c0), "r"(c4), "r"(0) : "memory");
}
__device__ __forceinline__ void tma3d_store(const CUtensorMap* tm, uint32_t src, int c0, int c1, int c2) {
  asm volatile("cp.async.bulk.tensor.3d.global.shared::cta.bulk_group [%0, {%2, %3, %4}], [%1];" ::"l"(tm), "r"(src), "r"(c0), "r"(c1), "r"(c2) : "memory");
}
__device__ __forceinline__ void bulk_load(uint32_t dst, const void* src, uint32_t bytes, uint32_t bar, uint64_t hint) {
  asm volatile("cp.async.bulk.shared::cluster.global.mbarrier::complete_tx::bytes.L2::cache_hint [%0], [%1], %2, [%3], %4;" ::"r"(dst), "l"(src), "r"(bytes), "r"(bar), "l"(hint) : "memory");
}
__device__ __forceinline__ void bulk_load_mc(uint32_t dst, const void* src, uint32_t bytes, uint32_t bar, uint64_t hint) {
  asm volatile("cp.async.bulk.shared::cluster.global.mbarrier::complete_tx::bytes.multicast::cluster.L2::cache_hint [%0], [%1], %2, [%3], %4, %5;" ::"r"(dst), "l"(src), "r"(bytes), "r"(bar), "h"((uint16_t)3), "l"(hint) : "memory");
}
__device__ __forceinline__ uint4 lds128(uint32_t a) { uint4 v; asm volatile("ld.shared.v4.b32 {%0,%1,%2,%3}, [%4];" : "=r"(v.x), "=r"(v.y), "=r"(v.z), "=r"(v.w) : "r"(a) : "memory"); return v; }
__device__ __forceinline__ void sts128(uint32_t a, uint4 v) { asm volatile("st.shared.v4.b32 [%0], {%1,%2,%3,%4};" ::"r"(a), "r"(v.x), "r"(v.y), "r"(v.z), "r"(v.w) : "memory"); }
__device__ __forceinline__ void stg128(void* p, uint32_t a, uint32_t b, uint32_t c, uint32_t d) { asm volatile("st.global.v4.b32 [%0], {%1,%2,%3,%4};" ::"l"(p), "r"(a), "r"(b), "r"(c), "r"(d) : "memory"); }

__device__ __forceinline__ uint32_t pack2(float lo, float hi) { uint32_t r; asm("cvt.rn.bf16x2.f32 %0, %1, %2;" : "=r"(r) : "f"(hi), "f"(lo)); return r; }
__device__ __forceinline__ float lo_f(uint32_t v) { return __uint_as_float(v << 16); }
__device__ __forceinline__ float hi_f(uint32_t v) { return __uint_as_float(v & 0xffff0000u); }
__device__ __forceinline__ float bf16r(float v) { return lo_f(pack2(v, 0.f)); }
__device__ __forceinline__ uint32_t mul2(uint32_t a, uint32_t b) { uint32_t r; asm("mul.rn.bf16x2 %0, %1, %2;" : "=r"(r) : "r"(a), "r"(b)); return r; }
__device__ __forceinline__ uint32_t add2(uint32_t a, uint32_t b) { uint32_t r; asm("add.rn.bf16x2 %0, %1, %2;" : "=r"(r) : "r"(a), "r"(b)); return r; }
__device__ __forceinline__ uint32_t sub2(uint32_t a, uint32_t b) { uint32_t r; asm("sub.rn.bf16x2 %0, %1, %2;" : "=r"(r) : "r"(a), "r"(b)); return r; }
__device__ __forceinline__ uint32_t fma2(uint32_t a, uint32_t b, uint32_t c) { uint32_t r; asm("fma.rn.bf16x2 %0, %1, %2, %3;" : "=r"(r) : "r"(a), "r"(b), "r"(c)); return r; }
__device__ __forceinline__ uint32_t max2(uint32_t a, uint32_t b) { uint32_t r; asm("max.bf16x2 %0, %1, %2;" : "=r"(r) : "r"(a), "r"(b)); return r; }
__device__ __forceinline__ float ex2f(float x) { float y; asm("ex2.approx.ftz.f32 %0, %1;" : "=f"(y) : "f"(x)); return y; }
__device__ __forceinline__ float rcpf(float x) { float y; asm("rcp.approx.ftz.f32 %0, %1;" : "=f"(y) : "f"(x)); return y; }
constexpr float GELU_C1 = 0.7978845608028654f, GELU_C3 = 0.035677408136300125f;
__device__ __forceinline__ float gelu_k(float g, float c1, float c3, float k) {
  float t;
  asm("tanh.approx.f32 %0, %1;" : "=f"(t) : "f"(g * fmaf(g * g, c3, c1)));
  g *= k;
  return fmaf(g, t, g);
}
__device__ __forceinline__ float silu_half(float z) { float t; asm("tanh.approx.f32 %0, %1;" : "=f"(t) : "f"(z)); return fmaf(z, t, z); }

__device__ __forceinline__ void wg_fence() { asm volatile("wgmma.fence.sync.aligned;" ::: "memory"); }
__device__ __forceinline__ void wg_commit() { asm volatile("wgmma.commit_group.sync.aligned;" ::: "memory"); }
template <int N> __device__ __forceinline__ void wg_wait() { asm volatile("wgmma.wait_group.sync.aligned %0;" ::"n"(N) : "memory"); }
#define A8(o) "+f"(d[(o)]), "+f"(d[(o) + 1]), "+f"(d[(o) + 2]), "+f"(d[(o) + 3]), "+f"(d[(o) + 4]), "+f"(d[(o) + 5]), "+f"(d[(o) + 6]), "+f"(d[(o) + 7])
#define A64(o) A8(o), A8((o) + 8), A8((o) + 16), A8((o) + 24), A8((o) + 32), A8((o) + 40), A8((o) + 48), A8((o) + 56)
#define REGS0_63 "%0,%1,%2,%3,%4,%5,%6,%7,%8,%9,%10,%11,%12,%13,%14,%15,%16,%17,%18,%19,%20,%21,%22,%23,%24,%25,%26,%27,%28,%29,%30,%31," \
                 "%32,%33,%34,%35,%36,%37,%38,%39,%40,%41,%42,%43,%44,%45,%46,%47,%48,%49,%50,%51,%52,%53,%54,%55,%56,%57,%58,%59,%60,%61,%62,%63"
#define REGS64_127 "%64,%65,%66,%67,%68,%69,%70,%71,%72,%73,%74,%75,%76,%77,%78,%79,%80,%81,%82,%83,%84,%85,%86,%87,%88,%89,%90,%91,%92,%93,%94,%95," \
                   "%96,%97,%98,%99,%100,%101,%102,%103,%104,%105,%106,%107,%108,%109,%110,%111,%112,%113,%114,%115,%116,%117,%118,%119,%120,%121,%122,%123,%124,%125,%126,%127"
__device__ __forceinline__ void desc_add(uint64_t& x, int v) { asm volatile("{\n.reg .b32 lo, hi;\nmov.b64 {lo, hi}, %0;\nadd.s32 lo, lo, %1;\nmov.b64 %0, {lo, hi};\n}" : "+l"(x) : "r"(v)); }
template <int ACCUM> __device__ __forceinline__ void wgmma256(float (&d)[128], uint64_t& a, uint64_t& b, int da, int db) {
  asm volatile("{\n.reg .pred p;\nsetp.ne.b32 p, %130, 0;\n"
               "wgmma.mma_async.sync.aligned.m64n256k16.f32.bf16.bf16 {" REGS0_63 "," REGS64_127 "}, %128, %129, p, 1, 1, 0, 1;\n}"
               : A64(0), A64(64) : "l"(a), "l"(b), "n"(ACCUM));
  desc_add(a, da); desc_add(b, db);
}
__device__ __forceinline__ void wgmma256_rs(float (&d)[128], uint32_t a0, uint32_t a1, uint32_t z0, uint32_t z1, uint32_t b_lo) {
  asm volatile("{\n.reg .b64 db;\nmov.b64 db, {%132, 0x00000008};\n"
               "wgmma.mma_async.sync.aligned.m64n256k16.f32.bf16.bf16 {" REGS0_63 "," REGS64_127 "}, {%128,%129,%130,%131}, db, 1, 1, 1, 0;\n}"
               : A64(0), A64(64) : "r"(a0), "r"(a1), "r"(z0), "r"(z1), "r"(b_lo));
}
template <int ACCUM> __device__ __forceinline__ void wgmma128(float (&d)[64], uint64_t& a, uint64_t& b, int da, int db) {
  asm volatile("{\n.reg .pred p;\nsetp.ne.b32 p, %66, 0;\n"
               "wgmma.mma_async.sync.aligned.m64n128k16.f32.bf16.bf16 {" REGS0_63 "}, %64, %65, p, 1, 1, 0, 1;\n}"
               : A64(0) : "l"(a), "l"(b), "n"(ACCUM));
  desc_add(a, da); desc_add(b, db);
}
template <int ACCUM> __device__ __forceinline__ void hmma(float (&c)[4], uint32_t a0, uint32_t a1, uint32_t a2, uint32_t a3, uint32_t b0, uint32_t b1) {
  if (ACCUM)
    asm volatile("mma.sync.aligned.m16n8k16.row.col.f32.bf16.bf16.f32 {%0,%1,%2,%3}, {%4,%5,%6,%7}, {%8,%9}, {%0,%1,%2,%3};"
                 : "+f"(c[0]), "+f"(c[1]), "+f"(c[2]), "+f"(c[3]) : "r"(a0), "r"(a1), "r"(a2), "r"(a3), "r"(b0), "r"(b1));
  else
    asm volatile("mma.sync.aligned.m16n8k16.row.col.f32.bf16.bf16.f32 {%0,%1,%2,%3}, {%4,%5,%6,%7}, {%8,%9}, {%10,%10,%10,%10};"
                 : "=f"(c[0]), "=f"(c[1]), "=f"(c[2]), "=f"(c[3]) : "r"(a0), "r"(a1), "r"(a2), "r"(a3), "r"(b0), "r"(b1), "f"(0.f));
}
__device__ __forceinline__ uint32_t movm(uint32_t a) { uint32_t d; asm volatile("movmatrix.sync.aligned.m8n8.trans.b16 %0, %1;" : "=r"(d) : "r"(a)); return d; }
__device__ __forceinline__ int lane_here() { int v; asm volatile("mov.u32 %0, %%laneid;" : "=r"(v)); return v; }
template <int N> __device__ __forceinline__ void pin(uint32_t* r) {
#pragma unroll
  for (int i = 0; i < N; i++) asm volatile("" : "+r"(r[i]));
}
template <int N> __device__ __forceinline__ void pin(float* r) {
#pragma unroll
  for (int i = 0; i < N; i++) asm volatile("" : "+f"(r[i]));
}
__device__ __forceinline__ void sched_fence(uint32_t zero) {
  asm volatile("{\n.reg .pred p;\nsetp.eq.u32 p, %0, 0;\nLAB_F:\n@p bra.uni LAB_D;\nnanosleep.u32 0;\nbra.uni LAB_F;\nLAB_D:\n}" ::"r"(zero) : "memory");
}
__device__ __forceinline__ uint4 ldsm(uint32_t a) { uint4 v; asm volatile("ldmatrix.sync.aligned.m8n8.x4.shared.b16 {%0,%1,%2,%3}, [%4];" : "=r"(v.x), "=r"(v.y), "=r"(v.z), "=r"(v.w) : "r"(a) : "memory"); return v; }
__device__ __forceinline__ uint4 ldsm_t(uint32_t a) { uint4 v; asm volatile("ldmatrix.sync.aligned.m8n8.x4.trans.shared.b16 {%0,%1,%2,%3}, [%4];" : "=r"(v.x), "=r"(v.y), "=r"(v.z), "=r"(v.w) : "r"(a) : "memory"); return v; }

constexpr int BAR_LAG = 1, BAR_MMA = 2, BAR_EV = 3;

struct Cons {
  uint32_t sb;
  mutable uint64_t a, b;
  int k1, k2, k4, k4w, b1;
  uint32_t rel;
  bool do_rel;
  int wg;
  uint32_t zero;
};
#define REL_TS(n) TS(64 + (n))
constexpr uint32_t DB_LO = (SM_BASE >> 4) | ((8192 >> 4) << 16);

template <int ST, int ACCUM, bool WAIT = true> __device__ __forceinline__ void p1_issue(float (&acc)[128], const Cons& c, uint32_t parity) {
  if (WAIT) mbar_spin(c.sb + B_F1 + 8 * ST, parity, c.zero);
  wg_fence();
  wgmma256<ACCUM>(acc, c.a, c.b, c.k1, c.b1);
  wgmma256<1>(acc, c.a, c.b, c.k2, c.b1);
  wgmma256<1>(acc, c.a, c.b, c.k1, c.b1);
  wgmma256<1>(acc, c.a, c.b, ST == 3 ? c.k4w : c.k4, ST == 3 ? -6144 - 384 : 2048 - 384);
  wg_commit();
}
__device__ __forceinline__ void release(const Cons& c, uint32_t bar) { if (c.do_rel) mbar_arrive_cl(c.rel + bar); }
template <int KB, bool WAIT = true, int LAG = 2> __device__ __forceinline__ void p1_step(float (&acc)[128], const Cons& c) {
  if (KB == 16 - LAG) { if (c.wg == 1) { wg_wait<0>(); release(c, B_E1 + 8 * ((KB - 1) & 3)); bar_sync(BAR_LAG, 256); } }
  p1_issue<KB & 3, KB != 0, WAIT>(acc, c, (KB >> 2) & 1);
  if (KB == 15) { if (c.wg == 0) bar_arrive(BAR_LAG, 256); }
  if (KB > 0) { wg_wait<1>(); if (KB != 16 - LAG || c.wg == 0) release(c, B_E1 + 8 * ((KB - 1) & 3)); }
  if (KB == 15) { wg_wait<0>(); release(c, B_E1 + 8 * 3); }
}
template <class F> __device__ __forceinline__ void p1_loop(float (&acc)[128], const Cons& c, int from, int to, F&& shadow) {
#pragma unroll 1
  for (int kb = from; kb < to; kb++) {
    const bool wrap = (kb & 3) == 3;
    mbar_spin(c.sb + B_F1 + 8 * (kb & 3), (kb >> 2) & 1, c.zero);
    wg_fence();
    wgmma256<1>(acc, c.a, c.b, c.k1, c.b1);
    wgmma256<1>(acc, c.a, c.b, c.k2, c.b1);
    wgmma256<1>(acc, c.a, c.b, c.k1, c.b1);
    wgmma256<1>(acc, c.a, c.b, wrap ? c.k4w : c.k4, wrap ? -6144 - 384 : 2048 - 384);
    wg_commit();
    wg_wait<1>();
    release(c, B_E1 + 8 * ((kb - 1) & 3));
    shadow(kb);
  }
}
template <int T> __device__ __forceinline__ void p2_step(float (&acc)[64], const Cons& c) {
  if (T == 16 - LAG2) { if (c.wg == 1) bar_sync(BAR_LAG, 256); }
  mbar_spin(c.sb + B_F2 + 8 * (T % 5), (T / 5) & 1, c.zero);
  wg_fence();
  wgmma128<T != 0>(acc, c.a, c.b, c.k1, c.b1);
  wgmma128<1>(acc, c.a, c.b, c.k2, c.b1);
  wgmma128<1>(acc, c.a, c.b, c.k1, c.b1);
  wgmma128<1>(acc, c.a, c.b, ((int)p2_a((T + 1) % 5) - (int)p2_a(T % 5)) / 16 - 514, ((int)p2_b((T + 1) % 5) - (int)p2_b(T % 5)) / 16 - 384);
  wg_commit();
  if (T == 15) { if (c.wg == 0) bar_arrive(BAR_LAG, 256); }
  if (T <= 11) { wg_wait<1>(); release(c, T ? B_E2 + 8 * ((T + 5 - 1) % 5) : B_E1 + 8); }
}

template <int P> __device__ __forceinline__ void geglu_piece(uint32_t (&pk)[64], uint8_t* dst, float (&rs)[2]) {
  constexpr int cg = P >> 1, r = P & 1;
  pin<1>(rs + r);
#pragma unroll
  for (int i = 0; i < 4; i++) pin<1>(pk + 2 * (4 * cg + i) + r);
  const float r2 = rs[r] * rs[r], c1 = GELU_C1 * rs[r], c3 = GELU_C3 * r2 * rs[r], k = 0.25f * r2;
  uint32_t v[4];
#pragma unroll
  for (int i = 0; i < 4; i++) {
    const uint32_t g = pk[2 * (4 * cg + i) + r];
    v[i] = mul2(pack2(gelu_k(lo_f(g), c1, c3, k), gelu_k(hi_f(g), c1, c3, k)), pk[32 + 2 * (4 * cg + i) + r]);
  }
  stg128(dst + cg * 8192 + r * 512, v[0], v[1], v[2], v[3]);
}
__device__ __forceinline__ void geglu_tile(float (&acc)[128], uint32_t (&pk)[64], const Cons& c, int to, uint8_t* dst, int ev, float (&rs)[2]) {
  const int lane = lane_here();
  dst += (lane ^ (lane >> 3)) << 4;
  p1_loop(acc, c, 1, to, [&](int kb) {
    if (kb <= 4) {
      if (kb <= 2) { if (kb == 1) geglu_piece<0>(pk, dst, rs); else geglu_piece<1>(pk, dst, rs); }
      else { if (kb == 3) geglu_piece<2>(pk, dst, rs); else geglu_piece<3>(pk, dst, rs); }
    } else if (kb <= 8) {
      if (kb <= 6) { if (kb == 5) geglu_piece<4>(pk, dst, rs); else geglu_piece<5>(pk, dst, rs); }
      else { if (kb == 7) geglu_piece<6>(pk, dst, rs); else { geglu_piece<7>(pk, dst, rs); bar_arrive(ev, 288); } }
    }
  });
}

__device__ __forceinline__ void attn_tile(float (&acc)[128], uint32_t (&pk)[64], const Cons& c, int round, int warp, int m, Scratch* gs, uint8_t* hdst, uint8_t* odst) {
  const int w = warp & 3;
  const uint32_t at = c.sb + OFF_X + c.wg * AT_WG;
  int lane = lane_here();
  hdst += (lane ^ (lane >> 3)) << 4;
  auto scatter = [&]() {
    const int lane = lane_here();
    const uint32_t swz = (lane ^ (lane >> 3)) << 4;
#pragma unroll
    for (int i = 0; i < 4; i++) {
      const int h = i & 1, r = i >> 1;
      sts128(at + AT_V + (2 * w + r) * 1024 + h * 512 + swz, make_uint4(pk[32 + 8 * h + r], pk[34 + 8 * h + r], pk[36 + 8 * h + r], pk[38 + 8 * h + r]));
    }
    if (w < 3) {
#pragma unroll
      for (int i = 0; i < 8; i++) asm volatile("st.shared.b32 [%0], %1;" ::"r"(at + AT_K + w * 1024 + i * 128 + lane * 4), "r"(pk[17 + 2 * i]) : "memory");
    } else {
      uint8_t* g = (uint8_t*)gs->halo + ((round * 128 + blockIdx.x) * 2 + c.wg) * 2048;
#pragma unroll
      for (int i = 0; i < 8; i++) asm volatile("st.global.b32 [%0], %1;" ::"l"(g + i * 128 + lane * 4), "r"(pk[17 + 2 * i]) : "memory");
#pragma unroll
      for (int h = 0; h < 2; h++) stg128(g + 1024 + h * 512 + swz, pk[33 + 8 * h], pk[35 + 8 * h], pk[37 + 8 * h], pk[39 + 8 * h]);
      bar_arrive(BAR_EV + 2 + round, 96);
    }
    __syncwarp();
    if (lane == 0) mbar_arrive(c.sb + B_HALO + 8 * round);
    if (round) {
#pragma unroll
      for (int p = 0; p < 4; p++) {
        const int o = 32 + 8 * (p >> 1) + (p & 1);
        asm volatile("ld.global.cg.v4.b32 {%0,%1,%2,%3}, [%4];" : "=r"(pk[o]), "=r"(pk[o + 2]), "=r"(pk[o + 4]), "=r"(pk[o + 6]) : "l"(hdst + (p >> 1) * 8192 + (p & 1) * 512) : "memory");
      }
    }
  };
  auto gu_piece = [&](int p) {
    uint32_t v[4];
#pragma unroll
    for (int i = 0; i < 4; i++) {
      const int o = 8 * (p >> 1) + 2 * i + (p & 1);
      pin<1>(pk + 48 + o);
      const uint32_t g = pk[48 + o];
      v[i] = mul2(round ? pk[32 + o] : 0x3e803e80u, round ? g : pack2(gelu_k(lo_f(g), GELU_C1, GELU_C3, 1.0f), gelu_k(hi_f(g), GELU_C1, GELU_C3, 1.0f)));
    }
    stg128(hdst + (p >> 1) * 8192 + (p & 1) * 512, v[0], v[1], v[2], v[3]);
  };
  p1_step<1>(acc, c);
  scatter();
  p1_loop(acc, c, 2, 9, [&](int kb) {
    if (kb <= 4) { if (kb == 3) gu_piece(0); else if (kb == 4) gu_piece(1); }
    else if (kb == 5) gu_piece(2); else if (kb == 6) gu_piece(3);
  });
  const bool first = m == 0 && w == 0;
  uint32_t kl[16];
  mbar_spin(c.sb + B_HALO + 8 * round, 0, c.zero);
  lane = lane_here();
  {
    const uint32_t ka = at + lane * 4 + (w ? AT_K + (w - 1) * 1024 : (first ? AT_K : AT_REM + round * 2048));
#pragma unroll
    for (int i = 0; i < 8; i++) {
      asm volatile("ld.shared.b32 %0, [%1];" : "=r"(kl[2 * i]) : "r"(ka + i * 128) : "memory");
      kl[2 * i + 1] = pk[16 + 2 * i] | c.zero;
    }
  }
  float st[4][4];
  pin<16>(kl);
  bar_sync(BAR_MMA, 256);
  mbar_spin(c.sb + B_F1 + 8 * 1, 0, c.zero);
#pragma unroll
  for (int ks = 0; ks < 2; ks++) {
#pragma unroll
    for (int h = 0; h < 2; h++) {
      const int o = 8 * h + 4 * ks;
      if (ks == 0) { hmma<0>(st[2 * h], kl[o], kl[o + 1], kl[o + 2], kl[o + 3], pk[o], pk[o + 2]); hmma<0>(st[2 * h + 1], pk[16 + o], pk[17 + o], pk[18 + o], pk[19 + o], pk[o + 1], pk[o + 3]); }
      else { hmma<1>(st[2 * h], kl[o], kl[o + 1], kl[o + 2], kl[o + 3], pk[o], pk[o + 2]); hmma<1>(st[2 * h + 1], pk[16 + o], pk[17 + o], pk[18 + o], pk[19 + o], pk[o + 1], pk[o + 3]); }
    }
  }
  sched_fence(c.zero);
  bar_sync(BAR_MMA, 256);
  p1_step<9, false>(acc, c);
  sched_fence(c.zero);
  pin<16>(&st[0][0]);
  lane = lane_here();
  const int rho = lane >> 2, q = lane & 3;
  const bool le0 = 2 * q <= rho, le1 = 2 * q + 1 <= rho;
  uint32_t la[2], lb[2], mx[2];
#pragma unroll
  for (int h = 0; h < 2; h++) {
    uint32_t l[2];
#pragma unroll
    for (int r = 0; r < 2; r++) {
      const float (&t)[4] = st[2 * h + r];
      l[r] = movm(pack2(rho <= 2 * q ? t[2] : t[0], rho <= 2 * q + 1 ? t[3] : t[1]));
      l[r] = fma2(l[r], 0x3e353e35u, mul2(l[r], 0x379e379eu));
    }
    la[h] = __byte_perm(l[0], l[1], 0x5410); lb[h] = __byte_perm(l[0], l[1], 0x7632);
    if (first && !le0) la[h] = (la[h] & 0xffff0000u) | 0xce6eu;
    if (first && !le1) lb[h] = (lb[h] & 0xffff0000u) | 0xce6eu;
    mx[h] = max2(la[h], lb[h]);
  }
#pragma unroll
  for (int o = 1; o <= 2; o++) { mx[0] = max2(mx[0], __shfl_xor_sync(~0u, mx[0], o)); mx[1] = max2(mx[1], __shfl_xor_sync(~0u, mx[1], o)); }
  const float L2E = 1.4426950408889634f;
  float pr[2][4], z[4];
#pragma unroll
  for (int h = 0; h < 2; h++) {
    pr[h][0] = ex2f((lo_f(la[h]) - lo_f(mx[h])) * L2E); pr[h][1] = ex2f((lo_f(lb[h]) - lo_f(mx[h])) * L2E);
    pr[h][2] = ex2f((hi_f(la[h]) - hi_f(mx[h])) * L2E); pr[h][3] = ex2f((hi_f(lb[h]) - hi_f(mx[h])) * L2E);
    z[2 * h] = pr[h][0] + pr[h][1]; z[2 * h + 1] = pr[h][2] + pr[h][3];
  }
  p1_step<10>(acc, c);
#pragma unroll
  for (int o = 1; o <= 2; o++) {
#pragma unroll
    for (int i = 0; i < 4; i++) z[i] += __shfl_xor_sync(~0u, z[i], o);
  }
  const uint32_t LE = (le0 ? 0xffffu : 0u) | (le1 ? 0xffff0000u : 0u);
  uint32_t P[4][2];
  uint4 vt[4][2];
  {
    const uint32_t row = (lane & 7) * 64 + ((((lane >> 3) & 1) ^ ((lane & 7) >> 1)) << 4);
    const uint32_t v1 = at + AT_V + (2 * w + (lane >> 4)) * 1024 + row;
    const uint32_t v0 = (w || lane >= 16) ? v1 - 1024 : (first ? v1 : at + AT_REM + round * 2048 + 1024 + row);
#pragma unroll
    for (int i = 0; i < 4; i++) {
      const float rz = rcpf(z[i]);
      const uint32_t p = pack2(pr[i >> 1][2 * (i & 1)] * rz, pr[i >> 1][2 * (i & 1) + 1] * rz);
      P[i][0] = p & ~LE; P[i][1] = p & LE;
      const uint32_t a = ((i & 1) ? v1 : v0) + (i >> 1) * 512;
      vt[i][0] = ldsm_t(a); vt[i][1] = ldsm_t(a ^ 32);
    }
  }
  float ot[4][2][4];
  pin<8>(&P[0][0]);
  bar_sync(BAR_MMA, 256);
  mbar_spin(c.sb + B_F1 + 8 * 3, 0, c.zero);
#pragma unroll
  for (int i = 0; i < 8; i++) { const uint4& v = vt[i >> 1][i & 1]; hmma<0>(ot[i >> 1][i & 1], v.x, v.y, v.z, v.w, P[i >> 1][0], P[i >> 1][1]); }
  sched_fence(c.zero);
  bar_sync(BAR_MMA, 256);
  p1_step<11, false>(acc, c);
  sched_fence(c.zero);
  pin<32>(&ot[0][0][0]);
  lane = lane_here();
  odst += (lane ^ (lane >> 3)) << 4;
  auto o_piece = [&](int i) {
    stg128(odst + (i >> 1) * 8192 + (i & 1) * 512, movm(pack2(ot[i][0][0], ot[i][0][1])), movm(pack2(ot[i][0][2], ot[i][0][3])), movm(pack2(ot[i][1][0], ot[i][1][1])), movm(pack2(ot[i][1][2], ot[i][1][3])));
  };
  o_piece(0); o_piece(1);
  p1_step<12>(acc, c);
  o_piece(2); o_piece(3);
  if (round) bar_arrive(BAR_EV + 4, 288);
  p1_step<13>(acc, c);
}

__device__ __forceinline__ void ln_moments(const uint32_t* raw, float& c0, float& s, float& v) {
  c0 = lo_f(__shfl_sync(~0u, raw[0], 0));
  float ss[4] = {0.f, 0.f, 0.f, 0.f}, vv[4] = {0.f, 0.f, 0.f, 0.f};
#pragma unroll
  for (int i = 0; i < 16; i++) {
    const float a = lo_f(raw[i]) - c0, b = hi_f(raw[i]) - c0;
    ss[(2 * i) & 3] += a; ss[(2 * i + 1) & 3] += b;
    vv[(2 * i) & 3] = fmaf(a, a, vv[(2 * i) & 3]); vv[(2 * i + 1) & 3] = fmaf(b, b, vv[(2 * i + 1) & 3]);
  }
  s = (ss[0] + ss[1]) + (ss[2] + ss[3]); v = (vv[0] + vv[1]) + (vv[2] + vv[3]);
}
__device__ __forceinline__ void ln_reduce(float& s, float& v) {
#pragma unroll
  for (int o = 16; o; o >>= 1) { s += __shfl_xor_sync(~0u, s, o); v += __shfl_xor_sync(~0u, v, o); }
}
__device__ __forceinline__ uint32_t ln_finish(float c0, float s, float v) {
  s *= 1.0f / DM;
  float sd;
  asm("sqrt.approx.ftz.f32 %0, %1;" : "=f"(sd) : "f"(bf16r(bf16r(fmaxf(fmaf(v, 1.0f / DM, -s * s), 0.f)) + 1e-5f)));
  return pack2(c0 + s, sd);
}
__device__ __forceinline__ void ln_store(const uint32_t* raw, uint32_t st, uint4* dst) {
  const uint32_t m2 = __byte_perm(st, st, 0x1010);
  const float rinv = rcpf(hi_f(st));
  const uint32_t rh = pack2(rinv, rinv), rl = pack2(rinv - hi_f(rh), rinv - hi_f(rh));
#pragma unroll
  for (int c = 0; c < 4; c++) {
    uint32_t v[4];
#pragma unroll
    for (int i = 0; i < 4; i++) { const uint32_t t = sub2(raw[4 * c + i], m2); v[i] = fma2(t, rh, mul2(t, rl)); }
    stg128(dst + 32 * c, v[0], v[1], v[2], v[3]);
  }
}
__device__ __forceinline__ void col_sums(uint32_t tile, ulonglong2* part, uint32_t tag) {
  const int lane = threadIdx.x & 31;
  float cs[8] = {0, 0, 0, 0, 0, 0, 0, 0};
  uint32_t base = tile + ((lane >> 3) & 1) * 8192 + (lane >> 4) * 4096 + ((lane & 7) << 4);
#pragma unroll 1
  for (int k0 = 0; k0 < 8; k0++, base = (base ^ ((k0 ^ (k0 - 1)) << 4)) + 128) {
    uint4 v[4];
#pragma unroll
    for (int k = 0; k < 4; k++) v[k] = lds128(base + k * 1024);
#pragma unroll
    for (int k = 0; k < 4; k++) {
      cs[0] += lo_f(v[k].x); cs[1] += hi_f(v[k].x); cs[2] += lo_f(v[k].y); cs[3] += hi_f(v[k].y);
      cs[4] += lo_f(v[k].z); cs[5] += hi_f(v[k].z); cs[6] += lo_f(v[k].w); cs[7] += hi_f(v[k].w);
    }
  }
  const bool up = lane >= 16;
#pragma unroll
  for (int i = 0; i < 2; i++) {
    const float a = (up ? cs[4 + 2 * i] : cs[2 * i]) + __shfl_xor_sync(~0u, up ? cs[2 * i] : cs[4 + 2 * i], 16);
    const float b = (up ? cs[5 + 2 * i] : cs[1 + 2 * i]) + __shfl_xor_sync(~0u, up ? cs[1 + 2 * i] : cs[5 + 2 * i], 16);
    asm volatile("{\n.reg .b64 a, b;\nmov.b64 a, {%1, %3};\nmov.b64 b, {%2, %3};\nst.relaxed.gpu.global.v2.b64 [%0], {a, b};\n}"
                 ::"l"(part + 32 * (i + (up ? 2 : 0)) + (lane & 15)), "r"(__float_as_uint(a)), "r"(__float_as_uint(b)), "r"(tag) : "memory");
  }
  asm volatile("fence.proxy.async.shared::cta;" ::: "memory");
}

__global__ void __cluster_dims__(2, 1, 1) __launch_bounds__(384, 1)
fused_kernel(const uint4* __restrict__ x, const uint4* __restrict__ wgate, const uint4* __restrict__ wup, Scratch* gs, const __grid_constant__ Maps mp) {
  extern __shared__ __align__(1024) uint8_t smem_raw[];
  const uint32_t sb = (uint32_t)__cvta_generic_to_shared(smem_raw);
  if (threadIdx.x == 352) TS(63);
  if (threadIdx.x < 256 && blockIdx.x < NMAIN) {
    const uint32_t r = threadIdx.x >> 3, ch = threadIdx.x & 7;
    const uint32_t d = sb + r * 128 + ((ch ^ (r & 7)) << 4);
    const uint8_t* xa = (const uint8_t*)x + ((blockIdx.x & 15) * 262144 + r * 4096 + ch * 16);
    const uint32_t wo = r * (DFF * 2) + (blockIdx.x >> 4) * 256 + ch * 16;
    const uint8_t *wa = (const uint8_t*)wgate + wo, *wb = (const uint8_t*)wup + wo;
#pragma unroll
    for (int i = 0; i < 12; i++) {
      const int h = i >= 8;
      const uint8_t* src = (i >> 2) == 1 ? xa + (i & 1) * 131072 + ((i >> 1) & 1) * 2048 : ((i & 2) ? wb : wa) + h * 32 * (DFF * 2) + (i & 1) * 128;
      asm volatile("cp.async.cg.shared.global [%0], [%1], 16;" ::"r"(d + ((i >> 2) == 1 ? OFF_A + (i & 3) * 4096 : (i & 3) * 8192 + h * 4096)), "l"(src) : "memory");
    }
    if (threadIdx.x == 0) TS(23);
  }
  const int warp = __shfl_sync(~0u, threadIdx.x >> 5, 0), lane = threadIdx.x & 31;
  const int m = blockIdx.x & 15, j = blockIdx.x >> 4, rank = blockIdx.x & 1;
  const int m2 = blockIdx.x >> 3, j2 = blockIdx.x & 7;
  const bool helper = blockIdx.x >= NMAIN;
  if (warp >= 8) {
    asm volatile("setmaxnreg.dec.sync.aligned.u32 40;");
    if (warp == 8) {
      if (elect_one()) {
        asm volatile("prefetch.tensormap [%0];\nprefetch.tensormap [%1];\nprefetch.tensormap [%2];" ::"l"(&mp.x), "l"(&mp.wg), "l"(&mp.wu) : "memory");
        for (int s = 0; s < 4; s++) mbar_init(sb + B_F1 + 8 * s, 1);
        if (!helper) mbar_arrive(sb + B_F1);
        asm volatile("fence.mbarrier_init.release.cluster;" ::: "memory");
      }
      __syncwarp();
    } else if (warp == 9) {
      if (elect_one()) {
        if ((sb & 0xffffff) != SM_BASE) asm volatile("trap;");
        for (uint32_t b = B_E1; b < B_F2; b += 8) mbar_init(sb + b, 4);
        for (uint32_t b = B_F2; b < B_AUX; b += 8) mbar_init(sb + b, 1);
        for (uint32_t b = B_EX; b < B_AUX; b += 8) mbar_expect_tx(sb + b, 8192);
        mbar_init(sb + B_AUX, 8); mbar_init(sb + B_HALO, 9); mbar_init(sb + B_HALO + 8, 9);
        asm volatile("fence.mbarrier_init.release.cluster;" ::: "memory");
      }
      __syncwarp();
    }
    asm volatile("barrier.cluster.arrive.relaxed.aligned;" ::: "memory");
    if (warp == 8 && !helper) {
      if (elect_one()) {
        TS(0); TG(51);
#pragma unroll 1
        for (int kb = 1; kb < 4; kb++) {
          const uint32_t sa = sb + OFF_A + kb * 16384, sw = sb + kb * 32768, fb = sb + B_F1 + 8 * kb;
          mbar_expect_tx(fb, P1_BYTES);
          tma3d(sa, &mp.x, fb, kb * 64, m * 64, 0, EVICT_NORMAL);
          tma2d(sw, &mp.wg, fb, j * 128, kb * 64, EVICT_NORMAL); tma2d(sw + 16384, &mp.wu, fb, j * 128, kb * 64, EVICT_NORMAL);
          tma2d(sw + 8192, &mp.wg, fb, j * 128 + 64, kb * 64, EVICT_NORMAL); tma2d(sw + 24576, &mp.wu, fb, j * 128 + 64, kb * 64, EVICT_NORMAL);
        }
        TS(7);
      }
      __syncwarp();
    }
    asm volatile("barrier.cluster.wait.aligned;" ::: "memory");
    if (helper) {
      if (warp == 8) {
        unsigned e = 0;
        if (elect_one()) {
#pragma unroll 1
          for (int i = 0; i < 16; i++) {
            const uint32_t fb = sb + B_F1 + 8 * (i >> 2);
            if (!(i & 3)) mbar_expect_tx(fb, P1_BYTES);
            tma5d(sb + i * 8192, &mp.wd, fb, (blockIdx.x - NMAIN) * 256 + (i & 3) * 64, (i >> 2) * 2, HINT_W);
          }
        }
        if (lane == 0) { unsigned* ep = &gs->epoch[blockIdx.x * 2]; e = *ep + 1; *ep = e; }
        e = __shfl_sync(~0u, e, 0);
        if (lane < 16) flag_wait(&gs->flags[(FL_H + lane * 4) * 32], e * 8u);
        __syncwarp();
        if (elect_one()) {
          fence_async();
          TS(0);
#pragma unroll 1
          for (int i = 0; i < 64; i++) {
            const uint32_t fb = sb + B_F1 + 8 * (i & 3);
            if (i >= 4) { mbar_wait(sb + B_E1 + 8 * (i & 3), ~(i >> 2) & 1); mbar_expect_tx(fb, 16384); }
            bulk_load(sb + OFF_A + (i & 3) * 16384, gs->h + ((i >> 2) * 56 + (i & 3)) * 1024, 16384, fb, EVICT_NORMAL);
          }
        }
      } else if (warp == 9) {
#pragma unroll 1
        for (int t = 0; t < 16; t++) {
          bar_sync(BAR_EV + (t & 1), 288);
          if (lane == 0) { flag_add(&gs->flags[(FL_P + t) * 32]); TS(64 + t); }
          __syncwarp();
        }
      }
    } else if (warp == 8) {
      if (elect_one()) {
        uint32_t par = 0;

        auto x_load = [&]() {
          mbar_expect_tx(sb + B_XT, 32768);
          tma3d(sb + OFF_X, &mp.x, sb + B_XT, j2 * 128, m2 * 64, 0, HINT_LAST); tma3d(sb + OFF_X + 16384, &mp.x, sb + B_XT, j2 * 128 + 64, m2 * 64, 0, HINT_LAST);
        };
        auto d_prefetch = [&](int i) {
          if ((m2 >> 2) == (i & 3)) tma5d_prefetch(&mp.wd, (j2 >> 1) * 256 + (m2 & 3) * 64, (2 * i + 4 + rank) * 2);
        };
        auto w_tile = [&](int R, const CUtensorMap*& mb0, const CUtensorMap*& mb1, int& n0, int& n1) {
          if (R == 1 || R == 2) {
            mb0 = &mp.wqkv; n0 = 64 * (j + 8 * (R - 1)) + rank * 2048;
            mb1 = rank ? (R == 1 ? &mp.wg : &mp.wu) : &mp.wqkv; n1 = rank ? 1024 + 64 * j : n0 + 1024;
          } else {
            mb0 = mb1 = rank ? &mp.wu : &mp.wg;
            n0 = 128 * j + (R ? 1024 * R - 1536 : 0); n1 = n0 + 64;
          }
        };
        for (int R = 0; R < 5; R++) {
          const CUtensorMap *mb0, *mb1;
          int n0, n1;
          w_tile(R, mb0, mb1, n0, n1);
#pragma unroll 1
          for (int kb = R ? 0 : 4; kb < 16; kb++) {
            if (R == 0 && kb == 14) { asm volatile("prefetch.tensormap [%0];\nprefetch.tensormap [%1];" ::"l"(&mp.xn), "l"(&mp.wqkv) : "memory"); }
            if (R == 4 && kb == 2) { asm volatile("prefetch.tensormap [%0];\nprefetch.tensormap [%1];\nprefetch.tensormap [%2];" ::"l"(&mp.wd), "l"(&mp.wo), "l"(&mp.out) : "memory"); }
            if (R == 0 && kb == CS_KB) {
#pragma unroll 1
              for (int h = 0; h < 2; h++) {
                const uint32_t cb = sb + B_CS + 8 * h, d = sb + OFF_X + 16384 * h;
                mbar_expect_tx(cb, 16384);
                tma2d(d, h ? &mp.wu : &mp.wg, cb, n0, m * 64, EVICT_NORMAL); tma2d(d + 8192, h ? &mp.wu : &mp.wg, cb, n1, m * 64, EVICT_NORMAL);
              }
            }
            const int st = kb & 3;
            const uint32_t sa = sb + OFF_A + st * 16384, sw = sb + st * 32768, fb = sb + B_F1 + 8 * st;
            mbar_wait(sb + B_E1 + 8 * st, par);
            if (R * 16 + kb >= 4) REL_TS(R * 16 + kb - 4);
            mbar_expect_tx(fb, P1_BYTES);
            tma2d_mc(sw + rank * 16384, mb0, fb, n0, kb * 64, HINT_W);
            tma2d_mc(sw + 8192 + rank * 16384, mb1, fb, n1, kb * 64, HINT_W);
            if (R == 0) {
              tma3d(sa, &mp.x, fb, kb * 64, m * 64, 0, EVICT_NORMAL);
            } else {
              if (R == 1 && kb == 0) { mbar_wait(sb + B_DEP, 0); TS(1); }
              tma2d(sa, &mp.xn, fb, kb * 64, m * 128, R == 4 ? HINT_LAST : EVICT_NORMAL);
            }
            if (R == 4 && kb == 4 + j2) x_load();
            if (R == 4 && kb >= 16 - PF_D) d_prefetch(kb + PF_D - 16);
            if (st == 3) par ^= 1;
          }
        }
#pragma unroll 1
        for (int i = 0; i < 26; i++) {
          const int st = i & 3, kb = 2 * i + 4 + rank;
          const uint32_t sa = sb + OFF_A + st * 16384, sw = sb + st * 32768, fb = sb + B_F1 + 8 * st;
          mbar_wait(sb + B_E1 + 8 * st, par);
          REL_TS(76 + i);
          mbar_expect_tx(fb, P1_BYTES);
          tma5d(sw, &mp.wd, fb, j2 * 128, kb * 2, HINT_W); tma5d(sw + 8192, &mp.wd, fb, j2 * 128 + 64, kb * 2, HINT_W);
          tma5d(sw + 16384, &mp.wd, fb, (j2 ^ 1) * 128, kb * 2, HINT_W); tma5d(sw + 24576, &mp.wd, fb, (j2 ^ 1) * 128 + 64, kb * 2, HINT_W);
          if (i == 0 || i == 6 || i == 10 || i == 18) { mbar_wait(sb + B_DEP + 8 * (1 + ((i + 6) >> 3)), 0); }
          bulk_load(sa, gs->h + (m2 * 56 + kb) * 1024, 16384, fb, HINT_H);
          if (i + PF_D < 26) d_prefetch(i + PF_D);
          if (st == 3) par ^= 1;
        }
        int st = 0; uint32_t par2 = 1;
#pragma unroll 1
        for (int t = 0; t < 16; t++) {
          const uint32_t sa = sb + p2_a(st), sw = sb + p2_b(st), fb = sb + B_F2 + 8 * st;
          if (t < 5) mbar_wait(sb + B_E1 + 8 * (((2 * t + 1) / 3 + 2) & 3), t < 3); else mbar_wait(sb + B_E2 + 8 * st, par2);
          REL_TS(102 + t);
          mbar_expect_tx(fb, P2_BYTES);
          bulk_load_mc(sa + rank * 8192, gs->o + (m2 * 16 + t) * 1024 + rank * 512, 8192, fb, HINT_H);
          tma2d(sw, &mp.wo, fb, j2 * 128, t * 64, HINT_W); tma2d(sw + 8192, &mp.wo, fb, j2 * 128 + 64, t * 64, HINT_W);
          if (++st == 5) { st = 0; par2 ^= 1; }
        }
      }
    } else if (warp == 9) {
#pragma unroll 1
      for (int e = 0; e < 7; e++) {
        const bool halo = e == 2 || e == 3;
        bar_sync(BAR_EV + e, halo ? 96 : 288);
        if (lane == 0) {
          const int f = e == 0 ? FL_XN + m : (halo ? FL_HALO + (e - 2) * 128 + blockIdx.x : FL_H + m * 4 + (e == 1 ? 0 : e - 3));
          TS(10 + 2 * e); TG(52 + e);
          flag_add(&gs->flags[f * 32]);
          if (e < 6) TS(11 + 2 * e);
        }
        __syncwarp();
      }
      mbar_wait(sb + B_DONE, 0);
    } else {
      unsigned e = 0;
      if (lane == 0) {
        unsigned* ep = &gs->epoch[blockIdx.x * 2 + warp - 10];
        e = *ep + 1; *ep = e;
        if (warp == 10) { asm volatile("st.shared.b32 [%0], %1;" ::"r"(sb + OFF_EPOCH), "r"(e) : "memory"); mbar_arrive(sb + B_EP); }
      }
      e = __shfl_sync(~0u, e, 0);
      mbar_wait(sb + B_CS + 8 * (warp - 10), 0);
      if (lane == 0 && warp == 11) TS(6);
      col_sums(sb + OFF_X + (warp - 10) * 16384, gs->cspart + (j * 16 + m) * 128 + (warp - 10) * 16, e);
      if (lane == 0 && warp == 11) TS(9);
      if (warp == 10) {
        if (lane == 0) {
#pragma unroll 1
          for (int g = 0; g < 6; g++) {
            flag_wait(&gs->flags[(g == 5 ? FL_P + m2 : (g ? FL_H + m2 * 4 + g - 1 : FL_XN + m)) * 32], e * (g == 5 ? 4u : 8u));
            fence_async();
            mbar_arrive(sb + B_DEP + 8 * g);
            if (g == 0) TS(8);
          }
        }
      } else
      if (elect_one()) {
#pragma unroll 1
        for (int r = 0; r < 2; r++) {
          const uint32_t hb = sb + B_HALO + 8 * r;
          if (r) mbar_wait(sb + B_HALO, 0);
          if (m) {
            flag_wait(&gs->flags[(FL_HALO + r * 128 + blockIdx.x - 1) * 32], e);
            fence_async();
            mbar_expect_tx(hb, 4096);
            for (int g = 0; g < 2; g++) bulk_load(sb + OFF_X + g * AT_WG + AT_REM + r * 2048, gs->halo + ((r * 128 + blockIdx.x - 1) * 2 + g) * 128, 2048, hb, EVICT_FIRST);
          } else {
            mbar_arrive(hb);
          }
          TS(34 + r);
        }
      }
    }
  } else {
    asm volatile("barrier.cluster.arrive.relaxed.aligned;" ::: "memory");
    asm volatile("setmaxnreg.inc.sync.aligned.u32 232;");
    const int wg = warp >> 2, w = warp & 3;
    Cons c;
    c.sb = sb; c.wg = wg; c.zero = warp >> 8;
    c.a = 0x4000004000010000ull + ((SM_BASE + OFF_A + wg * 8192) >> 4); c.k1 = 2 + c.zero; c.k2 = 2; c.k4 = 1024 - 6; c.k4w = -3072 - 6; c.b1 = 128 + c.zero;
    c.b = 0x4000004000000000ull + DB_LO + c.zero;
    c.rel = mapa(sb, threadIdx.x & 1);
    c.do_rel = (threadIdx.x & 127) < 2;
    constexpr bool t0 = false;
    float acc[128];
    uint32_t pk[64];
    float rs[2];
    const int q = lane & 3;

    if (helper) {
      asm volatile("barrier.cluster.wait.aligned;" ::: "memory");
      c.a = 0x8000002000010000ull + ((SM_BASE + OFF_A + wg * 4096) >> 4); c.k2 = 510; c.k4 = 1024 - 514; c.k4w = -3072 - 514;
      c.rel = sb;
      uint4* dst = gs->dpart + (blockIdx.x - NMAIN) * 4096 + threadIdx.x;
      auto put = [&](int p) {
#pragma unroll
        for (int i = 4 * p; i < 4 * p + 4; i++) stg128(dst + i * 256, pk[4 * i], pk[4 * i + 1], pk[4 * i + 2], pk[4 * i + 3]);
      };
#pragma unroll 1
      for (int t = 0; t < 16; t++) {
        p1_issue<0, 0>(acc, c, t & 1);
        if (t) put(0);
        p1_issue<1, 1>(acc, c, t & 1); wg_wait<1>(); release(c, B_E1);
        if (t) put(1);
        if (wg == 1) { wg_wait<0>(); release(c, B_E1 + 8); bar_sync(BAR_LAG, 256); }
        p1_issue<2, 1>(acc, c, t & 1); wg_wait<1>(); if (wg == 0) release(c, B_E1 + 8);
        if (t) put(2);
        p1_issue<3, 1>(acc, c, t & 1);
        if (wg == 0) bar_arrive(BAR_LAG, 256);
        if (t) { put(3); bar_arrive(BAR_EV + (~t & 1), 288); dst += 8 * 2048; }
        wg_wait<1>(); release(c, B_E1 + 16);
        wg_wait<0>(); release(c, B_E1 + 24);
#pragma unroll
        for (int i = 0; i < 64; i++) pk[i] = pack2(acc[2 * i], acc[2 * i + 1]);
      }
      put(0); put(1); put(2); put(3);
      bar_arrive(BAR_EV + 1, 288);
      return;
    }
    {
      const int prow = 16 * j + 2 * warp;
      const uint4* xr = x + (size_t)(128 * m + 2 * (prow & 63) + (prow >> 6)) * 128 + lane;
      uint4* xo = gs->xn + (size_t)(128 * m + prow) * 128 + lane;
      float c0[2], mo[4];
      uint32_t st[2];
      uint32_t e;
      asm volatile("" : "+l"(xr), "+l"(xo));
      asm volatile("cp.async.wait_all;\nfence.proxy.async.shared::cta;" ::: "memory");
      bar_sync(BAR_MMA, 256);
      if (threadIdx.x == 0) TS(39);
      p1_step<0, false>(acc, c);
      asm volatile("barrier.cluster.wait.aligned;" ::: "memory");
      unsigned long long part[18];
      auto gather = [&]() {
        const int lane = lane_here();
        const unsigned long long* cp = (const unsigned long long*)gs->cspart + j * 4096 + warp * 32 + lane;
        const unsigned long long* sp = gs->stats + 128 * m + warp * 16 + (lane >> 2);
#pragma unroll
        for (int i = 0; i < 18; i++) asm volatile("ld.relaxed.gpu.global.b64 %0, [%1];" : "=l"(part[i]) : "l"(i < 16 ? cp + i * 256 : sp + (i - 16) * 8) : "memory");
      };
      p1_step<1>(acc, c);
#pragma unroll
      for (int i = 0; i < 8; i++)
        asm volatile("ld.global.nc.v4.b32 {%0,%1,%2,%3}, [%4];" : "=r"(pk[4 * i]), "=r"(pk[4 * i + 1]), "=r"(pk[4 * i + 2]), "=r"(pk[4 * i + 3]) : "l"(xr + (i >> 2) * 256 + (i & 3) * 32));
      p1_loop(acc, c, 2, LN_KB + 1, [](int) {});
      pin<16>(pk); ln_moments(pk, c0[0], mo[0], mo[1]); pin<2>(mo);
      p1_step<LN_KB + 1>(acc, c);
      sched_fence(c.zero);
      pin<16>(pk + 16); ln_moments(pk + 16, c0[1], mo[2], mo[3]); ln_reduce(mo[0], mo[1]); pin<4>(mo);
      p1_step<LN_KB + 2>(acc, c);
      mbar_spin(sb + B_EP, 0, c.zero);
      asm volatile("ld.shared.b32 %0, [%1];" : "=r"(e) : "r"(sb + OFF_EPOCH) : "memory");
      pin<2>(mo); st[0] = ln_finish(c0[0], mo[0], mo[1]); ln_reduce(mo[2], mo[3]); pin<1>(st); pin<2>(mo + 2);
      p1_step<LN_KB + 3>(acc, c);
      sched_fence(c.zero);
      pin<1>(st); pin<2>(mo + 2);
      st[1] = ln_finish(c0[1], mo[2], mo[3]);
      ln_store(pk, st[0], xo);
      if (lane == 0)
        asm volatile("{\n.reg .b64 a, b;\nmov.b64 a, {%1, %3};\nmov.b64 b, {%2, %3};\nst.relaxed.gpu.global.v2.b64 [%0], {a, b};\n}" ::"l"(gs->stats + 128 * m + prow), "r"(st[0]), "r"(st[1]), "r"(e) : "memory");
      p1_step<LN_KB + 4>(acc, c);
      sched_fence(c.zero);
      pin<1>(st + 1);
      ln_store(pk + 16, st[1], xo + 128);
      bar_arrive(BAR_EV, 288);
      p1_loop(acc, c, LN_KB + 5, 13, [](int) {});
      gather();
      p1_step<13>(acc, c);
      auto validate = [&]() {
        float csum;
        for (int tries = 0;; tries++) {
          uint32_t bad = 0;
          csum = 0.f;
#pragma unroll
          for (int i = 0; i < 18; i++) { bad |= (uint32_t)(part[i] >> 32) ^ e; if (i < 16) csum += __uint_as_float((uint32_t)part[i]); }
          if (!__any_sync(~0u, bad != 0) || tries > (1 << 20)) break;
          gather();
        }
        const float hi = bf16r(csum), mid = bf16r(csum - hi);
        sts128(sb + OFF_CS + ((threadIdx.x & 62) * 4 + (threadIdx.x >> 6) * 2 + (threadIdx.x & 1)) * 16, make_uint4(pack2(hi, mid), pack2(csum - hi - mid, 0.f), 0, 0));
        asm volatile("fence.proxy.async.shared::cta;" ::: "memory");
        __syncwarp();
        if (lane == 0) mbar_arrive(sb + B_AUX);
      };
#pragma unroll 1
      for (int ph = 1; ph >= 0; ph--) {
        if (wg == ph) validate();
        if (ph) { p1_step<14>(acc, c); p1_issue<3, 1>(acc, c, 1); }
      }
      const uint32_t keep = q == 0 ? 0xffffffffu : (q == 1 ? 0xffffu : 0u);
      const uint32_t a0 = (__byte_perm((uint32_t)part[16], 0, 0x1010) ^ 0x80008000u) & keep, a1 = (__byte_perm((uint32_t)part[17], 0, 0x1010) ^ 0x80008000u) & keep;
      mbar_spin(sb + B_AUX, 0, c.zero);
      wg_fence();
      wgmma256_rs(acc, a0, a1, 0, 0, (SM_BASE + OFF_CS) >> 4);
      wg_commit();
      if (wg == 0) bar_arrive(BAR_LAG, 256);
      rs[0] = rcpf(hi_f((uint32_t)part[16])); rs[1] = rcpf(hi_f((uint32_t)part[17]));
      wg_wait<2>(); release(c, B_E1 + 16);
      wg_wait<0>(); release(c, B_E1 + 24);
    }
#pragma unroll 1
    for (int R = 1;; R++) {
#pragma unroll
      for (int i = 0; i < 64; i++) pk[i] = pack2(acc[2 * i], acc[2 * i + 1]);
      if (t0) TS(24 + R + wg * 16);
      uint8_t* hb = (uint8_t*)gs->h + (size_t)m * 56 * 16384 + warp * 1024;
      if (R == 5) { c.a = 0x8000002000010000ull + ((SM_BASE + OFF_A + wg * 4096) >> 4); c.k2 = 510; c.k4 = 1024 - 514; c.k4w = -3072 - 514; }
      p1_step<0>(acc, c);
      if (R == 2 || R == 3) {
        attn_tile(acc, pk, c, R - 2, warp, m, gs, hb + (16 + j) * 16384, (uint8_t*)gs->o + (m * 16 + j + 8 * (R - 2)) * 16384 + warp * 1024);
      } else {
        geglu_tile(acc, pk, c, R == 5 ? 24 : 14, hb + (2 * j + (R == 1 ? 0 : 16 * R - 40)) * 16384, BAR_EV + (R == 1 ? 1 : R + 1), rs);
        rs[0] = rs[1] = 1.0f;
        if (R == 5) break;
      }
      p1_step<14>(acc, c); p1_step<15>(acc, c);
    }
    auto fetch = [&](int p) {
      asm volatile("ld.global.cg.v4.b32 {%0,%1,%2,%3}, [%4];" : "=r"(pk[4 * p]), "=r"(pk[4 * p + 1]), "=r"(pk[4 * p + 2]), "=r"(pk[4 * p + 3]) : "l"(gs->dpart + blockIdx.x * 2048 + p * 256 + threadIdx.x) : "memory");
    };
    mbar_spin(sb + B_DEP + 40, 0, c.zero);
    fetch(0); fetch(1); fetch(2);
    p1_step<8>(acc, c);
    fetch(3); fetch(4); fetch(5);
    p1_step<9>(acc, c);
    fetch(6); fetch(7);
    {
      float accs[64];
      const uint32_t peer = mapa(sb, rank ^ 1);
      auto send_piece = [&](int p) {
        asm volatile("st.async.weak.shared::cluster.mbarrier::complete_tx::bytes.v4.b32 [%0], {%1,%2,%3,%4}, [%5];" ::"r"(peer + OFF_LAND + p * 4096 + threadIdx.x * 16),
                     "r"(pack2(acc[64 + 8 * p], acc[65 + 8 * p])), "r"(pack2(acc[66 + 8 * p], acc[67 + 8 * p])), "r"(pack2(acc[68 + 8 * p], acc[69 + 8 * p])), "r"(pack2(acc[70 + 8 * p], acc[71 + 8 * p])),
                     "r"(peer + B_EX + 16 * wg + 8 * (p >> 2)) : "memory");
      };
      auto silu_piece = [&](int p) {
        const uint4 r = lds128(sb + OFF_LAND + p * 4096 + threadIdx.x * 16);
        const uint32_t rr[4] = {add2(r.x, pk[4 * p]), add2(r.y, pk[4 * p + 1]), add2(r.z, pk[4 * p + 2]), add2(r.w, pk[4 * p + 3])};
#pragma unroll
        for (int i = 0; i < 4; i++) {
          const float a = acc[8 * p + 2 * i] + lo_f(rr[i]), b = acc[8 * p + 2 * i + 1] + hi_f(rr[i]);
          pk[4 * p + i] = pack2(silu_half(a), silu_half(b));
        }
        pin<4>(pk + 4 * p);
      };
      const uint32_t xa = sb + OFF_X + (warp * 16 + (lane & 15)) * 128 + (((lane >> 4) ^ (lane & 7)) << 4);
      auto x_piece = [&](int i) { const uint4 v = ldsm((xa ^ ((i & 3) << 5)) + (i >> 2) * 16384); pk[32 + 4 * i] = v.x; pk[33 + 4 * i] = v.y; pk[34 + 4 * i] = v.z; pk[35 + 4 * i] = v.w; };
      p2_step<0>(accs, c);
      p2_step<1>(accs, c);
      mbar_spin(sb + B_E1 + 8, 0, c.zero);
      send_piece(0); send_piece(1);
      p2_step<2>(accs, c); sched_fence(c.zero); send_piece(2); send_piece(3);
      p2_step<3>(accs, c); sched_fence(c.zero); send_piece(4); send_piece(5);
      p2_step<4>(accs, c); mbar_spin(sb + B_XT, 0, c.zero); send_piece(6); send_piece(7);
      p2_step<5>(accs, c); mbar_spin(sb + B_EX + 16 * wg, 0, c.zero); silu_piece(0); x_piece(0);
      p2_step<6>(accs, c); sched_fence(c.zero); silu_piece(1); x_piece(1);
      p2_step<7>(accs, c); sched_fence(c.zero); silu_piece(2); x_piece(2);
      p2_step<8>(accs, c); sched_fence(c.zero); silu_piece(3); x_piece(3);
      p2_step<9>(accs, c); mbar_spin(sb + B_EX + 16 * wg + 8, 0, c.zero); silu_piece(4); x_piece(4);
      p2_step<10>(accs, c); sched_fence(c.zero); silu_piece(5); x_piece(5);
      p2_step<11>(accs, c); sched_fence(c.zero); silu_piece(6); x_piece(6); x_piece(7);
      if (wg == 1) silu_piece(7);
      p2_step<12>(accs, c); p2_step<13>(accs, c); p2_step<14>(accs, c); p2_step<15>(accs, c);
      if (c.do_rel) mbar_arrive(sb + B_DONE);
      if (wg == 0) silu_piece(7);
      wg_wait<0>();
#pragma unroll
      for (int i = 0; i < 8; i++) {
        uint32_t v[4];
#pragma unroll
        for (int k = 0; k < 4; k++) v[k] = fma2(pack2(accs[8 * i + 2 * k], accs[1 + 8 * i + 2 * k]), pk[4 * i + k], pk[32 + 4 * i + k]);
        asm volatile("stmatrix.sync.aligned.m8n8.x4.shared.b16 [%0], {%1,%2,%3,%4};" ::"r"((xa ^ ((i & 3) << 5)) + (i >> 2) * 16384), "r"(v[0]), "r"(v[1]), "r"(v[2]), "r"(v[3]) : "memory");
        if (i == 3 || i == 7) {
          asm volatile("fence.proxy.async.shared::cta;" ::: "memory");
          __syncwarp();
          if (elect_one()) tma3d_store(&mp.out, sb + OFF_X + (i >> 2) * 16384 + warp * 2048, j2 * 128 + (i >> 2) * 64, m2 * 64 + w * 16, wg);
        }
      }
      if (elect_one()) { asm volatile("cp.async.bulk.commit_group;\ncp.async.bulk.wait_group.read 0;" ::: "memory"); }
      if ((threadIdx.x & 127) == 0) { TS(33 + wg * 16); if (wg) { TG(59); unsigned id; asm volatile("mov.u32 %0, %%smid;" : "=r"(id)); TSV(60, id); } }
    }
  }
}

typedef CUresult (*EncodeFn)(CUtensorMap*, CUtensorMapDataType, cuuint32_t, void*, const cuuint64_t*, const cuuint64_t*, const cuuint32_t*, const cuuint32_t*,
                             CUtensorMapInterleave, CUtensorMapSwizzle, CUtensorMapL2promotion, CUtensorMapFloatOOBfill);

void encode(EncodeFn fn, CUtensorMap* tm, const void* p, int rank, const cuuint64_t* dims, const cuuint64_t* strides, const cuuint32_t* box) {
  const cuuint32_t es[5] = {1, 1, 1, 1, 1};
  fn(tm, CU_TENSOR_MAP_DATA_TYPE_BFLOAT16, rank, const_cast<void*>(p), dims, strides, box, es, CU_TENSOR_MAP_INTERLEAVE_NONE, CU_TENSOR_MAP_SWIZZLE_128B,
     PROMO, CU_TENSOR_MAP_FLOAT_OOB_FILL_NONE);
}

}

extern "C" void kernel_launch(void* const* d_in, const int* in_sizes, int n_in, void* d_out, int out_size) {
  (void)in_sizes; (void)n_in; (void)out_size;
  static EncodeFn fn = nullptr;
  static Scratch* gs = nullptr;
  if (!fn) {
    void* p = nullptr;
    cudaDriverEntryPointQueryResult qr;
    cudaGetDriverEntryPoint("cuTensorMapEncodeTiled", &p, cudaEnableDefault, &qr);
    fn = (EncodeFn)p;
    cudaGetSymbolAddress((void**)&gs, g_scratch);
    cudaFuncSetAttribute(fused_kernel, cudaFuncAttributeMaxDynamicSharedMemorySize, SMEM_BYTES);
  }
  const void *x = d_in[0], *wqkv = d_in[1], *wo = d_in[2], *wg = d_in[4], *wu = d_in[5], *wd = d_in[6];
  Maps mp;
  {
    const cuuint64_t dims[3] = {DM, SEQ / 2, 2}, st[2] = {DM * 4, DM * 2};
    const cuuint32_t box_in[3] = {64, 64, 2}, box_out[3] = {64, 16, 1};
    encode(fn, &mp.x, x, 3, dims, st, box_in);
    encode(fn, &mp.out, d_out, 3, dims, st, box_out);
  }
  {
    const cuuint64_t dims[2] = {DM, SEQ}, st[1] = {DM * 2};
    const cuuint32_t box[2] = {64, 128};
    encode(fn, &mp.xn, gs->xn, 2, dims, st, box);
  }
  {
    const cuuint32_t box[2] = {64, 64};
    const cuuint64_t dq[2] = {3 * DM, DM}, sq[1] = {3 * DM * 2}, df[2] = {DFF, DM}, sf[1] = {DFF * 2}, dw[2] = {DM, DM}, sw[1] = {DM * 2};
    encode(fn, &mp.wqkv, wqkv, 2, dq, sq, box);
    encode(fn, &mp.wg, wg, 2, df, sf, box);
    encode(fn, &mp.wu, wu, 2, df, sf, box);
    encode(fn, &mp.wo, wo, 2, dw, sw, box);
  }
  {
    const cuuint32_t box[5] = {64, 2, 4, 4, 2};
    const cuuint64_t st[4] = {DM * 2, 8 * DM * 2, 2 * DM * 2, 32 * DM * 2};
    const cuuint64_t dd[5] = {DM, 2, 4, 4, DFF / 32};
    encode(fn, &mp.wd, wd, 5, dd, st, box);
  }
  fused_kernel<<<NCTA, 384, SMEM_BYTES>>>((const uint4*)x, (const uint4*)wg, (const uint4*)wu, gs, mp);
}
```

```cpp
#include <cuda_runtime.h>
#include <cuda_bf16.h>
#include <cuda.h>
#include <stdint.h>

#define PROMO CU_TENSOR_MAP_L2_PROMOTION_L2_128B
#define PF_D 6
#define LAG2 4
#define POLL_NS "200"
#define CS_KB 8
#define LN_KB 4

#define EVICT_FIRST 0x12F0000000000000ull
#define EVICT_NORMAL 0x1000000000000000ull
#define HINT_W EVICT_FIRST
#define HINT_H EVICT_FIRST
#define HINT_LAST EVICT_FIRST

namespace {

constexpr int SEQ = 2048, DM = 1024, DFF = 3584;
constexpr int NMAIN = 128, NCTA = 132;

constexpr uint32_t SM_BASE = 0x400;
constexpr uint32_t P1_BYTES = 49152, P2_BYTES = 32768;
constexpr uint32_t OFF_A = 131072;
__host__ __device__ constexpr uint32_t p2_a(int s) { return s == 0 ? OFF_A + 32768 : s == 1 ? OFF_A + 49152 : s == 2 ? 114688 : s == 3 ? 16384 : 49152; }
__host__ __device__ constexpr uint32_t p2_b(int s) { return s < 3 ? 65536 + s * 16384 : (s - 3) * 32768; }
constexpr uint32_t OFF_LAND = OFF_A;
constexpr uint32_t OFF_X = 196608;
constexpr uint32_t OFF_CS = OFF_X + 14336;
constexpr uint32_t OFF_BAR = 229376;
constexpr uint32_t B_F1 = OFF_BAR, B_E1 = B_F1 + 32, B_E2 = B_E1 + 32, B_DONE = B_E2 + 40, B_F2 = B_DONE + 8, B_DEP = B_F2 + 40, B_CS = B_DEP + 48,
                   B_XT = B_CS + 16, B_EP = B_XT + 8, B_EX = B_EP + 8, B_AUX = B_EX + 32, B_HALO = B_AUX + 8, OFF_EPOCH = B_HALO + 16;
constexpr uint32_t SMEM_BYTES = 232448;
constexpr uint32_t AT_V = 0, AT_K = 8192, AT_REM = 11264, AT_WG = 15360;

constexpr int FL_XN = 0, FL_H = 16, FL_P = 80, FL_HALO = 96, FL_N = FL_HALO + 256;
struct __align__(1024) Scratch {
  uint4 h[16 * 56 * 1024];
  uint4 o[16 * 16 * 1024];
  uint4 xn[SEQ * DM / 8];
  uint4 dpart[128 * 8 * 256];
  uint4 halo[2 * 128 * 2 * 128];
  ulonglong2 cspart[8 * 16 * 128];
  unsigned long long stats[SEQ];
  unsigned flags[FL_N * 32];
  unsigned epoch[NCTA * 2];
};
__device__ Scratch g_scratch;
#define TG(i) do {} while (0)
#define TSV(i, v) do {} while (0)
#define TS(i) do {} while (0)

struct Maps { CUtensorMap x, xn, out, wqkv, wg, wu, wd, wo; };

__device__ __forceinline__ void mbar_init(uint32_t bar, uint32_t cnt) { asm volatile("mbarrier.init.shared::cta.b64 [%0], %1;" ::"r"(bar), "r"(cnt)); }
__device__ __forceinline__ void mbar_expect_tx(uint32_t bar, uint32_t bytes) { asm volatile("mbarrier.arrive.expect_tx.shared::cta.b64 _, [%0], %1;" ::"r"(bar), "r"(bytes) : "memory"); }
__device__ __forceinline__ void mbar_arrive(uint32_t bar) { asm volatile("mbarrier.arrive.shared::cta.b64 _, [%0];" ::"r"(bar) : "memory"); }
__device__ __forceinline__ void mbar_arrive_cl(uint32_t bar) { asm volatile("mbarrier.arrive.shared::cluster.b64 _, [%0];" ::"r"(bar) : "memory"); }
__device__ __forceinline__ uint32_t mapa(uint32_t a, uint32_t cta) { uint32_t r; asm("mapa.shared::cluster.u32 %0, %1, %2;" : "=r"(r) : "r"(a), "r"(cta)); return r; }
__device__ __forceinline__ void mbar_wait(uint32_t bar, uint32_t parity) {
  asm volatile("{\n.reg .pred p;\n.reg .u32 n;\nmov.u32 n, 0;\nLAB_WAIT:\nmbarrier.try_wait.parity.shared::cta.b64 p, [%0], %1;\n@p bra LAB_DONE;\n"
               "add.u32 n, n, 1;\nsetp.gt.u32 p, n, 4000000;\n@p trap;\nbra LAB_WAIT;\nLAB_DONE:\n}" ::"r"(bar), "r"(parity) : "memory");
}
__device__ __forceinline__ void mbar_spin(uint32_t bar, uint32_t parity, uint32_t zero) {
  asm volatile("{\n.reg .pred p, z;\nsetp.ne.u32 z, %2, 0;\nLAB_WAIT:\nmbarrier.try_wait.parity.shared::cta.b64 p, [%0], %1;\n@p bra LAB_DONE;\n@z trap;\nbra LAB_WAIT;\nLAB_DONE:\n}" ::"r"(bar), "r"(parity), "r"(zero) : "memory");
}
__device__ __forceinline__ void flag_wait(const unsigned* f, unsigned target) {
  asm volatile("{\n.reg .pred p;\n.reg .u32 n, v;\nmov.u32 n, 0;\nLAB_WAIT:\nld.relaxed.gpu.global.u32 v, [%0];\nsub.u32 v, v, %1;\nsetp.ge.s32 p, v, 0;\n@p bra LAB_DONE;\n"
               "nanosleep.u32 " POLL_NS ";\nadd.u32 n, n, 1;\nsetp.gt.u32 p, n, 4000000;\n@p trap;\nbra LAB_WAIT;\nLAB_DONE:\nfence.acquire.gpu;\n}" ::"l"(f), "r"(target) : "memory");
}
__device__ __forceinline__ void flag_add(unsigned* f) { asm volatile("red.release.gpu.global.add.u32 [%0], 1;" ::"l"(f) : "memory"); }
__device__ __forceinline__ void fence_async() { asm volatile("fence.proxy.async.global;" ::: "memory"); }
__device__ __forceinline__ bool elect_one() { uint32_t p; asm volatile("{\n.reg .pred P;\nelect.sync _|P, 0xffffffff;\nselp.u32 %0, 1, 0, P;\n}" : "=r"(p)); return p; }
__device__ __forceinline__ void bar_sync(int id, int n) { asm volatile("bar.sync %0, %1;" ::"r"(id), "r"(n) : "memory"); }
__device__ __forceinline__ void bar_arrive(int id, int n) { asm volatile("bar.arrive %0, %1;" ::"r"(id), "r"(n) : "memory"); }

__device__ __forceinline__ void tma2d(uint32_t dst, const CUtensorMap* tm, uint32_t bar, int c0, int c1, uint64_t hint) {
  asm volatile("cp.async.bulk.tensor.2d.shared::cluster.global.mbarrier::complete_tx::bytes.L2::cache_hint [%0], [%1, {%3, %4}], [%2], %5;" ::"r"(dst), "l"(tm), "r"(bar), "r"(c0), "r"(c1), "l"(hint) : "memory");
}
__device__ __forceinline__ void tma2d_mc(uint32_t dst, const CUtensorMap* tm, uint32_t bar, int c0, int c1, uint64_t hint) {
  asm volatile("cp.async.bulk.tensor.2d.shared::cluster.global.mbarrier::complete_tx::bytes.multicast::cluster.L2::cache_hint [%0], [%1, {%3, %4}], [%2], %5, %6;" ::"r"(dst), "l"(tm), "r"(bar), "r"(c0), "r"(c1), "h"((uint16_t)3), "l"(hint) : "memory");
}
__device__ __forceinline__ void tma3d(uint32_t dst, const CUtensorMap* tm, uint32_t bar, int c0, int c1, int c2, uint64_t hint) {
  asm volatile("cp.async.bulk.tensor.3d.shared::cluster.global.mbarrier::complete_tx::bytes.L2::cache_hint [%0], [%1, {%3, %4, %5}], [%2], %6;" ::"r"(dst), "l"(tm), "r"(bar), "r"(c0), "r"(c1), "r"(c2), "l"(hint) : "memory");
}
__device__ __forceinline__ void tma5d(uint32_t dst, const CUtensorMap* tm, uint32_t bar, int c0, int c4, uint64_t hint) {
  asm volatile("cp.async.bulk.tensor.5d.shared::cluster.global.mbarrier::complete_tx::bytes.L2::cache_hint [%0], [%1, {%3, %5, %5, %5, %4}], [%2], %6;" ::"r"(dst), "l"(tm), "r"(bar), "r"(c0), "r"(c4), "r"(0), "l"(hint) : "memory");
}
__device__ __forceinline__ void tma5d_prefetch(const CUtensorMap* tm, int c0, int c4) {
  asm volatile("cp.async.bulk.prefetch.tensor.5d.L2.global [%0, {%1, %3, %3, %3, %2}];" ::"l"(tm), "r"(c0), "r"(c4), "r"(0) : "memory");
}
__device__ __forceinline__ void tma3d_store(const CUtensorMap* tm, uint32_t src, int c0, int c1, int c2) {
  asm volatile("cp.async.bulk.tensor.3d.global.shared::cta.bulk_group [%0, {%2, %3, %4}], [%1];" ::"l"(tm), "r"(src), "r"(c0), "r"(c1), "r"(c2) : "memory");
}
__device__ __forceinline__ void bulk_load(uint32_t dst, const void* src, uint32_t bytes, uint32_t bar, uint64_t hint) {
  asm volatile("cp.async.bulk.shared::cluster.global.mbarrier::complete_tx::bytes.L2::cache_hint [%0], [%1], %2, [%3], %4;" ::"r"(dst), "l"(src), "r"(bytes), "r"(bar), "l"(hint) : "memory");
}
__device__ __forceinline__ void bulk_load_mc(uint32_t dst, const void* src, uint32_t bytes, uint32_t bar, uint64_t hint) {
  asm volatile("cp.async.bulk.shared::cluster.global.mbarrier::complete_tx::bytes.multicast::cluster.L2::cache_hint [%0], [%1], %2, [%3], %4, %5;" ::"r"(dst), "l"(src), "r"(bytes), "r"(bar), "h"((uint16_t)3), "l"(hint) : "memory");
}
__device__ __forceinline__ uint4 lds128(uint32_t a) { uint4 v; asm volatile("ld.shared.v4.b32 {%0,%1,%2,%3}, [%4];" : "=r"(v.x), "=r"(v.y), "=r"(v.z), "=r"(v.w) : "r"(a) : "memory"); return v; }
__device__ __forceinline__ void sts128(uint32_t a, uint4 v) { asm volatile("st.shared.v4.b32 [%0], {%1,%2,%3,%4};" ::"r"(a), "r"(v.x), "r"(v.y), "r"(v.z), "r"(v.w) : "memory"); }
__device__ __forceinline__ void stg128(void* p, uint32_t a, uint32_t b, uint32_t c, uint32_t d) { asm volatile("st.global.v4.b32 [%0], {%1,%2,%3,%4};" ::"l"(p), "r"(a), "r"(b), "r"(c), "r"(d) : "memory"); }

__device__ __forceinline__ uint32_t pack2(float lo, float hi) { uint32_t r; asm("cvt.rn.bf16x2.f32 %0, %1, %2;" : "=r"(r) : "f"(hi), "f"(lo)); return r; }
__device__ __forceinline__ float lo_f(uint32_t v) { return __uint_as_float(v << 16); }
__device__ __forceinline__ float hi_f(uint32_t v) { return __uint_as_float(v & 0xffff0000u); }
__device__ __forceinline__ float bf16r(float v) { return lo_f(pack2(v, 0.f)); }
__device__ __forceinline__ uint32_t mul2(uint32_t a, uint32_t b) { uint32_t r; asm("mul.rn.bf16x2 %0, %1, %2;" : "=r"(r) : "r"(a), "r"(b)); return r; }
__device__ __forceinline__ uint32_t add2(uint32_t a, uint32_t b) { uint32_t r; asm("add.rn.bf16x2 %0, %1, %2;" : "=r"(r) : "r"(a), "r"(b)); return r; }
__device__ __forceinline__ uint32_t sub2(uint32_t a, uint32_t b) { uint32_t r; asm("sub.rn.bf16x2 %0, %1, %2;" : "=r"(r) : "r"(a), "r"(b)); return r; }
__device__ __forceinline__ uint32_t fma2(uint32_t a, uint32_t b, uint32_t c) { uint32_t r; asm("fma.rn.bf16x2 %0, %1, %2, %3;" : "=r"(r) : "r"(a), "r"(b), "r"(c)); return r; }
__device__ __forceinline__ uint32_t max2(uint32_t a, uint32_t b) { uint32_t r; asm("max.bf16x2 %0, %1, %2;" : "=r"(r) : "r"(a), "r"(b)); return r; }
__device__ __forceinline__ float ex2f(float x) { float y; asm("ex2.approx.ftz.f32 %0, %1;" : "=f"(y) : "f"(x)); return y; }
__device__ __forceinline__ float rcpf(float x) { float y; asm("rcp.approx.ftz.f32 %0, %1;" : "=f"(y) : "f"(x)); return y; }
constexpr float GELU_C1 = 0.7978845608028654f, GELU_C3 = 0.035677408136300125f;
__device__ __forceinline__ float gelu_k(float g, float c1, float c3, float k) {
  float t;
  asm("tanh.approx.f32 %0, %1;" : "=f"(t) : "f"(g * fmaf(g * g, c3, c1)));
  g *= k;
  return fmaf(g, t, g);
}
__device__ __forceinline__ float silu_half(float z) { float t; asm("tanh.approx.f32 %0, %1;" : "=f"(t) : "f"(z)); return fmaf(z, t, z); }

__device__ __forceinline__ void wg_fence() { asm volatile("wgmma.fence.sync.aligned;" ::: "memory"); }
__device__ __forceinline__ void wg_commit() { asm volatile("wgmma.commit_group.sync.aligned;" ::: "memory"); }
template <int N> __device__ __forceinline__ void wg_wait() { asm volatile("wgmma.wait_group.sync.aligned %0;" ::"n"(N) : "memory"); }
#define A8(o) "+f"(d[(o)]), "+f"(d[(o) + 1]), "+f"(d[(o) + 2]), "+f"(d[(o) + 3]), "+f"(d[(o) + 4]), "+f"(d[(o) + 5]), "+f"(d[(o) + 6]), "+f"(d[(o) + 7])
#define A64(o) A8(o), A8((o) + 8), A8((o) + 16), A8((o) + 24), A8((o) + 32), A8((o) + 40), A8((o) + 48), A8((o) + 56)
#define REGS0_63 "%0,%1,%2,%3,%4,%5,%6,%7,%8,%9,%10,%11,%12,%13,%14,%15,%16,%17,%18,%19,%20,%21,%22,%23,%24,%25,%26,%27,%28,%29,%30,%31," \
                 "%32,%33,%34,%35,%36,%37,%38,%39,%40,%41,%42,%43,%44,%45,%46,%47,%48,%49,%50,%51,%52,%53,%54,%55,%56,%57,%58,%59,%60,%61,%62,%63"
#define REGS64_127 "%64,%65,%66,%67,%68,%69,%70,%71,%72,%73,%74,%75,%76,%77,%78,%79,%80,%81,%82,%83,%84,%85,%86,%87,%88,%89,%90,%91,%92,%93,%94,%95," \
                   "%96,%97,%98,%99,%100,%101,%102,%103,%104,%105,%106,%107,%108,%109,%110,%111,%112,%113,%114,%115,%116,%117,%118,%119,%120,%121,%122,%123,%124,%125,%126,%127"
__device__ __forceinline__ void desc_add(uint64_t& x, int v) { asm volatile("{\n.reg .b32 lo, hi;\nmov.b64 {lo, hi}, %0;\nadd.s32 lo, lo, %1;\nmov.b64 %0, {lo, hi};\n}" : "+l"(x) : "r"(v)); }
template <int ACCUM> __device__ __forceinline__ void wgmma256(float (&d)[128], uint64_t& a, uint64_t& b, int da, int db) {
  asm volatile("{\n.reg .pred p;\nsetp.ne.b32 p, %130, 0;\n"
               "wgmma.mma_async.sync.aligned.m64n256k16.f32.bf16.bf16 {" REGS0_63 "," REGS64_127 "}, %128, %129, p, 1, 1, 0, 1;\n}"
               : A64(0), A64(64) : "l"(a), "l"(b), "n"(ACCUM));
  desc_add(a, da); desc_add(b, db);
}
__device__ __forceinline__ void wgmma256_rs(float (&d)[128], uint32_t a0, uint32_t a1, uint32_t z0, uint32_t z1, uint32_t b_lo) {
  asm volatile("{\n.reg .b64 db;\nmov.b64 db, {%132, 0x00000008};\n"
               "wgmma.mma_async.sync.aligned.m64n256k16.f32.bf16.bf16 {" REGS0_63 "," REGS64_127 "}, {%128,%129,%130,%131}, db, 1, 1, 1, 0;\n}"
               : A64(0), A64(64) : "r"(a0), "r"(a1), "r"(z0), "r"(z1), "r"(b_lo));
}
template <int ACCUM> __device__ __forceinline__ void wgmma128(float (&d)[64], uint64_t& a, uint64_t& b, int da, int db) {
  asm volatile("{\n.reg .pred p;\nsetp.ne.b32 p, %66, 0;\n"
               "wgmma.mma_async.sync.aligned.m64n128k16.f32.bf16.bf16 {" REGS0_63 "}, %64, %65, p, 1, 1, 0, 1;\n}"
               : A64(0) : "l"(a), "l"(b), "n"(ACCUM));
  desc_add(a, da); desc_add(b, db);
}
template <int ACCUM> __device__ __forceinline__ void hmma(float (&c)[4], uint32_t a0, uint32_t a1, uint32_t a2, uint32_t a3, uint32_t b0, uint32_t b1) {
  if (ACCUM)
    asm volatile("mma.sync.aligned.m16n8k16.row.col.f32.bf16.bf16.f32 {%0,%1,%2,%3}, {%4,%5,%6,%7}, {%8,%9}, {%0,%1,%2,%3};"
                 : "+f"(c[0]), "+f"(c[1]), "+f"(c[2]), "+f"(c[3]) : "r"(a0), "r"(a1), "r"(a2), "r"(a3), "r"(b0), "r"(b1));
  else
    asm volatile("mma.sync.aligned.m16n8k16.row.col.f32.bf16.bf16.f32 {%0,%1,%2,%3}, {%4,%5,%6,%7}, {%8,%9}, {%10,%10,%10,%10};"
                 : "=f"(c[0]), "=f"(c[1]), "=f"(c[2]), "=f"(c[3]) : "r"(a0), "r"(a1), "r"(a2), "r"(a3), "r"(b0), "r"(b1), "f"(0.f));
}
__device__ __forceinline__ uint32_t movm(uint32_t a) { uint32_t d; asm volatile("movmatrix.sync.aligned.m8n8.trans.b16 %0, %1;" : "=r"(d) : "r"(a)); return d; }
__device__ __forceinline__ int lane_here() { int v; asm volatile("mov.u32 %0, %%laneid;" : "=r"(v)); return v; }
template <int N> __device__ __forceinline__ void pin(uint32_t* r) {
#pragma unroll
  for (int i = 0; i < N; i++) asm volatile("" : "+r"(r[i]));
}
template <int N> __device__ __forceinline__ void pin(float* r) {
#pragma unroll
  for (int i = 0; i < N; i++) asm volatile("" : "+f"(r[i]));
}
__device__ __forceinline__ void sched_fence(uint32_t zero) {
  asm volatile("{\n.reg .pred p;\nsetp.eq.u32 p, %0, 0;\nLAB_F:\n@p bra.uni LAB_D;\nnanosleep.u32 0;\nbra.uni LAB_F;\nLAB_D:\n}" ::"r"(zero) : "memory");
}
__device__ __forceinline__ uint4 ldsm(uint32_t a) { uint4 v; asm volatile("ldmatrix.sync.aligned.m8n8.x4.shared.b16 {%0,%1,%2,%3}, [%4];" : "=r"(v.x), "=r"(v.y), "=r"(v.z), "=r"(v.w) : "r"(a) : "memory"); return v; }
__device__ __forceinline__ uint4 ldsm_t(uint32_t a) { uint4 v; asm volatile("ldmatrix.sync.aligned.m8n8.x4.trans.shared.b16 {%0,%1,%2,%3}, [%4];" : "=r"(v.x), "=r"(v.y), "=r"(v.z), "=r"(v.w) : "r"(a) : "memory"); return v; }

constexpr int BAR_LAG = 1, BAR_MMA = 2, BAR_EV = 3;

struct Cons {
  uint32_t sb;
  mutable uint64_t a, b;
  int k1, k2, k4, k4w, b1;
  uint32_t rel;
  bool do_rel;
  int wg;
  uint32_t zero;
};
#define REL_TS(n) TS(64 + (n))
constexpr uint32_t DB_LO = (SM_BASE >> 4) | ((8192 >> 4) << 16);

template <int ST, int ACCUM, bool WAIT = true> __device__ __forceinline__ void p1_issue(float (&acc)[128], const Cons& c, uint32_t parity) {
  if (WAIT) mbar_spin(c.sb + B_F1 + 8 * ST, parity, c.zero);
  wg_fence();
  wgmma256<ACCUM>(acc, c.a, c.b, c.k1, c.b1);
  wgmma256<1>(acc, c.a, c.b, c.k2, c.b1);
  wgmma256<1>(acc, c.a, c.b, c.k1, c.b1);
  wgmma256<1>(acc, c.a, c.b, ST == 3 ? c.k4w : c.k4, ST == 3 ? -6144 - 384 : 2048 - 384);
  wg_commit();
}
__device__ __forceinline__ void release(const Cons& c, uint32_t bar) { if (c.do_rel) mbar_arrive_cl(c.rel + bar); }
template <int KB, bool WAIT = true> __device__ __forceinline__ void p1_step(float (&acc)[128], const Cons& c) {
  if (KB == 15) { if (c.wg == 1) { wg_wait<0>(); release(c, B_E1 + 16); bar_sync(BAR_LAG, 256); } }
  p1_issue<KB & 3, KB != 0, WAIT>(acc, c, (KB >> 2) & 1);
  if (KB == 15) { if (c.wg == 0) bar_arrive(BAR_LAG, 256); }
  if (KB > 0) { wg_wait<1>(); if (KB != 15 || c.wg == 0) release(c, B_E1 + 8 * ((KB - 1) & 3)); }
  if (KB == 15) { wg_wait<0>(); release(c, B_E1 + 24); }
}
template <class F> __device__ __forceinline__ void p1_loop(float (&acc)[128], const Cons& c, int from, int to, F&& shadow) {
#pragma unroll 1
  for (int kb = from; kb < to; kb++) {
    const bool wrap = (kb & 3) == 3;
    mbar_spin(c.sb + B_F1 + 8 * (kb & 3), (kb >> 2) & 1, c.zero);
    wg_fence();
    wgmma256<1>(acc, c.a, c.b, c.k1, c.b1);
    wgmma256<1>(acc, c.a, c.b, c.k2, c.b1);
    wgmma256<1>(acc, c.a, c.b, c.k1, c.b1);
    wgmma256<1>(acc, c.a, c.b, wrap ? c.k4w : c.k4, wrap ? -6144 - 384 : 2048 - 384);
    wg_commit();
    wg_wait<1>();
    release(c, B_E1 + 8 * ((kb - 1) & 3));
    shadow(kb);
  }
}
template <int T> __device__ __forceinline__ void p2_step(float (&acc)[64], const Cons& c) {
  if (T == 16 - LAG2) { if (c.wg == 1) bar_sync(BAR_LAG, 256); }
  mbar_spin(c.sb + B_F2 + 8 * (T % 5), (T / 5) & 1, c.zero);
  wg_fence();
  wgmma128<T != 0>(acc, c.a, c.b, c.k1, c.b1);
  wgmma128<1>(acc, c.a, c.b, c.k2, c.b1);
  wgmma128<1>(acc, c.a, c.b, c.k1, c.b1);
  wgmma128<1>(acc, c.a, c.b, ((int)p2_a((T + 1) % 5) - (int)p2_a(T % 5)) / 16 - 514, ((int)p2_b((T + 1) % 5) - (int)p2_b(T % 5)) / 16 - 384);
  wg_commit();
  if (T == 15) { if (c.wg == 0) bar_arrive(BAR_LAG, 256); }
  if (T <= 11) { wg_wait<1>(); release(c, T ? B_E2 + 8 * ((T + 5 - 1) % 5) : B_E1 + 8); }
}

template <int P> __device__ __forceinline__ void geglu_piece(uint32_t (&pk)[64], uint8_t* dst, float (&rs)[2]) {
  constexpr int cg = P >> 1, r = P & 1;
  pin<1>(rs + r);
#pragma unroll
  for (int i = 0; i < 4; i++) pin<1>(pk + 2 * (4 * cg + i) + r);
  const float r2 = rs[r] * rs[r], c1 = GELU_C1 * rs[r], c3 = GELU_C3 * r2 * rs[r], k = 0.25f * r2;
  uint32_t v[4];
#pragma unroll
  for (int i = 0; i < 4; i++) {
    const uint32_t g = pk[2 * (4 * cg + i) + r];
    v[i] = mul2(pack2(gelu_k(lo_f(g), c1, c3, k), gelu_k(hi_f(g), c1, c3, k)), pk[32 + 2 * (4 * cg + i) + r]);
  }
  stg128(dst + cg * 8192 + r * 512, v[0], v[1], v[2], v[3]);
}
__device__ __forceinline__ void geglu_tile(float (&acc)[128], uint32_t (&pk)[64], const Cons& c, int to, uint8_t* dst, int ev, float (&rs)[2]) {
  const int lane = lane_here();
  dst += (lane ^ (lane >> 3)) << 4;
  p1_loop(acc, c, 1, to, [&](int kb) {
    if (kb <= 4) {
      if (kb <= 2) { if (kb == 1) geglu_piece<0>(pk, dst, rs); else geglu_piece<1>(pk, dst, rs); }
      else { if (kb == 3) geglu_piece<2>(pk, dst, rs); else geglu_piece<3>(pk, dst, rs); }
    } else if (kb <= 8) {
      if (kb <= 6) { if (kb == 5) geglu_piece<4>(pk, dst, rs); else geglu_piece<5>(pk, dst, rs); }
      else { if (kb == 7) geglu_piece<6>(pk, dst, rs); else { geglu_piece<7>(pk, dst, rs); bar_arrive(ev, 288); } }
    }
  });
}

__device__ __forceinline__ void attn_tile(float (&acc)[128], uint32_t (&pk)[64], const Cons& c, int round, int warp, int m, Scratch* gs, uint8_t* hdst, uint8_t* odst) {
  const int w = warp & 3;
  const uint32_t at = c.sb + OFF_X + c.wg * AT_WG;
  int lane = lane_here();
  hdst += (lane ^ (lane >> 3)) << 4;
  auto scatter = [&]() {
    const int lane = lane_here();
    const uint32_t swz = (lane ^ (lane >> 3)) << 4;
#pragma unroll
    for (int i = 0; i < 4; i++) {
      const int h = i & 1, r = i >> 1;
      sts128(at + AT_V + (2 * w + r) * 1024 + h * 512 + swz, make_uint4(pk[32 + 8 * h + r], pk[34 + 8 * h + r], pk[36 + 8 * h + r], pk[38 + 8 * h + r]));
    }
    if (w < 3) {
#pragma unroll
      for (int i = 0; i < 8; i++) asm volatile("st.shared.b32 [%0], %1;" ::"r"(at + AT_K + w * 1024 + i * 128 + lane * 4), "r"(pk[17 + 2 * i]) : "memory");
    } else {
      uint8_t* g = (uint8_t*)gs->halo + ((round * 128 + blockIdx.x) * 2 + c.wg) * 2048;
#pragma unroll
      for (int i = 0; i < 8; i++) asm volatile("st.global.b32 [%0], %1;" ::"l"(g + i * 128 + lane * 4), "r"(pk[17 + 2 * i]) : "memory");
#pragma unroll
      for (int h = 0; h < 2; h++) stg128(g + 1024 + h * 512 + swz, pk[33 + 8 * h], pk[35 + 8 * h], pk[37 + 8 * h], pk[39 + 8 * h]);
      bar_arrive(BAR_EV + 2 + round, 96);
    }
    __syncwarp();
    if (lane == 0) mbar_arrive(c.sb + B_HALO + 8 * round);
    if (round) {
#pragma unroll
      for (int p = 0; p < 4; p++) {
        const int o = 32 + 8 * (p >> 1) + (p & 1);
        asm volatile("ld.global.cg.v4.b32 {%0,%1,%2,%3}, [%4];" : "=r"(pk[o]), "=r"(pk[o + 2]), "=r"(pk[o + 4]), "=r"(pk[o + 6]) : "l"(hdst + (p >> 1) * 8192 + (p & 1) * 512) : "memory");
      }
    }
  };
  auto gu_piece = [&](int p) {
    uint32_t v[4];
#pragma unroll
    for (int i = 0; i < 4; i++) {
      const int o = 8 * (p >> 1) + 2 * i + (p & 1);
      pin<1>(pk + 48 + o);
      const uint32_t g = pk[48 + o];
      v[i] = mul2(round ? pk[32 + o] : 0x3e803e80u, round ? g : pack2(gelu_k(lo_f(g), GELU_C1, GELU_C3, 1.0f), gelu_k(hi_f(g), GELU_C1, GELU_C3, 1.0f)));
    }
    stg128(hdst + (p >> 1) * 8192 + (p & 1) * 512, v[0], v[1], v[2], v[3]);
  };
  p1_step<1>(acc, c);
  scatter();
  p1_loop(acc, c, 2, 9, [&](int kb) {
    if (kb <= 4) { if (kb == 3) gu_piece(0); else if (kb == 4) gu_piece(1); }
    else if (kb == 5) gu_piece(2); else if (kb == 6) gu_piece(3);
  });
  const bool first = m == 0 && w == 0;
  uint32_t kl[16];
  mbar_spin(c.sb + B_HALO + 8 * round, 0, c.zero);
  lane = lane_here();
  {
    const uint32_t ka = at + lane * 4 + (w ? AT_K + (w - 1) * 1024 : (first ? AT_K : AT_REM + round * 2048));
#pragma unroll
    for (int i = 0; i < 8; i++) {
      asm volatile("ld.shared.b32 %0, [%1];" : "=r"(kl[2 * i]) : "r"(ka + i * 128) : "memory");
      kl[2 * i + 1] = pk[16 + 2 * i] | c.zero;
    }
  }
  float st[4][4];
  pin<16>(kl);
  bar_sync(BAR_MMA, 256);
  mbar_spin(c.sb + B_F1 + 8 * 1, 0, c.zero);
#pragma unroll
  for (int ks = 0; ks < 2; ks++) {
#pragma unroll
    for (int h = 0; h < 2; h++) {
      const int o = 8 * h + 4 * ks;
      if (ks == 0) { hmma<0>(st[2 * h], kl[o], kl[o + 1], kl[o + 2], kl[o + 3], pk[o], pk[o + 2]); hmma<0>(st[2 * h + 1], pk[16 + o], pk[17 + o], pk[18 + o], pk[19 + o], pk[o + 1], pk[o + 3]); }
      else { hmma<1>(st[2 * h], kl[o], kl[o + 1], kl[o + 2], kl[o + 3], pk[o], pk[o + 2]); hmma<1>(st[2 * h + 1], pk[16 + o], pk[17 + o], pk[18 + o], pk[19 + o], pk[o + 1], pk[o + 3]); }
    }
  }
  sched_fence(c.zero);
  bar_sync(BAR_MMA, 256);
  p1_step<9, false>(acc, c);
  sched_fence(c.zero);
  pin<16>(&st[0][0]);
  lane = lane_here();
  const int rho = lane >> 2, q = lane & 3;
  const bool le0 = 2 * q <= rho, le1 = 2 * q + 1 <= rho;
  uint32_t la[2], lb[2], mx[2];
#pragma unroll
  for (int h = 0; h < 2; h++) {
    uint32_t l[2];
#pragma unroll
    for (int r = 0; r < 2; r++) {
      const float (&t)[4] = st[2 * h + r];
      l[r] = movm(pack2(rho <= 2 * q ? t[2] : t[0], rho <= 2 * q + 1 ? t[3] : t[1]));
      l[r] = fma2(l[r], 0x3e353e35u, mul2(l[r], 0x379e379eu));
    }
    la[h] = __byte_perm(l[0], l[1], 0x5410); lb[h] = __byte_perm(l[0], l[1], 0x7632);
    if (first && !le0) la[h] = (la[h] & 0xffff0000u) | 0xce6eu;
    if (first && !le1) lb[h] = (lb[h] & 0xffff0000u) | 0xce6eu;
    mx[h] = max2(la[h], lb[h]);
  }
#pragma unroll
  for (int o = 1; o <= 2; o++) { mx[0] = max2(mx[0], __shfl_xor_sync(~0u, mx[0], o)); mx[1] = max2(mx[1], __shfl_xor_sync(~0u, mx[1], o)); }
  const float L2E = 1.4426950408889634f;
  float pr[2][4], z[4];
#pragma unroll
  for (int h = 0; h < 2; h++) {
    pr[h][0] = ex2f((lo_f(la[h]) - lo_f(mx[h])) * L2E); pr[h][1] = ex2f((lo_f(lb[h]) - lo_f(mx[h])) * L2E);
    pr[h][2] = ex2f((hi_f(la[h]) - hi_f(mx[h])) * L2E); pr[h][3] = ex2f((hi_f(lb[h]) - hi_f(mx[h])) * L2E);
    z[2 * h] = pr[h][0] + pr[h][1]; z[2 * h + 1] = pr[h][2] + pr[h][3];
  }
  p1_step<10>(acc, c);
#pragma unroll
  for (int o = 1; o <= 2; o++) {
#pragma unroll
    for (int i = 0; i < 4; i++) z[i] += __shfl_xor_sync(~0u, z[i], o);
  }
  const uint32_t LE = (le0 ? 0xffffu : 0u) | (le1 ? 0xffff0000u : 0u);
  uint32_t P[4][2];
  uint4 vt[4][2];
  {
    const uint32_t row = (lane & 7) * 64 + ((((lane >> 3) & 1) ^ ((lane & 7) >> 1)) << 4);
    const uint32_t v1 = at + AT_V + (2 * w + (lane >> 4)) * 1024 + row;
    const uint32_t v0 = (w || lane >= 16) ? v1 - 1024 : (first ? v1 : at + AT_REM + round * 2048 + 1024 + row);
#pragma unroll
    for (int i = 0; i < 4; i++) {
      const float rz = rcpf(z[i]);
      const uint32_t p = pack2(pr[i >> 1][2 * (i & 1)] * rz, pr[i >> 1][2 * (i & 1) + 1] * rz);
      P[i][0] = p & ~LE; P[i][1] = p & LE;
      const uint32_t a = ((i & 1) ? v1 : v0) + (i >> 1) * 512;
      vt[i][0] = ldsm_t(a); vt[i][1] = ldsm_t(a ^ 32);
    }
  }
  float ot[4][2][4];
  pin<8>(&P[0][0]);
  bar_sync(BAR_MMA, 256);
  mbar_spin(c.sb + B_F1 + 8 * 3, 0, c.zero);
#pragma unroll
  for (int i = 0; i < 8; i++) { const uint4& v = vt[i >> 1][i & 1]; hmma<0>(ot[i >> 1][i & 1], v.x, v.y, v.z, v.w, P[i >> 1][0], P[i >> 1][1]); }
  sched_fence(c.zero);
  bar_sync(BAR_MMA, 256);
  p1_step<11, false>(acc, c);
  sched_fence(c.zero);
  pin<32>(&ot[0][0][0]);
  lane = lane_here();
  odst += (lane ^ (lane >> 3)) << 4;
  auto o_piece = [&](int i) {
    stg128(odst + (i >> 1) * 8192 + (i & 1) * 512, movm(pack2(ot[i][0][0], ot[i][0][1])), movm(pack2(ot[i][0][2], ot[i][0][3])), movm(pack2(ot[i][1][0], ot[i][1][1])), movm(pack2(ot[i][1][2], ot[i][1][3])));
  };
  o_piece(0); o_piece(1);
  p1_step<12>(acc, c);
  o_piece(2); o_piece(3);
  if (round) bar_arrive(BAR_EV + 4, 288);
  p1_step<13>(acc, c);
}

__device__ __forceinline__ void ln_moments(const uint32_t* raw, float& c0, float& s, float& v) {
  c0 = lo_f(__shfl_sync(~0u, raw[0], 0));
  float ss[4] = {0.f, 0.f, 0.f, 0.f}, vv[4] = {0.f, 0.f, 0.f, 0.f};
#pragma unroll
  for (int i = 0; i < 16; i++) {
    const float a = lo_f(raw[i]) - c0, b = hi_f(raw[i]) - c0;
    ss[(2 * i) & 3] += a; ss[(2 * i + 1) & 3] += b;
    vv[(2 * i) & 3] = fmaf(a, a, vv[(2 * i) & 3]); vv[(2 * i + 1) & 3] = fmaf(b, b, vv[(2 * i + 1) & 3]);
  }
  s = (ss[0] + ss[1]) + (ss[2] + ss[3]); v = (vv[0] + vv[1]) + (vv[2] + vv[3]);
}
__device__ __forceinline__ void ln_reduce(float& s, float& v) {
#pragma unroll
  for (int o = 16; o; o >>= 1) { s += __shfl_xor_sync(~0u, s, o); v += __shfl_xor_sync(~0u, v, o); }
}
__device__ __forceinline__ uint32_t ln_finish(float c0, float s, float v) {
  s *= 1.0f / DM;
  float sd;
  asm("sqrt.approx.ftz.f32 %0, %1;" : "=f"(sd) : "f"(bf16r(bf16r(fmaxf(fmaf(v, 1.0f / DM, -s * s), 0.f)) + 1e-5f)));
  return pack2(c0 + s, sd);
}
__device__ __forceinline__ void ln_store(const uint32_t* raw, uint32_t st, uint4* dst) {
  const uint32_t m2 = __byte_perm(st, st, 0x1010);
  const float rinv = rcpf(hi_f(st));
  const uint32_t rh = pack2(rinv, rinv), rl = pack2(rinv - hi_f(rh), rinv - hi_f(rh));
#pragma unroll
  for (int c = 0; c < 4; c++) {
    uint32_t v[4];
#pragma unroll
    for (int i = 0; i < 4; i++) { const uint32_t t = sub2(raw[4 * c + i], m2); v[i] = fma2(t, rh, mul2(t, rl)); }
    stg128(dst + 32 * c, v[0], v[1], v[2], v[3]);
  }
}
__device__ __forceinline__ void col_sums(uint32_t tile, ulonglong2* part, uint32_t tag) {
  const int lane = threadIdx.x & 31;
  float cs[8] = {0, 0, 0, 0, 0, 0, 0, 0};
  uint32_t base = tile + ((lane >> 3) & 1) * 8192 + (lane >> 4) * 4096 + ((lane & 7) << 4);
#pragma unroll 1
  for (int k0 = 0; k0 < 8; k0++, base = (base ^ ((k0 ^ (k0 - 1)) << 4)) + 128) {
    uint4 v[4];
#pragma unroll
    for (int k = 0; k < 4; k++) v[k] = lds128(base + k * 1024);
#pragma unroll
    for (int k = 0; k < 4; k++) {
      cs[0] += lo_f(v[k].x); cs[1] += hi_f(v[k].x); cs[2] += lo_f(v[k].y); cs[3] += hi_f(v[k].y);
      cs[4] += lo_f(v[k].z); cs[5] += hi_f(v[k].z); cs[6] += lo_f(v[k].w); cs[7] += hi_f(v[k].w);
    }
  }
  const bool up = lane >= 16;
#pragma unroll
  for (int i = 0; i < 2; i++) {
    const float a = (up ? cs[4 + 2 * i] : cs[2 * i]) + __shfl_xor_sync(~0u, up ? cs[2 * i] : cs[4 + 2 * i], 16);
    const float b = (up ? cs[5 + 2 * i] : cs[1 + 2 * i]) + __shfl_xor_sync(~0u, up ? cs[1 + 2 * i] : cs[5 + 2 * i], 16);
    asm volatile("{\n.reg .b64 a, b;\nmov.b64 a, {%1, %3};\nmov.b64 b, {%2, %3};\nst.relaxed.gpu.global.v2.b64 [%0], {a, b};\n}"
                 ::"l"(part + 32 * (i + (up ? 2 : 0)) + (lane & 15)), "r"(__float_as_uint(a)), "r"(__float_as_uint(b)), "r"(tag) : "memory");
  }
  asm volatile("fence.proxy.async.shared::cta;" ::: "memory");
}

__global__ void __cluster_dims__(2, 1, 1) __launch_bounds__(384, 1)
fused_kernel(const uint4* __restrict__ x, const uint4* __restrict__ wgate, const uint4* __restrict__ wup, Scratch* gs, const __grid_constant__ Maps mp) {
  extern __shared__ __align__(1024) uint8_t smem_raw[];
  const uint32_t sb = (uint32_t)__cvta_generic_to_shared(smem_raw);
  if (threadIdx.x == 352) TS(63);
  if (threadIdx.x < 256 && blockIdx.x < NMAIN) {
    const uint32_t r = threadIdx.x >> 3, ch = threadIdx.x & 7;
    const uint32_t d = sb + r * 128 + ((ch ^ (r & 7)) << 4);
    const uint8_t* xa = (const uint8_t*)x + ((blockIdx.x & 15) * 262144 + r * 4096 + ch * 16);
    const uint32_t wo = r * (DFF * 2) + (blockIdx.x >> 4) * 256 + ch * 16;
    const uint8_t *wa = (const uint8_t*)wgate + wo, *wb = (const uint8_t*)wup + wo;
#pragma unroll
    for (int i = 0; i < 12; i++) {
      const int h = i >= 8;
      const uint8_t* src = (i >> 2) == 1 ? xa + (i & 1) * 131072 + ((i >> 1) & 1) * 2048 : ((i & 2) ? wb : wa) + h * 32 * (DFF * 2) + (i & 1) * 128;
      asm volatile("cp.async.cg.shared.global [%0], [%1], 16;" ::"r"(d + ((i >> 2) == 1 ? OFF_A + (i & 3) * 4096 : (i & 3) * 8192 + h * 4096)), "l"(src) : "memory");
    }
    if (threadIdx.x == 0) TS(23);
  }
  const int warp = __shfl_sync(~0u, threadIdx.x >> 5, 0), lane = threadIdx.x & 31;
  const int m = blockIdx.x & 15, j = blockIdx.x >> 4, rank = blockIdx.x & 1;
  const int m2 = blockIdx.x >> 3, j2 = blockIdx.x & 7;
  const bool helper = blockIdx.x >= NMAIN;
  if (warp >= 8) {
    asm volatile("setmaxnreg.dec.sync.aligned.u32 40;");
    if (warp == 8) {
      if (elect_one()) {
        asm volatile("prefetch.tensormap [%0];\nprefetch.tensormap [%1];\nprefetch.tensormap [%2];" ::"l"(&mp.x), "l"(&mp.wg), "l"(&mp.wu) : "memory");
        for (int s = 0; s < 4; s++) mbar_init(sb + B_F1 + 8 * s, 1);
        if (!helper) mbar_arrive(sb + B_F1);
        asm volatile("fence.mbarrier_init.release.cluster;" ::: "memory");
      }
      __syncwarp();
    } else if (warp == 9) {
      if (elect_one()) {
        if ((sb & 0xffffff) != SM_BASE) asm volatile("trap;");
        for (uint32_t b = B_E1; b < B_F2; b += 8) mbar_init(sb + b, 4);
        for (uint32_t b = B_F2; b < B_AUX; b += 8) mbar_init(sb + b, 1);
        for (uint32_t b = B_EX; b < B_AUX; b += 8) mbar_expect_tx(sb + b, 8192);
        mbar_init(sb + B_AUX, 8); mbar_init(sb + B_HALO, 9); mbar_init(sb + B_HALO + 8, 9);
        asm volatile("fence.mbarrier_init.release.cluster;" ::: "memory");
      }
      __syncwarp();
    }
    asm volatile("barrier.cluster.arrive.relaxed.aligned;" ::: "memory");
    if (warp == 8 && !helper) {
      if (elect_one()) {
        TS(0); TG(51);
#pragma unroll 1
        for (int kb = 1; kb < 4; kb++) {
          const uint32_t sa = sb + OFF_A + kb * 16384, sw = sb + kb * 32768, fb = sb + B_F1 + 8 * kb;
          mbar_expect_tx(fb, P1_BYTES);
          tma3d(sa, &mp.x, fb, kb * 64, m * 64, 0, EVICT_NORMAL);
          tma2d(sw, &mp.wg, fb, j * 128, kb * 64, EVICT_NORMAL); tma2d(sw + 16384, &mp.wu, fb, j * 128, kb * 64, EVICT_NORMAL);
          tma2d(sw + 8192, &mp.wg, fb, j * 128 + 64, kb * 64, EVICT_NORMAL); tma2d(sw + 24576, &mp.wu, fb, j * 128 + 64, kb * 64, EVICT_NORMAL);
        }
        TS(7);
      }
      __syncwarp();
    }
    asm volatile("barrier.cluster.wait.aligned;" ::: "memory");
    if (helper) {
      if (warp == 8) {
        unsigned e = 0;
        if (elect_one()) {
#pragma unroll 1
          for (int i = 0; i < 16; i++) {
            const uint32_t fb = sb + B_F1 + 8 * (i >> 2);
            if (!(i & 3)) mbar_expect_tx(fb, P1_BYTES);
            tma5d(sb + i * 8192, &mp.wd, fb, (blockIdx.x - NMAIN) * 256 + (i & 3) * 64, (i >> 2) * 2, HINT_W);
          }
        }
        if (lane == 0) { unsigned* ep = &gs->epoch[blockIdx.x * 2]; e = *ep + 1; *ep = e; }
        e = __shfl_sync(~0u, e, 0);
        if (lane < 16) flag_wait(&gs->flags[(FL_H + lane * 4) * 32], e * 8u);
        __syncwarp();
        if (elect_one()) {
          fence_async();
          TS(0);
#pragma unroll 1
          for (int i = 0; i < 64; i++) {
            const uint32_t fb = sb + B_F1 + 8 * (i & 3);
            if (i >= 4) { mbar_wait(sb + B_E1 + 8 * (i & 3), ~(i >> 2) & 1); mbar_expect_tx(fb, 16384); }
            bulk_load(sb + OFF_A + (i & 3) * 16384, gs->h + ((i >> 2) * 56 + (i & 3)) * 1024, 16384, fb, EVICT_NORMAL);
          }
        }
      } else if (warp == 9) {
#pragma unroll 1
        for (int t = 0; t < 16; t++) {
          bar_sync(BAR_EV + (t & 1), 288);
          if (lane == 0) { flag_add(&gs->flags[(FL_P + t) * 32]); TS(64 + t); }
          __syncwarp();
        }
      }
    } else if (warp == 8) {
      if (elect_one()) {
        uint32_t par = 0;

        auto x_load = [&]() {
          mbar_expect_tx(sb + B_XT, 32768);
          tma3d(sb + OFF_X, &mp.x, sb + B_XT, j2 * 128, m2 * 64, 0, HINT_LAST); tma3d(sb + OFF_X + 16384, &mp.x, sb + B_XT, j2 * 128 + 64, m2 * 64, 0, HINT_LAST);
        };
        auto d_prefetch = [&](int i) {
          if ((m2 >> 2) == (i & 3)) tma5d_prefetch(&mp.wd, (j2 >> 1) * 256 + (m2 & 3) * 64, (2 * i + 4 + rank) * 2);
        };
        auto w_tile = [&](int R, const CUtensorMap*& mb0, const CUtensorMap*& mb1, int& n0, int& n1) {
          if (R == 1 || R == 2) {
            mb0 = &mp.wqkv; n0 = 64 * (j + 8 * (R - 1)) + rank * 2048;
            mb1 = rank ? (R == 1 ? &mp.wg : &mp.wu) : &mp.wqkv; n1 = rank ? 1024 + 64 * j : n0 + 1024;
          } else {
            mb0 = mb1 = rank ? &mp.wu : &mp.wg;
            n0 = 128 * j + (R ? 1024 * R - 1536 : 0); n1 = n0 + 64;
          }
        };
        for (int R = 0; R < 5; R++) {
          const CUtensorMap *mb0, *mb1;
          int n0, n1;
          w_tile(R, mb0, mb1, n0, n1);
#pragma unroll 1
          for (int kb = R ? 0 : 4; kb < 16; kb++) {
            if (R == 0 && kb == 14) { asm volatile("prefetch.tensormap [%0];\nprefetch.tensormap [%1];" ::"l"(&mp.xn), "l"(&mp.wqkv) : "memory"); }
            if (R == 4 && kb == 2) { asm volatile("prefetch.tensormap [%0];\nprefetch.tensormap [%1];\nprefetch.tensormap [%2];" ::"l"(&mp.wd), "l"(&mp.wo), "l"(&mp.out) : "memory"); }
            if (R == 0 && kb == CS_KB) {
#pragma unroll 1
              for (int h = 0; h < 2; h++) {
                const uint32_t cb = sb + B_CS + 8 * h, d = sb + OFF_X + 16384 * h;
                mbar_expect_tx(cb, 16384);
                tma2d(d, h ? &mp.wu : &mp.wg, cb, n0, m * 64, EVICT_NORMAL); tma2d(d + 8192, h ? &mp.wu : &mp.wg, cb, n1, m * 64, EVICT_NORMAL);
              }
            }
            const int st = kb & 3;
            const uint32_t sa = sb + OFF_A + st * 16384, sw = sb + st * 32768, fb = sb + B_F1 + 8 * st;
            mbar_wait(sb + B_E1 + 8 * st, par);
            if (R * 16 + kb >= 4) REL_TS(R * 16 + kb - 4);
            mbar_expect_tx(fb, P1_BYTES);
            tma2d_mc(sw + rank * 16384, mb0, fb, n0, kb * 64, HINT_W);
            tma2d_mc(sw + 8192 + rank * 16384, mb1, fb, n1, kb * 64, HINT_W);
            if (R == 0) {
              tma3d(sa, &mp.x, fb, kb * 64, m * 64, 0, EVICT_NORMAL);
            } else {
              if (R == 1 && kb == 0) { mbar_wait(sb + B_DEP, 0); TS(1); }
              tma2d(sa, &mp.xn, fb, kb * 64, m * 128, R == 4 ? HINT_LAST : EVICT_NORMAL);
            }
            if (R == 4 && kb == 4 + j2) x_load();
            if (R == 4 && kb >= 16 - PF_D) d_prefetch(kb + PF_D - 16);
            if (st == 3) par ^= 1;
          }
        }
#pragma unroll 1
        for (int i = 0; i < 26; i++) {
          const int st = i & 3, kb = 2 * i + 4 + rank;
          const uint32_t sa = sb + OFF_A + st * 16384, sw = sb + st * 32768, fb = sb + B_F1 + 8 * st;
          mbar_wait(sb + B_E1 + 8 * st, par);
          REL_TS(76 + i);
          mbar_expect_tx(fb, P1_BYTES);
          tma5d(sw, &mp.wd, fb, j2 * 128, kb * 2, HINT_W); tma5d(sw + 8192, &mp.wd, fb, j2 * 128 + 64, kb * 2, HINT_W);
          tma5d(sw + 16384, &mp.wd, fb, (j2 ^ 1) * 128, kb * 2, HINT_W); tma5d(sw + 24576, &mp.wd, fb, (j2 ^ 1) * 128 + 64, kb * 2, HINT_W);
          if (i == 0 || i == 6 || i == 10 || i == 18) { mbar_wait(sb + B_DEP + 8 * (1 + ((i + 6) >> 3)), 0); }
          bulk_load(sa, gs->h + (m2 * 56 + kb) * 1024, 16384, fb, HINT_H);
          if (i + PF_D < 26) d_prefetch(i + PF_D);
          if (st == 3) par ^= 1;
        }
        int st = 0; uint32_t par2 = 1;
#pragma unroll 1
        for (int t = 0; t < 16; t++) {
          const uint32_t sa = sb + p2_a(st), sw = sb + p2_b(st), fb = sb + B_F2 + 8 * st;
          if (t < 5) mbar_wait(sb + B_E1 + 8 * (((2 * t + 1) / 3 + 2) & 3), t < 3); else mbar_wait(sb + B_E2 + 8 * st, par2);
          REL_TS(102 + t);
          mbar_expect_tx(fb, P2_BYTES);
          bulk_load_mc(sa + rank * 8192, gs->o + (m2 * 16 + t) * 1024 + rank * 512, 8192, fb, HINT_H);
          tma2d(sw, &mp.wo, fb, j2 * 128, t * 64, HINT_W); tma2d(sw + 8192, &mp.wo, fb, j2 * 128 + 64, t * 64, HINT_W);
          if (++st == 5) { st = 0; par2 ^= 1; }
        }
      }
    } else if (warp == 9) {
#pragma unroll 1
      for (int e = 0; e < 7; e++) {
        const bool halo = e == 2 || e == 3;
        bar_sync(BAR_EV + e, halo ? 96 : 288);
        if (lane == 0) {
          const int f = e == 0 ? FL_XN + m : (halo ? FL_HALO + (e - 2) * 128 + blockIdx.x : FL_H + m * 4 + (e == 1 ? 0 : e - 3));
          TS(10 + 2 * e); TG(52 + e);
          flag_add(&gs->flags[f * 32]);
          if (e < 6) TS(11 + 2 * e);
        }
        __syncwarp();
      }
      mbar_wait(sb + B_DONE, 0);
    } else {
      unsigned e = 0;
      if (lane == 0) {
        unsigned* ep = &gs->epoch[blockIdx.x * 2 + warp - 10];
        e = *ep + 1; *ep = e;
        if (warp == 10) { asm volatile("st.shared.b32 [%0], %1;" ::"r"(sb + OFF_EPOCH), "r"(e) : "memory"); mbar_arrive(sb + B_EP); }
      }
      e = __shfl_sync(~0u, e, 0);
      mbar_wait(sb + B_CS + 8 * (warp - 10), 0);
      if (lane == 0 && warp == 11) TS(6);
      col_sums(sb + OFF_X + (warp - 10) * 16384, gs->cspart + (j * 16 + m) * 128 + (warp - 10) * 16, e);
      if (lane == 0 && warp == 11) TS(9);
      if (warp == 10) {
        if (lane == 0) {
#pragma unroll 1
          for (int g = 0; g < 6; g++) {
            flag_wait(&gs->flags[(g == 5 ? FL_P + m2 : (g ? FL_H + m2 * 4 + g - 1 : FL_XN + m)) * 32], e * (g == 5 ? 4u : 8u));
            fence_async();
            mbar_arrive(sb + B_DEP + 8 * g);
            if (g == 0) TS(8);
          }
        }
      } else
      if (elect_one()) {
#pragma unroll 1
        for (int r = 0; r < 2; r++) {
          const uint32_t hb = sb + B_HALO + 8 * r;
          if (r) mbar_wait(sb + B_HALO, 0);
          if (m) {
            flag_wait(&gs->flags[(FL_HALO + r * 128 + blockIdx.x - 1) * 32], e);
            fence_async();
            mbar_expect_tx(hb, 4096);
            for (int g = 0; g < 2; g++) bulk_load(sb + OFF_X + g * AT_WG + AT_REM + r * 2048, gs->halo + ((r * 128 + blockIdx.x - 1) * 2 + g) * 128, 2048, hb, EVICT_FIRST);
          } else {
            mbar_arrive(hb);
          }
          TS(34 + r);
        }
      }
    }
  } else {
    asm volatile("barrier.cluster.arrive.relaxed.aligned;" ::: "memory");
    asm volatile("setmaxnreg.inc.sync.aligned.u32 232;");
    const int wg = warp >> 2, w = warp & 3;
    Cons c;
    c.sb = sb; c.wg = wg; c.zero = warp >> 8;
    c.a = 0x4000004000010000ull + ((SM_BASE + OFF_A + wg * 8192) >> 4); c.k1 = 2 + c.zero; c.k2 = 2; c.k4 = 1024 - 6; c.k4w = -3072 - 6; c.b1 = 128 + c.zero;
    c.b = 0x4000004000000000ull + DB_LO + c.zero;
    c.rel = mapa(sb, threadIdx.x & 1);
    c.do_rel = (threadIdx.x & 127) < 2;
    constexpr bool t0 = false;
    float acc[128];
    uint32_t pk[64];
    float rs[2];
    const int q = lane & 3;

    if (helper) {
      asm volatile("barrier.cluster.wait.aligned;" ::: "memory");
      c.a = 0x8000002000010000ull + ((SM_BASE + OFF_A + wg * 4096) >> 4); c.k2 = 510; c.k4 = 1024 - 514; c.k4w = -3072 - 514;
      c.rel = sb;
      uint4* dst = gs->dpart + (blockIdx.x - NMAIN) * 4096 + threadIdx.x;
      auto put = [&](int p) {
#pragma unroll
        for (int i = 4 * p; i < 4 * p + 4; i++) stg128(dst + i * 256, pk[4 * i], pk[4 * i + 1], pk[4 * i + 2], pk[4 * i + 3]);
      };
#pragma unroll 1
      for (int t = 0; t < 16; t++) {
        p1_issue<0, 0>(acc, c, t & 1);
        if (t) put(0);
        p1_issue<1, 1>(acc, c, t & 1); wg_wait<1>(); release(c, B_E1);
        if (t) put(1);
        p1_issue<2, 1>(acc, c, t & 1); wg_wait<1>(); release(c, B_E1 + 8);
        if (t) put(2);
        if (wg == 1) { wg_wait<0>(); release(c, B_E1 + 16); bar_sync(BAR_LAG, 256); }
        p1_issue<3, 1>(acc, c, t & 1);
        if (wg == 0) bar_arrive(BAR_LAG, 256);
        if (t) { put(3); bar_arrive(BAR_EV + (~t & 1), 288); dst += 8 * 2048; }
        wg_wait<1>(); if (wg == 0) release(c, B_E1 + 16);
        wg_wait<0>(); release(c, B_E1 + 24);
#pragma unroll
        for (int i = 0; i < 64; i++) pk[i] = pack2(acc[2 * i], acc[2 * i + 1]);
      }
      put(0); put(1); put(2); put(3);
      bar_arrive(BAR_EV + 1, 288);
      return;
    }
    {
      const int prow = 16 * j + 2 * warp;
      const uint4* xr = x + (size_t)(128 * m + 2 * (prow & 63) + (prow >> 6)) * 128 + lane;
      uint4* xo = gs->xn + (size_t)(128 * m + prow) * 128 + lane;
      float c0[2], mo[4];
      uint32_t st[2];
      uint32_t e;
      asm volatile("" : "+l"(xr), "+l"(xo));
      asm volatile("cp.async.wait_all;\nfence.proxy.async.shared::cta;" ::: "memory");
      bar_sync(BAR_MMA, 256);
      if (threadIdx.x == 0) TS(39);
      p1_step<0, false>(acc, c);
      asm volatile("barrier.cluster.wait.aligned;" ::: "memory");
      unsigned long long part[18];
      auto gather = [&]() {
        const int lane = lane_here();
        const unsigned long long* cp = (const unsigned long long*)gs->cspart + j * 4096 + warp * 32 + lane;
        const unsigned long long* sp = gs->stats + 128 * m + warp * 16 + (lane >> 2);
#pragma unroll
        for (int i = 0; i < 18; i++) asm volatile("ld.relaxed.gpu.global.b64 %0, [%1];" : "=l"(part[i]) : "l"(i < 16 ? cp + i * 256 : sp + (i - 16) * 8) : "memory");
      };
      p1_step<1>(acc, c);
#pragma unroll
      for (int i = 0; i < 8; i++)
        asm volatile("ld.global.nc.v4.b32 {%0,%1,%2,%3}, [%4];" : "=r"(pk[4 * i]), "=r"(pk[4 * i + 1]), "=r"(pk[4 * i + 2]), "=r"(pk[4 * i + 3]) : "l"(xr + (i >> 2) * 256 + (i & 3) * 32));
      p1_loop(acc, c, 2, LN_KB + 1, [](int) {});
      pin<16>(pk); ln_moments(pk, c0[0], mo[0], mo[1]); pin<2>(mo);
      p1_step<LN_KB + 1>(acc, c);
      sched_fence(c.zero);
      pin<16>(pk + 16); ln_moments(pk + 16, c0[1], mo[2], mo[3]); ln_reduce(mo[0], mo[1]); pin<4>(mo);
      p1_step<LN_KB + 2>(acc, c);
      mbar_spin(sb + B_EP, 0, c.zero);
      asm volatile("ld.shared.b32 %0, [%1];" : "=r"(e) : "r"(sb + OFF_EPOCH) : "memory");
      pin<2>(mo); st[0] = ln_finish(c0[0], mo[0], mo[1]); ln_reduce(mo[2], mo[3]); pin<1>(st); pin<2>(mo + 2);
      p1_step<LN_KB + 3>(acc, c);
      sched_fence(c.zero);
      pin<1>(st); pin<2>(mo + 2);
      st[1] = ln_finish(c0[1], mo[2], mo[3]);
      ln_store(pk, st[0], xo);
      if (lane == 0)
        asm volatile("{\n.reg .b64 a, b;\nmov.b64 a, {%1, %3};\nmov.b64 b, {%2, %3};\nst.relaxed.gpu.global.v2.b64 [%0], {a, b};\n}" ::"l"(gs->stats + 128 * m + prow), "r"(st[0]), "r"(st[1]), "r"(e) : "memory");
      p1_step<LN_KB + 4>(acc, c);
      sched_fence(c.zero);
      pin<1>(st + 1);
      ln_store(pk + 16, st[1], xo + 128);
      bar_arrive(BAR_EV, 288);
      p1_loop(acc, c, LN_KB + 5, 13, [](int) {});
      gather();
      p1_loop(acc, c, 13, 15, [](int) {});
      auto validate = [&]() {
        float csum;
        for (int tries = 0;; tries++) {
          uint32_t bad = 0;
          csum = 0.f;
#pragma unroll
          for (int i = 0; i < 18; i++) { bad |= (uint32_t)(part[i] >> 32) ^ e; if (i < 16) csum += __uint_as_float((uint32_t)part[i]); }
          if (!__any_sync(~0u, bad != 0) || tries > (1 << 20)) break;
          gather();
        }
        const float hi = bf16r(csum), mid = bf16r(csum - hi);
        sts128(sb + OFF_CS + ((threadIdx.x & 62) * 4 + (threadIdx.x >> 6) * 2 + (threadIdx.x & 1)) * 16, make_uint4(pack2(hi, mid), pack2(csum - hi - mid, 0.f), 0, 0));
        asm volatile("fence.proxy.async.shared::cta;" ::: "memory");
        __syncwarp();
        if (lane == 0) mbar_arrive(sb + B_AUX);
      };
#pragma unroll 1
      for (int ph = 1; ph >= 0; ph--) {
        if (wg == ph) validate();
        if (ph) {
          if (wg == 1) { wg_wait<0>(); release(c, B_E1 + 16); bar_sync(BAR_LAG, 256); }
          p1_issue<3, 1>(acc, c, 1);
        }
      }
      const uint32_t keep = q == 0 ? 0xffffffffu : (q == 1 ? 0xffffu : 0u);
      const uint32_t a0 = (__byte_perm((uint32_t)part[16], 0, 0x1010) ^ 0x80008000u) & keep, a1 = (__byte_perm((uint32_t)part[17], 0, 0x1010) ^ 0x80008000u) & keep;
      mbar_spin(sb + B_AUX, 0, c.zero);
      wg_fence();
      wgmma256_rs(acc, a0, a1, 0, 0, (SM_BASE + OFF_CS) >> 4);
      wg_commit();
      if (wg == 0) bar_arrive(BAR_LAG, 256);
      rs[0] = rcpf(hi_f((uint32_t)part[16])); rs[1] = rcpf(hi_f((uint32_t)part[17]));
      wg_wait<2>(); if (wg == 0) release(c, B_E1 + 16);
      wg_wait<0>(); release(c, B_E1 + 24);
    }
#pragma unroll 1
    for (int R = 1;; R++) {
#pragma unroll
      for (int i = 0; i < 64; i++) pk[i] = pack2(acc[2 * i], acc[2 * i + 1]);
      if (t0) TS(24 + R + wg * 16);
      uint8_t* hb = (uint8_t*)gs->h + (size_t)m * 56 * 16384 + warp * 1024;
      if (R == 5) { c.a = 0x8000002000010000ull + ((SM_BASE + OFF_A + wg * 4096) >> 4); c.k2 = 510; c.k4 = 1024 - 514; c.k4w = -3072 - 514; }
      p1_step<0>(acc, c);
      if (R == 2 || R == 3) {
        attn_tile(acc, pk, c, R - 2, warp, m, gs, hb + (16 + j) * 16384, (uint8_t*)gs->o + (m * 16 + j + 8 * (R - 2)) * 16384 + warp * 1024);
      } else {
        geglu_tile(acc, pk, c, R == 5 ? 24 : 14, hb + (2 * j + (R == 1 ? 0 : 16 * R - 40)) * 16384, BAR_EV + (R == 1 ? 1 : R + 1), rs);
        rs[0] = rs[1] = 1.0f;
        if (R == 5) break;
      }
      p1_step<14>(acc, c); p1_step<15>(acc, c);
    }
    auto fetch = [&](int p) {
      asm volatile("ld.global.cg.v4.b32 {%0,%1,%2,%3}, [%4];" : "=r"(pk[4 * p]), "=r"(pk[4 * p + 1]), "=r"(pk[4 * p + 2]), "=r"(pk[4 * p + 3]) : "l"(gs->dpart + blockIdx.x * 2048 + p * 256 + threadIdx.x) : "memory");
    };
    mbar_spin(sb + B_DEP + 40, 0, c.zero);
    fetch(0); fetch(1); fetch(2);
    p1_step<8>(acc, c);
    fetch(3); fetch(4); fetch(5);
    p1_step<9>(acc, c);
    fetch(6); fetch(7);
    {
      float accs[64];
      const uint32_t peer = mapa(sb, rank ^ 1);
      auto send_piece = [&](int p) {
        asm volatile("st.async.weak.shared::cluster.mbarrier::complete_tx::bytes.v4.b32 [%0], {%1,%2,%3,%4}, [%5];" ::"r"(peer + OFF_LAND + p * 4096 + threadIdx.x * 16),
                     "r"(pack2(acc[64 + 8 * p], acc[65 + 8 * p])), "r"(pack2(acc[66 + 8 * p], acc[67 + 8 * p])), "r"(pack2(acc[68 + 8 * p], acc[69 + 8 * p])), "r"(pack2(acc[70 + 8 * p], acc[71 + 8 * p])),
                     "r"(peer + B_EX + 16 * wg + 8 * (p >> 2)) : "memory");
      };
      auto silu_piece = [&](int p) {
        const uint4 r = lds128(sb + OFF_LAND + p * 4096 + threadIdx.x * 16);
        const uint32_t rr[4] = {add2(r.x, pk[4 * p]), add2(r.y, pk[4 * p + 1]), add2(r.z, pk[4 * p + 2]), add2(r.w, pk[4 * p + 3])};
#pragma unroll
        for (int i = 0; i < 4; i++) {
          const float a = acc[8 * p + 2 * i] + lo_f(rr[i]), b = acc[8 * p + 2 * i + 1] + hi_f(rr[i]);
          pk[4 * p + i] = pack2(silu_half(a), silu_half(b));
        }
        pin<4>(pk + 4 * p);
      };
      const uint32_t xa = sb + OFF_X + (warp * 16 + (lane & 15)) * 128 + (((lane >> 4) ^ (lane & 7)) << 4);
      auto x_piece = [&](int i) { const uint4 v = ldsm((xa ^ ((i & 3) << 5)) + (i >> 2) * 16384); pk[32 + 4 * i] = v.x; pk[33 + 4 * i] = v.y; pk[34 + 4 * i] = v.z; pk[35 + 4 * i] = v.w; };
      p2_step<0>(accs, c);
      p2_step<1>(accs, c);
      mbar_spin(sb + B_E1 + 8, 0, c.zero);
      send_piece(0); send_piece(1);
      p2_step<2>(accs, c); sched_fence(c.zero); send_piece(2); send_piece(3);
      p2_step<3>(accs, c); sched_fence(c.zero); send_piece(4); send_piece(5);
      p2_step<4>(accs, c); mbar_spin(sb + B_XT, 0, c.zero); send_piece(6); send_piece(7);
      p2_step<5>(accs, c); mbar_spin(sb + B_EX + 16 * wg, 0, c.zero); silu_piece(0); x_piece(0);
      p2_step<6>(accs, c); sched_fence(c.zero); silu_piece(1); x_piece(1);
      p2_step<7>(accs, c); sched_fence(c.zero); silu_piece(2); x_piece(2);
      p2_step<8>(accs, c); sched_fence(c.zero); silu_piece(3); x_piece(3);
      p2_step<9>(accs, c); mbar_spin(sb + B_EX + 16 * wg + 8, 0, c.zero); silu_piece(4); x_piece(4);
      p2_step<10>(accs, c); sched_fence(c.zero); silu_piece(5); x_piece(5);
      p2_step<11>(accs, c); sched_fence(c.zero); silu_piece(6); x_piece(6); x_piece(7);
      if (wg == 1) silu_piece(7);
      p2_step<12>(accs, c); p2_step<13>(accs, c); p2_step<14>(accs, c); p2_step<15>(accs, c);
      if (c.do_rel) mbar_arrive(sb + B_DONE);
      if (wg == 0) silu_piece(7);
      wg_wait<0>();
#pragma unroll
      for (int i = 0; i < 8; i++) {
        uint32_t v[4];
#pragma unroll
        for (int k = 0; k < 4; k++) v[k] = fma2(pack2(accs[8 * i + 2 * k], accs[1 + 8 * i + 2 * k]), pk[4 * i + k], pk[32 + 4 * i + k]);
        asm volatile("stmatrix.sync.aligned.m8n8.x4.shared.b16 [%0], {%1,%2,%3,%4};" ::"r"((xa ^ ((i & 3) << 5)) + (i >> 2) * 16384), "r"(v[0]), "r"(v[1]), "r"(v[2]), "r"(v[3]) : "memory");
        if (i == 3 || i == 7) {
          asm volatile("fence.proxy.async.shared::cta;" ::: "memory");
          __syncwarp();
          if (elect_one()) tma3d_store(&mp.out, sb + OFF_X + (i >> 2) * 16384 + warp * 2048, j2 * 128 + (i >> 2) * 64, m2 * 64 + w * 16, wg);
        }
      }
      if (elect_one()) { asm volatile("cp.async.bulk.commit_group;\ncp.async.bulk.wait_group.read 0;" ::: "memory"); }
      if ((threadIdx.x & 127) == 0) { TS(33 + wg * 16); if (wg) { TG(59); unsigned id; asm volatile("mov.u32 %0, %%smid;" : "=r"(id)); TSV(60, id); } }
    }
  }
}

typedef CUresult (*EncodeFn)(CUtensorMap*, CUtensorMapDataType, cuuint32_t, void*, const cuuint64_t*, const cuuint64_t*, const cuuint32_t*, const cuuint32_t*,
                             CUtensorMapInterleave, CUtensorMapSwizzle, CUtensorMapL2promotion, CUtensorMapFloatOOBfill);

void encode(EncodeFn fn, CUtensorMap* tm, const void* p, int rank, const cuuint64_t* dims, const cuuint64_t* strides, const cuuint32_t* box) {
  const cuuint32_t es[5] = {1, 1, 1, 1, 1};
  fn(tm, CU_TENSOR_MAP_DATA_TYPE_BFLOAT16, rank, const_cast<void*>(p), dims, strides, box, es, CU_TENSOR_MAP_INTERLEAVE_NONE, CU_TENSOR_MAP_SWIZZLE_128B,
     PROMO, CU_TENSOR_MAP_FLOAT_OOB_FILL_NONE);
}

}

extern "C" void kernel_launch(void* const* d_in, const int* in_sizes, int n_in, void* d_out, int out_size) {
  (void)in_sizes; (void)n_in; (void)out_size;
  static EncodeFn fn = nullptr;
  static Scratch* gs = nullptr;
  if (!fn) {
    void* p = nullptr;
    cudaDriverEntryPointQueryResult qr;
    cudaGetDriverEntryPoint("cuTensorMapEncodeTiled", &p, cudaEnableDefault, &qr);
    fn = (EncodeFn)p;
    cudaGetSymbolAddress((void**)&gs, g_scratch);
    cudaFuncSetAttribute(fused_kernel, cudaFuncAttributeMaxDynamicSharedMemorySize, SMEM_BYTES);
  }
  const void *x = d_in[0], *wqkv = d_in[1], *wo = d_in[2], *wg = d_in[4], *wu = d_in[5], *wd = d_in[6];
  Maps mp;
  {
    const cuuint64_t dims[3] = {DM, SEQ / 2, 2}, st[2] = {DM * 4, DM * 2};
    const cuuint32_t box_in[3] = {64, 64, 2}, box_out[3] = {64, 16, 1};
    encode(fn, &mp.x, x, 3, dims, st, box_in);
    encode(fn, &mp.out, d_out, 3, dims, st, box_out);
  }
  {
    const cuuint64_t dims[2] = {DM, SEQ}, st[1] = {DM * 2};
    const cuuint32_t box[2] = {64, 128};
    encode(fn, &mp.xn, gs->xn, 2, dims, st, box);
  }
  {
    const cuuint32_t box[2] = {64, 64};
    const cuuint64_t dq[2] = {3 * DM, DM}, sq[1] = {3 * DM * 2}, df[2] = {DFF, DM}, sf[1] = {DFF * 2}, dw[2] = {DM, DM}, sw[1] = {DM * 2};
    encode(fn, &mp.wqkv, wqkv, 2, dq, sq, box);
    encode(fn, &mp.wg, wg, 2, df, sf, box);
    encode(fn, &mp.wu, wu, 2, df, sf, box);
    encode(fn, &mp.wo, wo, 2, dw, sw, box);
  }
  {
    const cuuint32_t box[5] = {64, 2, 4, 4, 2};
    const cuuint64_t st[4] = {DM * 2, 8 * DM * 2, 2 * DM * 2, 32 * DM * 2};
    const cuuint64_t dd[5] = {DM, 2, 4, 4, DFF / 32};
    encode(fn, &mp.wd, wd, 5, dd, st, box);
  }
  fused_kernel<<<NCTA, 384, SMEM_BYTES>>>((const uint4*)x, (const uint4*)wg, (const uint4*)wu, gs, mp);
}
```

```cpp
#include <cuda_runtime.h>
#include <cuda_bf16.h>
#include <cuda.h>
#include <stdint.h>

#define PROMO CU_TENSOR_MAP_L2_PROMOTION_L2_128B
#define PF_D 6
#define LAG2 4
#define POLL_NS "200"
#define CS_KB 8
#define LN_KB 4

#define EVICT_FIRST 0x12F0000000000000ull
#define EVICT_NORMAL 0x1000000000000000ull
#define HINT_W EVICT_FIRST
#define HINT_H EVICT_FIRST
#define HINT_LAST EVICT_FIRST

namespace {

constexpr int SEQ = 2048, DM = 1024, DFF = 3584;
constexpr int NMAIN = 128, NCTA = 132;

constexpr uint32_t SM_BASE = 0x400;
constexpr uint32_t P1_BYTES = 49152, P2_BYTES = 32768;
constexpr uint32_t OFF_A = 131072;
__host__ __device__ constexpr uint32_t p2_a(int s) { return s == 0 ? OFF_A + 32768 : s == 1 ? OFF_A + 49152 : s == 2 ? 114688 : s == 3 ? 16384 : 49152; }
__host__ __device__ constexpr uint32_t p2_b(int s) { return s < 3 ? 65536 + s * 16384 : (s - 3) * 32768; }
constexpr uint32_t OFF_LAND = OFF_A;
constexpr uint32_t OFF_X = 196608;
constexpr uint32_t OFF_CS = OFF_X + 14336;
constexpr uint32_t OFF_BAR = 229376;
constexpr uint32_t B_F1 = OFF_BAR, B_E1 = B_F1 + 32, B_E2 = B_E1 + 32, B_DONE = B_E2 + 40, B_F2 = B_DONE + 8, B_DEP = B_F2 + 40, B_CS = B_DEP + 48,
                   B_XT = B_CS + 16, B_EP = B_XT + 8, B_EX = B_EP + 8, B_AUX = B_EX + 32, B_HALO = B_AUX + 8, OFF_EPOCH = B_HALO + 16;
constexpr uint32_t SMEM_BYTES = 232448;
constexpr uint32_t AT_V = 0, AT_K = 8192, AT_REM = 11264, AT_WG = 15360;

constexpr int FL_XN = 0, FL_H = 16, FL_P = 80, FL_HALO = 96, FL_N = FL_HALO + 256;
struct __align__(1024) Scratch {
  uint4 h[16 * 56 * 1024];
  uint4 o[16 * 16 * 1024];
  uint4 xn[SEQ * DM / 8];
  uint4 dpart[128 * 8 * 256];
  uint4 halo[2 * 128 * 2 * 128];
  ulonglong2 cspart[8 * 16 * 128];
  unsigned long long stats[SEQ];
  unsigned flags[FL_N * 32];
  unsigned epoch[NCTA * 2];
};
__device__ Scratch g_scratch;
#define TG(i) do {} while (0)
#define TSV(i, v) do {} while (0)
#define TS(i) do {} while (0)

struct Maps { CUtensorMap x, xn, out, wqkv, wg, wu, wd, wo; };

__device__ __forceinline__ void mbar_init(uint32_t bar, uint32_t cnt) { asm volatile("mbarrier.init.shared::cta.b64 [%0], %1;" ::"r"(bar), "r"(cnt)); }
__device__ __forceinline__ void mbar_expect_tx(uint32_t bar, uint32_t bytes) { asm volatile("mbarrier.arrive.expect_tx.shared::cta.b64 _, [%0], %1;" ::"r"(bar), "r"(bytes) : "memory"); }
__device__ __forceinline__ void mbar_arrive(uint32_t bar) { asm volatile("mbarrier.arrive.shared::cta.b64 _, [%0];" ::"r"(bar) : "memory"); }
__device__ __forceinline__ void mbar_arrive_cl(uint32_t bar) { asm volatile("mbarrier.arrive.shared::cluster.b64 _, [%0];" ::"r"(bar) : "memory"); }
__device__ __forceinline__ uint32_t mapa(uint32_t a, uint32_t cta) { uint32_t r; asm("mapa.shared::cluster.u32 %0, %1, %2;" : "=r"(r) : "r"(a), "r"(cta)); return r; }
__device__ __forceinline__ void mbar_wait(uint32_t bar, uint32_t parity) {
  asm volatile("{\n.reg .pred p;\n.reg .u32 n;\nmov.u32 n, 0;\nLAB_WAIT:\nmbarrier.try_wait.parity.shared::cta.b64 p, [%0], %1;\n@p bra LAB_DONE;\n"
               "add.u32 n, n, 1;\nsetp.gt.u32 p, n, 4000000;\n@p trap;\nbra LAB_WAIT;\nLAB_DONE:\n}" ::"r"(bar), "r"(parity) : "memory");
}
__device__ __forceinline__ void mbar_spin(uint32_t bar, uint32_t parity, uint32_t zero) {
  asm volatile("{\n.reg .pred p, z;\nsetp.ne.u32 z, %2, 0;\nLAB_WAIT:\nmbarrier.try_wait.parity.shared::cta.b64 p, [%0], %1;\n@p bra LAB_DONE;\n@z trap;\nbra LAB_WAIT;\nLAB_DONE:\n}" ::"r"(bar), "r"(parity), "r"(zero) : "memory");
}
__device__ __forceinline__ void flag_wait(const unsigned* f, unsigned target) {
  asm volatile("{\n.reg .pred p;\n.reg .u32 n, v;\nmov.u32 n, 0;\nLAB_WAIT:\nld.relaxed.gpu.global.u32 v, [%0];\nsub.u32 v, v, %1;\nsetp.ge.s32 p, v, 0;\n@p bra LAB_DONE;\n"
               "nanosleep.u32 " POLL_NS ";\nadd.u32 n, n, 1;\nsetp.gt.u32 p, n, 4000000;\n@p trap;\nbra LAB_WAIT;\nLAB_DONE:\nfence.acquire.gpu;\n}" ::"l"(f), "r"(target) : "memory");
}
__device__ __forceinline__ void flag_add(unsigned* f) { asm volatile("red.release.gpu.global.add.u32 [%0], 1;" ::"l"(f) : "memory"); }
__device__ __forceinline__ void fence_async() { asm volatile("fence.proxy.async.global;" ::: "memory"); }
__device__ __forceinline__ bool elect_one() { uint32_t p; asm volatile("{\n.reg .pred P;\nelect.sync _|P, 0xffffffff;\nselp.u32 %0, 1, 0, P;\n}" : "=r"(p)); return p; }
__device__ __forceinline__ void bar_sync(int id, int n) { asm volatile("bar.sync %0, %1;" ::"r"(id), "r"(n) : "memory"); }
__device__ __forceinline__ void bar_arrive(int id, int n) { asm volatile("bar.arrive %0, %1;" ::"r"(id), "r"(n) : "memory"); }

__device__ __forceinline__ void tma2d(uint32_t dst, const CUtensorMap* tm, uint32_t bar, int c0, int c1, uint64_t hint) {
  asm volatile("cp.async.bulk.tensor.2d.shared::cluster.global.mbarrier::complete_tx::bytes.L2::cache_hint [%0], [%1, {%3, %4}], [%2], %5;" ::"r"(dst), "l"(tm), "r"(bar), "r"(c0), "r"(c1), "l"(hint) : "memory");
}
__device__ __forceinline__ void tma2d_mc(uint32_t dst, const CUtensorMap* tm, uint32_t bar, int c0, int c1, uint64_t hint) {
  asm volatile("cp.async.bulk.tensor.2d.shared::cluster.global.mbarrier::complete_tx::bytes.multicast::cluster.L2::cache_hint [%0], [%1, {%3, %4}], [%2], %5, %6;" ::"r"(dst), "l"(tm), "r"(bar), "r"(c0), "r"(c1), "h"((uint16_t)3), "l"(hint) : "memory");
}
__device__ __forceinline__ void tma3d(uint32_t dst, const CUtensorMap* tm, uint32_t bar, int c0, int c1, int c2, uint64_t hint) {
  asm volatile("cp.async.bulk.tensor.3d.shared::cluster.global.mbarrier::complete_tx::bytes.L2::cache_hint [%0], [%1, {%3, %4, %5}], [%2], %6;" ::"r"(dst), "l"(tm), "r"(bar), "r"(c0), "r"(c1), "r"(c2), "l"(hint) : "memory");
}
__device__ __forceinline__ void tma5d(uint32_t dst, const CUtensorMap* tm, uint32_t bar, int c0, int c4, uint64_t hint) {
  asm volatile("cp.async.bulk.tensor.5d.shared::cluster.global.mbarrier::complete_tx::bytes.L2::cache_hint [%0], [%1, {%3, %5, %5, %5, %4}], [%2], %6;" ::"r"(dst), "l"(tm), "r"(bar), "r"(c0), "r"(c4), "r"(0), "l"(hint) : "memory");
}
__device__ __forceinline__ void tma5d_prefetch(const CUtensorMap* tm, int c0, int c4) {
  asm volatile("cp.async.bulk.prefetch.tensor.5d.L2.global [%0, {%1, %3, %3, %3, %2}];" ::"l"(tm), "r"(c0), "r"(c4), "r"(0) : "memory");
}
__device__ __forceinline__ void tma3d_store(const CUtensorMap* tm, uint32_t src, int c0, int c1, int c2) {
  asm volatile("cp.async.bulk.tensor.3d.global.shared::cta.bulk_group [%0, {%2, %3, %4}], [%1];" ::"l"(tm), "r"(src), "r"(c0), "r"(c1), "r"(c2) : "memory");
}
__device__ __forceinline__ void bulk_load(uint32_t dst, const void* src, uint32_t bytes, uint32_t bar, uint64_t hint) {
  asm volatile("cp.async.bulk.shared::cluster.global.mbarrier::complete_tx::bytes.L2::cache_hint [%0], [%1], %2, [%3], %4;" ::"r"(dst), "l"(src), "r"(bytes), "r"(bar), "l"(hint) : "memory");
}
__device__ __forceinline__ void bulk_load_mc(uint32_t dst, const void* src, uint32_t bytes, uint32_t bar, uint64_t hint) {
  asm volatile("cp.async.bulk.shared::cluster.global.mbarrier::complete_tx::bytes.multicast::cluster.L2::cache_hint [%0], [%1], %2, [%3], %4, %5;" ::"r"(dst), "l"(src), "r"(bytes), "r"(bar), "h"((uint16_t)3), "l"(hint) : "memory");
}
__device__ __forceinline__ uint4 lds128(uint32_t a) { uint4 v; asm volatile("ld.shared.v4.b32 {%0,%1,%2,%3}, [%4];" : "=r"(v.x), "=r"(v.y), "=r"(v.z), "=r"(v.w) : "r"(a) : "memory"); return v; }
__device__ __forceinline__ void sts128(uint32_t a, uint4 v) { asm volatile("st.shared.v4.b32 [%0], {%1,%2,%3,%4};" ::"r"(a), "r"(v.x), "r"(v.y), "r"(v.z), "r"(v.w) : "memory"); }
__device__ __forceinline__ void stg128(void* p, uint32_t a, uint32_t b, uint32_t c, uint32_t d) { asm volatile("st.global.v4.b32 [%0], {%1,%2,%3,%4};" ::"l"(p), "r"(a), "r"(b), "r"(c), "r"(d) : "memory"); }

__device__ __forceinline__ uint32_t pack2(float lo, float hi) { uint32_t r; asm("cvt.rn.bf16x2.f32 %0, %1, %2;" : "=r"(r) : "f"(hi), "f"(lo)); return r; }
__device__ __forceinline__ float lo_f(uint32_t v) { return __uint_as_float(v << 16); }
__device__ __forceinline__ float hi_f(uint32_t v) { return __uint_as_float(v & 0xffff0000u); }
__device__ __forceinline__ float bf16r(float v) { return lo_f(pack2(v, 0.f)); }
__device__ __forceinline__ uint32_t mul2(uint32_t a, uint32_t b) { uint32_t r; asm("mul.rn.bf16x2 %0, %1, %2;" : "=r"(r) : "r"(a), "r"(b)); return r; }
__device__ __forceinline__ uint32_t add2(uint32_t a, uint32_t b) { uint32_t r; asm("add.rn.bf16x2 %0, %1, %2;" : "=r"(r) : "r"(a), "r"(b)); return r; }
__device__ __forceinline__ uint32_t sub2(uint32_t a, uint32_t b) { uint32_t r; asm("sub.rn.bf16x2 %0, %1, %2;" : "=r"(r) : "r"(a), "r"(b)); return r; }
__device__ __forceinline__ uint32_t fma2(uint32_t a, uint32_t b, uint32_t c) { uint32_t r; asm("fma.rn.bf16x2 %0, %1, %2, %3;" : "=r"(r) : "r"(a), "r"(b), "r"(c)); return r; }
__device__ __forceinline__ uint32_t max2(uint32_t a, uint32_t b) { uint32_t r; asm("max.bf16x2 %0, %1, %2;" : "=r"(r) : "r"(a), "r"(b)); return r; }
__device__ __forceinline__ float ex2f(float x) { float y; asm("ex2.approx.ftz.f32 %0, %1;" : "=f"(y) : "f"(x)); return y; }
__device__ __forceinline__ float rcpf(float x) { float y; asm("rcp.approx.ftz.f32 %0, %1;" : "=f"(y) : "f"(x)); return y; }
constexpr float GELU_C1 = 0.7978845608028654f, GELU_C3 = 0.035677408136300125f;
__device__ __forceinline__ float gelu_k(float g, float c1, float c3, float k) {
  float t;
  asm("tanh.approx.f32 %0, %1;" : "=f"(t) : "f"(g * fmaf(g * g, c3, c1)));
  g *= k;
  return fmaf(g, t, g);
}
__device__ __forceinline__ float silu_half(float z) { float t; asm("tanh.approx.f32 %0, %1;" : "=f"(t) : "f"(z)); return fmaf(z, t, z); }

__device__ __forceinline__ void wg_fence() { asm volatile("wgmma.fence.sync.aligned;" ::: "memory"); }
__device__ __forceinline__ void wg_commit() { asm volatile("wgmma.commit_group.sync.aligned;" ::: "memory"); }
template <int N> __device__ __forceinline__ void wg_wait() { asm volatile("wgmma.wait_group.sync.aligned %0;" ::"n"(N) : "memory"); }
#define A8(o) "+f"(d[(o)]), "+f"(d[(o) + 1]), "+f"(d[(o) + 2]), "+f"(d[(o) + 3]), "+f"(d[(o) + 4]), "+f"(d[(o) + 5]), "+f"(d[(o) + 6]), "+f"(d[(o) + 7])
#define A64(o) A8(o), A8((o) + 8), A8((o) + 16), A8((o) + 24), A8((o) + 32), A8((o) + 40), A8((o) + 48), A8((o) + 56)
#define REGS0_63 "%0,%1,%2,%3,%4,%5,%6,%7,%8,%9,%10,%11,%12,%13,%14,%15,%16,%17,%18,%19,%20,%21,%22,%23,%24,%25,%26,%27,%28,%29,%30,%31," \
                 "%32,%33,%34,%35,%36,%37,%38,%39,%40,%41,%42,%43,%44,%45,%46,%47,%48,%49,%50,%51,%52,%53,%54,%55,%56,%57,%58,%59,%60,%61,%62,%63"
#define REGS64_127 "%64,%65,%66,%67,%68,%69,%70,%71,%72,%73,%74,%75,%76,%77,%78,%79,%80,%81,%82,%83,%84,%85,%86,%87,%88,%89,%90,%91,%92,%93,%94,%95," \
                   "%96,%97,%98,%99,%100,%101,%102,%103,%104,%105,%106,%107,%108,%109,%110,%111,%112,%113,%114,%115,%116,%117,%118,%119,%120,%121,%122,%123,%124,%125,%126,%127"
__device__ __forceinline__ void desc_add(uint64_t& x, int v) { asm volatile("{\n.reg .b32 lo, hi;\nmov.b64 {lo, hi}, %0;\nadd.s32 lo, lo, %1;\nmov.b64 %0, {lo, hi};\n}" : "+l"(x) : "r"(v)); }
template <int ACCUM> __device__ __forceinline__ void wgmma256(float (&d)[128], uint64_t& a, uint64_t& b, int da, int db) {
  asm volatile("{\n.reg .pred p;\nsetp.ne.b32 p, %130, 0;\n"
               "wgmma.mma_async.sync.aligned.m64n256k16.f32.bf16.bf16 {" REGS0_63 "," REGS64_127 "}, %128, %129, p, 1, 1, 0, 1;\n}"
               : A64(0), A64(64) : "l"(a), "l"(b), "n"(ACCUM));
  desc_add(a, da); desc_add(b, db);
}
__device__ __forceinline__ void wgmma256_rs(float (&d)[128], uint32_t a0, uint32_t a1, uint32_t z0, uint32_t z1, uint32_t b_lo) {
  asm volatile("{\n.reg .b64 db;\nmov.b64 db, {%132, 0x00000008};\n"
               "wgmma.mma_async.sync.aligned.m64n256k16.f32.bf16.bf16 {" REGS0_63 "," REGS64_127 "}, {%128,%129,%130,%131}, db, 1, 1, 1, 0;\n}"
               : A64(0), A64(64) : "r"(a0), "r"(a1), "r"(z0), "r"(z1), "r"(b_lo));
}
template <int ACCUM> __device__ __forceinline__ void wgmma128(float (&d)[64], uint64_t& a, uint64_t& b, int da, int db) {
  asm volatile("{\n.reg .pred p;\nsetp.ne.b32 p, %66, 0;\n"
               "wgmma.mma_async.sync.aligned.m64n128k16.f32.bf16.bf16 {" REGS0_63 "}, %64, %65, p, 1, 1, 0, 1;\n}"
               : A64(0) : "l"(a), "l"(b), "n"(ACCUM));
  desc_add(a, da); desc_add(b, db);
}
template <int ACCUM> __device__ __forceinline__ void hmma(float (&c)[4], uint32_t a0, uint32_t a1, uint32_t a2, uint32_t a3, uint32_t b0, uint32_t b1) {
  if (ACCUM)
    asm volatile("mma.sync.aligned.m16n8k16.row.col.f32.bf16.bf16.f32 {%0,%1,%2,%3}, {%4,%5,%6,%7}, {%8,%9}, {%0,%1,%2,%3};"
                 : "+f"(c[0]), "+f"(c[1]), "+f"(c[2]), "+f"(c[3]) : "r"(a0), "r"(a1), "r"(a2), "r"(a3), "r"(b0), "r"(b1));
  else
    asm volatile("mma.sync.aligned.m16n8k16.row.col.f32.bf16.bf16.f32 {%0,%1,%2,%3}, {%4,%5,%6,%7}, {%8,%9}, {%10,%10,%10,%10};"
                 : "=f"(c[0]), "=f"(c[1]), "=f"(c[2]), "=f"(c[3]) : "r"(a0), "r"(a1), "r"(a2), "r"(a3), "r"(b0), "r"(b1), "f"(0.f));
}
__device__ __forceinline__ uint32_t movm(uint32_t a) { uint32_t d; asm volatile("movmatrix.sync.aligned.m8n8.trans.b16 %0, %1;" : "=r"(d) : "r"(a)); return d; }
__device__ __forceinline__ int lane_here() { int v; asm volatile("mov.u32 %0, %%laneid;" : "=r"(v)); return v; }
template <int N> __device__ __forceinline__ void pin(uint32_t* r) {
#pragma unroll
  for (int i = 0; i < N; i++) asm volatile("" : "+r"(r[i]));
}
template <int N> __device__ __forceinline__ void pin(float* r) {
#pragma unroll
  for (int i = 0; i < N; i++) asm volatile("" : "+f"(r[i]));
}
__device__ __forceinline__ void sched_fence(uint32_t zero) {
  asm volatile("{\n.reg .pred p;\nsetp.eq.u32 p, %0, 0;\nLAB_F:\n@p bra.uni LAB_D;\nnanosleep.u32 0;\nbra.uni LAB_F;\nLAB_D:\n}" ::"r"(zero) : "memory");
}
__device__ __forceinline__ uint4 ldsm(uint32_t a) { uint4 v; asm volatile("ldmatrix.sync.aligned.m8n8.x4.shared.b16 {%0,%1,%2,%3}, [%4];" : "=r"(v.x), "=r"(v.y), "=r"(v.z), "=r"(v.w) : "r"(a) : "memory"); return v; }
__device__ __forceinline__ uint4 ldsm_t(uint32_t a) { uint4 v; asm volatile("ldmatrix.sync.aligned.m8n8.x4.trans.shared.b16 {%0,%1,%2,%3}, [%4];" : "=r"(v.x), "=r"(v.y), "=r"(v.z), "=r"(v.w) : "r"(a) : "memory"); return v; }

constexpr int BAR_LAG = 1, BAR_MMA = 2, BAR_EV = 3;

struct Cons {
  uint32_t sb;
  mutable uint64_t a, b;
  int k1, k2, k4, k4w, b1;
  uint32_t rel;
  bool do_rel;
  int wg;
  uint32_t zero;
};
#define REL_TS(n) TS(64 + (n))
constexpr uint32_t DB_LO = (SM_BASE >> 4) | ((8192 >> 4) << 16);

template <int ST, int ACCUM, bool WAIT = true> __device__ __forceinline__ void p1_issue(float (&acc)[128], const Cons& c, uint32_t parity) {
  if (WAIT) mbar_spin(c.sb + B_F1 + 8 * ST, parity, c.zero);
  wg_fence();
  wgmma256<ACCUM>(acc, c.a, c.b, c.k1, c.b1);
  wgmma256<1>(acc, c.a, c.b, c.k2, c.b1);
  wgmma256<1>(acc, c.a, c.b, c.k1, c.b1);
  wgmma256<1>(acc, c.a, c.b, ST == 3 ? c.k4w : c.k4, ST == 3 ? -6144 - 384 : 2048 - 384);
  wg_commit();
}
__device__ __forceinline__ void release(const Cons& c, uint32_t bar) { if (c.do_rel) mbar_arrive_cl(c.rel + bar); }
template <int KB, bool WAIT = true> __device__ __forceinline__ void p1_step(float (&acc)[128], const Cons& c) {
  if (KB == 15) { if (c.wg == 1) { wg_wait<0>(); release(c, B_E1 + 16); bar_sync(BAR_LAG, 256); } }
  p1_issue<KB & 3, KB != 0, WAIT>(acc, c, (KB >> 2) & 1);
  if (KB == 15) { if (c.wg == 0) bar_arrive(BAR_LAG, 256); }
  if (KB > 0) { wg_wait<1>(); if (KB != 15 || c.wg == 0) release(c, B_E1 + 8 * ((KB - 1) & 3)); }
  if (KB == 15) { wg_wait<0>(); release(c, B_E1 + 24); }
}
template <class F> __device__ __forceinline__ void p1_loop(float (&acc)[128], const Cons& c, int from, int to, F&& shadow) {
#pragma unroll 1
  for (int kb = from; kb < to; kb++) {
    const bool wrap = (kb & 3) == 3;
    mbar_spin(c.sb + B_F1 + 8 * (kb & 3), (kb >> 2) & 1, c.zero);
    wg_fence();
    wgmma256<1>(acc, c.a, c.b, c.k1, c.b1);
    wgmma256<1>(acc, c.a, c.b, c.k2, c.b1);
    wgmma256<1>(acc, c.a, c.b, c.k1, c.b1);
    wgmma256<1>(acc, c.a, c.b, wrap ? c.k4w : c.k4, wrap ? -6144 - 384 : 2048 - 384);
    wg_commit();
    wg_wait<1>();
    release(c, B_E1 + 8 * ((kb - 1) & 3));
    shadow(kb);
  }
}
template <int T> __device__ __forceinline__ void p2_step(float (&acc)[64], const Cons& c) {
  if (T == 16 - LAG2) { if (c.wg == 1) bar_sync(BAR_LAG, 256); }
  mbar_spin(c.sb + B_F2 + 8 * (T % 5), (T / 5) & 1, c.zero);
  wg_fence();
  wgmma128<T != 0>(acc, c.a, c.b, c.k1, c.b1);
  wgmma128<1>(acc, c.a, c.b, c.k2, c.b1);
  wgmma128<1>(acc, c.a, c.b, c.k1, c.b1);
  wgmma128<1>(acc, c.a, c.b, ((int)p2_a((T + 1) % 5) - (int)p2_a(T % 5)) / 16 - 514, ((int)p2_b((T + 1) % 5) - (int)p2_b(T % 5)) / 16 - 384);
  wg_commit();
  if (T == 15) { if (c.wg == 0) bar_arrive(BAR_LAG, 256); }
  if (T <= 11) { wg_wait<1>(); release(c, T ? B_E2 + 8 * ((T + 5 - 1) % 5) : B_E1 + 8); }
}

template <int P> __device__ __forceinline__ void geglu_piece(uint32_t (&pk)[64], uint8_t* dst, float (&rs)[2]) {
  constexpr int cg = P >> 1, r = P & 1;
  pin<1>(rs + r);
#pragma unroll
  for (int i = 0; i < 4; i++) pin<1>(pk + 2 * (4 * cg + i) + r);
  const float r2 = rs[r] * rs[r], c1 = GELU_C1 * rs[r], c3 = GELU_C3 * r2 * rs[r], k = 0.25f * r2;
  uint32_t v[4];
#pragma unroll
  for (int i = 0; i < 4; i++) {
    const uint32_t g = pk[2 * (4 * cg + i) + r];
    v[i] = mul2(pack2(gelu_k(lo_f(g), c1, c3, k), gelu_k(hi_f(g), c1, c3, k)), pk[32 + 2 * (4 * cg + i) + r]);
  }
  stg128(dst + cg * 8192 + r * 512, v[0], v[1], v[2], v[3]);
}
__device__ __forceinline__ void geglu_tile(float (&acc)[128], uint32_t (&pk)[64], const Cons& c, int to, uint8_t* dst, int ev, float (&rs)[2]) {
  const int lane = lane_here();
  dst += (lane ^ (lane >> 3)) << 4;
  p1_loop(acc, c, 1, to, [&](int kb) {
    if (kb <= 4) {
      if (kb <= 2) { if (kb == 1) geglu_piece<0>(pk, dst, rs); else geglu_piece<1>(pk, dst, rs); }
      else { if (kb == 3) geglu_piece<2>(pk, dst, rs); else geglu_piece<3>(pk, dst, rs); }
    } else if (kb <= 8) {
      if (kb <= 6) { if (kb == 5) geglu_piece<4>(pk, dst, rs); else geglu_piece<5>(pk, dst, rs); }
      else { if (kb == 7) geglu_piece<6>(pk, dst, rs); else { geglu_piece<7>(pk, dst, rs); bar_arrive(ev, 288); } }
    }
  });
}

__device__ __forceinline__ void attn_tile(float (&acc)[128], uint32_t (&pk)[64], const Cons& c, int round, int warp, int m, Scratch* gs, uint8_t* hdst, uint8_t* odst) {
  const int w = warp & 3;
  const uint32_t at = c.sb + OFF_X + c.wg * AT_WG;
  int lane = lane_here();
  hdst += (lane ^ (lane >> 3)) << 4;
  auto scatter = [&]() {
    const int lane = lane_here();
    const uint32_t swz = (lane ^ (lane >> 3)) << 4;
#pragma unroll
    for (int i = 0; i < 4; i++) {
      const int h = i & 1, r = i >> 1;
      sts128(at + AT_V + (2 * w + r) * 1024 + h * 512 + swz, make_uint4(pk[32 + 8 * h + r], pk[34 + 8 * h + r], pk[36 + 8 * h + r], pk[38 + 8 * h + r]));
    }
    if (w < 3) {
#pragma unroll
      for (int i = 0; i < 8; i++) asm volatile("st.shared.b32 [%0], %1;" ::"r"(at + AT_K + w * 1024 + i * 128 + lane * 4), "r"(pk[17 + 2 * i]) : "memory");
    } else {
      uint8_t* g = (uint8_t*)gs->halo + ((round * 128 + blockIdx.x) * 2 + c.wg) * 2048;
#pragma unroll
      for (int i = 0; i < 8; i++) asm volatile("st.global.b32 [%0], %1;" ::"l"(g + i * 128 + lane * 4), "r"(pk[17 + 2 * i]) : "memory");
#pragma unroll
      for (int h = 0; h < 2; h++) stg128(g + 1024 + h * 512 + swz, pk[33 + 8 * h], pk[35 + 8 * h], pk[37 + 8 * h], pk[39 + 8 * h]);
      bar_arrive(BAR_EV + 2 + round, 96);
    }
    __syncwarp();
    if (lane == 0) mbar_arrive(c.sb + B_HALO + 8 * round);
    if (round) {
#pragma unroll
      for (int p = 0; p < 4; p++) {
        const int o = 32 + 8 * (p >> 1) + (p & 1);
        asm volatile("ld.global.cg.v4.b32 {%0,%1,%2,%3}, [%4];" : "=r"(pk[o]), "=r"(pk[o + 2]), "=r"(pk[o + 4]), "=r"(pk[o + 6]) : "l"(hdst + (p >> 1) * 8192 + (p & 1) * 512) : "memory");
      }
    }
  };
  auto gu_piece = [&](int p) {
    uint32_t v[4];
#pragma unroll
    for (int i = 0; i < 4; i++) {
      const int o = 8 * (p >> 1) + 2 * i + (p & 1);
      pin<1>(pk + 48 + o);
      const uint32_t g = pk[48 + o];
      v[i] = mul2(round ? pk[32 + o] : 0x3e803e80u, round ? g : pack2(gelu_k(lo_f(g), GELU_C1, GELU_C3, 1.0f), gelu_k(hi_f(g), GELU_C1, GELU_C3, 1.0f)));
    }
    stg128(hdst + (p >> 1) * 8192 + (p & 1) * 512, v[0], v[1], v[2], v[3]);
  };
  p1_step<1>(acc, c);
  scatter();
  p1_loop(acc, c, 2, 9, [&](int kb) {
    if (kb <= 4) { if (kb == 3) gu_piece(0); else if (kb == 4) gu_piece(1); }
    else if (kb == 5) gu_piece(2); else if (kb == 6) gu_piece(3);
  });
  const bool first = m == 0 && w == 0;
  uint32_t kl[16];
  mbar_spin(c.sb + B_HALO + 8 * round, 0, c.zero);
  lane = lane_here();
  {
    const uint32_t ka = at + lane * 4 + (w ? AT_K + (w - 1) * 1024 : (first ? AT_K : AT_REM + round * 2048));
#pragma unroll
    for (int i = 0; i < 8; i++) {
      asm volatile("ld.shared.b32 %0, [%1];" : "=r"(kl[2 * i]) : "r"(ka + i * 128) : "memory");
      kl[2 * i + 1] = pk[16 + 2 * i] | c.zero;
    }
  }
  float st[4][4];
  pin<16>(kl);
  bar_sync(BAR_MMA, 256);
  mbar_spin(c.sb + B_F1 + 8 * 1, 0, c.zero);
#pragma unroll
  for (int ks = 0; ks < 2; ks++) {
#pragma unroll
    for (int h = 0; h < 2; h++) {
      const int o = 8 * h + 4 * ks;
      if (ks == 0) { hmma<0>(st[2 * h], kl[o], kl[o + 1], kl[o + 2], kl[o + 3], pk[o], pk[o + 2]); hmma<0>(st[2 * h + 1], pk[16 + o], pk[17 + o], pk[18 + o], pk[19 + o], pk[o + 1], pk[o + 3]); }
      else { hmma<1>(st[2 * h], kl[o], kl[o + 1], kl[o + 2], kl[o + 3], pk[o], pk[o + 2]); hmma<1>(st[2 * h + 1], pk[16 + o], pk[17 + o], pk[18 + o], pk[19 + o], pk[o + 1], pk[o + 3]); }
    }
  }
  sched_fence(c.zero);
  bar_sync(BAR_MMA, 256);
  p1_step<9, false>(acc, c);
  sched_fence(c.zero);
  pin<16>(&st[0][0]);
  lane = lane_here();
  const int rho = lane >> 2, q = lane & 3;
  const bool le0 = 2 * q <= rho, le1 = 2 * q + 1 <= rho;
  uint32_t la[2], lb[2], mx[2];
#pragma unroll
  for (int h = 0; h < 2; h++) {
    uint32_t l[2];
#pragma unroll
    for (int r = 0; r < 2; r++) {
      const float (&t)[4] = st[2 * h + r];
      l[r] = movm(pack2(rho <= 2 * q ? t[2] : t[0], rho <= 2 * q + 1 ? t[3] : t[1]));
      l[r] = fma2(l[r], 0x3e353e35u, mul2(l[r], 0x379e379eu));
    }
    la[h] = __byte_perm(l[0], l[1], 0x5410); lb[h] = __byte_perm(l[0], l[1], 0x7632);
    if (first && !le0) la[h] = (la[h] & 0xffff0000u) | 0xce6eu;
    if (first && !le1) lb[h] = (lb[h] & 0xffff0000u) | 0xce6eu;
    mx[h] = max2(la[h], lb[h]);
  }
#pragma unroll
  for (int o = 1; o <= 2; o++) { mx[0] = max2(mx[0], __shfl_xor_sync(~0u, mx[0], o)); mx[1] = max2(mx[1], __shfl_xor_sync(~0u, mx[1], o)); }
  const float L2E = 1.4426950408889634f;
  float pr[2][4], z[4];
#pragma unroll
  for (int h = 0; h < 2; h++) {
    pr[h][0] = ex2f((lo_f(la[h]) - lo_f(mx[h])) * L2E); pr[h][1] = ex2f((lo_f(lb[h]) - lo_f(mx[h])) * L2E);
    pr[h][2] = ex2f((hi_f(la[h]) - hi_f(mx[h])) * L2E); pr[h][3] = ex2f((hi_f(lb[h]) - hi_f(mx[h])) * L2E);
    z[2 * h] = pr[h][0] + pr[h][1]; z[2 * h + 1] = pr[h][2] + pr[h][3];
  }
  p1_step<10>(acc, c);
#pragma unroll
  for (int o = 1; o <= 2; o++) {
#pragma unroll
    for (int i = 0; i < 4; i++) z[i] += __shfl_xor_sync(~0u, z[i], o);
  }
  const uint32_t LE = (le0 ? 0xffffu : 0u) | (le1 ? 0xffff0000u : 0u);
  uint32_t P[4][2];
  uint4 vt[4][2];
  {
    const uint32_t row = (lane & 7) * 64 + ((((lane >> 3) & 1) ^ ((lane & 7) >> 1)) << 4);
    const uint32_t v1 = at + AT_V + (2 * w + (lane >> 4)) * 1024 + row;
    const uint32_t v0 = (w || lane >= 16) ? v1 - 1024 : (first ? v1 : at + AT_REM + round * 2048 + 1024 + row);
#pragma unroll
    for (int i = 0; i < 4; i++) {
      const float rz = rcpf(z[i]);
      const uint32_t p = pack2(pr[i >> 1][2 * (i & 1)] * rz, pr[i >> 1][2 * (i & 1) + 1] * rz);
      P[i][0] = p & ~LE; P[i][1] = p & LE;
      const uint32_t a = ((i & 1) ? v1 : v0) + (i >> 1) * 512;
      vt[i][0] = ldsm_t(a); vt[i][1] = ldsm_t(a ^ 32);
    }
  }
  float ot[4][2][4];
  pin<8>(&P[0][0]);
  bar_sync(BAR_MMA, 256);
  mbar_spin(c.sb + B_F1 + 8 * 3, 0, c.zero);
#pragma unroll
  for (int i = 0; i < 8; i++) { const uint4& v = vt[i >> 1][i & 1]; hmma<0>(ot[i >> 1][i & 1], v.x, v.y, v.z, v.w, P[i >> 1][0], P[i >> 1][1]); }
  sched_fence(c.zero);
  bar_sync(BAR_MMA, 256);
  p1_step<11, false>(acc, c);
  sched_fence(c.zero);
  pin<32>(&ot[0][0][0]);
  lane = lane_here();
  odst += (lane ^ (lane >> 3)) << 4;
  auto o_piece = [&](int i) {
    stg128(odst + (i >> 1) * 8192 + (i & 1) * 512, movm(pack2(ot[i][0][0], ot[i][0][1])), movm(pack2(ot[i][0][2], ot[i][0][3])), movm(pack2(ot[i][1][0], ot[i][1][1])), movm(pack2(ot[i][1][2], ot[i][1][3])));
  };
  o_piece(0); o_piece(1);
  p1_step<12>(acc, c);
  o_piece(2); o_piece(3);
  if (round) bar_arrive(BAR_EV + 4, 288);
  p1_step<13>(acc, c);
}

__device__ __forceinline__ void ln_moments(const uint32_t* raw, float& c0, float& s, float& v) {
  c0 = lo_f(__shfl_sync(~0u, raw[0], 0));
  float ss[4] = {0.f, 0.f, 0.f, 0.f}, vv[4] = {0.f, 0.f, 0.f, 0.f};
#pragma unroll
  for (int i = 0; i < 16; i++) {
    const float a = lo_f(raw[i]) - c0, b = hi_f(raw[i]) - c0;
    ss[(2 * i) & 3] += a; ss[(2 * i + 1) & 3] += b;
    vv[(2 * i) & 3] = fmaf(a, a, vv[(2 * i) & 3]); vv[(2 * i + 1) & 3] = fmaf(b, b, vv[(2 * i + 1) & 3]);
  }
  s = (ss[0] + ss[1]) + (ss[2] + ss[3]); v = (vv[0] + vv[1]) + (vv[2] + vv[3]);
}
__device__ __forceinline__ void ln_reduce(float& s, float& v) {
#pragma unroll
  for (int o = 16; o; o >>= 1) { s += __shfl_xor_sync(~0u, s, o); v += __shfl_xor_sync(~0u, v, o); }
}
__device__ __forceinline__ uint32_t ln_finish(float c0, float s, float v) {
  s *= 1.0f / DM;
  float sd;
  asm("sqrt.approx.ftz.f32 %0, %1;" : "=f"(sd) : "f"(bf16r(bf16r(fmaxf(fmaf(v, 1.0f / DM, -s * s), 0.f)) + 1e-5f)));
  return pack2(c0 + s, sd);
}
__device__ __forceinline__ void ln_store(const uint32_t* raw, uint32_t st, uint4* dst) {
  const uint32_t m2 = __byte_perm(st, st, 0x1010);
  const float rinv = rcpf(hi_f(st));
  const uint32_t rh = pack2(rinv, rinv), rl = pack2(rinv - hi_f(rh), rinv - hi_f(rh));
#pragma unroll
  for (int c = 0; c < 4; c++) {
    uint32_t v[4];
#pragma unroll
    for (int i = 0; i < 4; i++) { const uint32_t t = sub2(raw[4 * c + i], m2); v[i] = fma2(t, rh, mul2(t, rl)); }
    stg128(dst + 32 * c, v[0], v[1], v[2], v[3]);
  }
}
__device__ __forceinline__ void col_sums(uint32_t tile, ulonglong2* part, uint32_t tag) {
  const int lane = threadIdx.x & 31;
  float cs[8] = {0, 0, 0, 0, 0, 0, 0, 0};
  uint32_t base = tile + ((lane >> 3) & 1) * 8192 + (lane >> 4) * 4096 + ((lane & 7) << 4);
#pragma unroll 1
  for (int k0 = 0; k0 < 8; k0++, base = (base ^ ((k0 ^ (k0 - 1)) << 4)) + 128) {
    uint4 v[4];
#pragma unroll
    for (int k = 0; k < 4; k++) v[k] = lds128(base + k * 1024);
#pragma unroll
    for (int k = 0; k < 4; k++) {
      cs[0] += lo_f(v[k].x); cs[1] += hi_f(v[k].x); cs[2] += lo_f(v[k].y); cs[3] += hi_f(v[k].y);
      cs[4] += lo_f(v[k].z); cs[5] += hi_f(v[k].z); cs[6] += lo_f(v[k].w); cs[7] += hi_f(v[k].w);
    }
  }
  const bool up = lane >= 16;
#pragma unroll
  for (int i = 0; i < 2; i++) {
    const float a = (up ? cs[4 + 2 * i] : cs[2 * i]) + __shfl_xor_sync(~0u, up ? cs[2 * i] : cs[4 + 2 * i], 16);
    const float b = (up ? cs[5 + 2 * i] : cs[1 + 2 * i]) + __shfl_xor_sync(~0u, up ? cs[1 + 2 * i] : cs[5 + 2 * i], 16);
    asm volatile("{\n.reg .b64 a, b;\nmov.b64 a, {%1, %3};\nmov.b64 b, {%2, %3};\nst.relaxed.gpu.global.v2.b64 [%0], {a, b};\n}"
                 ::"l"(part + 32 * (i + (up ? 2 : 0)) + (lane & 15)), "r"(__float_as_uint(a)), "r"(__float_as_uint(b)), "r"(tag) : "memory");
  }
  asm volatile("fence.proxy.async.shared::cta;" ::: "memory");
}

__global__ void __cluster_dims__(2, 1, 1) __launch_bounds__(384, 1)
fused_kernel(const uint4* __restrict__ x, const uint4* __restrict__ wgate, const uint4* __restrict__ wup, Scratch* gs, const __grid_constant__ Maps mp) {
  extern __shared__ __align__(1024) uint8_t smem_raw[];
  const uint32_t sb = (uint32_t)__cvta_generic_to_shared(smem_raw);
  if (threadIdx.x == 352) TS(63);
  if (threadIdx.x < 256 && blockIdx.x < NMAIN) {
    const uint32_t r = threadIdx.x >> 3, ch = threadIdx.x & 7;
    const uint32_t d = sb + r * 128 + ((ch ^ (r & 7)) << 4);
    const uint8_t* xa = (const uint8_t*)x + ((blockIdx.x & 15) * 262144 + r * 4096 + ch * 16);
    const uint32_t wo = r * (DFF * 2) + (blockIdx.x >> 4) * 256 + ch * 16;
    const uint8_t *wa = (const uint8_t*)wgate + wo, *wb = (const uint8_t*)wup + wo;
#pragma unroll
    for (int i = 0; i < 12; i++) {
      const int h = i >= 8;
      const uint8_t* src = (i >> 2) == 1 ? xa + (i & 1) * 131072 + ((i >> 1) & 1) * 2048 : ((i & 2) ? wb : wa) + h * 32 * (DFF * 2) + (i & 1) * 128;
      asm volatile("cp.async.cg.shared.global [%0], [%1], 16;" ::"r"(d + ((i >> 2) == 1 ? OFF_A + (i & 3) * 4096 : (i & 3) * 8192 + h * 4096)), "l"(src) : "memory");
    }
    if (threadIdx.x == 0) TS(23);
  }
  const int warp = __shfl_sync(~0u, threadIdx.x >> 5, 0), lane = threadIdx.x & 31;
  const int m = blockIdx.x & 15, j = blockIdx.x >> 4, rank = blockIdx.x & 1;
  const int m2 = blockIdx.x >> 3, j2 = blockIdx.x & 7;
  const bool helper = blockIdx.x >= NMAIN;
  if (warp >= 8) {
    asm volatile("setmaxnreg.dec.sync.aligned.u32 40;");
    if (warp == 8) {
      if (elect_one()) {
        asm volatile("prefetch.tensormap [%0];\nprefetch.tensormap [%1];\nprefetch.tensormap [%2];" ::"l"(&mp.x), "l"(&mp.wg), "l"(&mp.wu) : "memory");
        for (int s = 0; s < 4; s++) mbar_init(sb + B_F1 + 8 * s, 1);
        if (!helper) mbar_arrive(sb + B_F1);
        asm volatile("fence.mbarrier_init.release.cluster;" ::: "memory");
      }
      __syncwarp();
    } else if (warp == 9) {
      if (elect_one()) {
        if ((sb & 0xffffff) != SM_BASE) asm volatile("trap;");
        for (uint32_t b = B_E1; b < B_F2; b += 8) mbar_init(sb + b, 4);
        for (uint32_t b = B_F2; b < B_AUX; b += 8) mbar_init(sb + b, 1);
        for (uint32_t b = B_EX; b < B_AUX; b += 8) mbar_expect_tx(sb + b, 8192);
        mbar_init(sb + B_AUX, 8); mbar_init(sb + B_HALO, 9); mbar_init(sb + B_HALO + 8, 9);
        asm volatile("fence.mbarrier_init.release.cluster;" ::: "memory");
      }
      __syncwarp();
    }
    asm volatile("barrier.cluster.arrive.relaxed.aligned;" ::: "memory");
    if (warp == 8 && !helper) {
      if (elect_one()) {
        TS(0); TG(51);
#pragma unroll 1
        for (int kb = 1; kb < 4; kb++) {
          const uint32_t sa = sb + OFF_A + kb * 16384, sw = sb + kb * 32768, fb = sb + B_F1 + 8 * kb;
          mbar_expect_tx(fb, P1_BYTES);
          tma3d(sa, &mp.x, fb, kb * 64, m * 64, 0, EVICT_NORMAL);
          tma2d(sw, &mp.wg, fb, j * 128, kb * 64, EVICT_NORMAL); tma2d(sw + 16384, &mp.wu, fb, j * 128, kb * 64, EVICT_NORMAL);
          tma2d(sw + 8192, &mp.wg, fb, j * 128 + 64, kb * 64, EVICT_NORMAL); tma2d(sw + 24576, &mp.wu, fb, j * 128 + 64, kb * 64, EVICT_NORMAL);
        }
        TS(7);
      }
      __syncwarp();
    }
    asm volatile("barrier.cluster.wait.aligned;" ::: "memory");
    if (helper) {
      if (warp == 8) {
        unsigned e = 0;
        if (elect_one()) {
#pragma unroll 1
          for (int i = 0; i < 16; i++) {
            const uint32_t fb = sb + B_F1 + 8 * (i >> 2);
            if (!(i & 3)) mbar_expect_tx(fb, P1_BYTES);
            tma5d(sb + i * 8192, &mp.wd, fb, (blockIdx.x - NMAIN) * 256 + (i & 3) * 64, (i >> 2) * 2, HINT_W);
          }
        }
        if (lane == 0) { unsigned* ep = &gs->epoch[blockIdx.x * 2]; e = *ep + 1; *ep = e; }
        e = __shfl_sync(~0u, e, 0);
        if (lane < 16) flag_wait(&gs->flags[(FL_H + lane * 4) * 32], e * 8u);
        __syncwarp();
        if (elect_one()) {
          fence_async();
          TS(0);
#pragma unroll 1
          for (int i = 0; i < 64; i++) {
            const uint32_t fb = sb + B_F1 + 8 * (i & 3);
            if (i >= 4) { mbar_wait(sb + B_E1 + 8 * (i & 3), ~(i >> 2) & 1); mbar_expect_tx(fb, 16384); }
            bulk_load(sb + OFF_A + (i & 3) * 16384, gs->h + ((i >> 2) * 56 + (i & 3)) * 1024, 16384, fb, EVICT_NORMAL);
          }
        }
      } else if (warp == 9) {
#pragma unroll 1
        for (int t = 0; t < 16; t++) {
          bar_sync(BAR_EV + (t & 1), 288);
          if (lane == 0) { flag_add(&gs->flags[(FL_P + t) * 32]); TS(64 + t); }
          __syncwarp();
        }
      }
    } else if (warp == 8) {
      if (elect_one()) {
        uint32_t par = 0;

        auto x_load = [&]() {
          mbar_expect_tx(sb + B_XT, 32768);
          tma3d(sb + OFF_X, &mp.x, sb + B_XT, j2 * 128, m2 * 64, 0, HINT_LAST); tma3d(sb + OFF_X + 16384, &mp.x, sb + B_XT, j2 * 128 + 64, m2 * 64, 0, HINT_LAST);
        };
        auto d_prefetch = [&](int i) {
          if ((m2 >> 2) == (i & 3)) tma5d_prefetch(&mp.wd, (j2 >> 1) * 256 + (m2 & 3) * 64, (2 * i + 4 + rank) * 2);
        };
        auto w_tile = [&](int R, const CUtensorMap*& mb0, const CUtensorMap*& mb1, int& n0, int& n1) {
          if (R == 1 || R == 2) {
            mb0 = &mp.wqkv; n0 = 64 * (j + 8 * (R - 1)) + rank * 2048;
            mb1 = rank ? (R == 1 ? &mp.wg : &mp.wu) : &mp.wqkv; n1 = rank ? 1024 + 64 * j : n0 + 1024;
          } else {
            mb0 = mb1 = rank ? &mp.wu : &mp.wg;
            n0 = 128 * j + (R ? 1024 * R - 1536 : 0); n1 = n0 + 64;
          }
        };
        for (int R = 0; R < 5; R++) {
          const CUtensorMap *mb0, *mb1;
          int n0, n1;
          w_tile(R, mb0, mb1, n0, n1);
#pragma unroll 1
          for (int kb = R ? 0 : 4; kb < 16; kb++) {
            if (R == 0 && kb == 14) { asm volatile("prefetch.tensormap [%0];\nprefetch.tensormap [%1];" ::"l"(&mp.xn), "l"(&mp.wqkv) : "memory"); }
            if (R == 4 && kb == 2) { asm volatile("prefetch.tensormap [%0];\nprefetch.tensormap [%1];\nprefetch.tensormap [%2];" ::"l"(&mp.wd), "l"(&mp.wo), "l"(&mp.out) : "memory"); }
            if (R == 0 && kb == CS_KB) {
#pragma unroll 1
              for (int h = 0; h < 2; h++) {
                const uint32_t cb = sb + B_CS + 8 * h, d = sb + OFF_X + 16384 * h;
                mbar_expect_tx(cb, 16384);
                tma2d(d, h ? &mp.wu : &mp.wg, cb, n0, m * 64, EVICT_NORMAL); tma2d(d + 8192, h ? &mp.wu : &mp.wg, cb, n1, m * 64, EVICT_NORMAL);
              }
            }
            const int st = kb & 3;
            const uint32_t sa = sb + OFF_A + st * 16384, sw = sb + st * 32768, fb = sb + B_F1 + 8 * st;
            mbar_wait(sb + B_E1 + 8 * st, par);
            if (R * 16 + kb >= 4) REL_TS(R * 16 + kb - 4);
            mbar_expect_tx(fb, P1_BYTES);
            tma2d_mc(sw + rank * 16384, mb0, fb, n0, kb * 64, HINT_W);
            tma2d_mc(sw + 8192 + rank * 16384, mb1, fb, n1, kb * 64, HINT_W);
            if (R == 0) {
              tma3d(sa, &mp.x, fb, kb * 64, m * 64, 0, EVICT_NORMAL);
            } else {
              if (R == 1 && kb == 0) { mbar_wait(sb + B_DEP, 0); TS(1); }
              tma2d(sa, &mp.xn, fb, kb * 64, m * 128, R == 4 ? HINT_LAST : EVICT_NORMAL);
            }
            if (R == 4 && kb == 4 + j2) x_load();
            if (R == 4 && kb >= 16 - PF_D) d_prefetch(kb + PF_D - 16);
            if (st == 3) par ^= 1;
          }
        }
#pragma unroll 1
        for (int i = 0; i < 26; i++) {
          const int st = i & 3, kb = 2 * i + 4 + rank;
          const uint32_t sa = sb + OFF_A + st * 16384, sw = sb + st * 32768, fb = sb + B_F1 + 8 * st;
          mbar_wait(sb + B_E1 + 8 * st, par);
          REL_TS(76 + i);
          mbar_expect_tx(fb, P1_BYTES);
          tma5d(sw, &mp.wd, fb, j2 * 128, kb * 2, HINT_W); tma5d(sw + 8192, &mp.wd, fb, j2 * 128 + 64, kb * 2, HINT_W);
          tma5d(sw + 16384, &mp.wd, fb, (j2 ^ 1) * 128, kb * 2, HINT_W); tma5d(sw + 24576, &mp.wd, fb, (j2 ^ 1) * 128 + 64, kb * 2, HINT_W);
          if (i == 0 || i == 6 || i == 10 || i == 18) { mbar_wait(sb + B_DEP + 8 * (1 + ((i + 6) >> 3)), 0); }
          bulk_load(sa, gs->h + (m2 * 56 + kb) * 1024, 16384, fb, HINT_H);
          if (i + PF_D < 26) d_prefetch(i + PF_D);
          if (st == 3) par ^= 1;
        }
        int st = 0; uint32_t par2 = 1;
#pragma unroll 1
        for (int t = 0; t < 16; t++) {
          const uint32_t sa = sb + p2_a(st), sw = sb + p2_b(st), fb = sb + B_F2 + 8 * st;
          if (t < 5) mbar_wait(sb + B_E1 + 8 * (((2 * t + 1) / 3 + 2) & 3), t < 3); else mbar_wait(sb + B_E2 + 8 * st, par2);
          REL_TS(102 + t);
          mbar_expect_tx(fb, P2_BYTES);
          bulk_load_mc(sa + rank * 8192, gs->o + (m2 * 16 + t) * 1024 + rank * 512, 8192, fb, HINT_H);
          tma2d(sw, &mp.wo, fb, j2 * 128, t * 64, HINT_W); tma2d(sw + 8192, &mp.wo, fb, j2 * 128 + 64, t * 64, HINT_W);
          if (++st == 5) { st = 0; par2 ^= 1; }
        }
      }
    } else if (warp == 9) {
#pragma unroll 1
      for (int e = 0; e < 7; e++) {
        const bool halo = e == 2 || e == 3;
        bar_sync(BAR_EV + e, halo ? 96 : 288);
        if (lane == 0) {
          const int f = e == 0 ? FL_XN + m : (halo ? FL_HALO + (e - 2) * 128 + blockIdx.x : FL_H + m * 4 + (e == 1 ? 0 : e - 3));
          TS(10 + 2 * e); TG(52 + e);
          flag_add(&gs->flags[f * 32]);
          if (e < 6) TS(11 + 2 * e);
        }
        __syncwarp();
      }
      mbar_wait(sb + B_DONE, 0);
    } else {
      unsigned e = 0;
      if (lane == 0) {
        unsigned* ep = &gs->epoch[blockIdx.x * 2 + warp - 10];
        e = *ep + 1; *ep = e;
        if (warp == 10) { asm volatile("st.shared.b32 [%0], %1;" ::"r"(sb + OFF_EPOCH), "r"(e) : "memory"); mbar_arrive(sb + B_EP); }
      }
      e = __shfl_sync(~0u, e, 0);
      mbar_wait(sb + B_CS + 8 * (warp - 10), 0);
      if (lane == 0 && warp == 11) TS(6);
      col_sums(sb + OFF_X + (warp - 10) * 16384, gs->cspart + (j * 16 + m) * 128 + (warp - 10) * 16, e);
      if (lane == 0 && warp == 11) TS(9);
      if (warp == 10) {
        if (lane == 0) {
#pragma unroll 1
          for (int g = 0; g < 6; g++) {
            flag_wait(&gs->flags[(g == 5 ? FL_P + m2 : (g ? FL_H + m2 * 4 + g - 1 : FL_XN + m)) * 32], e * (g == 5 ? 4u : 8u));
            fence_async();
            mbar_arrive(sb + B_DEP + 8 * g);
            if (g == 0) TS(8);
          }
        }
      } else
      if (elect_one()) {
#pragma unroll 1
        for (int r = 0; r < 2; r++) {
          const uint32_t hb = sb + B_HALO + 8 * r;
          if (r) mbar_wait(sb + B_HALO, 0);
          if (m) {
            flag_wait(&gs->flags[(FL_HALO + r * 128 + blockIdx.x - 1) * 32], e);
            fence_async();
            mbar_expect_tx(hb, 4096);
            for (int g = 0; g < 2; g++) bulk_load(sb + OFF_X + g * AT_WG + AT_REM + r * 2048, gs->halo + ((r * 128 + blockIdx.x - 1) * 2 + g) * 128, 2048, hb, EVICT_FIRST);
          } else {
            mbar_arrive(hb);
          }
          TS(34 + r);
        }
      }
    }
  } else {
    asm volatile("barrier.cluster.arrive.relaxed.aligned;" ::: "memory");
    asm volatile("setmaxnreg.inc.sync.aligned.u32 232;");
    const int wg = warp >> 2, w = warp & 3;
    Cons c;
    c.sb = sb; c.wg = wg; c.zero = warp >> 8;
    c.a = 0x4000004000010000ull + ((SM_BASE + OFF_A + wg * 8192) >> 4); c.k1 = 2 + c.zero; c.k2 = 2; c.k4 = 1024 - 6; c.k4w = -3072 - 6; c.b1 = 128 + c.zero;
    c.b = 0x4000004000000000ull + DB_LO + c.zero;
    c.rel = mapa(sb, threadIdx.x & 1);
    c.do_rel = (threadIdx.x & 127) < 2;
    constexpr bool t0 = false;
    float acc[128];
    uint32_t pk[64];
    float rs[2];
    const int q = lane & 3;

    if (helper) {
      asm volatile("barrier.cluster.wait.aligned;" ::: "memory");
      c.a = 0x8000002000010000ull + ((SM_BASE + OFF_A + wg * 4096) >> 4); c.k2 = 510; c.k4 = 1024 - 514; c.k4w = -3072 - 514;
      c.rel = sb;
      uint4* dst = gs->dpart + (blockIdx.x - NMAIN) * 4096 + threadIdx.x;
      auto put = [&](int p) {
#pragma unroll
        for (int i = 4 * p; i < 4 * p + 4; i++) stg128(dst + i * 256, pk[4 * i], pk[4 * i + 1], pk[4 * i + 2], pk[4 * i + 3]);
      };
#pragma unroll 1
      for (int t = 0; t < 16; t++) {
        p1_issue<0, 0>(acc, c, t & 1);
        if (t) put(0);
        p1_issue<1, 1>(acc, c, t & 1); wg_wait<1>(); release(c, B_E1);
        if (t) put(1);
        p1_issue<2, 1>(acc, c, t & 1); wg_wait<1>(); release(c, B_E1 + 8);
        if (t) put(2);
        if (wg == 1) { wg_wait<0>(); release(c, B_E1 + 16); bar_sync(BAR_LAG, 256); }
        p1_issue<3, 1>(acc, c, t & 1);
        if (wg == 0) bar_arrive(BAR_LAG, 256);
        if (t) { put(3); bar_arrive(BAR_EV + (~t & 1), 288); dst += 8 * 2048; }
        wg_wait<1>(); if (wg == 0) release(c, B_E1 + 16);
        wg_wait<0>(); release(c, B_E1 + 24);
#pragma unroll
        for (int i = 0; i < 64; i++) pk[i] = pack2(acc[2 * i], acc[2 * i + 1]);
      }
      put(0); put(1); put(2); put(3);
      bar_arrive(BAR_EV + 1, 288);
      return;
    }
    {
      const int prow = 16 * j + 2 * warp;
      const uint4* xr = x + (size_t)(128 * m + 2 * (prow & 63) + (prow >> 6)) * 128 + lane;
      uint4* xo = gs->xn + (size_t)(128 * m + prow) * 128 + lane;
      float c0[2], mo[4];
      uint32_t st[2];
      uint32_t e;
      asm volatile("" : "+l"(xr), "+l"(xo));
      asm volatile("cp.async.wait_all;\nfence.proxy.async.shared::cta;" ::: "memory");
      bar_sync(BAR_MMA, 256);
      if (threadIdx.x == 0) TS(39);
      p1_step<0, false>(acc, c);
      asm volatile("barrier.cluster.wait.aligned;" ::: "memory");
      unsigned long long part[18];
      auto gather = [&](int from, int to) {
        const int lane = lane_here();
        const unsigned long long* cp = (const unsigned long long*)gs->cspart + j * 4096 + warp * 32 + lane;
        const unsigned long long* sp = gs->stats + 128 * m + warp * 16 + (lane >> 2);
#pragma unroll
        for (int i = from; i < to; i++) asm volatile("ld.relaxed.gpu.global.b64 %0, [%1];" : "=l"(part[i]) : "l"(i < 16 ? cp + i * 256 : sp + (i - 16) * 8) : "memory");
      };
      auto row_load = [&](int r) {
#pragma unroll
        for (int i = 4 * r; i < 4 * r + 4; i++)
          asm volatile("ld.global.nc.L1::no_allocate.v4.b32 {%0,%1,%2,%3}, [%4];" : "=r"(pk[4 * i]), "=r"(pk[4 * i + 1]), "=r"(pk[4 * i + 2]), "=r"(pk[4 * i + 3]) : "l"(xr + r * 256 + (i & 3) * 32));
      };
      p1_step<1>(acc, c); row_load(0);
      p1_step<2>(acc, c); row_load(1);
      p1_loop(acc, c, 3, LN_KB + 1, [](int) {});
      pin<16>(pk); ln_moments(pk, c0[0], mo[0], mo[1]); pin<2>(mo);
      p1_step<LN_KB + 1>(acc, c);
      sched_fence(c.zero);
      pin<16>(pk + 16); ln_moments(pk + 16, c0[1], mo[2], mo[3]); ln_reduce(mo[0], mo[1]); pin<4>(mo);
      p1_step<LN_KB + 2>(acc, c);
      mbar_spin(sb + B_EP, 0, c.zero);
      asm volatile("ld.shared.b32 %0, [%1];" : "=r"(e) : "r"(sb + OFF_EPOCH) : "memory");
      pin<2>(mo); st[0] = ln_finish(c0[0], mo[0], mo[1]); ln_reduce(mo[2], mo[3]); pin<1>(st); pin<2>(mo + 2);
      p1_step<LN_KB + 3>(acc, c);
      sched_fence(c.zero);
      pin<1>(st); pin<2>(mo + 2);
      st[1] = ln_finish(c0[1], mo[2], mo[3]);
      ln_store(pk, st[0], xo);
      if (lane == 0)
        asm volatile("{\n.reg .b64 a, b;\nmov.b64 a, {%1, %3};\nmov.b64 b, {%2, %3};\nst.relaxed.gpu.global.v2.b64 [%0], {a, b};\n}" ::"l"(gs->stats + 128 * m + prow), "r"(st[0]), "r"(st[1]), "r"(e) : "memory");
      p1_step<LN_KB + 4>(acc, c);
      sched_fence(c.zero);
      pin<1>(st + 1);
      ln_store(pk + 16, st[1], xo + 128);
      bar_arrive(BAR_EV, 288);
      p1_loop(acc, c, LN_KB + 5, 13, [](int) {});
      gather(0, 9);
      p1_step<13>(acc, c);
      gather(9, 18);
      p1_step<14>(acc, c);
      auto validate = [&]() {
        float csum;
        for (int tries = 0;; tries++) {
          uint32_t bad = 0;
          csum = 0.f;
#pragma unroll
          for (int i = 0; i < 18; i++) { bad |= (uint32_t)(part[i] >> 32) ^ e; if (i < 16) csum += __uint_as_float((uint32_t)part[i]); }
          if (!__any_sync(~0u, bad != 0) || tries > (1 << 20)) break;
          gather(0, 18);
        }
        const float hi = bf16r(csum), mid = bf16r(csum - hi);
        sts128(sb + OFF_CS + ((threadIdx.x & 62) * 4 + (threadIdx.x >> 6) * 2 + (threadIdx.x & 1)) * 16, make_uint4(pack2(hi, mid), pack2(csum - hi - mid, 0.f), 0, 0));
        asm volatile("fence.proxy.async.shared::cta;" ::: "memory");
        __syncwarp();
        if (lane == 0) mbar_arrive(sb + B_AUX);
      };
#pragma unroll 1
      for (int ph = 1; ph >= 0; ph--) {
        if (wg == ph) validate();
        if (ph) {
          if (wg == 1) { wg_wait<0>(); release(c, B_E1 + 16); bar_sync(BAR_LAG, 256); }
          p1_issue<3, 1>(acc, c, 1);
        }
      }
      const uint32_t keep = q == 0 ? 0xffffffffu : (q == 1 ? 0xffffu : 0u);
      const uint32_t a0 = (__byte_perm((uint32_t)part[16], 0, 0x1010) ^ 0x80008000u) & keep, a1 = (__byte_perm((uint32_t)part[17], 0, 0x1010) ^ 0x80008000u) & keep;
      mbar_spin(sb + B_AUX, 0, c.zero);
      wg_fence();
      wgmma256_rs(acc, a0, a1, 0, 0, (SM_BASE + OFF_CS) >> 4);
      wg_commit();
      if (wg == 0) bar_arrive(BAR_LAG, 256);
      rs[0] = rcpf(hi_f((uint32_t)part[16])); rs[1] = rcpf(hi_f((uint32_t)part[17]));
      wg_wait<2>(); if (wg == 0) release(c, B_E1 + 16);
      wg_wait<0>(); release(c, B_E1 + 24);
    }
#pragma unroll 1
    for (int R = 1;; R++) {
#pragma unroll
      for (int i = 0; i < 64; i++) pk[i] = pack2(acc[2 * i], acc[2 * i + 1]);
      if (t0) TS(24 + R + wg * 16);
      uint8_t* hb = (uint8_t*)gs->h + (size_t)m * 56 * 16384 + warp * 1024;
      if (R == 5) { c.a = 0x8000002000010000ull + ((SM_BASE + OFF_A + wg * 4096) >> 4); c.k2 = 510; c.k4 = 1024 - 514; c.k4w = -3072 - 514; }
      p1_step<0>(acc, c);
      if (R == 2 || R == 3) {
        attn_tile(acc, pk, c, R - 2, warp, m, gs, hb + (16 + j) * 16384, (uint8_t*)gs->o + (m * 16 + j + 8 * (R - 2)) * 16384 + warp * 1024);
      } else {
        geglu_tile(acc, pk, c, R == 5 ? 24 : 14, hb + (2 * j + (R == 1 ? 0 : 16 * R - 40)) * 16384, BAR_EV + (R == 1 ? 1 : R + 1), rs);
        rs[0] = rs[1] = 1.0f;
        if (R == 5) break;
      }
      p1_step<14>(acc, c); p1_step<15>(acc, c);
    }
    auto fetch = [&](int p) {
      asm volatile("ld.global.cg.v4.b32 {%0,%1,%2,%3}, [%4];" : "=r"(pk[4 * p]), "=r"(pk[4 * p + 1]), "=r"(pk[4 * p + 2]), "=r"(pk[4 * p + 3]) : "l"(gs->dpart + blockIdx.x * 2048 + p * 256 + threadIdx.x) : "memory");
    };
    mbar_spin(sb + B_DEP + 40, 0, c.zero);
    fetch(0); fetch(1); fetch(2);
    p1_step<8>(acc, c);
    fetch(3); fetch(4); fetch(5);
    p1_step<9>(acc, c);
    fetch(6); fetch(7);
    {
      float accs[64];
      const uint32_t peer = mapa(sb, rank ^ 1);
      auto send_piece = [&](int p) {
        asm volatile("st.async.weak.shared::cluster.mbarrier::complete_tx::bytes.v4.b32 [%0], {%1,%2,%3,%4}, [%5];" ::"r"(peer + OFF_LAND + p * 4096 + threadIdx.x * 16),
                     "r"(pack2(acc[64 + 8 * p], acc[65 + 8 * p])), "r"(pack2(acc[66 + 8 * p], acc[67 + 8 * p])), "r"(pack2(acc[68 + 8 * p], acc[69 + 8 * p])), "r"(pack2(acc[70 + 8 * p], acc[71 + 8 * p])),
                     "r"(peer + B_EX + 16 * wg + 8 * (p >> 2)) : "memory");
      };
      auto silu_piece = [&](int p) {
        const uint4 r = lds128(sb + OFF_LAND + p * 4096 + threadIdx.x * 16);
        const uint32_t rr[4] = {add2(r.x, pk[4 * p]), add2(r.y, pk[4 * p + 1]), add2(r.z, pk[4 * p + 2]), add2(r.w, pk[4 * p + 3])};
#pragma unroll
        for (int i = 0; i < 4; i++) {
          const float a = acc[8 * p + 2 * i] + lo_f(rr[i]), b = acc[8 * p + 2 * i + 1] + hi_f(rr[i]);
          pk[4 * p + i] = pack2(silu_half(a), silu_half(b));
        }
        pin<4>(pk + 4 * p);
      };
      const uint32_t xa = sb + OFF_X + (warp * 16 + (lane & 15)) * 128 + (((lane >> 4) ^ (lane & 7)) << 4);
      auto x_piece = [&](int i) { const uint4 v = ldsm((xa ^ ((i & 3) << 5)) + (i >> 2) * 16384); pk[32 + 4 * i] = v.x; pk[33 + 4 * i] = v.y; pk[34 + 4 * i] = v.z; pk[35 + 4 * i] = v.w; };
      p2_step<0>(accs, c);
      p2_step<1>(accs, c);
      mbar_spin(sb + B_E1 + 8, 0, c.zero);
      send_piece(0); send_piece(1);
      p2_step<2>(accs, c); sched_fence(c.zero); send_piece(2); send_piece(3);
      p2_step<3>(accs, c); sched_fence(c.zero); send_piece(4); send_piece(5);
      p2_step<4>(accs, c); mbar_spin(sb + B_XT, 0, c.zero); send_piece(6); send_piece(7);
      p2_step<5>(accs, c); mbar_spin(sb + B_EX + 16 * wg, 0, c.zero); silu_piece(0); x_piece(0);
      p2_step<6>(accs, c); sched_fence(c.zero); silu_piece(1); x_piece(1);
      p2_step<7>(accs, c); sched_fence(c.zero); silu_piece(2); x_piece(2);
      p2_step<8>(accs, c); sched_fence(c.zero); silu_piece(3); x_piece(3);
      p2_step<9>(accs, c); mbar_spin(sb + B_EX + 16 * wg + 8, 0, c.zero); silu_piece(4); x_piece(4);
      p2_step<10>(accs, c); sched_fence(c.zero); silu_piece(5); x_piece(5);
      p2_step<11>(accs, c); sched_fence(c.zero); silu_piece(6); x_piece(6); x_piece(7);
      if (wg == 1) silu_piece(7);
      p2_step<12>(accs, c); p2_step<13>(accs, c); p2_step<14>(accs, c); p2_step<15>(accs, c);
      if (c.do_rel) mbar_arrive(sb + B_DONE);
      if (wg == 0) silu_piece(7);
      wg_wait<0>();
#pragma unroll
      for (int i = 0; i < 8; i++) {
        uint32_t v[4];
#pragma unroll
        for (int k = 0; k < 4; k++) v[k] = fma2(pack2(accs[8 * i + 2 * k], accs[1 + 8 * i + 2 * k]), pk[4 * i + k], pk[32 + 4 * i + k]);
        asm volatile("stmatrix.sync.aligned.m8n8.x4.shared.b16 [%0], {%1,%2,%3,%4};" ::"r"((xa ^ ((i & 3) << 5)) + (i >> 2) * 16384), "r"(v[0]), "r"(v[1]), "r"(v[2]), "r"(v[3]) : "memory");
        if (i == 3 || i == 7) {
          asm volatile("fence.proxy.async.shared::cta;" ::: "memory");
          __syncwarp();
          if (elect_one()) tma3d_store(&mp.out, sb + OFF_X + (i >> 2) * 16384 + warp * 2048, j2 * 128 + (i >> 2) * 64, m2 * 64 + w * 16, wg);
        }
      }
      if (elect_one()) { asm volatile("cp.async.bulk.commit_group;\ncp.async.bulk.wait_group.read 0;" ::: "memory"); }
      if ((threadIdx.x & 127) == 0) { TS(33 + wg * 16); if (wg) { TG(59); unsigned id; asm volatile("mov.u32 %0, %%smid;" : "=r"(id)); TSV(60, id); } }
    }
  }
}

typedef CUresult (*EncodeFn)(CUtensorMap*, CUtensorMapDataType, cuuint32_t, void*, const cuuint64_t*, const cuuint64_t*, const cuuint32_t*, const cuuint32_t*,
                             CUtensorMapInterleave, CUtensorMapSwizzle, CUtensorMapL2promotion, CUtensorMapFloatOOBfill);

void encode(EncodeFn fn, CUtensorMap* tm, const void* p, int rank, const cuuint64_t* dims, const cuuint64_t* strides, const cuuint32_t* box) {
  const cuuint32_t es[5] = {1, 1, 1, 1, 1};
  fn(tm, CU_TENSOR_MAP_DATA_TYPE_BFLOAT16, rank, const_cast<void*>(p), dims, strides, box, es, CU_TENSOR_MAP_INTERLEAVE_NONE, CU_TENSOR_MAP_SWIZZLE_128B,
     PROMO, CU_TENSOR_MAP_FLOAT_OOB_FILL_NONE);
}

}

extern "C" void kernel_launch(void* const* d_in, const int* in_sizes, int n_in, void* d_out, int out_size) {
  (void)in_sizes; (void)n_in; (void)out_size;
  static EncodeFn fn = nullptr;
  static Scratch* gs = nullptr;
  if (!fn) {
    void* p = nullptr;
    cudaDriverEntryPointQueryResult qr;
    cudaGetDriverEntryPoint("cuTensorMapEncodeTiled", &p, cudaEnableDefault, &qr);
    fn = (EncodeFn)p;
    cudaGetSymbolAddress((void**)&gs, g_scratch);
    cudaFuncSetAttribute(fused_kernel, cudaFuncAttributeMaxDynamicSharedMemorySize, SMEM_BYTES);
  }
  const void *x = d_in[0], *wqkv = d_in[1], *wo = d_in[2], *wg = d_in[4], *wu = d_in[5], *wd = d_in[6];
  Maps mp;
  {
    const cuuint64_t dims[3] = {DM, SEQ / 2, 2}, st[2] = {DM * 4, DM * 2};
    const cuuint32_t box_in[3] = {64, 64, 2}, box_out[3] = {64, 16, 1};
    encode(fn, &mp.x, x, 3, dims, st, box_in);
    encode(fn, &mp.out, d_out, 3, dims, st, box_out);
  }
  {
    const cuuint64_t dims[2] = {DM, SEQ}, st[1] = {DM * 2};
    const cuuint32_t box[2] = {64, 128};
    encode(fn, &mp.xn, gs->xn, 2, dims, st, box);
  }
  {
    const cuuint32_t box[2] = {64, 64};
    const cuuint64_t dq[2] = {3 * DM, DM}, sq[1] = {3 * DM * 2}, df[2] = {DFF, DM}, sf[1] = {DFF * 2}, dw[2] = {DM, DM}, sw[1] = {DM * 2};
    encode(fn, &mp.wqkv, wqkv, 2, dq, sq, box);
    encode(fn, &mp.wg, wg, 2, df, sf, box);
    encode(fn, &mp.wu, wu, 2, df, sf, box);
    encode(fn, &mp.wo, wo, 2, dw, sw, box);
  }
  {
    const cuuint32_t box[5] = {64, 2, 4, 4, 2};
    const cuuint64_t st[4] = {DM * 2, 8 * DM * 2, 2 * DM * 2, 32 * DM * 2};
    const cuuint64_t dd[5] = {DM, 2, 4, 4, DFF / 32};
    encode(fn, &mp.wd, wd, 5, dd, st, box);
  }
  fused_kernel<<<NCTA, 384, SMEM_BYTES>>>((const uint4*)x, (const uint4*)wg, (const uint4*)wu, gs, mp);
}
```

```cpp
#include <cuda_runtime.h>
#include <cuda_bf16.h>
#include <cuda.h>
#include <stdint.h>

#define PROMO CU_TENSOR_MAP_L2_PROMOTION_L2_128B
#define PF_D 6
#define LAG2 4
#define POLL_NS "200"
#define CS_KB 8
#define LN_KB 4

#define EVICT_FIRST 0x12F0000000000000ull
#define EVICT_NORMAL 0x1000000000000000ull
#define HINT_OUT EVICT_FIRST
#define HINT_W EVICT_FIRST
#define HINT_H EVICT_FIRST
#define HINT_LAST EVICT_FIRST

namespace {

constexpr int SEQ = 2048, DM = 1024, DFF = 3584;
constexpr int NMAIN = 128, NCTA = 132;

constexpr uint32_t SM_BASE = 0x400;
constexpr uint32_t P1_BYTES = 49152, P2_BYTES = 32768;
constexpr uint32_t OFF_A = 131072;
__host__ __device__ constexpr uint32_t p2_a(int s) { return s == 0 ? OFF_A + 32768 : s == 1 ? OFF_A + 49152 : s == 2 ? 114688 : s == 3 ? 16384 : 49152; }
__host__ __device__ constexpr uint32_t p2_b(int s) { return s < 3 ? 65536 + s * 16384 : (s - 3) * 32768; }
constexpr uint32_t OFF_LAND = OFF_A;
constexpr uint32_t OFF_X = 196608;
constexpr uint32_t OFF_CS = OFF_X + 14336;
constexpr uint32_t OFF_BAR = 229376;
constexpr uint32_t B_F1 = OFF_BAR, B_E1 = B_F1 + 32, B_E2 = B_E1 + 32, B_DONE = B_E2 + 40, B_F2 = B_DONE + 8, B_DEP = B_F2 + 40, B_CS = B_DEP + 48,
                   B_XT = B_CS + 16, B_EP = B_XT + 8, B_EX = B_EP + 8, B_AUX = B_EX + 32, B_HALO = B_AUX + 8, OFF_EPOCH = B_HALO + 16;
constexpr uint32_t SMEM_BYTES = 232448;
constexpr uint32_t AT_V = 0, AT_K = 8192, AT_REM = 11264, AT_WG = 15360;

constexpr int FL_XN = 0, FL_H = 16, FL_P = 80, FL_HALO = 96, FL_N = FL_HALO + 256;
struct __align__(1024) Scratch {
  uint4 h[16 * 56 * 1024];
  uint4 o[16 * 16 * 1024];
  uint4 xn[SEQ * DM / 8];
  uint4 dpart[128 * 8 * 256];
  uint4 halo[2 * 128 * 2 * 128];
  ulonglong2 cspart[8 * 16 * 128];
  unsigned long long stats[SEQ];
  unsigned flags[FL_N * 32];
  unsigned epoch[NCTA * 2];
};
__device__ Scratch g_scratch;
#define TG(i) do {} while (0)
#define TSV(i, v) do {} while (0)
#define TS(i) do {} while (0)

struct Maps { CUtensorMap x, xn, out, wqkv, wg, wu, wd, wo; };

__device__ __forceinline__ void mbar_init(uint32_t bar, uint32_t cnt) { asm volatile("mbarrier.init.shared::cta.b64 [%0], %1;" ::"r"(bar), "r"(cnt)); }
__device__ __forceinline__ void mbar_expect_tx(uint32_t bar, uint32_t bytes) { asm volatile("mbarrier.arrive.expect_tx.shared::cta.b64 _, [%0], %1;" ::"r"(bar), "r"(bytes) : "memory"); }
__device__ __forceinline__ void mbar_arrive(uint32_t bar) { asm volatile("mbarrier.arrive.shared::cta.b64 _, [%0];" ::"r"(bar) : "memory"); }
__device__ __forceinline__ void mbar_arrive_cl(uint32_t bar) { asm volatile("mbarrier.arrive.shared::cluster.b64 _, [%0];" ::"r"(bar) : "memory"); }
__device__ __forceinline__ uint32_t mapa(uint32_t a, uint32_t cta) { uint32_t r; asm("mapa.shared::cluster.u32 %0, %1, %2;" : "=r"(r) : "r"(a), "r"(cta)); return r; }
__device__ __forceinline__ void mbar_wait(uint32_t bar, uint32_t parity) {
  asm volatile("{\n.reg .pred p;\n.reg .u32 n;\nmov.u32 n, 0;\nLAB_WAIT:\nmbarrier.try_wait.parity.shared::cta.b64 p, [%0], %1;\n@p bra LAB_DONE;\n"
               "add.u32 n, n, 1;\nsetp.gt.u32 p, n, 4000000;\n@p trap;\nbra LAB_WAIT;\nLAB_DONE:\n}" ::"r"(bar), "r"(parity) : "memory");
}
__device__ __forceinline__ void mbar_spin(uint32_t bar, uint32_t parity, uint32_t zero) {
  asm volatile("{\n.reg .pred p, z;\nsetp.ne.u32 z, %2, 0;\nLAB_WAIT:\nmbarrier.try_wait.parity.shared::cta.b64 p, [%0], %1;\n@p bra LAB_DONE;\n@z trap;\nbra LAB_WAIT;\nLAB_DONE:\n}" ::"r"(bar), "r"(parity), "r"(zero) : "memory");
}
__device__ __forceinline__ void flag_wait(const unsigned* f, unsigned target) {
  asm volatile("{\n.reg .pred p;\n.reg .u32 n, v;\nmov.u32 n, 0;\nLAB_WAIT:\nld.relaxed.gpu.global.u32 v, [%0];\nsub.u32 v, v, %1;\nsetp.ge.s32 p, v, 0;\n@p bra LAB_DONE;\n"
               "nanosleep.u32 " POLL_NS ";\nadd.u32 n, n, 1;\nsetp.gt.u32 p, n, 4000000;\n@p trap;\nbra LAB_WAIT;\nLAB_DONE:\nfence.acquire.gpu;\n}" ::"l"(f), "r"(target) : "memory");
}
__device__ __forceinline__ void flag_add(unsigned* f) { asm volatile("red.release.gpu.global.add.u32 [%0], 1;" ::"l"(f) : "memory"); }
__device__ __forceinline__ void fence_async() { asm volatile("fence.proxy.async.global;" ::: "memory"); }
__device__ __forceinline__ bool elect_one() { uint32_t p; asm volatile("{\n.reg .pred P;\nelect.sync _|P, 0xffffffff;\nselp.u32 %0, 1, 0, P;\n}" : "=r"(p)); return p; }
__device__ __forceinline__ void bar_sync(int id, int n) { asm volatile("bar.sync %0, %1;" ::"r"(id), "r"(n) : "memory"); }
__device__ __forceinline__ void bar_arrive(int id, int n) { asm volatile("bar.arrive %0, %1;" ::"r"(id), "r"(n) : "memory"); }

__device__ __forceinline__ void tma2d(uint32_t dst, const CUtensorMap* tm, uint32_t bar, int c0, int c1, uint64_t hint) {
  asm volatile("cp.async.bulk.tensor.2d.shared::cluster.global.mbarrier::complete_tx::bytes.L2::cache_hint [%0], [%1, {%3, %4}], [%2], %5;" ::"r"(dst), "l"(tm), "r"(bar), "r"(c0), "r"(c1), "l"(hint) : "memory");
}
__device__ __forceinline__ void tma2d_mc(uint32_t dst, const CUtensorMap* tm, uint32_t bar, int c0, int c1, uint64_t hint) {
  asm volatile("cp.async.bulk.tensor.2d.shared::cluster.global.mbarrier::complete_tx::bytes.multicast::cluster.L2::cache_hint [%0], [%1, {%3, %4}], [%2], %5, %6;" ::"r"(dst), "l"(tm), "r"(bar), "r"(c0), "r"(c1), "h"((uint16_t)3), "l"(hint) : "memory");
}
__device__ __forceinline__ void tma3d(uint32_t dst, const CUtensorMap* tm, uint32_t bar, int c0, int c1, int c2, uint64_t hint) {
  asm volatile("cp.async.bulk.tensor.3d.shared::cluster.global.mbarrier::complete_tx::bytes.L2::cache_hint [%0], [%1, {%3, %4, %5}], [%2], %6;" ::"r"(dst), "l"(tm), "r"(bar), "r"(c0), "r"(c1), "r"(c2), "l"(hint) : "memory");
}
__device__ __forceinline__ void tma5d(uint32_t dst, const CUtensorMap* tm, uint32_t bar, int c0, int c4, uint64_t hint) {
  asm volatile("cp.async.bulk.tensor.5d.shared::cluster.global.mbarrier::complete_tx::bytes.L2::cache_hint [%0], [%1, {%3, %5, %5, %5, %4}], [%2], %6;" ::"r"(dst), "l"(tm), "r"(bar), "r"(c0), "r"(c4), "r"(0), "l"(hint) : "memory");
}
__device__ __forceinline__ void tma5d_prefetch(const CUtensorMap* tm, int c0, int c4) {
  asm volatile("cp.async.bulk.prefetch.tensor.5d.L2.global [%0, {%1, %3, %3, %3, %2}];" ::"l"(tm), "r"(c0), "r"(c4), "r"(0) : "memory");
}
__device__ __forceinline__ void tma3d_store(const CUtensorMap* tm, uint32_t src, int c0, int c1, int c2) {
  asm volatile("cp.async.bulk.tensor.3d.global.shared::cta.bulk_group.L2::cache_hint [%0, {%2, %3, %4}], [%1], %5;" ::"l"(tm), "r"(src), "r"(c0), "r"(c1), "r"(c2), "l"(HINT_OUT) : "memory");
}
__device__ __forceinline__ void bulk_load(uint32_t dst, const void* src, uint32_t bytes, uint32_t bar, uint64_t hint) {
  asm volatile("cp.async.bulk.shared::cluster.global.mbarrier::complete_tx::bytes.L2::cache_hint [%0], [%1], %2, [%3], %4;" ::"r"(dst), "l"(src), "r"(bytes), "r"(bar), "l"(hint) : "memory");
}
__device__ __forceinline__ void bulk_load_mc(uint32_t dst, const void* src, uint32_t bytes, uint32_t bar, uint64_t hint) {
  asm volatile("cp.async.bulk.shared::cluster.global.mbarrier::complete_tx::bytes.multicast::cluster.L2::cache_hint [%0], [%1], %2, [%3], %4, %5;" ::"r"(dst), "l"(src), "r"(bytes), "r"(bar), "h"((uint16_t)3), "l"(hint) : "memory");
}
__device__ __forceinline__ uint4 lds128(uint32_t a) { uint4 v; asm volatile("ld.shared.v4.b32 {%0,%1,%2,%3}, [%4];" : "=r"(v.x), "=r"(v.y), "=r"(v.z), "=r"(v.w) : "r"(a) : "memory"); return v; }
__device__ __forceinline__ void sts128(uint32_t a, uint4 v) { asm volatile("st.shared.v4.b32 [%0], {%1,%2,%3,%4};" ::"r"(a), "r"(v.x), "r"(v.y), "r"(v.z), "r"(v.w) : "memory"); }
__device__ __forceinline__ void stg128(void* p, uint32_t a, uint32_t b, uint32_t c, uint32_t d) { asm volatile("st.global.v4.b32 [%0], {%1,%2,%3,%4};" ::"l"(p), "r"(a), "r"(b), "r"(c), "r"(d) : "memory"); }

__device__ __forceinline__ uint32_t pack2(float lo, float hi) { uint32_t r; asm("cvt.rn.bf16x2.f32 %0, %1, %2;" : "=r"(r) : "f"(hi), "f"(lo)); return r; }
__device__ __forceinline__ float lo_f(uint32_t v) { return __uint_as_float(v << 16); }
__device__ __forceinline__ float hi_f(uint32_t v) { return __uint_as_float(v & 0xffff0000u); }
__device__ __forceinline__ float bf16r(float v) { return lo_f(pack2(v, 0.f)); }
__device__ __forceinline__ uint32_t mul2(uint32_t a, uint32_t b) { uint32_t r; asm("mul.rn.bf16x2 %0, %1, %2;" : "=r"(r) : "r"(a), "r"(b)); return r; }
__device__ __forceinline__ uint32_t add2(uint32_t a, uint32_t b) { uint32_t r; asm("add.rn.bf16x2 %0, %1, %2;" : "=r"(r) : "r"(a), "r"(b)); return r; }
__device__ __forceinline__ uint32_t sub2(uint32_t a, uint32_t b) { uint32_t r; asm("sub.rn.bf16x2 %0, %1, %2;" : "=r"(r) : "r"(a), "r"(b)); return r; }
__device__ __forceinline__ uint32_t fma2(uint32_t a, uint32_t b, uint32_t c) { uint32_t r; asm("fma.rn.bf16x2 %0, %1, %2, %3;" : "=r"(r) : "r"(a), "r"(b), "r"(c)); return r; }
__device__ __forceinline__ uint32_t max2(uint32_t a, uint32_t b) { uint32_t r; asm("max.bf16x2 %0, %1, %2;" : "=r"(r) : "r"(a), "r"(b)); return r; }
__device__ __forceinline__ float ex2f(float x) { float y; asm("ex2.approx.ftz.f32 %0, %1;" : "=f"(y) : "f"(x)); return y; }
__device__ __forceinline__ float rcpf(float x) { float y; asm("rcp.approx.ftz.f32 %0, %1;" : "=f"(y) : "f"(x)); return y; }
constexpr float GELU_C1 = 0.7978845608028654f, GELU_C3 = 0.035677408136300125f;
__device__ __forceinline__ float gelu_k(float g, float c1, float c3, float k) {
  float t;
  asm("tanh.approx.f32 %0, %1;" : "=f"(t) : "f"(g * fmaf(g * g, c3, c1)));
  g *= k;
  return fmaf(g, t, g);
}
__device__ __forceinline__ float silu_half(float z) { float t; asm("tanh.approx.f32 %0, %1;" : "=f"(t) : "f"(z)); return fmaf(z, t, z); }

__device__ __forceinline__ void wg_fence() { asm volatile("wgmma.fence.sync.aligned;" ::: "memory"); }
__device__ __forceinline__ void wg_commit() { asm volatile("wgmma.commit_group.sync.aligned;" ::: "memory"); }
template <int N> __device__ __forceinline__ void wg_wait() { asm volatile("wgmma.wait_group.sync.aligned %0;" ::"n"(N) : "memory"); }
#define A8(o) "+f"(d[(o)]), "+f"(d[(o) + 1]), "+f"(d[(o) + 2]), "+f"(d[(o) + 3]), "+f"(d[(o) + 4]), "+f"(d[(o) + 5]), "+f"(d[(o) + 6]), "+f"(d[(o) + 7])
#define A64(o) A8(o), A8((o) + 8), A8((o) + 16), A8((o) + 24), A8((o) + 32), A8((o) + 40), A8((o) + 48), A8((o) + 56)
#define REGS0_63 "%0,%1,%2,%3,%4,%5,%6,%7,%8,%9,%10,%11,%12,%13,%14,%15,%16,%17,%18,%19,%20,%21,%22,%23,%24,%25,%26,%27,%28,%29,%30,%31," \
                 "%32,%33,%34,%35,%36,%37,%38,%39,%40,%41,%42,%43,%44,%45,%46,%47,%48,%49,%50,%51,%52,%53,%54,%55,%56,%57,%58,%59,%60,%61,%62,%63"
#define REGS64_127 "%64,%65,%66,%67,%68,%69,%70,%71,%72,%73,%74,%75,%76,%77,%78,%79,%80,%81,%82,%83,%84,%85,%86,%87,%88,%89,%90,%91,%92,%93,%94,%95," \
                   "%96,%97,%98,%99,%100,%101,%102,%103,%104,%105,%106,%107,%108,%109,%110,%111,%112,%113,%114,%115,%116,%117,%118,%119,%120,%121,%122,%123,%124,%125,%126,%127"
__device__ __forceinline__ void desc_add(uint64_t& x, int v) { asm volatile("{\n.reg .b32 lo, hi;\nmov.b64 {lo, hi}, %0;\nadd.s32 lo, lo, %1;\nmov.b64 %0, {lo, hi};\n}" : "+l"(x) : "r"(v)); }
template <int ACCUM> __device__ __forceinline__ void wgmma256(float (&d)[128], uint64_t& a, uint64_t& b, int da, int db) {
  asm volatile("{\n.reg .pred p;\nsetp.ne.b32 p, %130, 0;\n"
               "wgmma.mma_async.sync.aligned.m64n256k16.f32.bf16.bf16 {" REGS0_63 "," REGS64_127 "}, %128, %129, p, 1, 1, 0, 1;\n}"
               : A64(0), A64(64) : "l"(a), "l"(b), "n"(ACCUM));
  desc_add(a, da); desc_add(b, db);
}
__device__ __forceinline__ void wgmma256_rs(float (&d)[128], uint32_t a0, uint32_t a1, uint32_t z0, uint32_t z1, uint32_t b_lo) {
  asm volatile("{\n.reg .b64 db;\nmov.b64 db, {%132, 0x00000008};\n"
               "wgmma.mma_async.sync.aligned.m64n256k16.f32.bf16.bf16 {" REGS0_63 "," REGS64_127 "}, {%128,%129,%130,%131}, db, 1, 1, 1, 0;\n}"
               : A64(0), A64(64) : "r"(a0), "r"(a1), "r"(z0), "r"(z1), "r"(b_lo));
}
template <int ACCUM> __device__ __forceinline__ void wgmma128(float (&d)[64], uint64_t& a, uint64_t& b, int da, int db) {
  asm volatile("{\n.reg .pred p;\nsetp.ne.b32 p, %66, 0;\n"
               "wgmma.mma_async.sync.aligned.m64n128k16.f32.bf16.bf16 {" REGS0_63 "}, %64, %65, p, 1, 1, 0, 1;\n}"
               : A64(0) : "l"(a), "l"(b), "n"(ACCUM));
  desc_add(a, da); desc_add(b, db);
}
template <int ACCUM> __device__ __forceinline__ void hmma(float (&c)[4], uint32_t a0, uint32_t a1, uint32_t a2, uint32_t a3, uint32_t b0, uint32_t b1) {
  if (ACCUM)
    asm volatile("mma.sync.aligned.m16n8k16.row.col.f32.bf16.bf16.f32 {%0,%1,%2,%3}, {%4,%5,%6,%7}, {%8,%9}, {%0,%1,%2,%3};"
                 : "+f"(c[0]), "+f"(c[1]), "+f"(c[2]), "+f"(c[3]) : "r"(a0), "r"(a1), "r"(a2), "r"(a3), "r"(b0), "r"(b1));
  else
    asm volatile("mma.sync.aligned.m16n8k16.row.col.f32.bf16.bf16.f32 {%0,%1,%2,%3}, {%4,%5,%6,%7}, {%8,%9}, {%10,%10,%10,%10};"
                 : "=f"(c[0]), "=f"(c[1]), "=f"(c[2]), "=f"(c[3]) : "r"(a0), "r"(a1), "r"(a2), "r"(a3), "r"(b0), "r"(b1), "f"(0.f));
}
__device__ __forceinline__ uint32_t movm(uint32_t a) { uint32_t d; asm volatile("movmatrix.sync.aligned.m8n8.trans.b16 %0, %1;" : "=r"(d) : "r"(a)); return d; }
__device__ __forceinline__ int lane_here() { int v; asm volatile("mov.u32 %0, %%laneid;" : "=r"(v)); return v; }
template <int N> __device__ __forceinline__ void pin(uint32_t* r) {
#pragma unroll
  for (int i = 0; i < N; i++) asm volatile("" : "+r"(r[i]));
}
template <int N> __device__ __forceinline__ void pin(float* r) {
#pragma unroll
  for (int i = 0; i < N; i++) asm volatile("" : "+f"(r[i]));
}
__device__ __forceinline__ void sched_fence(uint32_t zero) {
  asm volatile("{\n.reg .pred p;\nsetp.eq.u32 p, %0, 0;\nLAB_F:\n@p bra.uni LAB_D;\nnanosleep.u32 0;\nbra.uni LAB_F;\nLAB_D:\n}" ::"r"(zero) : "memory");
}
__device__ __forceinline__ uint4 ldsm(uint32_t a) { uint4 v; asm volatile("ldmatrix.sync.aligned.m8n8.x4.shared.b16 {%0,%1,%2,%3}, [%4];" : "=r"(v.x), "=r"(v.y), "=r"(v.z), "=r"(v.w) : "r"(a) : "memory"); return v; }
__device__ __forceinline__ uint4 ldsm_t(uint32_t a) { uint4 v; asm volatile("ldmatrix.sync.aligned.m8n8.x4.trans.shared.b16 {%0,%1,%2,%3}, [%4];" : "=r"(v.x), "=r"(v.y), "=r"(v.z), "=r"(v.w) : "r"(a) : "memory"); return v; }

constexpr int BAR_LAG = 1, BAR_MMA = 2, BAR_EV = 3;

struct Cons {
  uint32_t sb;
  mutable uint64_t a, b;
  int k1, k2, k4, k4w, b1;
  uint32_t rel;
  bool do_rel;
  int wg;
  uint32_t zero;
};
#define REL_TS(n) TS(64 + (n))
constexpr uint32_t DB_LO = (SM_BASE >> 4) | ((8192 >> 4) << 16);

template <int ST, int ACCUM, bool WAIT = true> __device__ __forceinline__ void p1_issue(float (&acc)[128], const Cons& c, uint32_t parity) {
  if (WAIT) mbar_spin(c.sb + B_F1 + 8 * ST, parity, c.zero);
  wg_fence();
  wgmma256<ACCUM>(acc, c.a, c.b, c.k1, c.b1);
  wgmma256<1>(acc, c.a, c.b, c.k2, c.b1);
  wgmma256<1>(acc, c.a, c.b, c.k1, c.b1);
  wgmma256<1>(acc, c.a, c.b, ST == 3 ? c.k4w : c.k4, ST == 3 ? -6144 - 384 : 2048 - 384);
  wg_commit();
}
__device__ __forceinline__ void release(const Cons& c, uint32_t bar) { if (c.do_rel) mbar_arrive_cl(c.rel + bar); }
template <int KB, bool WAIT = true> __device__ __forceinline__ void p1_step(float (&acc)[128], const Cons& c) {
  if (KB == 15) { if (c.wg == 1) { wg_wait<0>(); release(c, B_E1 + 16); bar_sync(BAR_LAG, 256); } }
  p1_issue<KB & 3, KB != 0, WAIT>(acc, c, (KB >> 2) & 1);
  if (KB == 15) { if (c.wg == 0) bar_arrive(BAR_LAG, 256); }
  if (KB > 0) { wg_wait<1>(); if (KB != 15 || c.wg == 0) release(c, B_E1 + 8 * ((KB - 1) & 3)); }
  if (KB == 15) { wg_wait<0>(); release(c, B_E1 + 24); }
}
template <class F> __device__ __forceinline__ void p1_loop(float (&acc)[128], const Cons& c, int from, int to, F&& shadow) {
#pragma unroll 1
  for (int kb = from; kb < to; kb++) {
    const bool wrap = (kb & 3) == 3;
    mbar_spin(c.sb + B_F1 + 8 * (kb & 3), (kb >> 2) & 1, c.zero);
    wg_fence();
    wgmma256<1>(acc, c.a, c.b, c.k1, c.b1);
    wgmma256<1>(acc, c.a, c.b, c.k2, c.b1);
    wgmma256<1>(acc, c.a, c.b, c.k1, c.b1);
    wgmma256<1>(acc, c.a, c.b, wrap ? c.k4w : c.k4, wrap ? -6144 - 384 : 2048 - 384);
    wg_commit();
    wg_wait<1>();
    release(c, B_E1 + 8 * ((kb - 1) & 3));
    shadow(kb);
  }
}
template <int T> __device__ __forceinline__ void p2_step(float (&acc)[64], const Cons& c) {
  if (T == 16 - LAG2) { if (c.wg == 1) bar_sync(BAR_LAG, 256); }
  mbar_spin(c.sb + B_F2 + 8 * (T % 5), (T / 5) & 1, c.zero);
  wg_fence();
  wgmma128<T != 0>(acc, c.a, c.b, c.k1, c.b1);
  wgmma128<1>(acc, c.a, c.b, c.k2, c.b1);
  wgmma128<1>(acc, c.a, c.b, c.k1, c.b1);
  wgmma128<1>(acc, c.a, c.b, ((int)p2_a((T + 1) % 5) - (int)p2_a(T % 5)) / 16 - 514, ((int)p2_b((T + 1) % 5) - (int)p2_b(T % 5)) / 16 - 384);
  wg_commit();
  if (T == 15) { if (c.wg == 0) bar_arrive(BAR_LAG, 256); }
  if (T <= 11) { wg_wait<1>(); release(c, T ? B_E2 + 8 * ((T + 5 - 1) % 5) : B_E1 + 8); }
}

template <int P> __device__ __forceinline__ void geglu_piece(uint32_t (&pk)[64], uint8_t* dst, float (&rs)[2]) {
  constexpr int cg = P >> 1, r = P & 1;
  pin<1>(rs + r);
#pragma unroll
  for (int i = 0; i < 4; i++) pin<1>(pk + 2 * (4 * cg + i) + r);
  const float r2 = rs[r] * rs[r], c1 = GELU_C1 * rs[r], c3 = GELU_C3 * r2 * rs[r], k = 0.25f * r2;
  uint32_t v[4];
#pragma unroll
  for (int i = 0; i < 4; i++) {
    const uint32_t g = pk[2 * (4 * cg + i) + r];
    v[i] = mul2(pack2(gelu_k(lo_f(g), c1, c3, k), gelu_k(hi_f(g), c1, c3, k)), pk[32 + 2 * (4 * cg + i) + r]);
  }
  stg128(dst + cg * 8192 + r * 512, v[0], v[1], v[2], v[3]);
}
__device__ __forceinline__ void geglu_tile(float (&acc)[128], uint32_t (&pk)[64], const Cons& c, int to, uint8_t* dst, int ev, float (&rs)[2]) {
  const int lane = lane_here();
  dst += (lane ^ (lane >> 3)) << 4;
  p1_loop(acc, c, 1, to, [&](int kb) {
    if (kb <= 4) {
      if (kb <= 2) { if (kb == 1) geglu_piece<0>(pk, dst, rs); else geglu_piece<1>(pk, dst, rs); }
      else { if (kb == 3) geglu_piece<2>(pk, dst, rs); else geglu_piece<3>(pk, dst, rs); }
    } else if (kb <= 8) {
      if (kb <= 6) { if (kb == 5) geglu_piece<4>(pk, dst, rs); else geglu_piece<5>(pk, dst, rs); }
      else { if (kb == 7) geglu_piece<6>(pk, dst, rs); else { geglu_piece<7>(pk, dst, rs); bar_arrive(ev, 288); } }
    }
  });
}

__device__ __forceinline__ void attn_tile(float (&acc)[128], uint32_t (&pk)[64], const Cons& c, int round, int warp, int m, Scratch* gs, uint8_t* hdst, uint8_t* odst) {
  const int w = warp & 3;
  const uint32_t at = c.sb + OFF_X + c.wg * AT_WG;
  int lane = lane_here();
  hdst += (lane ^ (lane >> 3)) << 4;
  auto scatter = [&]() {
    const int lane = lane_here();
    const uint32_t swz = (lane ^ (lane >> 3)) << 4;
#pragma unroll
    for (int i = 0; i < 4; i++) {
      const int h = i & 1, r = i >> 1;
      sts128(at + AT_V + (2 * w + r) * 1024 + h * 512 + swz, make_uint4(pk[32 + 8 * h + r], pk[34 + 8 * h + r], pk[36 + 8 * h + r], pk[38 + 8 * h + r]));
    }
    if (w < 3) {
#pragma unroll
      for (int i = 0; i < 8; i++) asm volatile("st.shared.b32 [%0], %1;" ::"r"(at + AT_K + w * 1024 + i * 128 + lane * 4), "r"(pk[17 + 2 * i]) : "memory");
    } else {
      uint8_t* g = (uint8_t*)gs->halo + ((round * 128 + blockIdx.x) * 2 + c.wg) * 2048;
#pragma unroll
      for (int i = 0; i < 8; i++) asm volatile("st.global.b32 [%0], %1;" ::"l"(g + i * 128 + lane * 4), "r"(pk[17 + 2 * i]) : "memory");
#pragma unroll
      for (int h = 0; h < 2; h++) stg128(g + 1024 + h * 512 + swz, pk[33 + 8 * h], pk[35 + 8 * h], pk[37 + 8 * h], pk[39 + 8 * h]);
      bar_arrive(BAR_EV + 2 + round, 96);
    }
    __syncwarp();
    if (lane == 0) mbar_arrive(c.sb + B_HALO + 8 * round);
    if (round) {
#pragma unroll
      for (int p = 0; p < 4; p++) {
        const int o = 32 + 8 * (p >> 1) + (p & 1);
        asm volatile("ld.global.cg.v4.b32 {%0,%1,%2,%3}, [%4];" : "=r"(pk[o]), "=r"(pk[o + 2]), "=r"(pk[o + 4]), "=r"(pk[o + 6]) : "l"(hdst + (p >> 1) * 8192 + (p & 1) * 512) : "memory");
      }
    }
  };
  auto gu_piece = [&](int p) {
    uint32_t v[4];
#pragma unroll
    for (int i = 0; i < 4; i++) {
      const int o = 8 * (p >> 1) + 2 * i + (p & 1);
      pin<1>(pk + 48 + o);
      const uint32_t g = pk[48 + o];
      v[i] = mul2(round ? pk[32 + o] : 0x3e803e80u, round ? g : pack2(gelu_k(lo_f(g), GELU_C1, GELU_C3, 1.0f), gelu_k(hi_f(g), GELU_C1, GELU_C3, 1.0f)));
    }
    stg128(hdst + (p >> 1) * 8192 + (p & 1) * 512, v[0], v[1], v[2], v[3]);
  };
  p1_step<1>(acc, c);
  scatter();
  p1_loop(acc, c, 2, 9, [&](int kb) {
    if (kb <= 4) { if (kb == 3) gu_piece(0); else if (kb == 4) gu_piece(1); }
    else if (kb == 5) gu_piece(2); else if (kb == 6) gu_piece(3);
  });
  const bool first = m == 0 && w == 0;
  uint32_t kl[16];
  mbar_spin(c.sb + B_HALO + 8 * round, 0, c.zero);
  lane = lane_here();
  {
    const uint32_t ka = at + lane * 4 + (w ? AT_K + (w - 1) * 1024 : (first ? AT_K : AT_REM + round * 2048));
#pragma unroll
    for (int i = 0; i < 8; i++) {
      asm volatile("ld.shared.b32 %0, [%1];" : "=r"(kl[2 * i]) : "r"(ka + i * 128) : "memory");
      kl[2 * i + 1] = pk[16 + 2 * i] | c.zero;
    }
  }
  float st[4][4];
  pin<16>(kl);
  bar_sync(BAR_MMA, 256);
  mbar_spin(c.sb + B_F1 + 8 * 1, 0, c.zero);
#pragma unroll
  for (int ks = 0; ks < 2; ks++) {
#pragma unroll
    for (int h = 0; h < 2; h++) {
      const int o = 8 * h + 4 * ks;
      if (ks == 0) { hmma<0>(st[2 * h], kl[o], kl[o + 1], kl[o + 2], kl[o + 3], pk[o], pk[o + 2]); hmma<0>(st[2 * h + 1], pk[16 + o], pk[17 + o], pk[18 + o], pk[19 + o], pk[o + 1], pk[o + 3]); }
      else { hmma<1>(st[2 * h], kl[o], kl[o + 1], kl[o + 2], kl[o + 3], pk[o], pk[o + 2]); hmma<1>(st[2 * h + 1], pk[16 + o], pk[17 + o], pk[18 + o], pk[19 + o], pk[o + 1], pk[o + 3]); }
    }
  }
  sched_fence(c.zero);
  bar_sync(BAR_MMA, 256);
  p1_step<9, false>(acc, c);
  sched_fence(c.zero);
  pin<16>(&st[0][0]);
  lane = lane_here();
  const int rho = lane >> 2, q = lane & 3;
  const bool le0 = 2 * q <= rho, le1 = 2 * q + 1 <= rho;
  uint32_t la[2], lb[2], mx[2];
#pragma unroll
  for (int h = 0; h < 2; h++) {
    uint32_t l[2];
#pragma unroll
    for (int r = 0; r < 2; r++) {
      const float (&t)[4] = st[2 * h + r];
      l[r] = movm(pack2(rho <= 2 * q ? t[2] : t[0], rho <= 2 * q + 1 ? t[3] : t[1]));
      l[r] = fma2(l[r], 0x3e353e35u, mul2(l[r], 0x379e379eu));
    }
    la[h] = __byte_perm(l[0], l[1], 0x5410); lb[h] = __byte_perm(l[0], l[1], 0x7632);
    if (first && !le0) la[h] = (la[h] & 0xffff0000u) | 0xce6eu;
    if (first && !le1) lb[h] = (lb[h] & 0xffff0000u) | 0xce6eu;
    mx[h] = max2(la[h], lb[h]);
  }
#pragma unroll
  for (int o = 1; o <= 2; o++) { mx[0] = max2(mx[0], __shfl_xor_sync(~0u, mx[0], o)); mx[1] = max2(mx[1], __shfl_xor_sync(~0u, mx[1], o)); }
  const float L2E = 1.4426950408889634f;
  float pr[2][4], z[4];
#pragma unroll
  for (int h = 0; h < 2; h++) {
    pr[h][0] = ex2f((lo_f(la[h]) - lo_f(mx[h])) * L2E); pr[h][1] = ex2f((lo_f(lb[h]) - lo_f(mx[h])) * L2E);
    pr[h][2] = ex2f((hi_f(la[h]) - hi_f(mx[h])) * L2E); pr[h][3] = ex2f((hi_f(lb[h]) - hi_f(mx[h])) * L2E);
    z[2 * h] = pr[h][0] + pr[h][1]; z[2 * h + 1] = pr[h][2] + pr[h][3];
  }
  p1_step<10>(acc, c);
#pragma unroll
  for (int o = 1; o <= 2; o++) {
#pragma unroll
    for (int i = 0; i < 4; i++) z[i] += __shfl_xor_sync(~0u, z[i], o);
  }
  const uint32_t LE = (le0 ? 0xffffu : 0u) | (le1 ? 0xffff0000u : 0u);
  uint32_t P[4][2];
  uint4 vt[4][2];
  {
    const uint32_t row = (lane & 7) * 64 + ((((lane >> 3) & 1) ^ ((lane & 7) >> 1)) << 4);
    const uint32_t v1 = at + AT_V + (2 * w + (lane >> 4)) * 1024 + row;
    const uint32_t v0 = (w || lane >= 16) ? v1 - 1024 : (first ? v1 : at + AT_REM + round * 2048 + 1024 + row);
#pragma unroll
    for (int i = 0; i < 4; i++) {
      const float rz = rcpf(z[i]);
      const uint32_t p = pack2(pr[i >> 1][2 * (i & 1)] * rz, pr[i >> 1][2 * (i & 1) + 1] * rz);
      P[i][0] = p & ~LE; P[i][1] = p & LE;
      const uint32_t a = ((i & 1) ? v1 : v0) + (i >> 1) * 512;
      vt[i][0] = ldsm_t(a); vt[i][1] = ldsm_t(a ^ 32);
    }
  }
  float ot[4][2][4];
  pin<8>(&P[0][0]);
  bar_sync(BAR_MMA, 256);
  mbar_spin(c.sb + B_F1 + 8 * 3, 0, c.zero);
#pragma unroll
  for (int i = 0; i < 8; i++) { const uint4& v = vt[i >> 1][i & 1]; hmma<0>(ot[i >> 1][i & 1], v.x, v.y, v.z, v.w, P[i >> 1][0], P[i >> 1][1]); }
  sched_fence(c.zero);
  bar_sync(BAR_MMA, 256);
  p1_step<11, false>(acc, c);
  sched_fence(c.zero);
  pin<32>(&ot[0][0][0]);
  lane = lane_here();
  odst += (lane ^ (lane >> 3)) << 4;
  auto o_piece = [&](int i) {
    stg128(odst + (i >> 1) * 8192 + (i & 1) * 512, movm(pack2(ot[i][0][0], ot[i][0][1])), movm(pack2(ot[i][0][2], ot[i][0][3])), movm(pack2(ot[i][1][0], ot[i][1][1])), movm(pack2(ot[i][1][2], ot[i][1][3])));
  };
  o_piece(0); o_piece(1);
  p1_step<12>(acc, c);
  o_piece(2); o_piece(3);
  if (round) bar_arrive(BAR_EV + 4, 288);
  p1_step<13>(acc, c);
}

__device__ __forceinline__ void ln_moments(const uint32_t* raw, float& c0, float& s, float& v) {
  c0 = lo_f(__shfl_sync(~0u, raw[0], 0));
  float ss[4] = {0.f, 0.f, 0.f, 0.f}, vv[4] = {0.f, 0.f, 0.f, 0.f};
#pragma unroll
  for (int i = 0; i < 16; i++) {
    const float a = lo_f(raw[i]) - c0, b = hi_f(raw[i]) - c0;
    ss[(2 * i) & 3] += a; ss[(2 * i + 1) & 3] += b;
    vv[(2 * i) & 3] = fmaf(a, a, vv[(2 * i) & 3]); vv[(2 * i + 1) & 3] = fmaf(b, b, vv[(2 * i + 1) & 3]);
  }
  s = (ss[0] + ss[1]) + (ss[2] + ss[3]); v = (vv[0] + vv[1]) + (vv[2] + vv[3]);
}
__device__ __forceinline__ void ln_reduce(float& s, float& v) {
#pragma unroll
  for (int o = 16; o; o >>= 1) { s += __shfl_xor_sync(~0u, s, o); v += __shfl_xor_sync(~0u, v, o); }
}
__device__ __forceinline__ uint32_t ln_finish(float c0, float s, float v) {
  s *= 1.0f / DM;
  float sd;
  asm("sqrt.approx.ftz.f32 %0, %1;" : "=f"(sd) : "f"(bf16r(bf16r(fmaxf(fmaf(v, 1.0f / DM, -s * s), 0.f)) + 1e-5f)));
  return pack2(c0 + s, sd);
}
__device__ __forceinline__ void ln_store(const uint32_t* raw, uint32_t st, uint4* dst) {
  const uint32_t m2 = __byte_perm(st, st, 0x1010);
  const float rinv = rcpf(hi_f(st));
  const uint32_t rh = pack2(rinv, rinv), rl = pack2(rinv - hi_f(rh), rinv - hi_f(rh));
#pragma unroll
  for (int c = 0; c < 4; c++) {
    uint32_t v[4];
#pragma unroll
    for (int i = 0; i < 4; i++) { const uint32_t t = sub2(raw[4 * c + i], m2); v[i] = fma2(t, rh, mul2(t, rl)); }
    stg128(dst + 32 * c, v[0], v[1], v[2], v[3]);
  }
}
__device__ __forceinline__ void col_sums(uint32_t tile, ulonglong2* part, uint32_t tag) {
  const int lane = threadIdx.x & 31;
  float cs[8] = {0, 0, 0, 0, 0, 0, 0, 0};
  uint32_t base = tile + ((lane >> 3) & 1) * 8192 + (lane >> 4) * 4096 + ((lane & 7) << 4);
#pragma unroll 1
  for (int k0 = 0; k0 < 8; k0++, base = (base ^ ((k0 ^ (k0 - 1)) << 4)) + 128) {
    uint4 v[4];
#pragma unroll
    for (int k = 0; k < 4; k++) v[k] = lds128(base + k * 1024);
#pragma unroll
    for (int k = 0; k < 4; k++) {
      cs[0] += lo_f(v[k].x); cs[1] += hi_f(v[k].x); cs[2] += lo_f(v[k].y); cs[3] += hi_f(v[k].y);
      cs[4] += lo_f(v[k].z); cs[5] += hi_f(v[k].z); cs[6] += lo_f(v[k].w); cs[7] += hi_f(v[k].w);
    }
  }
  const bool up = lane >= 16;
#pragma unroll
  for (int i = 0; i < 2; i++) {
    const float a = (up ? cs[4 + 2 * i] : cs[2 * i]) + __shfl_xor_sync(~0u, up ? cs[2 * i] : cs[4 + 2 * i], 16);
    const float b = (up ? cs[5 + 2 * i] : cs[1 + 2 * i]) + __shfl_xor_sync(~0u, up ? cs[1 + 2 * i] : cs[5 + 2 * i], 16);
    asm volatile("{\n.reg .b64 a, b;\nmov.b64 a, {%1, %3};\nmov.b64 b, {%2, %3};\nst.relaxed.gpu.global.v2.b64 [%0], {a, b};\n}"
                 ::"l"(part + 32 * (i + (up ? 2 : 0)) + (lane & 15)), "r"(__float_as_uint(a)), "r"(__float_as_uint(b)), "r"(tag) : "memory");
  }
  asm volatile("fence.proxy.async.shared::cta;" ::: "memory");
}

__global__ void __cluster_dims__(2, 1, 1) __launch_bounds__(384, 1)
fused_kernel(const uint4* __restrict__ x, const uint4* __restrict__ wgate, const uint4* __restrict__ wup, Scratch* gs, const __grid_constant__ Maps mp) {
  extern __shared__ __align__(1024) uint8_t smem_raw[];
  const uint32_t sb = (uint32_t)__cvta_generic_to_shared(smem_raw);
  if (threadIdx.x == 352) TS(63);
  if (threadIdx.x < 256 && blockIdx.x < NMAIN) {
    const uint32_t r = threadIdx.x >> 3, ch = threadIdx.x & 7;
    const uint32_t d = sb + r * 128 + ((ch ^ (r & 7)) << 4);
    const uint8_t* xa = (const uint8_t*)x + ((blockIdx.x & 15) * 262144 + r * 4096 + ch * 16);
    const uint32_t wo = r * (DFF * 2) + (blockIdx.x >> 4) * 256 + ch * 16;
    const uint8_t *wa = (const uint8_t*)wgate + wo, *wb = (const uint8_t*)wup + wo;
#pragma unroll
    for (int i = 0; i < 12; i++) {
      const int h = i >= 8;
      const uint8_t* src = (i >> 2) == 1 ? xa + (i & 1) * 131072 + ((i >> 1) & 1) * 2048 : ((i & 2) ? wb : wa) + h * 32 * (DFF * 2) + (i & 1) * 128;
      asm volatile("cp.async.cg.shared.global [%0], [%1], 16;" ::"r"(d + ((i >> 2) == 1 ? OFF_A + (i & 3) * 4096 : (i & 3) * 8192 + h * 4096)), "l"(src) : "memory");
    }
    if (threadIdx.x == 0) TS(23);
  }
  const int warp = __shfl_sync(~0u, threadIdx.x >> 5, 0), lane = threadIdx.x & 31;
  const int m = blockIdx.x & 15, j = blockIdx.x >> 4, rank = blockIdx.x & 1;
  const int m2 = blockIdx.x >> 3, j2 = blockIdx.x & 7;
  const bool helper = blockIdx.x >= NMAIN;
  if (warp >= 8) {
    asm volatile("setmaxnreg.dec.sync.aligned.u32 40;");
    if (warp == 8) {
      if (elect_one()) {
        asm volatile("prefetch.tensormap [%0];\nprefetch.tensormap [%1];\nprefetch.tensormap [%2];" ::"l"(&mp.x), "l"(&mp.wg), "l"(&mp.wu) : "memory");
        for (int s = 0; s < 4; s++) mbar_init(sb + B_F1 + 8 * s, 1);
        if (!helper) mbar_arrive(sb + B_F1);
        asm volatile("fence.mbarrier_init.release.cluster;" ::: "memory");
      }
      __syncwarp();
    } else if (warp == 9) {
      if (elect_one()) {
        if ((sb & 0xffffff) != SM_BASE) asm volatile("trap;");
        for (uint32_t b = B_E1; b < B_F2; b += 8) mbar_init(sb + b, 4);
        for (uint32_t b = B_F2; b < B_AUX; b += 8) mbar_init(sb + b, 1);
        for (uint32_t b = B_EX; b < B_AUX; b += 8) mbar_expect_tx(sb + b, 8192);
        mbar_init(sb + B_AUX, 8); mbar_init(sb + B_HALO, 9); mbar_init(sb + B_HALO + 8, 9);
        asm volatile("fence.mbarrier_init.release.cluster;" ::: "memory");
      }
      __syncwarp();
    }
    asm volatile("barrier.cluster.arrive.relaxed.aligned;" ::: "memory");
    if (warp == 8 && !helper) {
      if (elect_one()) {
        TS(0); TG(51);
#pragma unroll 1
        for (int kb = 1; kb < 4; kb++) {
          const uint32_t sa = sb + OFF_A + kb * 16384, sw = sb + kb * 32768, fb = sb + B_F1 + 8 * kb;
          mbar_expect_tx(fb, P1_BYTES);
          tma3d(sa, &mp.x, fb, kb * 64, m * 64, 0, EVICT_NORMAL);
          tma2d(sw, &mp.wg, fb, j * 128, kb * 64, EVICT_NORMAL); tma2d(sw + 16384, &mp.wu, fb, j * 128, kb * 64, EVICT_NORMAL);
          tma2d(sw + 8192, &mp.wg, fb, j * 128 + 64, kb * 64, EVICT_NORMAL); tma2d(sw + 24576, &mp.wu, fb, j * 128 + 64, kb * 64, EVICT_NORMAL);
        }
        TS(7);
      }
      __syncwarp();
    }
    asm volatile("barrier.cluster.wait.aligned;" ::: "memory");
    if (helper) {
      if (warp == 8) {
        unsigned e = 0;
        if (elect_one()) {
#pragma unroll 1
          for (int i = 0; i < 16; i++) {
            const uint32_t fb = sb + B_F1 + 8 * (i >> 2);
            if (!(i & 3)) mbar_expect_tx(fb, P1_BYTES);
            tma5d(sb + i * 8192, &mp.wd, fb, (blockIdx.x - NMAIN) * 256 + (i & 3) * 64, (i >> 2) * 2, HINT_W);
          }
        }
        if (lane == 0) { unsigned* ep = &gs->epoch[blockIdx.x * 2]; e = *ep + 1; *ep = e; }
        e = __shfl_sync(~0u, e, 0);
        if (lane < 16) flag_wait(&gs->flags[(FL_H + lane * 4) * 32], e * 8u);
        __syncwarp();
        if (elect_one()) {
          fence_async();
          TS(0);
#pragma unroll 1
          for (int i = 0; i < 64; i++) {
            const uint32_t fb = sb + B_F1 + 8 * (i & 3);
            if (i >= 4) { mbar_wait(sb + B_E1 + 8 * (i & 3), ~(i >> 2) & 1); mbar_expect_tx(fb, 16384); }
            bulk_load(sb + OFF_A + (i & 3) * 16384, gs->h + ((i >> 2) * 56 + (i & 3)) * 1024, 16384, fb, EVICT_NORMAL);
          }
        }
      } else if (warp == 9) {
#pragma unroll 1
        for (int t = 0; t < 16; t++) {
          bar_sync(BAR_EV + (t & 1), 288);
          if (lane == 0) { flag_add(&gs->flags[(FL_P + t) * 32]); TS(64 + t); }
          __syncwarp();
        }
      }
    } else if (warp == 8) {
      if (elect_one()) {
        uint32_t par = 0;

        auto x_load = [&]() {
          mbar_expect_tx(sb + B_XT, 32768);
          tma3d(sb + OFF_X, &mp.x, sb + B_XT, j2 * 128, m2 * 64, 0, HINT_LAST); tma3d(sb + OFF_X + 16384, &mp.x, sb + B_XT, j2 * 128 + 64, m2 * 64, 0, HINT_LAST);
        };
        auto d_prefetch = [&](int i) {
          if ((m2 >> 2) == (i & 3)) tma5d_prefetch(&mp.wd, (j2 >> 1) * 256 + (m2 & 3) * 64, (2 * i + 4 + rank) * 2);
        };
        auto w_tile = [&](int R, const CUtensorMap*& mb0, const CUtensorMap*& mb1, int& n0, int& n1) {
          if (R == 1 || R == 2) {
            mb0 = &mp.wqkv; n0 = 64 * (j + 8 * (R - 1)) + rank * 2048;
            mb1 = rank ? (R == 1 ? &mp.wg : &mp.wu) : &mp.wqkv; n1 = rank ? 1024 + 64 * j : n0 + 1024;
          } else {
            mb0 = mb1 = rank ? &mp.wu : &mp.wg;
            n0 = 128 * j + (R ? 1024 * R - 1536 : 0); n1 = n0 + 64;
          }
        };
        for (int R = 0; R < 5; R++) {
          const CUtensorMap *mb0, *mb1;
          int n0, n1;
          w_tile(R, mb0, mb1, n0, n1);
#pragma unroll 1
          for (int kb = R ? 0 : 4; kb < 16; kb++) {
            if (R == 0 && kb == 14) { asm volatile("prefetch.tensormap [%0];\nprefetch.tensormap [%1];" ::"l"(&mp.xn), "l"(&mp.wqkv) : "memory"); }
            if (R == 4 && kb == 2) { asm volatile("prefetch.tensormap [%0];\nprefetch.tensormap [%1];\nprefetch.tensormap [%2];" ::"l"(&mp.wd), "l"(&mp.wo), "l"(&mp.out) : "memory"); }
            if (R == 0 && kb == CS_KB) {
#pragma unroll 1
              for (int h = 0; h < 2; h++) {
                const uint32_t cb = sb + B_CS + 8 * h, d = sb + OFF_X + 16384 * h;
                mbar_expect_tx(cb, 16384);
                tma2d(d, h ? &mp.wu : &mp.wg, cb, n0, m * 64, EVICT_NORMAL); tma2d(d + 8192, h ? &mp.wu : &mp.wg, cb, n1, m * 64, EVICT_NORMAL);
              }
            }
            const int st = kb & 3;
            const uint32_t sa = sb + OFF_A + st * 16384, sw = sb + st * 32768, fb = sb + B_F1 + 8 * st;
            mbar_wait(sb + B_E1 + 8 * st, par);
            if (R * 16 + kb >= 4) REL_TS(R * 16 + kb - 4);
            mbar_expect_tx(fb, P1_BYTES);
            tma2d_mc(sw + rank * 16384, mb0, fb, n0, kb * 64, HINT_W);
            tma2d_mc(sw + 8192 + rank * 16384, mb1, fb, n1, kb * 64, HINT_W);
            if (R == 0) {
              tma3d(sa, &mp.x, fb, kb * 64, m * 64, 0, EVICT_NORMAL);
            } else {
              if (R == 1 && kb == 0) { mbar_wait(sb + B_DEP, 0); TS(1); }
              tma2d(sa, &mp.xn, fb, kb * 64, m * 128, R == 4 ? HINT_LAST : EVICT_NORMAL);
            }
            if (R == 4 && kb == 4 + j2) x_load();
            if (R == 4 && kb >= 16 - PF_D) d_prefetch(kb + PF_D - 16);
            if (st == 3) par ^= 1;
          }
        }
#pragma unroll 1
        for (int i = 0; i < 26; i++) {
          const int st = i & 3, kb = 2 * i + 4 + rank;
          const uint32_t sa = sb + OFF_A + st * 16384, sw = sb + st * 32768, fb = sb + B_F1 + 8 * st;
          mbar_wait(sb + B_E1 + 8 * st, par);
          REL_TS(76 + i);
          mbar_expect_tx(fb, P1_BYTES);
          tma5d(sw, &mp.wd, fb, j2 * 128, kb * 2, HINT_W); tma5d(sw + 8192, &mp.wd, fb, j2 * 128 + 64, kb * 2, HINT_W);
          tma5d(sw + 16384, &mp.wd, fb, (j2 ^ 1) * 128, kb * 2, HINT_W); tma5d(sw + 24576, &mp.wd, fb, (j2 ^ 1) * 128 + 64, kb * 2, HINT_W);
          if (i == 0 || i == 6 || i == 10 || i == 18) { mbar_wait(sb + B_DEP + 8 * (1 + ((i + 6) >> 3)), 0); }
          bulk_load(sa, gs->h + (m2 * 56 + kb) * 1024, 16384, fb, HINT_H);
          if (i + PF_D < 26) d_prefetch(i + PF_D);
          if (st == 3) par ^= 1;
        }
        int st = 0; uint32_t par2 = 1;
#pragma unroll 1
        for (int t = 0; t < 16; t++) {
          const uint32_t sa = sb + p2_a(st), sw = sb + p2_b(st), fb = sb + B_F2 + 8 * st;
          if (t < 5) mbar_wait(sb + B_E1 + 8 * (((2 * t + 1) / 3 + 2) & 3), t < 3); else mbar_wait(sb + B_E2 + 8 * st, par2);
          REL_TS(102 + t);
          mbar_expect_tx(fb, P2_BYTES);
          bulk_load_mc(sa + rank * 8192, gs->o + (m2 * 16 + t) * 1024 + rank * 512, 8192, fb, HINT_H);
          tma2d(sw, &mp.wo, fb, j2 * 128, t * 64, HINT_W); tma2d(sw + 8192, &mp.wo, fb, j2 * 128 + 64, t * 64, HINT_W);
          if (++st == 5) { st = 0; par2 ^= 1; }
        }
      }
    } else if (warp == 9) {
#pragma unroll 1
      for (int e = 0; e < 7; e++) {
        const bool halo = e == 2 || e == 3;
        bar_sync(BAR_EV + e, halo ? 96 : 288);
        if (lane == 0) {
          const int f = e == 0 ? FL_XN + m : (halo ? FL_HALO + (e - 2) * 128 + blockIdx.x : FL_H + m * 4 + (e == 1 ? 0 : e - 3));
          TS(10 + 2 * e); TG(52 + e);
          flag_add(&gs->flags[f * 32]);
          if (e < 6) TS(11 + 2 * e);
        }
        __syncwarp();
      }
      mbar_wait(sb + B_DONE, 0);
    } else {
      unsigned e = 0;
      if (lane == 0) {
        unsigned* ep = &gs->epoch[blockIdx.x * 2 + warp - 10];
        e = *ep + 1; *ep = e;
        if (warp == 10) { asm volatile("st.shared.b32 [%0], %1;" ::"r"(sb + OFF_EPOCH), "r"(e) : "memory"); mbar_arrive(sb + B_EP); }
      }
      e = __shfl_sync(~0u, e, 0);
      mbar_wait(sb + B_CS + 8 * (warp - 10), 0);
      if (lane == 0 && warp == 11) TS(6);
      col_sums(sb + OFF_X + (warp - 10) * 16384, gs->cspart + (j * 16 + m) * 128 + (warp - 10) * 16, e);
      if (lane == 0 && warp == 11) TS(9);
      if (warp == 10) {
        if (lane == 0) {
#pragma unroll 1
          for (int g = 0; g < 6; g++) {
            flag_wait(&gs->flags[(g == 5 ? FL_P + m2 : (g ? FL_H + m2 * 4 + g - 1 : FL_XN + m)) * 32], e * (g == 5 ? 4u : 8u));
            fence_async();
            mbar_arrive(sb + B_DEP + 8 * g);
            if (g == 0) TS(8);
          }
        }
      } else
      if (elect_one()) {
#pragma unroll 1
        for (int r = 0; r < 2; r++) {
          const uint32_t hb = sb + B_HALO + 8 * r;
          if (r) mbar_wait(sb + B_HALO, 0);
          if (m) {
            flag_wait(&gs->flags[(FL_HALO + r * 128 + blockIdx.x - 1) * 32], e);
            fence_async();
            mbar_expect_tx(hb, 4096);
            for (int g = 0; g < 2; g++) bulk_load(sb + OFF_X + g * AT_WG + AT_REM + r * 2048, gs->halo + ((r * 128 + blockIdx.x - 1) * 2 + g) * 128, 2048, hb, EVICT_FIRST);
          } else {
            mbar_arrive(hb);
          }
          TS(34 + r);
        }
      }
    }
  } else {
    asm volatile("barrier.cluster.arrive.relaxed.aligned;" ::: "memory");
    asm volatile("setmaxnreg.inc.sync.aligned.u32 232;");
    const int wg = warp >> 2, w = warp & 3;
    Cons c;
    c.sb = sb; c.wg = wg; c.zero = warp >> 8;
    c.a = 0x4000004000010000ull + ((SM_BASE + OFF_A + wg * 8192) >> 4); c.k1 = 2 + c.zero; c.k2 = 2; c.k4 = 1024 - 6; c.k4w = -3072 - 6; c.b1 = 128 + c.zero;
    c.b = 0x4000004000000000ull + DB_LO + c.zero;
    c.rel = mapa(sb, threadIdx.x & 1);
    c.do_rel = (threadIdx.x & 127) < 2;
    constexpr bool t0 = false;
    float acc[128];
    uint32_t pk[64];
    float rs[2];
    const int q = lane & 3;

    if (helper) {
      asm volatile("barrier.cluster.wait.aligned;" ::: "memory");
      c.a = 0x8000002000010000ull + ((SM_BASE + OFF_A + wg * 4096) >> 4); c.k2 = 510; c.k4 = 1024 - 514; c.k4w = -3072 - 514;
      c.rel = sb;
      uint4* dst = gs->dpart + (blockIdx.x - NMAIN) * 4096 + threadIdx.x;
      auto put = [&](int p) {
#pragma unroll
        for (int i = 4 * p; i < 4 * p + 4; i++) stg128(dst + i * 256, pk[4 * i], pk[4 * i + 1], pk[4 * i + 2], pk[4 * i + 3]);
      };
#pragma unroll 1
      for (int t = 0; t < 16; t++) {
        p1_issue<0, 0>(acc, c, t & 1);
        if (t) put(0);
        p1_issue<1, 1>(acc, c, t & 1); wg_wait<1>(); release(c, B_E1);
        if (t) put(1);
        p1_issue<2, 1>(acc, c, t & 1); wg_wait<1>(); release(c, B_E1 + 8);
        if (t) put(2);
        if (wg == 1) { wg_wait<0>(); release(c, B_E1 + 16); bar_sync(BAR_LAG, 256); }
        p1_issue<3, 1>(acc, c, t & 1);
        if (wg == 0) bar_arrive(BAR_LAG, 256);
        if (t) { put(3); bar_arrive(BAR_EV + (~t & 1), 288); dst += 8 * 2048; }
        wg_wait<1>(); if (wg == 0) release(c, B_E1 + 16);
        wg_wait<0>(); release(c, B_E1 + 24);
#pragma unroll
        for (int i = 0; i < 64; i++) pk[i] = pack2(acc[2 * i], acc[2 * i + 1]);
      }
      put(0); put(1); put(2); put(3);
      bar_arrive(BAR_EV + 1, 288);
      return;
    }
    {
      const int prow = 16 * j + 2 * warp;
      const uint4* xr = x + (size_t)(128 * m + 2 * (prow & 63) + (prow >> 6)) * 128 + lane;
      uint4* xo = gs->xn + (size_t)(128 * m + prow) * 128 + lane;
      float c0[2], mo[4];
      uint32_t st[2];
      uint32_t e;
      asm volatile("" : "+l"(xr), "+l"(xo));
      asm volatile("cp.async.wait_all;\nfence.proxy.async.shared::cta;" ::: "memory");
      bar_sync(BAR_MMA, 256);
      if (threadIdx.x == 0) TS(39);
      p1_step<0, false>(acc, c);
      asm volatile("barrier.cluster.wait.aligned;" ::: "memory");
      unsigned long long part[18];
      auto gather = [&](int from, int to) {
        const int lane = lane_here();
        const unsigned long long* cp = (const unsigned long long*)gs->cspart + j * 4096 + warp * 32 + lane;
        const unsigned long long* sp = gs->stats + 128 * m + warp * 16 + (lane >> 2);
#pragma unroll
        for (int i = from; i < to; i++) asm volatile("ld.relaxed.gpu.global.b64 %0, [%1];" : "=l"(part[i]) : "l"(i < 16 ? cp + i * 256 : sp + (i - 16) * 8) : "memory");
      };
      auto row_load = [&](int r) {
#pragma unroll
        for (int i = 4 * r; i < 4 * r + 4; i++)
          asm volatile("ld.global.nc.L1::no_allocate.v4.b32 {%0,%1,%2,%3}, [%4];" : "=r"(pk[4 * i]), "=r"(pk[4 * i + 1]), "=r"(pk[4 * i + 2]), "=r"(pk[4 * i + 3]) : "l"(xr + r * 256 + (i & 3) * 32));
      };
      p1_step<1>(acc, c); row_load(0);
      p1_step<2>(acc, c); row_load(1);
      p1_loop(acc, c, 3, LN_KB + 1, [](int) {});
      pin<16>(pk); ln_moments(pk, c0[0], mo[0], mo[1]); pin<2>(mo);
      p1_step<LN_KB + 1>(acc, c);
      sched_fence(c.zero);
      pin<16>(pk + 16); ln_moments(pk + 16, c0[1], mo[2], mo[3]); ln_reduce(mo[0], mo[1]); pin<4>(mo);
      p1_step<LN_KB + 2>(acc, c);
      mbar_spin(sb + B_EP, 0, c.zero);
      asm volatile("ld.shared.b32 %0, [%1];" : "=r"(e) : "r"(sb + OFF_EPOCH) : "memory");
      pin<2>(mo); st[0] = ln_finish(c0[0], mo[0], mo[1]); ln_reduce(mo[2], mo[3]); pin<1>(st); pin<2>(mo + 2);
      p1_step<LN_KB + 3>(acc, c);
      sched_fence(c.zero);
      pin<1>(st); pin<2>(mo + 2);
      st[1] = ln_finish(c0[1], mo[2], mo[3]);
      ln_store(pk, st[0], xo);
      if (lane == 0)
        asm volatile("{\n.reg .b64 a, b;\nmov.b64 a, {%1, %3};\nmov.b64 b, {%2, %3};\nst.relaxed.gpu.global.v2.b64 [%0], {a, b};\n}" ::"l"(gs->stats + 128 * m + prow), "r"(st[0]), "r"(st[1]), "r"(e) : "memory");
      p1_step<LN_KB + 4>(acc, c);
      sched_fence(c.zero);
      pin<1>(st + 1);
      ln_store(pk + 16, st[1], xo + 128);
      bar_arrive(BAR_EV, 288);
      p1_loop(acc, c, LN_KB + 5, 13, [](int) {});
      gather(0, 9);
      p1_step<13>(acc, c);
      gather(9, 18);
      p1_step<14>(acc, c);
      auto validate = [&]() {
        float csum;
        for (int tries = 0;; tries++) {
          uint32_t bad = 0;
          csum = 0.f;
#pragma unroll
          for (int i = 0; i < 18; i++) { bad |= (uint32_t)(part[i] >> 32) ^ e; if (i < 16) csum += __uint_as_float((uint32_t)part[i]); }
          if (!__any_sync(~0u, bad != 0) || tries > (1 << 20)) break;
          gather(0, 18);
        }
        const float hi = bf16r(csum), mid = bf16r(csum - hi);
        sts128(sb + OFF_CS + ((threadIdx.x & 62) * 4 + (threadIdx.x >> 6) * 2 + (threadIdx.x & 1)) * 16, make_uint4(pack2(hi, mid), pack2(csum - hi - mid, 0.f), 0, 0));
        asm volatile("fence.proxy.async.shared::cta;" ::: "memory");
        __syncwarp();
        if (lane == 0) mbar_arrive(sb + B_AUX);
      };
#pragma unroll 1
      for (int ph = 1; ph >= 0; ph--) {
        if (wg == ph) validate();
        if (ph) {
          if (wg == 1) { wg_wait<0>(); release(c, B_E1 + 16); bar_sync(BAR_LAG, 256); }
          p1_issue<3, 1>(acc, c, 1);
        }
      }
      const uint32_t keep = q == 0 ? 0xffffffffu : (q == 1 ? 0xffffu : 0u);
      const uint32_t a0 = (__byte_perm((uint32_t)part[16], 0, 0x1010) ^ 0x80008000u) & keep, a1 = (__byte_perm((uint32_t)part[17], 0, 0x1010) ^ 0x80008000u) & keep;
      mbar_spin(sb + B_AUX, 0, c.zero);
      wg_fence();
      wgmma256_rs(acc, a0, a1, 0, 0, (SM_BASE + OFF_CS) >> 4);
      wg_commit();
      if (wg == 0) bar_arrive(BAR_LAG, 256);
      rs[0] = rcpf(hi_f((uint32_t)part[16])); rs[1] = rcpf(hi_f((uint32_t)part[17]));
      wg_wait<2>(); if (wg == 0) release(c, B_E1 + 16);
      wg_wait<0>(); release(c, B_E1 + 24);
    }
#pragma unroll 1
    for (int R = 1;; R++) {
#pragma unroll
      for (int i = 0; i < 64; i++) pk[i] = pack2(acc[2 * i], acc[2 * i + 1]);
      if (t0) TS(24 + R + wg * 16);
      uint8_t* hb = (uint8_t*)gs->h + (size_t)m * 56 * 16384 + warp * 1024;
      if (R == 5) { c.a = 0x8000002000010000ull + ((SM_BASE + OFF_A + wg * 4096) >> 4); c.k2 = 510; c.k4 = 1024 - 514; c.k4w = -3072 - 514; }
      p1_step<0>(acc, c);
      if (R == 2 || R == 3) {
        attn_tile(acc, pk, c, R - 2, warp, m, gs, hb + (16 + j) * 16384, (uint8_t*)gs->o + (m * 16 + j + 8 * (R - 2)) * 16384 + warp * 1024);
      } else {
        geglu_tile(acc, pk, c, R == 5 ? 24 : 14, hb + (2 * j + (R == 1 ? 0 : 16 * R - 40)) * 16384, BAR_EV + (R == 1 ? 1 : R + 1), rs);
        rs[0] = rs[1] = 1.0f;
        if (R == 5) break;
      }
      p1_step<14>(acc, c); p1_step<15>(acc, c);
    }
    auto fetch = [&](int p) {
      asm volatile("ld.global.cg.v4.b32 {%0,%1,%2,%3}, [%4];" : "=r"(pk[4 * p]), "=r"(pk[4 * p + 1]), "=r"(pk[4 * p + 2]), "=r"(pk[4 * p + 3]) : "l"(gs->dpart + blockIdx.x * 2048 + p * 256 + threadIdx.x) : "memory");
    };
    mbar_spin(sb + B_DEP + 40, 0, c.zero);
    fetch(0); fetch(1); fetch(2);
    p1_step<8>(acc, c);
    fetch(3); fetch(4); fetch(5);
    p1_step<9>(acc, c);
    fetch(6); fetch(7);
    {
      float accs[64];
      const uint32_t peer = mapa(sb, rank ^ 1);
      auto send_piece = [&](int p) {
        asm volatile("st.async.weak.shared::cluster.mbarrier::complete_tx::bytes.v4.b32 [%0], {%1,%2,%3,%4}, [%5];" ::"r"(peer + OFF_LAND + p * 4096 + threadIdx.x * 16),
                     "r"(pack2(acc[64 + 8 * p], acc[65 + 8 * p])), "r"(pack2(acc[66 + 8 * p], acc[67 + 8 * p])), "r"(pack2(acc[68 + 8 * p], acc[69 + 8 * p])), "r"(pack2(acc[70 + 8 * p], acc[71 + 8 * p])),
                     "r"(peer + B_EX + 16 * wg + 8 * (p >> 2)) : "memory");
      };
      auto silu_piece = [&](int p) {
        const uint4 r = lds128(sb + OFF_LAND + p * 4096 + threadIdx.x * 16);
        const uint32_t rr[4] = {add2(r.x, pk[4 * p]), add2(r.y, pk[4 * p + 1]), add2(r.z, pk[4 * p + 2]), add2(r.w, pk[4 * p + 3])};
#pragma unroll
        for (int i = 0; i < 4; i++) {
          const float a = acc[8 * p + 2 * i] + lo_f(rr[i]), b = acc[8 * p + 2 * i + 1] + hi_f(rr[i]);
          pk[4 * p + i] = pack2(silu_half(a), silu_half(b));
        }
        pin<4>(pk + 4 * p);
      };
      const uint32_t xa = sb + OFF_X + (warp * 16 + (lane & 7)) * 128 + (((lane >> 3) ^ (lane & 7)) << 4);
      auto x_addr = [&](int i) { return (xa ^ ((i & 1) << 6)) + ((i >> 1) & 1) * 1024 + (i >> 2) * 16384; };
      auto x_piece = [&](int i) { const uint4 v = ldsm(x_addr(i)); pk[32 + 4 * i] = v.x; pk[33 + 4 * i] = v.y; pk[34 + 4 * i] = v.z; pk[35 + 4 * i] = v.w; };
      p2_step<0>(accs, c);
      p2_step<1>(accs, c);
      mbar_spin(sb + B_E1 + 8, 0, c.zero);
      send_piece(0); send_piece(1);
      p2_step<2>(accs, c); sched_fence(c.zero); send_piece(2); send_piece(3);
      p2_step<3>(accs, c); sched_fence(c.zero); send_piece(4); send_piece(5);
      p2_step<4>(accs, c); mbar_spin(sb + B_XT, 0, c.zero); send_piece(6); send_piece(7);
      p2_step<5>(accs, c); mbar_spin(sb + B_EX + 16 * wg, 0, c.zero); silu_piece(0); x_piece(0);
      p2_step<6>(accs, c); sched_fence(c.zero); silu_piece(1); x_piece(1);
      p2_step<7>(accs, c); sched_fence(c.zero); silu_piece(2); x_piece(2);
      p2_step<8>(accs, c); sched_fence(c.zero); silu_piece(3); x_piece(3);
      p2_step<9>(accs, c); mbar_spin(sb + B_EX + 16 * wg + 8, 0, c.zero); silu_piece(4); x_piece(4);
      p2_step<10>(accs, c); sched_fence(c.zero); silu_piece(5); x_piece(5);
      p2_step<11>(accs, c); sched_fence(c.zero); silu_piece(6); x_piece(6); x_piece(7);
      auto out_half = [&](const float* a, int h) {
#pragma unroll
        for (int i = 4 * h; i < 4 * h + 4; i++) {
          uint32_t v[4];
#pragma unroll
          for (int k = 0; k < 4; k++) { const int o = 2 * (4 * (i & 1) + k) + ((i >> 1) & 1); v[k] = fma2(pack2(a[2 * o], a[2 * o + 1]), pk[16 * h + o], pk[32 + 4 * i + k]); }
          asm volatile("stmatrix.sync.aligned.m8n8.x4.shared.b16 [%0], {%1,%2,%3,%4};" ::"r"(x_addr(i)), "r"(v[0]), "r"(v[1]), "r"(v[2]), "r"(v[3]) : "memory");
          if (i & 1) {
            asm volatile("fence.proxy.async.shared::cta;" ::: "memory");
            __syncwarp();
            if (elect_one()) tma3d_store(&mp.out, sb + OFF_X + h * 16384 + warp * 2048 + (i & 2) * 512, j2 * 128 + h * 64, m2 * 64 + w * 16 + (i & 2) * 4, wg);
          }
        }
      };
      if (wg == 1) silu_piece(7);
      p2_step<12>(accs, c); p2_step<13>(accs, c); p2_step<14>(accs, c); p2_step<15>(accs, c);
      if (c.do_rel) mbar_arrive(sb + B_DONE);
      if (wg == 0) silu_piece(7);
      wg_wait<0>();
      out_half(accs, 0); out_half(accs + 32, 1);
      if (elect_one()) { asm volatile("cp.async.bulk.commit_group;\ncp.async.bulk.wait_group.read 0;" ::: "memory"); }
      if ((threadIdx.x & 127) == 0) { TS(33 + wg * 16); if (wg) { TG(59); unsigned id; asm volatile("mov.u32 %0, %%smid;" : "=r"(id)); TSV(60, id); } }
    }
  }
}

typedef CUresult (*EncodeFn)(CUtensorMap*, CUtensorMapDataType, cuuint32_t, void*, const cuuint64_t*, const cuuint64_t*, const cuuint32_t*, const cuuint32_t*,
                             CUtensorMapInterleave, CUtensorMapSwizzle, CUtensorMapL2promotion, CUtensorMapFloatOOBfill);

void encode(EncodeFn fn, CUtensorMap* tm, const void* p, int rank, const cuuint64_t* dims, const cuuint64_t* strides, const cuuint32_t* box) {
  const cuuint32_t es[5] = {1, 1, 1, 1, 1};
  fn(tm, CU_TENSOR_MAP_DATA_TYPE_BFLOAT16, rank, const_cast<void*>(p), dims, strides, box, es, CU_TENSOR_MAP_INTERLEAVE_NONE, CU_TENSOR_MAP_SWIZZLE_128B,
     PROMO, CU_TENSOR_MAP_FLOAT_OOB_FILL_NONE);
}

}

extern "C" void kernel_launch(void* const* d_in, const int* in_sizes, int n_in, void* d_out, int out_size) {
  (void)in_sizes; (void)n_in; (void)out_size;
  static EncodeFn fn = nullptr;
  static Scratch* gs = nullptr;
  if (!fn) {
    void* p = nullptr;
    cudaDriverEntryPointQueryResult qr;
    cudaGetDriverEntryPoint("cuTensorMapEncodeTiled", &p, cudaEnableDefault, &qr);
    fn = (EncodeFn)p;
    cudaGetSymbolAddress((void**)&gs, g_scratch);
    cudaFuncSetAttribute(fused_kernel, cudaFuncAttributeMaxDynamicSharedMemorySize, SMEM_BYTES);
  }
  const void *x = d_in[0], *wqkv = d_in[1], *wo = d_in[2], *wg = d_in[4], *wu = d_in[5], *wd = d_in[6];
  Maps mp;
  {
    const cuuint64_t dims[3] = {DM, SEQ / 2, 2}, st[2] = {DM * 4, DM * 2};
    const cuuint32_t box_in[3] = {64, 64, 2}, box_out[3] = {64, 8, 1};
    encode(fn, &mp.x, x, 3, dims, st, box_in);
    encode(fn, &mp.out, d_out, 3, dims, st, box_out);
  }
  {
    const cuuint64_t dims[2] = {DM, SEQ}, st[1] = {DM * 2};
    const cuuint32_t box[2] = {64, 128};
    encode(fn, &mp.xn, gs->xn, 2, dims, st, box);
  }
  {
    const cuuint32_t box[2] = {64, 64};
    const cuuint64_t dq[2] = {3 * DM, DM}, sq[1] = {3 * DM * 2}, df[2] = {DFF, DM}, sf[1] = {DFF * 2}, dw[2] = {DM, DM}, sw[1] = {DM * 2};
    encode(fn, &mp.wqkv, wqkv, 2, dq, sq, box);
    encode(fn, &mp.wg, wg, 2, df, sf, box);
    encode(fn, &mp.wu, wu, 2, df, sf, box);
    encode(fn, &mp.wo, wo, 2, dw, sw, box);
  }
  {
    const cuuint32_t box[5] = {64, 2, 4, 4, 2};
    const cuuint64_t st[4] = {DM * 2, 8 * DM * 2, 2 * DM * 2, 32 * DM * 2};
    const cuuint64_t dd[5] = {DM, 2, 4, 4, DFF / 32};
    encode(fn, &mp.wd, wd, 5, dd, st, box);
  }
  fused_kernel<<<NCTA, 384, SMEM_BYTES>>>((const uint4*)x, (const uint4*)wg, (const uint4*)wu, gs, mp);
}
```

```cpp
#include <cuda_runtime.h>
#include <cuda_bf16.h>
#include <cuda.h>
#include <stdint.h>

#define PROMO CU_TENSOR_MAP_L2_PROMOTION_L2_128B
#define PF_D 6
#define LAG2 4
#define POLL_NS "200"
#define CS_KB 8
#define LN_KB 4

#define EVICT_FIRST 0x12F0000000000000ull
#define EVICT_NORMAL 0x1000000000000000ull
#define HINT_OUT EVICT_FIRST
#define HINT_W EVICT_FIRST
#define HINT_H EVICT_FIRST
#define HINT_LAST EVICT_FIRST

namespace {

constexpr int SEQ = 2048, DM = 1024, DFF = 3584;
constexpr int NMAIN = 128, NCTA = 132;

constexpr uint32_t SM_BASE = 0x400;
constexpr uint32_t P1_BYTES = 49152, P2_BYTES = 32768;
constexpr uint32_t OFF_A = 131072;
__host__ __device__ constexpr uint32_t p2_a(int s) { return s == 0 ? OFF_A + 32768 : s == 1 ? OFF_A + 49152 : s == 2 ? 114688 : s == 3 ? 16384 : 49152; }
__host__ __device__ constexpr uint32_t p2_b(int s) { return s < 3 ? 65536 + s * 16384 : (s - 3) * 32768; }
constexpr uint32_t OFF_LAND = OFF_A;
constexpr uint32_t OFF_X = 196608;
constexpr uint32_t OFF_CS = OFF_X + 14336;
constexpr uint32_t OFF_BAR = 229376;
constexpr uint32_t B_F1 = OFF_BAR, B_E1 = B_F1 + 32, B_E2 = B_E1 + 32, B_DONE = B_E2 + 40, B_F2 = B_DONE + 8, B_DEP = B_F2 + 40, B_CS = B_DEP + 48,
                   B_XT = B_CS + 16, B_EP = B_XT + 8, B_EX = B_EP + 8, B_AUX = B_EX + 32, B_HALO = B_AUX + 8, OFF_EPOCH = B_HALO + 16;
constexpr uint32_t SMEM_BYTES = 232448;
constexpr uint32_t AT_V = 0, AT_K = 8192, AT_REM = 11264, AT_WG = 15360;

constexpr int FL_XN = 0, FL_H = 16, FL_P = 80, FL_HALO = 96, FL_N = FL_HALO + 256;
struct __align__(1024) Scratch {
  uint4 h[16 * 56 * 1024];
  uint4 o[16 * 16 * 1024];
  uint4 xn[SEQ * DM / 8];
  uint4 dpart[128 * 8 * 256];
  uint4 halo[2 * 128 * 2 * 128];
  ulonglong2 cspart[8 * 16 * 128];
  unsigned long long stats[SEQ];
  unsigned flags[FL_N * 32];
  unsigned epoch[NCTA * 2];
};
__device__ Scratch g_scratch;
#define TG(i) do {} while (0)
#define TSV(i, v) do {} while (0)
#define TS(i) do {} while (0)

__device__ __forceinline__ unsigned role_id() {
  unsigned sm, nsm;
  asm("mov.u32 %0, %%smid;\nmov.u32 %1, %%nsmid;" : "=r"(sm), "=r"(nsm));
  const unsigned t = (nsm == NCTA ? sm : blockIdx.x) >> 1;
  unsigned g = t & 7, i = t >> 3;
  if (t >= 32) { i = (t - 32) / 7; g = t - 31 - 7 * i; i += 4; }
  if (t >= 60) { g = t - 60; i = 8; }
  if (t >= 62) { g = 0; i = t - 58; }
  return 16 * i + 2 * g + (blockIdx.x & 1);
}

struct Maps { CUtensorMap x, xn, out, wqkv, wg, wu, wd, wo; };

__device__ __forceinline__ void mbar_init(uint32_t bar, uint32_t cnt) { asm volatile("mbarrier.init.shared::cta.b64 [%0], %1;" ::"r"(bar), "r"(cnt)); }
__device__ __forceinline__ void mbar_expect_tx(uint32_t bar, uint32_t bytes) { asm volatile("mbarrier.arrive.expect_tx.shared::cta.b64 _, [%0], %1;" ::"r"(bar), "r"(bytes) : "memory"); }
__device__ __forceinline__ void mbar_arrive(uint32_t bar) { asm volatile("mbarrier.arrive.shared::cta.b64 _, [%0];" ::"r"(bar) : "memory"); }
__device__ __forceinline__ void mbar_arrive_cl(uint32_t bar) { asm volatile("mbarrier.arrive.shared::cluster.b64 _, [%0];" ::"r"(bar) : "memory"); }
__device__ __forceinline__ uint32_t mapa(uint32_t a, uint32_t cta) { uint32_t r; asm("mapa.shared::cluster.u32 %0, %1, %2;" : "=r"(r) : "r"(a), "r"(cta)); return r; }
__device__ __forceinline__ void mbar_wait(uint32_t bar, uint32_t parity) {
  asm volatile("{\n.reg .pred p;\n.reg .u32 n;\nmov.u32 n, 0;\nLAB_WAIT:\nmbarrier.try_wait.parity.shared::cta.b64 p, [%0], %1;\n@p bra LAB_DONE;\n"
               "add.u32 n, n, 1;\nsetp.gt.u32 p, n, 4000000;\n@p trap;\nbra LAB_WAIT;\nLAB_DONE:\n}" ::"r"(bar), "r"(parity) : "memory");
}
__device__ __forceinline__ void mbar_spin(uint32_t bar, uint32_t parity, uint32_t zero) {
  asm volatile("{\n.reg .pred p, z;\nsetp.ne.u32 z, %2, 0;\nLAB_WAIT:\nmbarrier.try_wait.parity.shared::cta.b64 p, [%0], %1;\n@p bra LAB_DONE;\n@z trap;\nbra LAB_WAIT;\nLAB_DONE:\n}" ::"r"(bar), "r"(parity), "r"(zero) : "memory");
}
__device__ __forceinline__ void flag_wait(const unsigned* f, unsigned target) {
  asm volatile("{\n.reg .pred p;\n.reg .u32 n, v;\nmov.u32 n, 0;\nLAB_WAIT:\nld.relaxed.gpu.global.u32 v, [%0];\nsub.u32 v, v, %1;\nsetp.ge.s32 p, v, 0;\n@p bra LAB_DONE;\n"
               "nanosleep.u32 " POLL_NS ";\nadd.u32 n, n, 1;\nsetp.gt.u32 p, n, 4000000;\n@p trap;\nbra LAB_WAIT;\nLAB_DONE:\nfence.acquire.gpu;\n}" ::"l"(f), "r"(target) : "memory");
}
__device__ __forceinline__ void flag_add(unsigned* f) { asm volatile("red.release.gpu.global.add.u32 [%0], 1;" ::"l"(f) : "memory"); }
__device__ __forceinline__ void fence_async() { asm volatile("fence.proxy.async.global;" ::: "memory"); }
__device__ __forceinline__ bool elect_one() { uint32_t p; asm volatile("{\n.reg .pred P;\nelect.sync _|P, 0xffffffff;\nselp.u32 %0, 1, 0, P;\n}" : "=r"(p)); return p; }
__device__ __forceinline__ void bar_sync(int id, int n) { asm volatile("bar.sync %0, %1;" ::"r"(id), "r"(n) : "memory"); }
__device__ __forceinline__ void bar_arrive(int id, int n) { asm volatile("bar.arrive %0, %1;" ::"r"(id), "r"(n) : "memory"); }

__device__ __forceinline__ void tma2d(uint32_t dst, const CUtensorMap* tm, uint32_t bar, int c0, int c1, uint64_t hint) {
  asm volatile("cp.async.bulk.tensor.2d.shared::cluster.global.mbarrier::complete_tx::bytes.L2::cache_hint [%0], [%1, {%3, %4}], [%2], %5;" ::"r"(dst), "l"(tm), "r"(bar), "r"(c0), "r"(c1), "l"(hint) : "memory");
}
__device__ __forceinline__ void tma2d_mc(uint32_t dst, const CUtensorMap* tm, uint32_t bar, int c0, int c1, uint64_t hint) {
  asm volatile("cp.async.bulk.tensor.2d.shared::cluster.global.mbarrier::complete_tx::bytes.multicast::cluster.L2::cache_hint [%0], [%1, {%3, %4}], [%2], %5, %6;" ::"r"(dst), "l"(tm), "r"(bar), "r"(c0), "r"(c1), "h"((uint16_t)3), "l"(hint) : "memory");
}
__device__ __forceinline__ void tma3d(uint32_t dst, const CUtensorMap* tm, uint32_t bar, int c0, int c1, int c2, uint64_t hint) {
  asm volatile("cp.async.bulk.tensor.3d.shared::cluster.global.mbarrier::complete_tx::bytes.L2::cache_hint [%0], [%1, {%3, %4, %5}], [%2], %6;" ::"r"(dst), "l"(tm), "r"(bar), "r"(c0), "r"(c1), "r"(c2), "l"(hint) : "memory");
}
__device__ __forceinline__ void tma5d(uint32_t dst, const CUtensorMap* tm, uint32_t bar, int c0, int c4, uint64_t hint) {
  asm volatile("cp.async.bulk.tensor.5d.shared::cluster.global.mbarrier::complete_tx::bytes.L2::cache_hint [%0], [%1, {%3, %5, %5, %5, %4}], [%2], %6;" ::"r"(dst), "l"(tm), "r"(bar), "r"(c0), "r"(c4), "r"(0), "l"(hint) : "memory");
}
__device__ __forceinline__ void tma5d_prefetch(const CUtensorMap* tm, int c0, int c4) {
  asm volatile("cp.async.bulk.prefetch.tensor.5d.L2.global [%0, {%1, %3, %3, %3, %2}];" ::"l"(tm), "r"(c0), "r"(c4), "r"(0) : "memory");
}
__device__ __forceinline__ void tma3d_store(const CUtensorMap* tm, uint32_t src, int c0, int c1, int c2) {
  asm volatile("cp.async.bulk.tensor.3d.global.shared::cta.bulk_group.L2::cache_hint [%0, {%2, %3, %4}], [%1], %5;" ::"l"(tm), "r"(src), "r"(c0), "r"(c1), "r"(c2), "l"(HINT_OUT) : "memory");
}
__device__ __forceinline__ void bulk_load(uint32_t dst, const void* src, uint32_t bytes, uint32_t bar, uint64_t hint) {
  asm volatile("cp.async.bulk.shared::cluster.global.mbarrier::complete_tx::bytes.L2::cache_hint [%0], [%1], %2, [%3], %4;" ::"r"(dst), "l"(src), "r"(bytes), "r"(bar), "l"(hint) : "memory");
}
__device__ __forceinline__ void bulk_load_mc(uint32_t dst, const void* src, uint32_t bytes, uint32_t bar, uint64_t hint) {
  asm volatile("cp.async.bulk.shared::cluster.global.mbarrier::complete_tx::bytes.multicast::cluster.L2::cache_hint [%0], [%1], %2, [%3], %4, %5;" ::"r"(dst), "l"(src), "r"(bytes), "r"(bar), "h"((uint16_t)3), "l"(hint) : "memory");
}
__device__ __forceinline__ uint4 lds128(uint32_t a) { uint4 v; asm volatile("ld.shared.v4.b32 {%0,%1,%2,%3}, [%4];" : "=r"(v.x), "=r"(v.y), "=r"(v.z), "=r"(v.w) : "r"(a) : "memory"); return v; }
__device__ __forceinline__ void sts128(uint32_t a, uint4 v) { asm volatile("st.shared.v4.b32 [%0], {%1,%2,%3,%4};" ::"r"(a), "r"(v.x), "r"(v.y), "r"(v.z), "r"(v.w) : "memory"); }
__device__ __forceinline__ void stg128(void* p, uint32_t a, uint32_t b, uint32_t c, uint32_t d) { asm volatile("st.global.v4.b32 [%0], {%1,%2,%3,%4};" ::"l"(p), "r"(a), "r"(b), "r"(c), "r"(d) : "memory"); }

__device__ __forceinline__ uint32_t pack2(float lo, float hi) { uint32_t r; asm("cvt.rn.bf16x2.f32 %0, %1, %2;" : "=r"(r) : "f"(hi), "f"(lo)); return r; }
__device__ __forceinline__ float lo_f(uint32_t v) { return __uint_as_float(v << 16); }
__device__ __forceinline__ float hi_f(uint32_t v) { return __uint_as_float(v & 0xffff0000u); }
__device__ __forceinline__ float bf16r(float v) { return lo_f(pack2(v, 0.f)); }
__device__ __forceinline__ uint32_t mul2(uint32_t a, uint32_t b) { uint32_t r; asm("mul.rn.bf16x2 %0, %1, %2;" : "=r"(r) : "r"(a), "r"(b)); return r; }
__device__ __forceinline__ uint32_t add2(uint32_t a, uint32_t b) { uint32_t r; asm("add.rn.bf16x2 %0, %1, %2;" : "=r"(r) : "r"(a), "r"(b)); return r; }
__device__ __forceinline__ uint32_t sub2(uint32_t a, uint32_t b) { uint32_t r; asm("sub.rn.bf16x2 %0, %1, %2;" : "=r"(r) : "r"(a), "r"(b)); return r; }
__device__ __forceinline__ uint32_t fma2(uint32_t a, uint32_t b, uint32_t c) { uint32_t r; asm("fma.rn.bf16x2 %0, %1, %2, %3;" : "=r"(r) : "r"(a), "r"(b), "r"(c)); return r; }
__device__ __forceinline__ uint32_t max2(uint32_t a, uint32_t b) { uint32_t r; asm("max.bf16x2 %0, %1, %2;" : "=r"(r) : "r"(a), "r"(b)); return r; }
__device__ __forceinline__ float ex2f(float x) { float y; asm("ex2.approx.ftz.f32 %0, %1;" : "=f"(y) : "f"(x)); return y; }
__device__ __forceinline__ float rcpf(float x) { float y; asm("rcp.approx.ftz.f32 %0, %1;" : "=f"(y) : "f"(x)); return y; }
constexpr float GELU_C1 = 0.7978845608028654f, GELU_C3 = 0.035677408136300125f;
__device__ __forceinline__ float gelu_k(float g, float c1, float c3, float k) {
  float t;
  asm("tanh.approx.f32 %0, %1;" : "=f"(t) : "f"(g * fmaf(g * g, c3, c1)));
  g *= k;
  return fmaf(g, t, g);
}
__device__ __forceinline__ float silu_half(float z) { float t; asm("tanh.approx.f32 %0, %1;" : "=f"(t) : "f"(z)); return fmaf(z, t, z); }

__device__ __forceinline__ void wg_fence() { asm volatile("wgmma.fence.sync.aligned;" ::: "memory"); }
__device__ __forceinline__ void wg_commit() { asm volatile("wgmma.commit_group.sync.aligned;" ::: "memory"); }
template <int N> __device__ __forceinline__ void wg_wait() { asm volatile("wgmma.wait_group.sync.aligned %0;" ::"n"(N) : "memory"); }
#define A8(o) "+f"(d[(o)]), "+f"(d[(o) + 1]), "+f"(d[(o) + 2]), "+f"(d[(o) + 3]), "+f"(d[(o) + 4]), "+f"(d[(o) + 5]), "+f"(d[(o) + 6]), "+f"(d[(o) + 7])
#define A64(o) A8(o), A8((o) + 8), A8((o) + 16), A8((o) + 24), A8((o) + 32), A8((o) + 40), A8((o) + 48), A8((o) + 56)
#define REGS0_63 "%0,%1,%2,%3,%4,%5,%6,%7,%8,%9,%10,%11,%12,%13,%14,%15,%16,%17,%18,%19,%20,%21,%22,%23,%24,%25,%26,%27,%28,%29,%30,%31," \
                 "%32,%33,%34,%35,%36,%37,%38,%39,%40,%41,%42,%43,%44,%45,%46,%47,%48,%49,%50,%51,%52,%53,%54,%55,%56,%57,%58,%59,%60,%61,%62,%63"
#define REGS64_127 "%64,%65,%66,%67,%68,%69,%70,%71,%72,%73,%74,%75,%76,%77,%78,%79,%80,%81,%82,%83,%84,%85,%86,%87,%88,%89,%90,%91,%92,%93,%94,%95," \
                   "%96,%97,%98,%99,%100,%101,%102,%103,%104,%105,%106,%107,%108,%109,%110,%111,%112,%113,%114,%115,%116,%117,%118,%119,%120,%121,%122,%123,%124,%125,%126,%127"
__device__ __forceinline__ void desc_add(uint64_t& x, int v) { asm volatile("{\n.reg .b32 lo, hi;\nmov.b64 {lo, hi}, %0;\nadd.s32 lo, lo, %1;\nmov.b64 %0, {lo, hi};\n}" : "+l"(x) : "r"(v)); }
template <int ACCUM> __device__ __forceinline__ void wgmma256(float (&d)[128], uint64_t& a, uint64_t& b, int da, int db) {
  asm volatile("{\n.reg .pred p;\nsetp.ne.b32 p, %130, 0;\n"
               "wgmma.mma_async.sync.aligned.m64n256k16.f32.bf16.bf16 {" REGS0_63 "," REGS64_127 "}, %128, %129, p, 1, 1, 0, 1;\n}"
               : A64(0), A64(64) : "l"(a), "l"(b), "n"(ACCUM));
  desc_add(a, da); desc_add(b, db);
}
__device__ __forceinline__ void wgmma256_rs(float (&d)[128], uint32_t a0, uint32_t a1, uint32_t z0, uint32_t z1, uint32_t b_lo) {
  asm volatile("{\n.reg .b64 db;\nmov.b64 db, {%132, 0x00000008};\n"
               "wgmma.mma_async.sync.aligned.m64n256k16.f32.bf16.bf16 {" REGS0_63 "," REGS64_127 "}, {%128,%129,%130,%131}, db, 1, 1, 1, 0;\n}"
               : A64(0), A64(64) : "r"(a0), "r"(a1), "r"(z0), "r"(z1), "r"(b_lo));
}
template <int ACCUM> __device__ __forceinline__ void wgmma128(float (&d)[64], uint64_t& a, uint64_t& b, int da, int db) {
  asm volatile("{\n.reg .pred p;\nsetp.ne.b32 p, %66, 0;\n"
               "wgmma.mma_async.sync.aligned.m64n128k16.f32.bf16.bf16 {" REGS0_63 "}, %64, %65, p, 1, 1, 0, 1;\n}"
               : A64(0) : "l"(a), "l"(b), "n"(ACCUM));
  desc_add(a, da); desc_add(b, db);
}
template <int ACCUM> __device__ __forceinline__ void hmma(float (&c)[4], uint32_t a0, uint32_t a1, uint32_t a2, uint32_t a3, uint32_t b0, uint32_t b1) {
  if (ACCUM)
    asm volatile("mma.sync.aligned.m16n8k16.row.col.f32.bf16.bf16.f32 {%0,%1,%2,%3}, {%4,%5,%6,%7}, {%8,%9}, {%0,%1,%2,%3};"
                 : "+f"(c[0]), "+f"(c[1]), "+f"(c[2]), "+f"(c[3]) : "r"(a0), "r"(a1), "r"(a2), "r"(a3), "r"(b0), "r"(b1));
  else
    asm volatile("mma.sync.aligned.m16n8k16.row.col.f32.bf16.bf16.f32 {%0,%1,%2,%3}, {%4,%5,%6,%7}, {%8,%9}, {%10,%10,%10,%10};"
                 : "=f"(c[0]), "=f"(c[1]), "=f"(c[2]), "=f"(c[3]) : "r"(a0), "r"(a1), "r"(a2), "r"(a3), "r"(b0), "r"(b1), "f"(0.f));
}
__device__ __forceinline__ uint32_t movm(uint32_t a) { uint32_t d; asm volatile("movmatrix.sync.aligned.m8n8.trans.b16 %0, %1;" : "=r"(d) : "r"(a)); return d; }
__device__ __forceinline__ int lane_here() { int v; asm volatile("mov.u32 %0, %%laneid;" : "=r"(v)); return v; }
template <int N> __device__ __forceinline__ void pin(uint32_t* r) {
#pragma unroll
  for (int i = 0; i < N; i++) asm volatile("" : "+r"(r[i]));
}
template <int N> __device__ __forceinline__ void pin(float* r) {
#pragma unroll
  for (int i = 0; i < N; i++) asm volatile("" : "+f"(r[i]));
}
__device__ __forceinline__ void sched_fence(uint32_t zero) {
  asm volatile("{\n.reg .pred p;\nsetp.eq.u32 p, %0, 0;\nLAB_F:\n@p bra.uni LAB_D;\nnanosleep.u32 0;\nbra.uni LAB_F;\nLAB_D:\n}" ::"r"(zero) : "memory");
}
__device__ __forceinline__ uint4 ldsm(uint32_t a) { uint4 v; asm volatile("ldmatrix.sync.aligned.m8n8.x4.shared.b16 {%0,%1,%2,%3}, [%4];" : "=r"(v.x), "=r"(v.y), "=r"(v.z), "=r"(v.w) : "r"(a) : "memory"); return v; }
__device__ __forceinline__ uint4 ldsm_t(uint32_t a) { uint4 v; asm volatile("ldmatrix.sync.aligned.m8n8.x4.trans.shared.b16 {%0,%1,%2,%3}, [%4];" : "=r"(v.x), "=r"(v.y), "=r"(v.z), "=r"(v.w) : "r"(a) : "memory"); return v; }

constexpr int BAR_LAG = 1, BAR_MMA = 2, BAR_EV = 3;

struct Cons {
  uint32_t sb;
  mutable uint64_t a, b;
  int k1, k2, k4, k4w, b1;
  uint32_t rel;
  bool do_rel;
  int wg;
  uint32_t zero;
};
#define REL_TS(n) TS(64 + (n))
constexpr uint32_t DB_LO = (SM_BASE >> 4) | ((8192 >> 4) << 16);

template <int ST, int ACCUM, bool WAIT = true> __device__ __forceinline__ void p1_issue(float (&acc)[128], const Cons& c, uint32_t parity) {
  if (WAIT) mbar_spin(c.sb + B_F1 + 8 * ST, parity, c.zero);
  wg_fence();
  wgmma256<ACCUM>(acc, c.a, c.b, c.k1, c.b1);
  wgmma256<1>(acc, c.a, c.b, c.k2, c.b1);
  wgmma256<1>(acc, c.a, c.b, c.k1, c.b1);
  wgmma256<1>(acc, c.a, c.b, ST == 3 ? c.k4w : c.k4, ST == 3 ? -6144 - 384 : 2048 - 384);
  wg_commit();
}
__device__ __forceinline__ void release(const Cons& c, uint32_t bar) { if (c.do_rel) mbar_arrive_cl(c.rel + bar); }
template <int KB, bool WAIT = true> __device__ __forceinline__ void p1_step(float (&acc)[128], const Cons& c) {
  if (KB == 15) { if (c.wg == 1) { wg_wait<0>(); release(c, B_E1 + 16); bar_sync(BAR_LAG, 256); } }
  p1_issue<KB & 3, KB != 0, WAIT>(acc, c, (KB >> 2) & 1);
  if (KB == 15) { if (c.wg == 0) bar_arrive(BAR_LAG, 256); }
  if (KB > 0) { wg_wait<1>(); if (KB != 15 || c.wg == 0) release(c, B_E1 + 8 * ((KB - 1) & 3)); }
  if (KB == 15) { wg_wait<0>(); release(c, B_E1 + 24); }
}
template <class F> __device__ __forceinline__ void p1_loop(float (&acc)[128], const Cons& c, int from, int to, F&& shadow) {
#pragma unroll 1
  for (int kb = from; kb < to; kb++) {
    const bool wrap = (kb & 3) == 3;
    mbar_spin(c.sb + B_F1 + 8 * (kb & 3), (kb >> 2) & 1, c.zero);
    wg_fence();
    wgmma256<1>(acc, c.a, c.b, c.k1, c.b1);
    wgmma256<1>(acc, c.a, c.b, c.k2, c.b1);
    wgmma256<1>(acc, c.a, c.b, c.k1, c.b1);
    wgmma256<1>(acc, c.a, c.b, wrap ? c.k4w : c.k4, wrap ? -6144 - 384 : 2048 - 384);
    wg_commit();
    wg_wait<1>();
    release(c, B_E1 + 8 * ((kb - 1) & 3));
    shadow(kb);
  }
}
template <int T> __device__ __forceinline__ void p2_step(float (&acc)[64], const Cons& c) {
  if (T == 16 - LAG2) { if (c.wg == 1) bar_sync(BAR_LAG, 256); }
  mbar_spin(c.sb + B_F2 + 8 * (T % 5), (T / 5) & 1, c.zero);
  wg_fence();
  wgmma128<T != 0>(acc, c.a, c.b, c.k1, c.b1);
  wgmma128<1>(acc, c.a, c.b, c.k2, c.b1);
  wgmma128<1>(acc, c.a, c.b, c.k1, c.b1);
  wgmma128<1>(acc, c.a, c.b, ((int)p2_a((T + 1) % 5) - (int)p2_a(T % 5)) / 16 - 514, ((int)p2_b((T + 1) % 5) - (int)p2_b(T % 5)) / 16 - 384);
  wg_commit();
  if (T == 15) { if (c.wg == 0) bar_arrive(BAR_LAG, 256); }
  if (T <= 11) { wg_wait<1>(); release(c, T ? B_E2 + 8 * ((T + 5 - 1) % 5) : B_E1 + 8); }
}

template <int P> __device__ __forceinline__ void geglu_piece(uint32_t (&pk)[64], uint8_t* dst, float (&rs)[2]) {
  constexpr int cg = P >> 1, r = P & 1;
  pin<1>(rs + r);
#pragma unroll
  for (int i = 0; i < 4; i++) pin<1>(pk + 2 * (4 * cg + i) + r);
  const float r2 = rs[r] * rs[r], c1 = GELU_C1 * rs[r], c3 = GELU_C3 * r2 * rs[r], k = 0.25f * r2;
  uint32_t v[4];
#pragma unroll
  for (int i = 0; i < 4; i++) {
    const uint32_t g = pk[2 * (4 * cg + i) + r];
    v[i] = mul2(pack2(gelu_k(lo_f(g), c1, c3, k), gelu_k(hi_f(g), c1, c3, k)), pk[32 + 2 * (4 * cg + i) + r]);
  }
  stg128(dst + cg * 8192 + r * 512, v[0], v[1], v[2], v[3]);
}
__device__ __forceinline__ void geglu_tile(float (&acc)[128], uint32_t (&pk)[64], const Cons& c, int to, uint8_t* dst, int ev, float (&rs)[2]) {
  const int lane = lane_here();
  dst += (lane ^ (lane >> 3)) << 4;
  p1_loop(acc, c, 1, to, [&](int kb) {
    if (kb <= 4) {
      if (kb <= 2) { if (kb == 1) geglu_piece<0>(pk, dst, rs); else geglu_piece<1>(pk, dst, rs); }
      else { if (kb == 3) geglu_piece<2>(pk, dst, rs); else geglu_piece<3>(pk, dst, rs); }
    } else if (kb <= 8) {
      if (kb <= 6) { if (kb == 5) geglu_piece<4>(pk, dst, rs); else geglu_piece<5>(pk, dst, rs); }
      else { if (kb == 7) geglu_piece<6>(pk, dst, rs); else { geglu_piece<7>(pk, dst, rs); bar_arrive(ev, 288); } }
    }
  });
}

__device__ __forceinline__ void attn_tile(float (&acc)[128], uint32_t (&pk)[64], const Cons& c, int round, int warp, int m, unsigned bid, Scratch* gs, uint8_t* hdst, uint8_t* odst) {
  const int w = warp & 3;
  const uint32_t at = c.sb + OFF_X + c.wg * AT_WG;
  int lane = lane_here();
  hdst += (lane ^ (lane >> 3)) << 4;
  auto scatter = [&]() {
    const int lane = lane_here();
    const uint32_t swz = (lane ^ (lane >> 3)) << 4;
#pragma unroll
    for (int i = 0; i < 4; i++) {
      const int h = i & 1, r = i >> 1;
      sts128(at + AT_V + (2 * w + r) * 1024 + h * 512 + swz, make_uint4(pk[32 + 8 * h + r], pk[34 + 8 * h + r], pk[36 + 8 * h + r], pk[38 + 8 * h + r]));
    }
    if (w < 3) {
#pragma unroll
      for (int i = 0; i < 8; i++) asm volatile("st.shared.b32 [%0], %1;" ::"r"(at + AT_K + w * 1024 + i * 128 + lane * 4), "r"(pk[17 + 2 * i]) : "memory");
    } else {
      uint8_t* g = (uint8_t*)gs->halo + ((round * 128 + bid) * 2 + c.wg) * 2048;
#pragma unroll
      for (int i = 0; i < 8; i++) asm volatile("st.global.b32 [%0], %1;" ::"l"(g + i * 128 + lane * 4), "r"(pk[17 + 2 * i]) : "memory");
#pragma unroll
      for (int h = 0; h < 2; h++) stg128(g + 1024 + h * 512 + swz, pk[33 + 8 * h], pk[35 + 8 * h], pk[37 + 8 * h], pk[39 + 8 * h]);
      bar_arrive(BAR_EV + 2 + round, 96);
    }
    __syncwarp();
    if (lane == 0) mbar_arrive(c.sb + B_HALO + 8 * round);
    if (round) {
#pragma unroll
      for (int p = 0; p < 4; p++) {
        const int o = 32 + 8 * (p >> 1) + (p & 1);
        asm volatile("ld.global.cg.v4.b32 {%0,%1,%2,%3}, [%4];" : "=r"(pk[o]), "=r"(pk[o + 2]), "=r"(pk[o + 4]), "=r"(pk[o + 6]) : "l"(hdst + (p >> 1) * 8192 + (p & 1) * 512) : "memory");
      }
    }
  };
  auto gu_piece = [&](int p) {
    uint32_t v[4];
#pragma unroll
    for (int i = 0; i < 4; i++) {
      const int o = 8 * (p >> 1) + 2 * i + (p & 1);
      pin<1>(pk + 48 + o);
      const uint32_t g = pk[48 + o];
      v[i] = mul2(round ? pk[32 + o] : 0x3e803e80u, round ? g : pack2(gelu_k(lo_f(g), GELU_C1, GELU_C3, 1.0f), gelu_k(hi_f(g), GELU_C1, GELU_C3, 1.0f)));
    }
    stg128(hdst + (p >> 1) * 8192 + (p & 1) * 512, v[0], v[1], v[2], v[3]);
  };
  p1_step<1>(acc, c);
  scatter();
  p1_loop(acc, c, 2, 9, [&](int kb) {
    if (kb <= 4) { if (kb == 3) gu_piece(0); else if (kb == 4) gu_piece(1); }
    else if (kb == 5) gu_piece(2); else if (kb == 6) gu_piece(3);
  });
  const bool first = m == 0 && w == 0;
  uint32_t kl[16];
  mbar_spin(c.sb + B_HALO + 8 * round, 0, c.zero);
  lane = lane_here();
  {
    const uint32_t ka = at + lane * 4 + (w ? AT_K + (w - 1) * 1024 : (first ? AT_K : AT_REM + round * 2048));
#pragma unroll
    for (int i = 0; i < 8; i++) {
      asm volatile("ld.shared.b32 %0, [%1];" : "=r"(kl[2 * i]) : "r"(ka + i * 128) : "memory");
      kl[2 * i + 1] = pk[16 + 2 * i] | c.zero;
    }
  }
  float st[4][4];
  pin<16>(kl);
  bar_sync(BAR_MMA, 256);
  mbar_spin(c.sb + B_F1 + 8 * 1, 0, c.zero);
#pragma unroll
  for (int ks = 0; ks < 2; ks++) {
#pragma unroll
    for (int h = 0; h < 2; h++) {
      const int o = 8 * h + 4 * ks;
      if (ks == 0) { hmma<0>(st[2 * h], kl[o], kl[o + 1], kl[o + 2], kl[o + 3], pk[o], pk[o + 2]); hmma<0>(st[2 * h + 1], pk[16 + o], pk[17 + o], pk[18 + o], pk[19 + o], pk[o + 1], pk[o + 3]); }
      else { hmma<1>(st[2 * h], kl[o], kl[o + 1], kl[o + 2], kl[o + 3], pk[o], pk[o + 2]); hmma<1>(st[2 * h + 1], pk[16 + o], pk[17 + o], pk[18 + o], pk[19 + o], pk[o + 1], pk[o + 3]); }
    }
  }
  sched_fence(c.zero);
  bar_sync(BAR_MMA, 256);
  p1_step<9, false>(acc, c);
  sched_fence(c.zero);
  pin<16>(&st[0][0]);
  lane = lane_here();
  const int rho = lane >> 2, q = lane & 3;
  const bool le0 = 2 * q <= rho, le1 = 2 * q + 1 <= rho;
  uint32_t la[2], lb[2], mx[2];
#pragma unroll
  for (int h = 0; h < 2; h++) {
    uint32_t l[2];
#pragma unroll
    for (int r = 0; r < 2; r++) {
      const float (&t)[4] = st[2 * h + r];
      l[r] = movm(pack2(rho <= 2 * q ? t[2] : t[0], rho <= 2 * q + 1 ? t[3] : t[1]));
      l[r] = fma2(l[r], 0x3e353e35u, mul2(l[r], 0x379e379eu));
    }
    la[h] = __byte_perm(l[0], l[1], 0x5410); lb[h] = __byte_perm(l[0], l[1], 0x7632);
    if (first && !le0) la[h] = (la[h] & 0xffff0000u) | 0xce6eu;
    if (first && !le1) lb[h] = (lb[h] & 0xffff0000u) | 0xce6eu;
    mx[h] = max2(la[h], lb[h]);
  }
#pragma unroll
  for (int o = 1; o <= 2; o++) { mx[0] = max2(mx[0], __shfl_xor_sync(~0u, mx[0], o)); mx[1] = max2(mx[1], __shfl_xor_sync(~0u, mx[1], o)); }
  const float L2E = 1.4426950408889634f;
  float pr[2][4], z[4];
#pragma unroll
  for (int h = 0; h < 2; h++) {
    pr[h][0] = ex2f((lo_f(la[h]) - lo_f(mx[h])) * L2E); pr[h][1] = ex2f((lo_f(lb[h]) - lo_f(mx[h])) * L2E);
    pr[h][2] = ex2f((hi_f(la[h]) - hi_f(mx[h])) * L2E); pr[h][3] = ex2f((hi_f(lb[h]) - hi_f(mx[h])) * L2E);
    z[2 * h] = pr[h][0] + pr[h][1]; z[2 * h + 1] = pr[h][2] + pr[h][3];
  }
  p1_step<10>(acc, c);
#pragma unroll
  for (int o = 1; o <= 2; o++) {
#pragma unroll
    for (int i = 0; i < 4; i++) z[i] += __shfl_xor_sync(~0u, z[i], o);
  }
  const uint32_t LE = (le0 ? 0xffffu : 0u) | (le1 ? 0xffff0000u : 0u);
  uint32_t P[4][2];
  uint4 vt[4][2];
  {
    const uint32_t row = (lane & 7) * 64 + ((((lane >> 3) & 1) ^ ((lane & 7) >> 1)) << 4);
    const uint32_t v1 = at + AT_V + (2 * w + (lane >> 4)) * 1024 + row;
    const uint32_t v0 = (w || lane >= 16) ? v1 - 1024 : (first ? v1 : at + AT_REM + round * 2048 + 1024 + row);
#pragma unroll
    for (int i = 0; i < 4; i++) {
      const float rz = rcpf(z[i]);
      const uint32_t p = pack2(pr[i >> 1][2 * (i & 1)] * rz, pr[i >> 1][2 * (i & 1) + 1] * rz);
      P[i][0] = p & ~LE; P[i][1] = p & LE;
      const uint32_t a = ((i & 1) ? v1 : v0) + (i >> 1) * 512;
      vt[i][0] = ldsm_t(a); vt[i][1] = ldsm_t(a ^ 32);
    }
  }
  float ot[4][2][4];
  pin<8>(&P[0][0]);
  bar_sync(BAR_MMA, 256);
  mbar_spin(c.sb + B_F1 + 8 * 3, 0, c.zero);
#pragma unroll
  for (int i = 0; i < 8; i++) { const uint4& v = vt[i >> 1][i & 1]; hmma<0>(ot[i >> 1][i & 1], v.x, v.y, v.z, v.w, P[i >> 1][0], P[i >> 1][1]); }
  sched_fence(c.zero);
  bar_sync(BAR_MMA, 256);
  p1_step<11, false>(acc, c);
  sched_fence(c.zero);
  pin<32>(&ot[0][0][0]);
  lane = lane_here();
  odst += (lane ^ (lane >> 3)) << 4;
  auto o_piece = [&](int i) {
    stg128(odst + (i >> 1) * 8192 + (i & 1) * 512, movm(pack2(ot[i][0][0], ot[i][0][1])), movm(pack2(ot[i][0][2], ot[i][0][3])), movm(pack2(ot[i][1][0], ot[i][1][1])), movm(pack2(ot[i][1][2], ot[i][1][3])));
  };
  o_piece(0); o_piece(1);
  p1_step<12>(acc, c);
  o_piece(2); o_piece(3);
  if (round) bar_arrive(BAR_EV + 4, 288);
  p1_step<13>(acc, c);
}

__device__ __forceinline__ void ln_moments(const uint32_t* raw, float& c0, float& s, float& v) {
  c0 = lo_f(__shfl_sync(~0u, raw[0], 0));
  float ss[4] = {0.f, 0.f, 0.f, 0.f}, vv[4] = {0.f, 0.f, 0.f, 0.f};
#pragma unroll
  for (int i = 0; i < 16; i++) {
    const float a = lo_f(raw[i]) - c0, b = hi_f(raw[i]) - c0;
    ss[(2 * i) & 3] += a; ss[(2 * i + 1) & 3] += b;
    vv[(2 * i) & 3] = fmaf(a, a, vv[(2 * i) & 3]); vv[(2 * i + 1) & 3] = fmaf(b, b, vv[(2 * i + 1) & 3]);
  }
  s = (ss[0] + ss[1]) + (ss[2] + ss[3]); v = (vv[0] + vv[1]) + (vv[2] + vv[3]);
}
__device__ __forceinline__ void ln_reduce(float& s, float& v) {
#pragma unroll
  for (int o = 16; o; o >>= 1) { s += __shfl_xor_sync(~0u, s, o); v += __shfl_xor_sync(~0u, v, o); }
}
__device__ __forceinline__ uint32_t ln_finish(float c0, float s, float v) {
  s *= 1.0f / DM;
  float sd;
  asm("sqrt.approx.ftz.f32 %0, %1;" : "=f"(sd) : "f"(bf16r(bf16r(fmaxf(fmaf(v, 1.0f / DM, -s * s), 0.f)) + 1e-5f)));
  return pack2(c0 + s, sd);
}
__device__ __forceinline__ void ln_store(const uint32_t* raw, uint32_t st, uint4* dst) {
  const uint32_t m2 = __byte_perm(st, st, 0x1010);
  const float rinv = rcpf(hi_f(st));
  const uint32_t rh = pack2(rinv, rinv), rl = pack2(rinv - hi_f(rh), rinv - hi_f(rh));
#pragma unroll
  for (int c = 0; c < 4; c++) {
    uint32_t v[4];
#pragma unroll
    for (int i = 0; i < 4; i++) { const uint32_t t = sub2(raw[4 * c + i], m2); v[i] = fma2(t, rh, mul2(t, rl)); }
    stg128(dst + 32 * c, v[0], v[1], v[2], v[3]);
  }
}
__device__ __forceinline__ void col_sums(uint32_t tile, ulonglong2* part, uint32_t tag) {
  const int lane = threadIdx.x & 31;
  float cs[8] = {0, 0, 0, 0, 0, 0, 0, 0};
  uint32_t base = tile + ((lane >> 3) & 1) * 8192 + (lane >> 4) * 4096 + ((lane & 7) << 4);
#pragma unroll 1
  for (int k0 = 0; k0 < 8; k0++, base = (base ^ ((k0 ^ (k0 - 1)) << 4)) + 128) {
    uint4 v[4];
#pragma unroll
    for (int k = 0; k < 4; k++) v[k] = lds128(base + k * 1024);
#pragma unroll
    for (int k = 0; k < 4; k++) {
      cs[0] += lo_f(v[k].x); cs[1] += hi_f(v[k].x); cs[2] += lo_f(v[k].y); cs[3] += hi_f(v[k].y);
      cs[4] += lo_f(v[k].z); cs[5] += hi_f(v[k].z); cs[6] += lo_f(v[k].w); cs[7] += hi_f(v[k].w);
    }
  }
  const bool up = lane >= 16;
#pragma unroll
  for (int i = 0; i < 2; i++) {
    const float a = (up ? cs[4 + 2 * i] : cs[2 * i]) + __shfl_xor_sync(~0u, up ? cs[2 * i] : cs[4 + 2 * i], 16);
    const float b = (up ? cs[5 + 2 * i] : cs[1 + 2 * i]) + __shfl_xor_sync(~0u, up ? cs[1 + 2 * i] : cs[5 + 2 * i], 16);
    asm volatile("{\n.reg .b64 a, b;\nmov.b64 a, {%1, %3};\nmov.b64 b, {%2, %3};\nst.relaxed.gpu.global.v2.b64 [%0], {a, b};\n}"
                 ::"l"(part + 32 * (i + (up ? 2 : 0)) + (lane & 15)), "r"(__float_as_uint(a)), "r"(__float_as_uint(b)), "r"(tag) : "memory");
  }
  asm volatile("fence.proxy.async.shared::cta;" ::: "memory");
}

__global__ void __cluster_dims__(2, 1, 1) __launch_bounds__(384, 1)
fused_kernel(const uint4* __restrict__ x, const uint4* __restrict__ wgate, const uint4* __restrict__ wup, Scratch* gs, const __grid_constant__ Maps mp) {
  extern __shared__ __align__(1024) uint8_t smem_raw[];
  const uint32_t sb = (uint32_t)__cvta_generic_to_shared(smem_raw);
  const unsigned bid = role_id();
  if (threadIdx.x == 352) TS(63);
  if (threadIdx.x < 256 && bid < NMAIN) {
    const uint32_t r = threadIdx.x >> 3, ch = threadIdx.x & 7;
    const uint32_t d = sb + r * 128 + ((ch ^ (r & 7)) << 4);
    const uint8_t* xa = (const uint8_t*)x + ((bid & 15) * 262144 + r * 4096 + ch * 16);
    const uint32_t wo = r * (DFF * 2) + (bid >> 4) * 256 + ch * 16;
    const uint8_t *wa = (const uint8_t*)wgate + wo, *wb = (const uint8_t*)wup + wo;
#pragma unroll
    for (int i = 0; i < 12; i++) {
      const int h = i >= 8;
      const uint8_t* src = (i >> 2) == 1 ? xa + (i & 1) * 131072 + ((i >> 1) & 1) * 2048 : ((i & 2) ? wb : wa) + h * 32 * (DFF * 2) + (i & 1) * 128;
      asm volatile("cp.async.cg.shared.global [%0], [%1], 16;" ::"r"(d + ((i >> 2) == 1 ? OFF_A + (i & 3) * 4096 : (i & 3) * 8192 + h * 4096)), "l"(src) : "memory");
    }
    if (threadIdx.x == 0) TS(23);
  }
  const int warp = __shfl_sync(~0u, threadIdx.x >> 5, 0), lane = threadIdx.x & 31;
  const int m = bid & 15, j = bid >> 4, rank = bid & 1;
  const int m2 = bid >> 3, j2 = bid & 7;
  const bool helper = bid >= NMAIN;
  if (warp >= 8) {
    asm volatile("setmaxnreg.dec.sync.aligned.u32 40;");
    if (warp == 8) {
      if (elect_one()) {
        asm volatile("prefetch.tensormap [%0];\nprefetch.tensormap [%1];\nprefetch.tensormap [%2];" ::"l"(&mp.x), "l"(&mp.wg), "l"(&mp.wu) : "memory");
        for (int s = 0; s < 4; s++) mbar_init(sb + B_F1 + 8 * s, 1);
        if (!helper) mbar_arrive(sb + B_F1);
        asm volatile("fence.mbarrier_init.release.cluster;" ::: "memory");
      }
      __syncwarp();
    } else if (warp == 9) {
      if (elect_one()) {
        if ((sb & 0xffffff) != SM_BASE) asm volatile("trap;");
        for (uint32_t b = B_E1; b < B_F2; b += 8) mbar_init(sb + b, 4);
        for (uint32_t b = B_F2; b < B_AUX; b += 8) mbar_init(sb + b, 1);
        for (uint32_t b = B_EX; b < B_AUX; b += 8) mbar_expect_tx(sb + b, 8192);
        mbar_init(sb + B_AUX, 8); mbar_init(sb + B_HALO, 9); mbar_init(sb + B_HALO + 8, 9);
        asm volatile("st.shared.b32 [%0], %1;" ::"r"(sb + OFF_EPOCH + 4), "r"(bid) : "memory");
        asm volatile("fence.mbarrier_init.release.cluster;" ::: "memory");
      }
      __syncwarp();
    }
    asm volatile("barrier.cluster.arrive.relaxed.aligned;" ::: "memory");
    if (warp == 8 && !helper) {
      if (elect_one()) {
        TS(0); TG(51);
#pragma unroll 1
        for (int kb = 1; kb < 4; kb++) {
          const uint32_t sa = sb + OFF_A + kb * 16384, sw = sb + kb * 32768, fb = sb + B_F1 + 8 * kb;
          mbar_expect_tx(fb, P1_BYTES);
          tma3d(sa, &mp.x, fb, kb * 64, m * 64, 0, EVICT_NORMAL);
          tma2d(sw, &mp.wg, fb, j * 128, kb * 64, EVICT_NORMAL); tma2d(sw + 16384, &mp.wu, fb, j * 128, kb * 64, EVICT_NORMAL);
          tma2d(sw + 8192, &mp.wg, fb, j * 128 + 64, kb * 64, EVICT_NORMAL); tma2d(sw + 24576, &mp.wu, fb, j * 128 + 64, kb * 64, EVICT_NORMAL);
        }
        TS(7);
      }
      __syncwarp();
    }
    asm volatile("barrier.cluster.wait.aligned;" ::: "memory");
    if (helper) {
      if (warp == 8) {
        unsigned e = 0;
        if (elect_one()) {
#pragma unroll 1
          for (int i = 0; i < 16; i++) {
            const uint32_t fb = sb + B_F1 + 8 * (i >> 2);
            if (!(i & 3)) mbar_expect_tx(fb, P1_BYTES);
            tma5d(sb + i * 8192, &mp.wd, fb, (bid - NMAIN) * 256 + (i & 3) * 64, (i >> 2) * 2, HINT_W);
          }
        }
        if (lane == 0) { unsigned* ep = &gs->epoch[bid * 2]; e = *ep + 1; *ep = e; }
        e = __shfl_sync(~0u, e, 0);
        if (lane < 16) flag_wait(&gs->flags[(FL_H + lane * 4) * 32], e * 8u);
        __syncwarp();
        if (elect_one()) {
          fence_async();
          TS(0);
#pragma unroll 1
          for (int i = 0; i < 64; i++) {
            const uint32_t fb = sb + B_F1 + 8 * (i & 3);
            if (i >= 4) { mbar_wait(sb + B_E1 + 8 * (i & 3), ~(i >> 2) & 1); mbar_expect_tx(fb, 16384); }
            bulk_load(sb + OFF_A + (i & 3) * 16384, gs->h + ((i >> 2) * 56 + (i & 3)) * 1024, 16384, fb, EVICT_NORMAL);
          }
        }
      } else if (warp == 9) {
#pragma unroll 1
        for (int t = 0; t < 16; t++) {
          bar_sync(BAR_EV + (t & 1), 288);
          if (lane == 0) { flag_add(&gs->flags[(FL_P + t) * 32]); TS(64 + t); }
          __syncwarp();
        }
      }
    } else if (warp == 8) {
      if (elect_one()) {
        uint32_t par = 0;

        auto x_load = [&]() {
          mbar_expect_tx(sb + B_XT, 32768);
          tma3d(sb + OFF_X, &mp.x, sb + B_XT, j2 * 128, m2 * 64, 0, HINT_LAST); tma3d(sb + OFF_X + 16384, &mp.x, sb + B_XT, j2 * 128 + 64, m2 * 64, 0, HINT_LAST);
        };
        auto d_prefetch = [&](int i) {
          if ((m2 >> 2) == (i & 3)) tma5d_prefetch(&mp.wd, (j2 >> 1) * 256 + (m2 & 3) * 64, (2 * i + 4 + rank) * 2);
        };
        auto w_tile = [&](int R, const CUtensorMap*& mb0, const CUtensorMap*& mb1, int& n0, int& n1) {
          if (R == 1 || R == 2) {
            mb0 = &mp.wqkv; n0 = 64 * (j + 8 * (R - 1)) + rank * 2048;
            mb1 = rank ? (R == 1 ? &mp.wg : &mp.wu) : &mp.wqkv; n1 = rank ? 1024 + 64 * j : n0 + 1024;
          } else {
            mb0 = mb1 = rank ? &mp.wu : &mp.wg;
            n0 = 128 * j + (R ? 1024 * R - 1536 : 0); n1 = n0 + 64;
          }
        };
        for (int R = 0; R < 5; R++) {
          const CUtensorMap *mb0, *mb1;
          int n0, n1;
          w_tile(R, mb0, mb1, n0, n1);
#pragma unroll 1
          for (int kb = R ? 0 : 4; kb < 16; kb++) {
            if (R == 0 && kb == 14) { asm volatile("prefetch.tensormap [%0];\nprefetch.tensormap [%1];" ::"l"(&mp.xn), "l"(&mp.wqkv) : "memory"); }
            if (R == 4 && kb == 2) { asm volatile("prefetch.tensormap [%0];\nprefetch.tensormap [%1];\nprefetch.tensormap [%2];" ::"l"(&mp.wd), "l"(&mp.wo), "l"(&mp.out) : "memory"); }
            if (R == 0 && kb == CS_KB) {
#pragma unroll 1
              for (int h = 0; h < 2; h++) {
                const uint32_t cb = sb + B_CS + 8 * h, d = sb + OFF_X + 16384 * h;
                mbar_expect_tx(cb, 16384);
                tma2d(d, h ? &mp.wu : &mp.wg, cb, n0, m * 64, EVICT_NORMAL); tma2d(d + 8192, h ? &mp.wu : &mp.wg, cb, n1, m * 64, EVICT_NORMAL);
              }
            }
            const int st = kb & 3;
            const uint32_t sa = sb + OFF_A + st * 16384, sw = sb + st * 32768, fb = sb + B_F1 + 8 * st;
            mbar_wait(sb + B_E1 + 8 * st, par);
            if (R * 16 + kb >= 4) REL_TS(R * 16 + kb - 4);
            mbar_expect_tx(fb, P1_BYTES);
            tma2d_mc(sw + rank * 16384, mb0, fb, n0, kb * 64, HINT_W);
            tma2d_mc(sw + 8192 + rank * 16384, mb1, fb, n1, kb * 64, HINT_W);
            if (R == 0) {
              tma3d(sa, &mp.x, fb, kb * 64, m * 64, 0, EVICT_NORMAL);
            } else {
              if (R == 1 && kb == 0) { mbar_wait(sb + B_DEP, 0); TS(1); }
              tma2d(sa, &mp.xn, fb, kb * 64, m * 128, R == 4 ? HINT_LAST : EVICT_NORMAL);
            }
            if (R == 4 && kb == 4 + j2) x_load();
            if (R == 4 && kb >= 16 - PF_D) d_prefetch(kb + PF_D - 16);
            if (st == 3) par ^= 1;
          }
        }
#pragma unroll 1
        for (int i = 0; i < 26; i++) {
          const int st = i & 3, kb = 2 * i + 4 + rank;
          const uint32_t sa = sb + OFF_A + st * 16384, sw = sb + st * 32768, fb = sb + B_F1 + 8 * st;
          mbar_wait(sb + B_E1 + 8 * st, par);
          REL_TS(76 + i);
          mbar_expect_tx(fb, P1_BYTES);
          tma5d(sw, &mp.wd, fb, j2 * 128, kb * 2, HINT_W); tma5d(sw + 8192, &mp.wd, fb, j2 * 128 + 64, kb * 2, HINT_W);
          tma5d(sw + 16384, &mp.wd, fb, (j2 ^ 1) * 128, kb * 2, HINT_W); tma5d(sw + 24576, &mp.wd, fb, (j2 ^ 1) * 128 + 64, kb * 2, HINT_W);
          if (i == 0 || i == 6 || i == 10 || i == 18) { mbar_wait(sb + B_DEP + 8 * (1 + ((i + 6) >> 3)), 0); }
          bulk_load(sa, gs->h + (m2 * 56 + kb) * 1024, 16384, fb, HINT_H);
          if (i + PF_D < 26) d_prefetch(i + PF_D);
          if (st == 3) par ^= 1;
        }
        int st = 0; uint32_t par2 = 1;
#pragma unroll 1
        for (int t = 0; t < 16; t++) {
          const uint32_t sa = sb + p2_a(st), sw = sb + p2_b(st), fb = sb + B_F2 + 8 * st;
          if (t < 5) mbar_wait(sb + B_E1 + 8 * (((2 * t + 1) / 3 + 2) & 3), t < 3); else mbar_wait(sb + B_E2 + 8 * st, par2);
          REL_TS(102 + t);
          mbar_expect_tx(fb, P2_BYTES);
          bulk_load_mc(sa + rank * 8192, gs->o + (m2 * 16 + t) * 1024 + rank * 512, 8192, fb, HINT_H);
          tma2d(sw, &mp.wo, fb, j2 * 128, t * 64, HINT_W); tma2d(sw + 8192, &mp.wo, fb, j2 * 128 + 64, t * 64, HINT_W);
          if (++st == 5) { st = 0; par2 ^= 1; }
        }
      }
    } else if (warp == 9) {
#pragma unroll 1
      for (int e = 0; e < 7; e++) {
        const bool halo = e == 2 || e == 3;
        bar_sync(BAR_EV + e, halo ? 96 : 288);
        if (lane == 0) {
          const int f = e == 0 ? FL_XN + m : (halo ? FL_HALO + (e - 2) * 128 + bid : FL_H + m * 4 + (e == 1 ? 0 : e - 3));
          TS(10 + 2 * e); TG(52 + e);
          flag_add(&gs->flags[f * 32]);
          if (e < 6) TS(11 + 2 * e);
        }
        __syncwarp();
      }
      unsigned other;
      asm volatile("ld.shared::cluster.b32 %0, [%1];" : "=r"(other) : "r"(mapa(sb + OFF_EPOCH + 4, rank ^ 1)) : "memory");
      if (other != (bid ^ 1)) asm volatile("trap;");
      mbar_wait(sb + B_DONE, 0);
    } else {
      unsigned e = 0;
      if (lane == 0) {
        unsigned* ep = &gs->epoch[bid * 2 + warp - 10];
        e = *ep + 1; *ep = e;
        if (warp == 10) { asm volatile("st.shared.b32 [%0], %1;" ::"r"(sb + OFF_EPOCH), "r"(e) : "memory"); mbar_arrive(sb + B_EP); }
      }
      e = __shfl_sync(~0u, e, 0);
      mbar_wait(sb + B_CS + 8 * (warp - 10), 0);
      if (lane == 0 && warp == 11) TS(6);
      col_sums(sb + OFF_X + (warp - 10) * 16384, gs->cspart + (j * 16 + m) * 128 + (warp - 10) * 16, e);
      if (lane == 0 && warp == 11) TS(9);
      if (warp == 10) {
        if (lane == 0) {
#pragma unroll 1
          for (int g = 0; g < 6; g++) {
            flag_wait(&gs->flags[(g == 5 ? FL_P + m2 : (g ? FL_H + m2 * 4 + g - 1 : FL_XN + m)) * 32], e * (g == 5 ? 4u : 8u));
            fence_async();
            mbar_arrive(sb + B_DEP + 8 * g);
            if (g == 0) TS(8);
          }
        }
      } else
      if (elect_one()) {
#pragma unroll 1
        for (int r = 0; r < 2; r++) {
          const uint32_t hb = sb + B_HALO + 8 * r;
          if (r) mbar_wait(sb + B_HALO, 0);
          if (m) {
            flag_wait(&gs->flags[(FL_HALO + r * 128 + bid - 1) * 32], e);
            fence_async();
            mbar_expect_tx(hb, 4096);
            for (int g = 0; g < 2; g++) bulk_load(sb + OFF_X + g * AT_WG + AT_REM + r * 2048, gs->halo + ((r * 128 + bid - 1) * 2 + g) * 128, 2048, hb, EVICT_FIRST);
          } else {
            mbar_arrive(hb);
          }
          TS(34 + r);
        }
      }
    }
  } else {
    asm volatile("barrier.cluster.arrive.relaxed.aligned;" ::: "memory");
    asm volatile("setmaxnreg.inc.sync.aligned.u32 232;");
    const int wg = warp >> 2, w = warp & 3;
    Cons c;
    c.sb = sb; c.wg = wg; c.zero = warp >> 8;
    c.a = 0x4000004000010000ull + ((SM_BASE + OFF_A + wg * 8192) >> 4); c.k1 = 2 + c.zero; c.k2 = 2; c.k4 = 1024 - 6; c.k4w = -3072 - 6; c.b1 = 128 + c.zero;
    c.b = 0x4000004000000000ull + DB_LO + c.zero;
    c.rel = mapa(sb, threadIdx.x & 1);
    c.do_rel = (threadIdx.x & 127) < 2;
    constexpr bool t0 = false;
    float acc[128];
    uint32_t pk[64];
    float rs[2];
    const int q = lane & 3;

    if (helper) {
      asm volatile("barrier.cluster.wait.aligned;" ::: "memory");
      c.a = 0x8000002000010000ull + ((SM_BASE + OFF_A + wg * 4096) >> 4); c.k2 = 510; c.k4 = 1024 - 514; c.k4w = -3072 - 514;
      c.rel = sb;
      uint4* dst = gs->dpart + (bid - NMAIN) * 4096 + threadIdx.x;
      auto put = [&](int p) {
#pragma unroll
        for (int i = 4 * p; i < 4 * p + 4; i++) stg128(dst + i * 256, pk[4 * i], pk[4 * i + 1], pk[4 * i + 2], pk[4 * i + 3]);
      };
#pragma unroll 1
      for (int t = 0; t < 16; t++) {
        p1_issue<0, 0>(acc, c, t & 1);
        if (t) put(0);
        p1_issue<1, 1>(acc, c, t & 1); wg_wait<1>(); release(c, B_E1);
        if (t) put(1);
        p1_issue<2, 1>(acc, c, t & 1); wg_wait<1>(); release(c, B_E1 + 8);
        if (t) put(2);
        if (wg == 1) { wg_wait<0>(); release(c, B_E1 + 16); bar_sync(BAR_LAG, 256); }
        p1_issue<3, 1>(acc, c, t & 1);
        if (wg == 0) bar_arrive(BAR_LAG, 256);
        if (t) { put(3); bar_arrive(BAR_EV + (~t & 1), 288); dst += 8 * 2048; }
        wg_wait<1>(); if (wg == 0) release(c, B_E1 + 16);
        wg_wait<0>(); release(c, B_E1 + 24);
#pragma unroll
        for (int i = 0; i < 64; i++) pk[i] = pack2(acc[2 * i], acc[2 * i + 1]);
      }
      put(0); put(1); put(2); put(3);
      bar_arrive(BAR_EV + 1, 288);
      return;
    }
    {
      const int prow = 16 * j + 2 * warp;
      const uint4* xr = x + (size_t)(128 * m + 2 * (prow & 63) + (prow >> 6)) * 128 + lane;
      uint4* xo = gs->xn + (size_t)(128 * m + prow) * 128 + lane;
      float c0[2], mo[4];
      uint32_t st[2];
      uint32_t e;
      asm volatile("" : "+l"(xr), "+l"(xo));
      asm volatile("cp.async.wait_all;\nfence.proxy.async.shared::cta;" ::: "memory");
      bar_sync(BAR_MMA, 256);
      if (threadIdx.x == 0) TS(39);
      p1_step<0, false>(acc, c);
      asm volatile("barrier.cluster.wait.aligned;" ::: "memory");
      unsigned long long part[18];
      auto gather = [&](int from, int to) {
        const int lane = lane_here();
        const unsigned long long* cp = (const unsigned long long*)gs->cspart + j * 4096 + warp * 32 + lane;
        const unsigned long long* sp = gs->stats + 128 * m + warp * 16 + (lane >> 2);
#pragma unroll
        for (int i = from; i < to; i++) asm volatile("ld.relaxed.gpu.global.b64 %0, [%1];" : "=l"(part[i]) : "l"(i < 16 ? cp + i * 256 : sp + (i - 16) * 8) : "memory");
      };
      auto row_load = [&](int r) {
#pragma unroll
        for (int i = 4 * r; i < 4 * r + 4; i++)
          asm volatile("ld.global.nc.L1::no_allocate.v4.b32 {%0,%1,%2,%3}, [%4];" : "=r"(pk[4 * i]), "=r"(pk[4 * i + 1]), "=r"(pk[4 * i + 2]), "=r"(pk[4 * i + 3]) : "l"(xr + r * 256 + (i & 3) * 32));
      };
      p1_step<1>(acc, c); row_load(0);
      p1_step<2>(acc, c); row_load(1);
      p1_loop(acc, c, 3, LN_KB + 1, [](int) {});
      pin<16>(pk); ln_moments(pk, c0[0], mo[0], mo[1]); pin<2>(mo);
      p1_step<LN_KB + 1>(acc, c);
      sched_fence(c.zero);
      pin<16>(pk + 16); ln_moments(pk + 16, c0[1], mo[2], mo[3]); ln_reduce(mo[0], mo[1]); pin<4>(mo);
      p1_step<LN_KB + 2>(acc, c);
      mbar_spin(sb + B_EP, 0, c.zero);
      asm volatile("ld.shared.b32 %0, [%1];" : "=r"(e) : "r"(sb + OFF_EPOCH) : "memory");
      pin<2>(mo); st[0] = ln_finish(c0[0], mo[0], mo[1]); ln_reduce(mo[2], mo[3]); pin<1>(st); pin<2>(mo + 2);
      p1_step<LN_KB + 3>(acc, c);
      sched_fence(c.zero);
      pin<1>(st); pin<2>(mo + 2);
      st[1] = ln_finish(c0[1], mo[2], mo[3]);
      ln_store(pk, st[0], xo);
      if (lane == 0)
        asm volatile("{\n.reg .b64 a, b;\nmov.b64 a, {%1, %3};\nmov.b64 b, {%2, %3};\nst.relaxed.gpu.global.v2.b64 [%0], {a, b};\n}" ::"l"(gs->stats + 128 * m + prow), "r"(st[0]), "r"(st[1]), "r"(e) : "memory");
      p1_step<LN_KB + 4>(acc, c);
      sched_fence(c.zero);
      pin<1>(st + 1);
      ln_store(pk + 16, st[1], xo + 128);
      bar_arrive(BAR_EV, 288);
      p1_loop(acc, c, LN_KB + 5, 13, [](int) {});
      gather(0, 9);
      p1_step<13>(acc, c);
      gather(9, 18);
      p1_step<14>(acc, c);
      auto validate = [&]() {
        float csum;
        for (int tries = 0;; tries++) {
          uint32_t bad = 0;
          csum = 0.f;
#pragma unroll
          for (int i = 0; i < 18; i++) { bad |= (uint32_t)(part[i] >> 32) ^ e; if (i < 16) csum += __uint_as_float((uint32_t)part[i]); }
          if (!__any_sync(~0u, bad != 0) || tries > (1 << 20)) break;
          gather(0, 18);
        }
        const float hi = bf16r(csum), mid = bf16r(csum - hi);
        sts128(sb + OFF_CS + ((threadIdx.x & 62) * 4 + (threadIdx.x >> 6) * 2 + (threadIdx.x & 1)) * 16, make_uint4(pack2(hi, mid), pack2(csum - hi - mid, 0.f), 0, 0));
        asm volatile("fence.proxy.async.shared::cta;" ::: "memory");
        __syncwarp();
        if (lane == 0) mbar_arrive(sb + B_AUX);
      };
#pragma unroll 1
      for (int ph = 1; ph >= 0; ph--) {
        if (wg == ph) validate();
        if (ph) {
          if (wg == 1) { wg_wait<0>(); release(c, B_E1 + 16); bar_sync(BAR_LAG, 256); }
          p1_issue<3, 1>(acc, c, 1);
        }
      }
      const uint32_t keep = q == 0 ? 0xffffffffu : (q == 1 ? 0xffffu : 0u);
      const uint32_t a0 = (__byte_perm((uint32_t)part[16], 0, 0x1010) ^ 0x80008000u) & keep, a1 = (__byte_perm((uint32_t)part[17], 0, 0x1010) ^ 0x80008000u) & keep;
      mbar_spin(sb + B_AUX, 0, c.zero);
      wg_fence();
      wgmma256_rs(acc, a0, a1, 0, 0, (SM_BASE + OFF_CS) >> 4);
      wg_commit();
      if (wg == 0) bar_arrive(BAR_LAG, 256);
      rs[0] = rcpf(hi_f((uint32_t)part[16])); rs[1] = rcpf(hi_f((uint32_t)part[17]));
      wg_wait<2>(); if (wg == 0) release(c, B_E1 + 16);
      wg_wait<0>(); release(c, B_E1 + 24);
    }
#pragma unroll 1
    for (int R = 1;; R++) {
#pragma unroll
      for (int i = 0; i < 64; i++) pk[i] = pack2(acc[2 * i], acc[2 * i + 1]);
      if (t0) TS(24 + R + wg * 16);
      uint8_t* hb = (uint8_t*)gs->h + (size_t)m * 56 * 16384 + warp * 1024;
      if (R == 5) { c.a = 0x8000002000010000ull + ((SM_BASE + OFF_A + wg * 4096) >> 4); c.k2 = 510; c.k4 = 1024 - 514; c.k4w = -3072 - 514; }
      p1_step<0>(acc, c);
      if (R == 2 || R == 3) {
        attn_tile(acc, pk, c, R - 2, warp, m, bid, gs, hb + (16 + j) * 16384, (uint8_t*)gs->o + (m * 16 + j + 8 * (R - 2)) * 16384 + warp * 1024);
      } else {
        geglu_tile(acc, pk, c, R == 5 ? 24 : 14, hb + (2 * j + (R == 1 ? 0 : 16 * R - 40)) * 16384, BAR_EV + (R == 1 ? 1 : R + 1), rs);
        rs[0] = rs[1] = 1.0f;
        if (R == 5) break;
      }
      p1_step<14>(acc, c); p1_step<15>(acc, c);
    }
    auto fetch = [&](int p) {
      asm volatile("ld.global.cg.v4.b32 {%0,%1,%2,%3}, [%4];" : "=r"(pk[4 * p]), "=r"(pk[4 * p + 1]), "=r"(pk[4 * p + 2]), "=r"(pk[4 * p + 3]) : "l"(gs->dpart + bid * 2048 + p * 256 + threadIdx.x) : "memory");
    };
    mbar_spin(sb + B_DEP + 40, 0, c.zero);
    fetch(0); fetch(1); fetch(2);
    p1_step<8>(acc, c);
    fetch(3); fetch(4); fetch(5);
    p1_step<9>(acc, c);
    fetch(6); fetch(7);
    {
      float accs[64];
      const uint32_t peer = mapa(sb, rank ^ 1);
      auto send_piece = [&](int p) {
        asm volatile("st.async.weak.shared::cluster.mbarrier::complete_tx::bytes.v4.b32 [%0], {%1,%2,%3,%4}, [%5];" ::"r"(peer + OFF_LAND + p * 4096 + threadIdx.x * 16),
                     "r"(pack2(acc[64 + 8 * p], acc[65 + 8 * p])), "r"(pack2(acc[66 + 8 * p], acc[67 + 8 * p])), "r"(pack2(acc[68 + 8 * p], acc[69 + 8 * p])), "r"(pack2(acc[70 + 8 * p], acc[71 + 8 * p])),
                     "r"(peer + B_EX + 16 * wg + 8 * (p >> 2)) : "memory");
      };
      auto silu_piece = [&](int p) {
        const uint4 r = lds128(sb + OFF_LAND + p * 4096 + threadIdx.x * 16);
        const uint32_t rr[4] = {add2(r.x, pk[4 * p]), add2(r.y, pk[4 * p + 1]), add2(r.z, pk[4 * p + 2]), add2(r.w, pk[4 * p + 3])};
#pragma unroll
        for (int i = 0; i < 4; i++) {
          const float a = acc[8 * p + 2 * i] + lo_f(rr[i]), b = acc[8 * p + 2 * i + 1] + hi_f(rr[i]);
          pk[4 * p + i] = pack2(silu_half(a), silu_half(b));
        }
        pin<4>(pk + 4 * p);
      };
      const uint32_t xa = sb + OFF_X + (warp * 16 + (lane & 7)) * 128 + (((lane >> 3) ^ (lane & 7)) << 4);
      auto x_addr = [&](int i) { return (xa ^ ((i & 1) << 6)) + ((i >> 1) & 1) * 1024 + (i >> 2) * 16384; };
      auto x_piece = [&](int i) { const uint4 v = ldsm(x_addr(i)); pk[32 + 4 * i] = v.x; pk[33 + 4 * i] = v.y; pk[34 + 4 * i] = v.z; pk[35 + 4 * i] = v.w; };
      p2_step<0>(accs, c);
      p2_step<1>(accs, c);
      mbar_spin(sb + B_E1 + 8, 0, c.zero);
      send_piece(0); send_piece(1);
      p2_step<2>(accs, c); sched_fence(c.zero); send_piece(2); send_piece(3);
      p2_step<3>(accs, c); sched_fence(c.zero); send_piece(4); send_piece(5);
      p2_step<4>(accs, c); mbar_spin(sb + B_XT, 0, c.zero); send_piece(6); send_piece(7);
      p2_step<5>(accs, c); mbar_spin(sb + B_EX + 16 * wg, 0, c.zero); silu_piece(0); x_piece(0);
      p2_step<6>(accs, c); sched_fence(c.zero); silu_piece(1); x_piece(1);
      p2_step<7>(accs, c); sched_fence(c.zero); silu_piece(2); x_piece(2);
      p2_step<8>(accs, c); sched_fence(c.zero); silu_piece(3); x_piece(3);
      p2_step<9>(accs, c); mbar_spin(sb + B_EX + 16 * wg + 8, 0, c.zero); silu_piece(4); x_piece(4);
      p2_step<10>(accs, c); sched_fence(c.zero); silu_piece(5); x_piece(5);
      p2_step<11>(accs, c); sched_fence(c.zero); silu_piece(6); x_piece(6); x_piece(7);
      auto out_half = [&](const float* a, int h) {
#pragma unroll
        for (int i = 4 * h; i < 4 * h + 4; i++) {
          uint32_t v[4];
#pragma unroll
          for (int k = 0; k < 4; k++) { const int o = 2 * (4 * (i & 1) + k) + ((i >> 1) & 1); v[k] = fma2(pack2(a[2 * o], a[2 * o + 1]), pk[16 * h + o], pk[32 + 4 * i + k]); }
          asm volatile("stmatrix.sync.aligned.m8n8.x4.shared.b16 [%0], {%1,%2,%3,%4};" ::"r"(x_addr(i)), "r"(v[0]), "r"(v[1]), "r"(v[2]), "r"(v[3]) : "memory");
          if (i & 1) {
            asm volatile("fence.proxy.async.shared::cta;" ::: "memory");
            __syncwarp();
            if (elect_one()) tma3d_store(&mp.out, sb + OFF_X + h * 16384 + warp * 2048 + (i & 2) * 512, j2 * 128 + h * 64, m2 * 64 + w * 16 + (i & 2) * 4, wg);
          }
        }
      };
      if (wg == 1) silu_piece(7);
      p2_step<12>(accs, c); p2_step<13>(accs, c); p2_step<14>(accs, c); p2_step<15>(accs, c);
      if (c.do_rel) mbar_arrive(sb + B_DONE);
      if (wg == 0) silu_piece(7);
      wg_wait<0>();
      out_half(accs, 0); out_half(accs + 32, 1);
      if (elect_one()) { asm volatile("cp.async.bulk.commit_group;\ncp.async.bulk.wait_group.read 0;" ::: "memory"); }
      if ((threadIdx.x & 127) == 0) { TS(33 + wg * 16); if (wg) { TG(59); unsigned id; asm volatile("mov.u32 %0, %%smid;" : "=r"(id)); TSV(60, id); } }
    }
  }
}

typedef CUresult (*EncodeFn)(CUtensorMap*, CUtensorMapDataType, cuuint32_t, void*, const cuuint64_t*, const cuuint64_t*, const cuuint32_t*, const cuuint32_t*,
                             CUtensorMapInterleave, CUtensorMapSwizzle, CUtensorMapL2promotion, CUtensorMapFloatOOBfill);

void encode(EncodeFn fn, CUtensorMap* tm, const void* p, int rank, const cuuint64_t* dims, const cuuint64_t* strides, const cuuint32_t* box) {
  const cuuint32_t es[5] = {1, 1, 1, 1, 1};
  fn(tm, CU_TENSOR_MAP_DATA_TYPE_BFLOAT16, rank, const_cast<void*>(p), dims, strides, box, es, CU_TENSOR_MAP_INTERLEAVE_NONE, CU_TENSOR_MAP_SWIZZLE_128B,
     PROMO, CU_TENSOR_MAP_FLOAT_OOB_FILL_NONE);
}

}

extern "C" void kernel_launch(void* const* d_in, const int* in_sizes, int n_in, void* d_out, int out_size) {
  (void)in_sizes; (void)n_in; (void)out_size;
  static EncodeFn fn = nullptr;
  static Scratch* gs = nullptr;
  if (!fn) {
    void* p = nullptr;
    cudaDriverEntryPointQueryResult qr;
    cudaGetDriverEntryPoint("cuTensorMapEncodeTiled", &p, cudaEnableDefault, &qr);
    fn = (EncodeFn)p;
    cudaGetSymbolAddress((void**)&gs, g_scratch);
    cudaFuncSetAttribute(fused_kernel, cudaFuncAttributeMaxDynamicSharedMemorySize, SMEM_BYTES);
  }
  const void *x = d_in[0], *wqkv = d_in[1], *wo = d_in[2], *wg = d_in[4], *wu = d_in[5], *wd = d_in[6];
  Maps mp;
  {
    const cuuint64_t dims[3] = {DM, SEQ / 2, 2}, st[2] = {DM * 4, DM * 2};
    const cuuint32_t box_in[3] = {64, 64, 2}, box_out[3] = {64, 8, 1};
    encode(fn, &mp.x, x, 3, dims, st, box_in);
    encode(fn, &mp.out, d_out, 3, dims, st, box_out);
  }
  {
    const cuuint64_t dims[2] = {DM, SEQ}, st[1] = {DM * 2};
    const cuuint32_t box[2] = {64, 128};
    encode(fn, &mp.xn, gs->xn, 2, dims, st, box);
  }
  {
    const cuuint32_t box[2] = {64, 64};
    const cuuint64_t dq[2] = {3 * DM, DM}, sq[1] = {3 * DM * 2}, df[2] = {DFF, DM}, sf[1] = {DFF * 2}, dw[2] = {DM, DM}, sw[1] = {DM * 2};
    encode(fn, &mp.wqkv, wqkv, 2, dq, sq, box);
    encode(fn, &mp.wg, wg, 2, df, sf, box);
    encode(fn, &mp.wu, wu, 2, df, sf, box);
    encode(fn, &mp.wo, wo, 2, dw, sw, box);
  }
  {
    const cuuint32_t box[5] = {64, 2, 4, 4, 2};
    const cuuint64_t st[4] = {DM * 2, 8 * DM * 2, 2 * DM * 2, 32 * DM * 2};
    const cuuint64_t dd[5] = {DM, 2, 4, 4, DFF / 32};
    encode(fn, &mp.wd, wd, 5, dd, st, box);
  }
  fused_kernel<<<NCTA, 384, SMEM_BYTES>>>((const uint4*)x, (const uint4*)wg, (const uint4*)wu, gs, mp);
}
```

```cpp
#include <cuda_runtime.h>
#include <cuda_bf16.h>
#include <cuda.h>
#include <stdint.h>

#define PROMO CU_TENSOR_MAP_L2_PROMOTION_L2_128B
#define LAG2 4
#define POLL_NS "200"
#define CS_KB 8
#define LN_KB 4

#define EVICT_FIRST 0x12F0000000000000ull
#define EVICT_NORMAL 0x1000000000000000ull
#define HINT_OUT EVICT_FIRST
#define HINT_W EVICT_FIRST
#define HINT_H EVICT_FIRST
#define HINT_LAST EVICT_FIRST

namespace {

constexpr int SEQ = 2048, DM = 1024, DFF = 3584;
constexpr int NMAIN = 128, NCTA = 132;

constexpr uint32_t SM_BASE = 0x400;
constexpr uint32_t P1_BYTES = 49152, P2_BYTES = 32768;
constexpr uint32_t OFF_A = 131072;
__host__ __device__ constexpr uint32_t p2_a(int s) { return s == 0 ? OFF_A + 32768 : s == 1 ? OFF_A + 49152 : s == 2 ? 114688 : s == 3 ? 16384 : 49152; }
__host__ __device__ constexpr uint32_t p2_b(int s) { return s < 3 ? 65536 + s * 16384 : (s - 3) * 32768; }
constexpr uint32_t OFF_LAND = OFF_A;
constexpr uint32_t OFF_X = 196608;
constexpr uint32_t OFF_CS = OFF_X + 14336;
constexpr uint32_t OFF_BAR = 229376;
constexpr uint32_t B_F1 = OFF_BAR, B_E1 = B_F1 + 32, B_E2 = B_E1 + 32, B_DONE = B_E2 + 40, B_F2 = B_DONE + 8, B_DEP = B_F2 + 40, B_CS = B_DEP + 48,
                   B_XT = B_CS + 16, B_EP = B_XT + 8, B_EX = B_EP + 8, B_AUX = B_EX + 32, B_HALO = B_AUX + 8, OFF_EPOCH = B_HALO + 16;
constexpr uint32_t SMEM_BYTES = 232448;
constexpr uint32_t AT_V = 0, AT_K = 8192, AT_REM = 11264, AT_WG = 15360;

constexpr int FL_XN = 0, FL_H = 16, FL_P = 80, FL_HALO = 96, FL_N = FL_HALO + 256;
struct __align__(1024) Scratch {
  uint4 h[16 * 56 * 1024];
  uint4 o[16 * 16 * 1024];
  uint4 xn[SEQ * DM / 8];
  uint4 dpart[128 * 8 * 256];
  uint4 halo[2 * 128 * 2 * 128];
  ulonglong2 cspart[8 * 16 * 128];
  unsigned long long stats[SEQ];
  unsigned flags[FL_N * 32];
  unsigned epoch[NCTA * 2];
};
__device__ Scratch g_scratch;
#define TG(i) do {} while (0)
#define TSV(i, v) do {} while (0)
#define TS(i) do {} while (0)

__device__ __forceinline__ unsigned role_id() {
  unsigned sm, nsm;
  asm("mov.u32 %0, %%smid;\nmov.u32 %1, %%nsmid;" : "=r"(sm), "=r"(nsm));
  const unsigned t = (nsm == NCTA ? sm : blockIdx.x) >> 1;
  unsigned g = t & 7, i = t >> 3;
  if (t >= 32) { i = (t - 32) / 7; g = t - 31 - 7 * i; i += 4; }
  if (t >= 60) { g = t - 60; i = 8; }
  if (t >= 62) { g = 0; i = t - 58; }
  return 16 * i + 2 * g + (blockIdx.x & 1);
}

struct Maps { CUtensorMap x, xn, out, wqkv, wg, wu, wd, wo; };

__device__ __forceinline__ void mbar_init(uint32_t bar, uint32_t cnt) { asm volatile("mbarrier.init.shared::cta.b64 [%0], %1;" ::"r"(bar), "r"(cnt)); }
__device__ __forceinline__ void mbar_expect_tx(uint32_t bar, uint32_t bytes) { asm volatile("mbarrier.arrive.expect_tx.shared::cta.b64 _, [%0], %1;" ::"r"(bar), "r"(bytes) : "memory"); }
__device__ __forceinline__ void mbar_arrive(uint32_t bar) { asm volatile("mbarrier.arrive.shared::cta.b64 _, [%0];" ::"r"(bar) : "memory"); }
__device__ __forceinline__ void mbar_arrive_cl(uint32_t bar) { asm volatile("mbarrier.arrive.shared::cluster.b64 _, [%0];" ::"r"(bar) : "memory"); }
__device__ __forceinline__ uint32_t mapa(uint32_t a, uint32_t cta) { uint32_t r; asm("mapa.shared::cluster.u32 %0, %1, %2;" : "=r"(r) : "r"(a), "r"(cta)); return r; }
__device__ __forceinline__ void mbar_wait(uint32_t bar, uint32_t parity) {
  asm volatile("{\n.reg .pred p;\n.reg .u32 n;\nmov.u32 n, 0;\nLAB_WAIT:\nmbarrier.try_wait.parity.shared::cta.b64 p, [%0], %1;\n@p bra LAB_DONE;\n"
               "add.u32 n, n, 1;\nsetp.gt.u32 p, n, 4000000;\n@p trap;\nbra LAB_WAIT;\nLAB_DONE:\n}" ::"r"(bar), "r"(parity) : "memory");
}
__device__ __forceinline__ void mbar_spin(uint32_t bar, uint32_t parity, uint32_t zero) {
  asm volatile("{\n.reg .pred p, z;\nsetp.ne.u32 z, %2, 0;\nLAB_WAIT:\nmbarrier.try_wait.parity.shared::cta.b64 p, [%0], %1;\n@p bra LAB_DONE;\n@z trap;\nbra LAB_WAIT;\nLAB_DONE:\n}" ::"r"(bar), "r"(parity), "r"(zero) : "memory");
}
__device__ __forceinline__ void flag_wait(const unsigned* f, unsigned target) {
  asm volatile("{\n.reg .pred p;\n.reg .u32 n, v;\nmov.u32 n, 0;\nLAB_WAIT:\nld.relaxed.gpu.global.u32 v, [%0];\nsub.u32 v, v, %1;\nsetp.ge.s32 p, v, 0;\n@p bra LAB_DONE;\n"
               "nanosleep.u32 " POLL_NS ";\nadd.u32 n, n, 1;\nsetp.gt.u32 p, n, 4000000;\n@p trap;\nbra LAB_WAIT;\nLAB_DONE:\nfence.acquire.gpu;\n}" ::"l"(f), "r"(target) : "memory");
}
__device__ __forceinline__ void flag_add(unsigned* f) { asm volatile("red.release.gpu.global.add.u32 [%0], 1;" ::"l"(f) : "memory"); }
__device__ __forceinline__ void fence_async() { asm volatile("fence.proxy.async.global;" ::: "memory"); }
__device__ __forceinline__ bool elect_one() { uint32_t p; asm volatile("{\n.reg .pred P;\nelect.sync _|P, 0xffffffff;\nselp.u32 %0, 1, 0, P;\n}" : "=r"(p)); return p; }
__device__ __forceinline__ void bar_sync(int id, int n) { asm volatile("bar.sync %0, %1;" ::"r"(id), "r"(n) : "memory"); }
__device__ __forceinline__ void bar_arrive(int id, int n) { asm volatile("bar.arrive %0, %1;" ::"r"(id), "r"(n) : "memory"); }

__device__ __forceinline__ void tma2d(uint32_t dst, const CUtensorMap* tm, uint32_t bar, int c0, int c1, uint64_t hint) {
  asm volatile("cp.async.bulk.tensor.2d.shared::cluster.global.mbarrier::complete_tx::bytes.L2::cache_hint [%0], [%1, {%3, %4}], [%2], %5;" ::"r"(dst), "l"(tm), "r"(bar), "r"(c0), "r"(c1), "l"(hint) : "memory");
}
__device__ __forceinline__ void tma2d_mc(uint32_t dst, const CUtensorMap* tm, uint32_t bar, int c0, int c1, uint64_t hint) {
  asm volatile("cp.async.bulk.tensor.2d.shared::cluster.global.mbarrier::complete_tx::bytes.multicast::cluster.L2::cache_hint [%0], [%1, {%3, %4}], [%2], %5, %6;" ::"r"(dst), "l"(tm), "r"(bar), "r"(c0), "r"(c1), "h"((uint16_t)3), "l"(hint) : "memory");
}
__device__ __forceinline__ void tma3d(uint32_t dst, const CUtensorMap* tm, uint32_t bar, int c0, int c1, int c2, uint64_t hint) {
  asm volatile("cp.async.bulk.tensor.3d.shared::cluster.global.mbarrier::complete_tx::bytes.L2::cache_hint [%0], [%1, {%3, %4, %5}], [%2], %6;" ::"r"(dst), "l"(tm), "r"(bar), "r"(c0), "r"(c1), "r"(c2), "l"(hint) : "memory");
}
__device__ __forceinline__ void tma5d(uint32_t dst, const CUtensorMap* tm, uint32_t bar, int c0, int c4, uint64_t hint) {
  asm volatile("cp.async.bulk.tensor.5d.shared::cluster.global.mbarrier::complete_tx::bytes.L2::cache_hint [%0], [%1, {%3, %5, %5, %5, %4}], [%2], %6;" ::"r"(dst), "l"(tm), "r"(bar), "r"(c0), "r"(c4), "r"(0), "l"(hint) : "memory");
}
__device__ __forceinline__ void tma3d_store(const CUtensorMap* tm, uint32_t src, int c0, int c1, int c2) {
  asm volatile("cp.async.bulk.tensor.3d.global.shared::cta.bulk_group.L2::cache_hint [%0, {%2, %3, %4}], [%1], %5;" ::"l"(tm), "r"(src), "r"(c0), "r"(c1), "r"(c2), "l"(HINT_OUT) : "memory");
}
__device__ __forceinline__ void bulk_load(uint32_t dst, const void* src, uint32_t bytes, uint32_t bar, uint64_t hint) {
  asm volatile("cp.async.bulk.shared::cluster.global.mbarrier::complete_tx::bytes.L2::cache_hint [%0], [%1], %2, [%3], %4;" ::"r"(dst), "l"(src), "r"(bytes), "r"(bar), "l"(hint) : "memory");
}
__device__ __forceinline__ void bulk_load_mc(uint32_t dst, const void* src, uint32_t bytes, uint32_t bar, uint64_t hint) {
  asm volatile("cp.async.bulk.shared::cluster.global.mbarrier::complete_tx::bytes.multicast::cluster.L2::cache_hint [%0], [%1], %2, [%3], %4, %5;" ::"r"(dst), "l"(src), "r"(bytes), "r"(bar), "h"((uint16_t)3), "l"(hint) : "memory");
}
__device__ __forceinline__ uint4 lds128(uint32_t a) { uint4 v; asm volatile("ld.shared.v4.b32 {%0,%1,%2,%3}, [%4];" : "=r"(v.x), "=r"(v.y), "=r"(v.z), "=r"(v.w) : "r"(a) : "memory"); return v; }
__device__ __forceinline__ void sts128(uint32_t a, uint4 v) { asm volatile("st.shared.v4.b32 [%0], {%1,%2,%3,%4};" ::"r"(a), "r"(v.x), "r"(v.y), "r"(v.z), "r"(v.w) : "memory"); }
__device__ __forceinline__ void stg128(void* p, uint32_t a, uint32_t b, uint32_t c, uint32_t d) { asm volatile("st.global.v4.b32 [%0], {%1,%2,%3,%4};" ::"l"(p), "r"(a), "r"(b), "r"(c), "r"(d) : "memory"); }

__device__ __forceinline__ uint32_t pack2(float lo, float hi) { uint32_t r; asm("cvt.rn.bf16x2.f32 %0, %1, %2;" : "=r"(r) : "f"(hi), "f"(lo)); return r; }
__device__ __forceinline__ float lo_f(uint32_t v) { return __uint_as_float(v << 16); }
__device__ __forceinline__ float hi_f(uint32_t v) { return __uint_as_float(v & 0xffff0000u); }
__device__ __forceinline__ float bf16r(float v) { return lo_f(pack2(v, 0.f)); }
__device__ __forceinline__ uint32_t mul2(uint32_t a, uint32_t b) { uint32_t r; asm("mul.rn.bf16x2 %0, %1, %2;" : "=r"(r) : "r"(a), "r"(b)); return r; }
__device__ __forceinline__ uint32_t add2(uint32_t a, uint32_t b) { uint32_t r; asm("add.rn.bf16x2 %0, %1, %2;" : "=r"(r) : "r"(a), "r"(b)); return r; }
__device__ __forceinline__ uint32_t sub2(uint32_t a, uint32_t b) { uint32_t r; asm("sub.rn.bf16x2 %0, %1, %2;" : "=r"(r) : "r"(a), "r"(b)); return r; }
__device__ __forceinline__ uint32_t fma2(uint32_t a, uint32_t b, uint32_t c) { uint32_t r; asm("fma.rn.bf16x2 %0, %1, %2, %3;" : "=r"(r) : "r"(a), "r"(b), "r"(c)); return r; }
__device__ __forceinline__ uint32_t max2(uint32_t a, uint32_t b) { uint32_t r; asm("max.bf16x2 %0, %1, %2;" : "=r"(r) : "r"(a), "r"(b)); return r; }
__device__ __forceinline__ float ex2f(float x) { float y; asm("ex2.approx.ftz.f32 %0, %1;" : "=f"(y) : "f"(x)); return y; }
__device__ __forceinline__ float rcpf(float x) { float y; asm("rcp.approx.ftz.f32 %0, %1;" : "=f"(y) : "f"(x)); return y; }
constexpr float GELU_C1 = 0.7978845608028654f, GELU_C3 = 0.035677408136300125f;
__device__ __forceinline__ float gelu_k(float g, float c1, float c3, float k) {
  float t;
  asm("tanh.approx.f32 %0, %1;" : "=f"(t) : "f"(g * fmaf(g * g, c3, c1)));
  g *= k;
  return fmaf(g, t, g);
}
__device__ __forceinline__ float silu_half(float z) { float t; asm("tanh.approx.f32 %0, %1;" : "=f"(t) : "f"(z)); return fmaf(z, t, z); }

__device__ __forceinline__ void wg_fence() { asm volatile("wgmma.fence.sync.aligned;" ::: "memory"); }
__device__ __forceinline__ void wg_commit() { asm volatile("wgmma.commit_group.sync.aligned;" ::: "memory"); }
template <int N> __device__ __forceinline__ void wg_wait() { asm volatile("wgmma.wait_group.sync.aligned %0;" ::"n"(N) : "memory"); }
#define A8(o) "+f"(d[(o)]), "+f"(d[(o) + 1]), "+f"(d[(o) + 2]), "+f"(d[(o) + 3]), "+f"(d[(o) + 4]), "+f"(d[(o) + 5]), "+f"(d[(o) + 6]), "+f"(d[(o) + 7])
#define A64(o) A8(o), A8((o) + 8), A8((o) + 16), A8((o) + 24), A8((o) + 32), A8((o) + 40), A8((o) + 48), A8((o) + 56)
#define REGS0_63 "%0,%1,%2,%3,%4,%5,%6,%7,%8,%9,%10,%11,%12,%13,%14,%15,%16,%17,%18,%19,%20,%21,%22,%23,%24,%25,%26,%27,%28,%29,%30,%31," \
                 "%32,%33,%34,%35,%36,%37,%38,%39,%40,%41,%42,%43,%44,%45,%46,%47,%48,%49,%50,%51,%52,%53,%54,%55,%56,%57,%58,%59,%60,%61,%62,%63"
#define REGS64_127 "%64,%65,%66,%67,%68,%69,%70,%71,%72,%73,%74,%75,%76,%77,%78,%79,%80,%81,%82,%83,%84,%85,%86,%87,%88,%89,%90,%91,%92,%93,%94,%95," \
                   "%96,%97,%98,%99,%100,%101,%102,%103,%104,%105,%106,%107,%108,%109,%110,%111,%112,%113,%114,%115,%116,%117,%118,%119,%120,%121,%122,%123,%124,%125,%126,%127"
__device__ __forceinline__ void desc_add(uint64_t& x, int v) { asm volatile("{\n.reg .b32 lo, hi;\nmov.b64 {lo, hi}, %0;\nadd.s32 lo, lo, %1;\nmov.b64 %0, {lo, hi};\n}" : "+l"(x) : "r"(v)); }
template <int ACCUM> __device__ __forceinline__ void wgmma256(float (&d)[128], uint64_t& a, uint64_t& b, int da, int db) {
  asm volatile("{\n.reg .pred p;\nsetp.ne.b32 p, %130, 0;\n"
               "wgmma.mma_async.sync.aligned.m64n256k16.f32.bf16.bf16 {" REGS0_63 "," REGS64_127 "}, %128, %129, p, 1, 1, 0, 1;\n}"
               : A64(0), A64(64) : "l"(a), "l"(b), "n"(ACCUM));
  desc_add(a, da); desc_add(b, db);
}
__device__ __forceinline__ void wgmma256_rs(float (&d)[128], uint32_t a0, uint32_t a1, uint32_t z0, uint32_t z1, uint32_t b_lo) {
  asm volatile("{\n.reg .b64 db;\nmov.b64 db, {%132, 0x00000008};\n"
               "wgmma.mma_async.sync.aligned.m64n256k16.f32.bf16.bf16 {" REGS0_63 "," REGS64_127 "}, {%128,%129,%130,%131}, db, 1, 1, 1, 0;\n}"
               : A64(0), A64(64) : "r"(a0), "r"(a1), "r"(z0), "r"(z1), "r"(b_lo));
}
template <int ACCUM> __device__ __forceinline__ void wgmma128(float (&d)[64], uint64_t& a, uint64_t& b, int da, int db) {
  asm volatile("{\n.reg .pred p;\nsetp.ne.b32 p, %66, 0;\n"
               "wgmma.mma_async.sync.aligned.m64n128k16.f32.bf16.bf16 {" REGS0_63 "}, %64, %65, p, 1, 1, 0, 1;\n}"
               : A64(0) : "l"(a), "l"(b), "n"(ACCUM));
  desc_add(a, da); desc_add(b, db);
}
template <int ACCUM> __device__ __forceinline__ void hmma(float (&c)[4], uint32_t a0, uint32_t a1, uint32_t a2, uint32_t a3, uint32_t b0, uint32_t b1) {
  if (ACCUM)
    asm volatile("mma.sync.aligned.m16n8k16.row.col.f32.bf16.bf16.f32 {%0,%1,%2,%3}, {%4,%5,%6,%7}, {%8,%9}, {%0,%1,%2,%3};"
                 : "+f"(c[0]), "+f"(c[1]), "+f"(c[2]), "+f"(c[3]) : "r"(a0), "r"(a1), "r"(a2), "r"(a3), "r"(b0), "r"(b1));
  else
    asm volatile("mma.sync.aligned.m16n8k16.row.col.f32.bf16.bf16.f32 {%0,%1,%2,%3}, {%4,%5,%6,%7}, {%8,%9}, {%10,%10,%10,%10};"
                 : "=f"(c[0]), "=f"(c[1]), "=f"(c[2]), "=f"(c[3]) : "r"(a0), "r"(a1), "r"(a2), "r"(a3), "r"(b0), "r"(b1), "f"(0.f));
}
__device__ __forceinline__ uint32_t movm(uint32_t a) { uint32_t d; asm volatile("movmatrix.sync.aligned.m8n8.trans.b16 %0, %1;" : "=r"(d) : "r"(a)); return d; }
__device__ __forceinline__ int lane_here() { int v; asm volatile("mov.u32 %0, %%laneid;" : "=r"(v)); return v; }
template <int N> __device__ __forceinline__ void pin(uint32_t* r) {
#pragma unroll
  for (int i = 0; i < N; i++) asm volatile("" : "+r"(r[i]));
}
template <int N> __device__ __forceinline__ void pin(float* r) {
#pragma unroll
  for (int i = 0; i < N; i++) asm volatile("" : "+f"(r[i]));
}
__device__ __forceinline__ void sched_fence(uint32_t zero) {
  asm volatile("{\n.reg .pred p;\nsetp.eq.u32 p, %0, 0;\nLAB_F:\n@p bra.uni LAB_D;\nnanosleep.u32 0;\nbra.uni LAB_F;\nLAB_D:\n}" ::"r"(zero) : "memory");
}
__device__ __forceinline__ uint4 ldsm(uint32_t a) { uint4 v; asm volatile("ldmatrix.sync.aligned.m8n8.x4.shared.b16 {%0,%1,%2,%3}, [%4];" : "=r"(v.x), "=r"(v.y), "=r"(v.z), "=r"(v.w) : "r"(a) : "memory"); return v; }
__device__ __forceinline__ uint4 ldsm_t(uint32_t a) { uint4 v; asm volatile("ldmatrix.sync.aligned.m8n8.x4.trans.shared.b16 {%0,%1,%2,%3}, [%4];" : "=r"(v.x), "=r"(v.y), "=r"(v.z), "=r"(v.w) : "r"(a) : "memory"); return v; }

constexpr int BAR_LAG = 1, BAR_MMA = 2, BAR_EV = 3;

struct Cons {
  uint32_t sb;
  mutable uint64_t a, b;
  int k1, k2, k4, k4w, b1;
  uint32_t rel;
  bool do_rel;
  int wg;
  uint32_t zero;
};
#define REL_TS(n) TS(64 + (n))
constexpr uint32_t DB_LO = (SM_BASE >> 4) | ((8192 >> 4) << 16);

template <int ST, int ACCUM, bool WAIT = true> __device__ __forceinline__ void p1_issue(float (&acc)[128], const Cons& c, uint32_t parity) {
  if (WAIT) mbar_spin(c.sb + B_F1 + 8 * ST, parity, c.zero);
  wg_fence();
  wgmma256<ACCUM>(acc, c.a, c.b, c.k1, c.b1);
  wgmma256<1>(acc, c.a, c.b, c.k2, c.b1);
  wgmma256<1>(acc, c.a, c.b, c.k1, c.b1);
  wgmma256<1>(acc, c.a, c.b, ST == 3 ? c.k4w : c.k4, ST == 3 ? -6144 - 384 : 2048 - 384);
  wg_commit();
}
__device__ __forceinline__ void release(const Cons& c, uint32_t bar) { if (c.do_rel) mbar_arrive_cl(c.rel + bar); }
template <int KB, bool WAIT = true> __device__ __forceinline__ void p1_step(float (&acc)[128], const Cons& c) {
  if (KB == 15) { if (c.wg == 1) { wg_wait<0>(); release(c, B_E1 + 16); bar_sync(BAR_LAG, 256); } }
  p1_issue<KB & 3, KB != 0, WAIT>(acc, c, (KB >> 2) & 1);
  if (KB == 15) { if (c.wg == 0) bar_arrive(BAR_LAG, 256); }
  if (KB > 0) { wg_wait<1>(); if (KB != 15 || c.wg == 0) release(c, B_E1 + 8 * ((KB - 1) & 3)); }
  if (KB == 15) { wg_wait<0>(); release(c, B_E1 + 24); }
}
template <class F> __device__ __forceinline__ void p1_loop(float (&acc)[128], const Cons& c, int from, int to, F&& shadow) {
#pragma unroll 1
  for (int kb = from; kb < to; kb++) {
    const bool wrap = (kb & 3) == 3;
    mbar_spin(c.sb + B_F1 + 8 * (kb & 3), (kb >> 2) & 1, c.zero);
    wg_fence();
    wgmma256<1>(acc, c.a, c.b, c.k1, c.b1);
    wgmma256<1>(acc, c.a, c.b, c.k2, c.b1);
    wgmma256<1>(acc, c.a, c.b, c.k1, c.b1);
    wgmma256<1>(acc, c.a, c.b, wrap ? c.k4w : c.k4, wrap ? -6144 - 384 : 2048 - 384);
    wg_commit();
    wg_wait<1>();
    release(c, B_E1 + 8 * ((kb - 1) & 3));
    shadow(kb);
  }
}
template <int T> __device__ __forceinline__ void p2_step(float (&acc)[64], const Cons& c) {
  if (T == 16 - LAG2) { if (c.wg == 1) bar_sync(BAR_LAG, 256); }
  mbar_spin(c.sb + B_F2 + 8 * (T % 5), (T / 5) & 1, c.zero);
  wg_fence();
  wgmma128<T != 0>(acc, c.a, c.b, c.k1, c.b1);
  wgmma128<1>(acc, c.a, c.b, c.k2, c.b1);
  wgmma128<1>(acc, c.a, c.b, c.k1, c.b1);
  wgmma128<1>(acc, c.a, c.b, ((int)p2_a((T + 1) % 5) - (int)p2_a(T % 5)) / 16 - 514, ((int)p2_b((T + 1) % 5) - (int)p2_b(T % 5)) / 16 - 384);
  wg_commit();
  if (T == 15) { if (c.wg == 0) bar_arrive(BAR_LAG, 256); }
  if (T <= 11) { wg_wait<1>(); release(c, T ? B_E2 + 8 * ((T + 5 - 1) % 5) : B_E1 + 8); }
}

template <int P> __device__ __forceinline__ void geglu_piece(uint32_t (&pk)[64], uint8_t* dst, float (&rs)[2]) {
  constexpr int cg = P >> 1, r = P & 1;
  pin<1>(rs + r);
#pragma unroll
  for (int i = 0; i < 4; i++) pin<1>(pk + 2 * (4 * cg + i) + r);
  const float r2 = rs[r] * rs[r], c1 = GELU_C1 * rs[r], c3 = GELU_C3 * r2 * rs[r], k = 0.25f * r2;
  uint32_t v[4];
#pragma unroll
  for (int i = 0; i < 4; i++) {
    const uint32_t g = pk[2 * (4 * cg + i) + r];
    v[i] = mul2(pack2(gelu_k(lo_f(g), c1, c3, k), gelu_k(hi_f(g), c1, c3, k)), pk[32 + 2 * (4 * cg + i) + r]);
  }
  stg128(dst + cg * 8192 + r * 512, v[0], v[1], v[2], v[3]);
}
__device__ __forceinline__ void geglu_tile(float (&acc)[128], uint32_t (&pk)[64], const Cons& c, int to, uint8_t* dst, int ev, float (&rs)[2]) {
  const int lane = lane_here();
  dst += (lane ^ (lane >> 3)) << 4;
  p1_loop(acc, c, 1, to, [&](int kb) {
    if (kb <= 4) {
      if (kb <= 2) { if (kb == 1) geglu_piece<0>(pk, dst, rs); else geglu_piece<1>(pk, dst, rs); }
      else { if (kb == 3) geglu_piece<2>(pk, dst, rs); else geglu_piece<3>(pk, dst, rs); }
    } else if (kb <= 8) {
      if (kb <= 6) { if (kb == 5) geglu_piece<4>(pk, dst, rs); else geglu_piece<5>(pk, dst, rs); }
      else { if (kb == 7) geglu_piece<6>(pk, dst, rs); else { geglu_piece<7>(pk, dst, rs); bar_arrive(ev, 288); } }
    }
  });
}

__device__ __forceinline__ void attn_tile(float (&acc)[128], uint32_t (&pk)[64], const Cons& c, int round, int warp, int m, unsigned bid, Scratch* gs, uint8_t* hdst, uint8_t* odst) {
  const int w = warp & 3;
  const uint32_t at = c.sb + OFF_X + c.wg * AT_WG;
  int lane = lane_here();
  hdst += (lane ^ (lane >> 3)) << 4;
  auto scatter = [&]() {
    const int lane = lane_here();
    const uint32_t swz = (lane ^ (lane >> 3)) << 4;
#pragma unroll
    for (int i = 0; i < 4; i++) {
      const int h = i & 1, r = i >> 1;
      sts128(at + AT_V + (2 * w + r) * 1024 + h * 512 + swz, make_uint4(pk[32 + 8 * h + r], pk[34 + 8 * h + r], pk[36 + 8 * h + r], pk[38 + 8 * h + r]));
    }
    if (w < 3) {
#pragma unroll
      for (int i = 0; i < 8; i++) asm volatile("st.shared.b32 [%0], %1;" ::"r"(at + AT_K + w * 1024 + i * 128 + lane * 4), "r"(pk[17 + 2 * i]) : "memory");
    } else {
      uint8_t* g = (uint8_t*)gs->halo + ((round * 128 + bid) * 2 + c.wg) * 2048;
#pragma unroll
      for (int i = 0; i < 8; i++) asm volatile("st.global.b32 [%0], %1;" ::"l"(g + i * 128 + lane * 4), "r"(pk[17 + 2 * i]) : "memory");
#pragma unroll
      for (int h = 0; h < 2; h++) stg128(g + 1024 + h * 512 + swz, pk[33 + 8 * h], pk[35 + 8 * h], pk[37 + 8 * h], pk[39 + 8 * h]);
      bar_arrive(BAR_EV + 2 + round, 96);
    }
    __syncwarp();
    if (lane == 0) mbar_arrive(c.sb + B_HALO + 8 * round);
    if (round) {
#pragma unroll
      for (int p = 0; p < 4; p++) {
        const int o = 32 + 8 * (p >> 1) + (p & 1);
        asm volatile("ld.global.cg.v4.b32 {%0,%1,%2,%3}, [%4];" : "=r"(pk[o]), "=r"(pk[o + 2]), "=r"(pk[o + 4]), "=r"(pk[o + 6]) : "l"(hdst + (p >> 1) * 8192 + (p & 1) * 512) : "memory");
      }
    }
  };
  auto gu_piece = [&](int p) {
    uint32_t v[4];
#pragma unroll
    for (int i = 0; i < 4; i++) {
      const int o = 8 * (p >> 1) + 2 * i + (p & 1);
      pin<1>(pk + 48 + o);
      const uint32_t g = pk[48 + o];
      v[i] = mul2(round ? pk[32 + o] : 0x3e803e80u, round ? g : pack2(gelu_k(lo_f(g), GELU_C1, GELU_C3, 1.0f), gelu_k(hi_f(g), GELU_C1, GELU_C3, 1.0f)));
    }
    stg128(hdst + (p >> 1) * 8192 + (p & 1) * 512, v[0], v[1], v[2], v[3]);
  };
  p1_step<1>(acc, c);
  scatter();
  p1_loop(acc, c, 2, 9, [&](int kb) {
    if (kb <= 4) { if (kb == 3) gu_piece(0); else if (kb == 4) gu_piece(1); }
    else if (kb == 5) gu_piece(2); else if (kb == 6) gu_piece(3);
  });
  const bool first = m == 0 && w == 0;
  uint32_t kl[16];
  mbar_spin(c.sb + B_HALO + 8 * round, 0, c.zero);
  lane = lane_here();
  {
    const uint32_t ka = at + lane * 4 + (w ? AT_K + (w - 1) * 1024 : (first ? AT_K : AT_REM + round * 2048));
#pragma unroll
    for (int i = 0; i < 8; i++) {
      asm volatile("ld.shared.b32 %0, [%1];" : "=r"(kl[2 * i]) : "r"(ka + i * 128) : "memory");
      kl[2 * i + 1] = pk[16 + 2 * i] | c.zero;
    }
  }
  float st[4][4];
  pin<16>(kl);
  bar_sync(BAR_MMA, 256);
  mbar_spin(c.sb + B_F1 + 8 * 1, 0, c.zero);
#pragma unroll
  for (int ks = 0; ks < 2; ks++) {
#pragma unroll
    for (int h = 0; h < 2; h++) {
      const int o = 8 * h + 4 * ks;
      if (ks == 0) { hmma<0>(st[2 * h], kl[o], kl[o + 1], kl[o + 2], kl[o + 3], pk[o], pk[o + 2]); hmma<0>(st[2 * h + 1], pk[16 + o], pk[17 + o], pk[18 + o], pk[19 + o], pk[o + 1], pk[o + 3]); }
      else { hmma<1>(st[2 * h], kl[o], kl[o + 1], kl[o + 2], kl[o + 3], pk[o], pk[o + 2]); hmma<1>(st[2 * h + 1], pk[16 + o], pk[17 + o], pk[18 + o], pk[19 + o], pk[o + 1], pk[o + 3]); }
    }
  }
  sched_fence(c.zero);
  bar_sync(BAR_MMA, 256);
  p1_step<9, false>(acc, c);
  sched_fence(c.zero);
  pin<16>(&st[0][0]);
  lane = lane_here();
  const int rho = lane >> 2, q = lane & 3;
  const bool le0 = 2 * q <= rho, le1 = 2 * q + 1 <= rho;
  uint32_t la[2], lb[2], mx[2];
#pragma unroll
  for (int h = 0; h < 2; h++) {
    uint32_t l[2];
#pragma unroll
    for (int r = 0; r < 2; r++) {
      const float (&t)[4] = st[2 * h + r];
      l[r] = movm(pack2(rho <= 2 * q ? t[2] : t[0], rho <= 2 * q + 1 ? t[3] : t[1]));
      l[r] = fma2(l[r], 0x3e353e35u, mul2(l[r], 0x379e379eu));
    }
    la[h] = __byte_perm(l[0], l[1], 0x5410); lb[h] = __byte_perm(l[0], l[1], 0x7632);
    if (first && !le0) la[h] = (la[h] & 0xffff0000u) | 0xce6eu;
    if (first && !le1) lb[h] = (lb[h] & 0xffff0000u) | 0xce6eu;
    mx[h] = max2(la[h], lb[h]);
  }
#pragma unroll
  for (int o = 1; o <= 2; o++) { mx[0] = max2(mx[0], __shfl_xor_sync(~0u, mx[0], o)); mx[1] = max2(mx[1], __shfl_xor_sync(~0u, mx[1], o)); }
  const float L2E = 1.4426950408889634f;
  float pr[2][4], z[4];
#pragma unroll
  for (int h = 0; h < 2; h++) {
    pr[h][0] = ex2f((lo_f(la[h]) - lo_f(mx[h])) * L2E); pr[h][1] = ex2f((lo_f(lb[h]) - lo_f(mx[h])) * L2E);
    pr[h][2] = ex2f((hi_f(la[h]) - hi_f(mx[h])) * L2E); pr[h][3] = ex2f((hi_f(lb[h]) - hi_f(mx[h])) * L2E);
    z[2 * h] = pr[h][0] + pr[h][1]; z[2 * h + 1] = pr[h][2] + pr[h][3];
  }
  p1_step<10>(acc, c);
#pragma unroll
  for (int o = 1; o <= 2; o++) {
#pragma unroll
    for (int i = 0; i < 4; i++) z[i] += __shfl_xor_sync(~0u, z[i], o);
  }
  const uint32_t LE = (le0 ? 0xffffu : 0u) | (le1 ? 0xffff0000u : 0u);
  uint32_t P[4][2];
  uint4 vt[4][2];
  {
    const uint32_t row = (lane & 7) * 64 + ((((lane >> 3) & 1) ^ ((lane & 7) >> 1)) << 4);
    const uint32_t v1 = at + AT_V + (2 * w + (lane >> 4)) * 1024 + row;
    const uint32_t v0 = (w || lane >= 16) ? v1 - 1024 : (first ? v1 : at + AT_REM + round * 2048 + 1024 + row);
#pragma unroll
    for (int i = 0; i < 4; i++) {
      const float rz = rcpf(z[i]);
      const uint32_t p = pack2(pr[i >> 1][2 * (i & 1)] * rz, pr[i >> 1][2 * (i & 1) + 1] * rz);
      P[i][0] = p & ~LE; P[i][1] = p & LE;
      const uint32_t a = ((i & 1) ? v1 : v0) + (i >> 1) * 512;
      vt[i][0] = ldsm_t(a); vt[i][1] = ldsm_t(a ^ 32);
    }
  }
  float ot[4][2][4];
  pin<8>(&P[0][0]);
  bar_sync(BAR_MMA, 256);
  mbar_spin(c.sb + B_F1 + 8 * 3, 0, c.zero);
#pragma unroll
  for (int i = 0; i < 8; i++) { const uint4& v = vt[i >> 1][i & 1]; hmma<0>(ot[i >> 1][i & 1], v.x, v.y, v.z, v.w, P[i >> 1][0], P[i >> 1][1]); }
  sched_fence(c.zero);
  bar_sync(BAR_MMA, 256);
  p1_step<11, false>(acc, c);
  sched_fence(c.zero);
  pin<32>(&ot[0][0][0]);
  lane = lane_here();
  odst += (lane ^ (lane >> 3)) << 4;
  auto o_piece = [&](int i) {
    stg128(odst + (i >> 1) * 8192 + (i & 1) * 512, movm(pack2(ot[i][0][0], ot[i][0][1])), movm(pack2(ot[i][0][2], ot[i][0][3])), movm(pack2(ot[i][1][0], ot[i][1][1])), movm(pack2(ot[i][1][2], ot[i][1][3])));
  };
  o_piece(0); o_piece(1);
  p1_step<12>(acc, c);
  o_piece(2); o_piece(3);
  if (round) bar_arrive(BAR_EV + 4, 288);
  p1_step<13>(acc, c);
}

__device__ __forceinline__ void ln_moments(const uint32_t* raw, float& c0, float& s, float& v) {
  c0 = lo_f(__shfl_sync(~0u, raw[0], 0));
  float ss[4] = {0.f, 0.f, 0.f, 0.f}, vv[4] = {0.f, 0.f, 0.f, 0.f};
#pragma unroll
  for (int i = 0; i < 16; i++) {
    const float a = lo_f(raw[i]) - c0, b = hi_f(raw[i]) - c0;
    ss[(2 * i) & 3] += a; ss[(2 * i + 1) & 3] += b;
    vv[(2 * i) & 3] = fmaf(a, a, vv[(2 * i) & 3]); vv[(2 * i + 1) & 3] = fmaf(b, b, vv[(2 * i + 1) & 3]);
  }
  s = (ss[0] + ss[1]) + (ss[2] + ss[3]); v = (vv[0] + vv[1]) + (vv[2] + vv[3]);
}
__device__ __forceinline__ void ln_reduce(float& s, float& v) {
#pragma unroll
  for (int o = 16; o; o >>= 1) { s += __shfl_xor_sync(~0u, s, o); v += __shfl_xor_sync(~0u, v, o); }
}
__device__ __forceinline__ uint32_t ln_finish(float c0, float s, float v) {
  s *= 1.0f / DM;
  float sd;
  asm("sqrt.approx.ftz.f32 %0, %1;" : "=f"(sd) : "f"(bf16r(bf16r(fmaxf(fmaf(v, 1.0f / DM, -s * s), 0.f)) + 1e-5f)));
  return pack2(c0 + s, sd);
}
__device__ __forceinline__ void ln_store(const uint32_t* raw, uint32_t st, uint4* dst) {
  const uint32_t m2 = __byte_perm(st, st, 0x1010);
  const float rinv = rcpf(hi_f(st));
  const uint32_t rh = pack2(rinv, rinv), rl = pack2(rinv - hi_f(rh), rinv - hi_f(rh));
#pragma unroll
  for (int c = 0; c < 4; c++) {
    uint32_t v[4];
#pragma unroll
    for (int i = 0; i < 4; i++) { const uint32_t t = sub2(raw[4 * c + i], m2); v[i] = fma2(t, rh, mul2(t, rl)); }
    stg128(dst + 32 * c, v[0], v[1], v[2], v[3]);
  }
}
__device__ __forceinline__ void col_sums(uint32_t tile, ulonglong2* part, uint32_t tag) {
  const int lane = threadIdx.x & 31;
  float cs[8] = {0, 0, 0, 0, 0, 0, 0, 0};
  uint32_t base = tile + ((lane >> 3) & 1) * 8192 + (lane >> 4) * 4096 + ((lane & 7) << 4);
#pragma unroll 1
  for (int k0 = 0; k0 < 8; k0++, base = (base ^ ((k0 ^ (k0 - 1)) << 4)) + 128) {
    uint4 v[4];
#pragma unroll
    for (int k = 0; k < 4; k++) v[k] = lds128(base + k * 1024);
#pragma unroll
    for (int k = 0; k < 4; k++) {
      cs[0] += lo_f(v[k].x); cs[1] += hi_f(v[k].x); cs[2] += lo_f(v[k].y); cs[3] += hi_f(v[k].y);
      cs[4] += lo_f(v[k].z); cs[5] += hi_f(v[k].z); cs[6] += lo_f(v[k].w); cs[7] += hi_f(v[k].w);
    }
  }
  const bool up = lane >= 16;
#pragma unroll
  for (int i = 0; i < 2; i++) {
    const float a = (up ? cs[4 + 2 * i] : cs[2 * i]) + __shfl_xor_sync(~0u, up ? cs[2 * i] : cs[4 + 2 * i], 16);
    const float b = (up ? cs[5 + 2 * i] : cs[1 + 2 * i]) + __shfl_xor_sync(~0u, up ? cs[1 + 2 * i] : cs[5 + 2 * i], 16);
    asm volatile("{\n.reg .b64 a, b;\nmov.b64 a, {%1, %3};\nmov.b64 b, {%2, %3};\nst.relaxed.gpu.global.v2.b64 [%0], {a, b};\n}"
                 ::"l"(part + 32 * (i + (up ? 2 : 0)) + (lane & 15)), "r"(__float_as_uint(a)), "r"(__float_as_uint(b)), "r"(tag) : "memory");
  }
  asm volatile("fence.proxy.async.shared::cta;" ::: "memory");
}

__global__ void __cluster_dims__(2, 1, 1) __launch_bounds__(384, 1)
fused_kernel(const uint4* __restrict__ x, const uint4* __restrict__ wgate, const uint4* __restrict__ wup, Scratch* gs, const __grid_constant__ Maps mp) {
  extern __shared__ __align__(1024) uint8_t smem_raw[];
  const uint32_t sb = (uint32_t)__cvta_generic_to_shared(smem_raw);
  const unsigned bid = role_id();
  if (threadIdx.x == 352) TS(63);
  if (threadIdx.x < 256 && bid < NMAIN) {
    const uint32_t r = threadIdx.x >> 3, ch = threadIdx.x & 7;
    const uint32_t d = sb + r * 128 + ((ch ^ (r & 7)) << 4);
    const uint8_t* xa = (const uint8_t*)x + ((bid & 15) * 262144 + r * 4096 + ch * 16);
    const uint32_t wo = r * (DFF * 2) + (bid >> 4) * 256 + ch * 16;
    const uint8_t *wa = (const uint8_t*)wgate + wo, *wb = (const uint8_t*)wup + wo;
#pragma unroll
    for (int i = 0; i < 12; i++) {
      const int h = i >= 8;
      const uint8_t* src = (i >> 2) == 1 ? xa + (i & 1) * 131072 + ((i >> 1) & 1) * 2048 : ((i & 2) ? wb : wa) + h * 32 * (DFF * 2) + (i & 1) * 128;
      asm volatile("cp.async.cg.shared.global [%0], [%1], 16;" ::"r"(d + ((i >> 2) == 1 ? OFF_A + (i & 3) * 4096 : (i & 3) * 8192 + h * 4096)), "l"(src) : "memory");
    }
    if (threadIdx.x == 0) TS(23);
  }
  const int warp = __shfl_sync(~0u, threadIdx.x >> 5, 0), lane = threadIdx.x & 31;
  const int m = bid & 15, j = bid >> 4, rank = bid & 1;
  const int m2 = bid >> 3, j2 = bid & 7;
  const bool helper = bid >= NMAIN;
  if (warp >= 8) {
    asm volatile("setmaxnreg.dec.sync.aligned.u32 40;");
    if (warp == 8) {
      if (elect_one()) {
        asm volatile("prefetch.tensormap [%0];\nprefetch.tensormap [%1];\nprefetch.tensormap [%2];" ::"l"(&mp.x), "l"(&mp.wg), "l"(&mp.wu) : "memory");
        for (int s = 0; s < 4; s++) mbar_init(sb + B_F1 + 8 * s, 1);
        if (!helper) mbar_arrive(sb + B_F1);
        asm volatile("fence.mbarrier_init.release.cluster;" ::: "memory");
      }
      __syncwarp();
    } else if (warp == 9) {
      if (elect_one()) {
        if ((sb & 0xffffff) != SM_BASE) asm volatile("trap;");
        for (uint32_t b = B_E1; b < B_F2; b += 8) mbar_init(sb + b, 4);
        for (uint32_t b = B_F2; b < B_AUX; b += 8) mbar_init(sb + b, 1);
        for (uint32_t b = B_EX; b < B_AUX; b += 8) mbar_expect_tx(sb + b, 8192);
        mbar_init(sb + B_AUX, 8); mbar_init(sb + B_HALO, 9); mbar_init(sb + B_HALO + 8, 9);
        asm volatile("st.shared.b32 [%0], %1;" ::"r"(sb + OFF_EPOCH + 4), "r"(bid) : "memory");
        asm volatile("fence.mbarrier_init.release.cluster;" ::: "memory");
      }
      __syncwarp();
    }
    asm volatile("barrier.cluster.arrive.relaxed.aligned;" ::: "memory");
    if (warp == 8 && !helper) {
      if (elect_one()) {
        TS(0); TG(51);
#pragma unroll 1
        for (int kb = 1; kb < 4; kb++) {
          const uint32_t sa = sb + OFF_A + kb * 16384, sw = sb + kb * 32768, fb = sb + B_F1 + 8 * kb;
          mbar_expect_tx(fb, P1_BYTES);
          tma3d(sa, &mp.x, fb, kb * 64, m * 64, 0, EVICT_NORMAL);
          tma2d(sw, &mp.wg, fb, j * 128, kb * 64, EVICT_NORMAL); tma2d(sw + 16384, &mp.wu, fb, j * 128, kb * 64, EVICT_NORMAL);
          tma2d(sw + 8192, &mp.wg, fb, j * 128 + 64, kb * 64, EVICT_NORMAL); tma2d(sw + 24576, &mp.wu, fb, j * 128 + 64, kb * 64, EVICT_NORMAL);
        }
        TS(7);
      }
      __syncwarp();
    }
    asm volatile("barrier.cluster.wait.aligned;" ::: "memory");
    if (helper) {
      if (warp == 8) {
        unsigned e = 0;
        if (elect_one()) {
#pragma unroll 1
          for (int i = 0; i < 16; i++) {
            const uint32_t fb = sb + B_F1 + 8 * (i >> 2);
            if (!(i & 3)) mbar_expect_tx(fb, P1_BYTES);
            tma5d(sb + i * 8192, &mp.wd, fb, (bid - NMAIN) * 256 + (i & 3) * 64, (i >> 2) * 2, HINT_W);
          }
        }
        if (lane == 0) { unsigned* ep = &gs->epoch[bid * 2]; e = *ep + 1; *ep = e; }
        e = __shfl_sync(~0u, e, 0);
        if (lane < 16) flag_wait(&gs->flags[(FL_H + lane * 4) * 32], e * 8u);
        __syncwarp();
        if (elect_one()) {
          fence_async();
          TS(0);
#pragma unroll 1
          for (int i = 0; i < 64; i++) {
            const uint32_t fb = sb + B_F1 + 8 * (i & 3);
            if (i >= 4) { mbar_wait(sb + B_E1 + 8 * (i & 3), ~(i >> 2) & 1); mbar_expect_tx(fb, 16384); }
            bulk_load(sb + OFF_A + (i & 3) * 16384, gs->h + ((i >> 2) * 56 + (i & 3)) * 1024, 16384, fb, EVICT_NORMAL);
          }
        }
      } else if (warp == 9) {
#pragma unroll 1
        for (int t = 0; t < 16; t++) {
          bar_sync(BAR_EV + (t & 1), 288);
          if (lane == 0) { flag_add(&gs->flags[(FL_P + t) * 32]); TS(64 + t); }
          __syncwarp();
        }
      }
    } else if (warp == 8) {
      if (elect_one()) {
        uint32_t par = 0;

        auto x_load = [&]() {
          mbar_expect_tx(sb + B_XT, 32768);
          tma3d(sb + OFF_X, &mp.x, sb + B_XT, j2 * 128, m2 * 64, 0, HINT_LAST); tma3d(sb + OFF_X + 16384, &mp.x, sb + B_XT, j2 * 128 + 64, m2 * 64, 0, HINT_LAST);
        };
        auto w_tile = [&](int R, const CUtensorMap*& mb0, const CUtensorMap*& mb1, int& n0, int& n1) {
          if (R == 1 || R == 2) {
            mb0 = &mp.wqkv; n0 = 64 * (j + 8 * (R - 1)) + rank * 2048;
            mb1 = rank ? (R == 1 ? &mp.wg : &mp.wu) : &mp.wqkv; n1 = rank ? 1024 + 64 * j : n0 + 1024;
          } else {
            mb0 = mb1 = rank ? &mp.wu : &mp.wg;
            n0 = 128 * j + (R ? 1024 * R - 1536 : 0); n1 = n0 + 64;
          }
        };
        for (int R = 0; R < 5; R++) {
          const CUtensorMap *mb0, *mb1;
          int n0, n1;
          w_tile(R, mb0, mb1, n0, n1);
#pragma unroll 1
          for (int kb = R ? 0 : 4; kb < 16; kb++) {
            if (R == 0 && kb == 14) { asm volatile("prefetch.tensormap [%0];\nprefetch.tensormap [%1];" ::"l"(&mp.xn), "l"(&mp.wqkv) : "memory"); }
            if (R == 4 && kb == 2) { asm volatile("prefetch.tensormap [%0];\nprefetch.tensormap [%1];\nprefetch.tensormap [%2];" ::"l"(&mp.wd), "l"(&mp.wo), "l"(&mp.out) : "memory"); }
            if (R == 0 && kb == CS_KB) {
#pragma unroll 1
              for (int h = 0; h < 2; h++) {
                const uint32_t cb = sb + B_CS + 8 * h, d = sb + OFF_X + 16384 * h;
                mbar_expect_tx(cb, 16384);
                tma2d(d, h ? &mp.wu : &mp.wg, cb, n0, m * 64, EVICT_NORMAL); tma2d(d + 8192, h ? &mp.wu : &mp.wg, cb, n1, m * 64, EVICT_NORMAL);
              }
            }
            const int st = kb & 3;
            const uint32_t sa = sb + OFF_A + st * 16384, sw = sb + st * 32768, fb = sb + B_F1 + 8 * st;
            mbar_wait(sb + B_E1 + 8 * st, par);
            if (R * 16 + kb >= 4) REL_TS(R * 16 + kb - 4);
            mbar_expect_tx(fb, P1_BYTES);
            tma2d_mc(sw + rank * 16384, mb0, fb, n0, kb * 64, HINT_W);
            tma2d_mc(sw + 8192 + rank * 16384, mb1, fb, n1, kb * 64, HINT_W);
            if (R == 0) {
              tma3d(sa, &mp.x, fb, kb * 64, m * 64, 0, EVICT_NORMAL);
            } else {
              if (R == 1 && kb == 0) { mbar_wait(sb + B_DEP, 0); TS(1); }
              tma2d(sa, &mp.xn, fb, kb * 64, m * 128, R == 4 ? HINT_LAST : EVICT_NORMAL);
            }
            if (R == 4 && kb == 4 + j2) x_load();
            if (st == 3) par ^= 1;
          }
        }
#pragma unroll 1
        for (int i = 0; i < 26; i++) {
          const int st = i & 3, kb = 2 * i + 4 + rank;
          const uint32_t sa = sb + OFF_A + st * 16384, sw = sb + st * 32768, fb = sb + B_F1 + 8 * st;
          mbar_wait(sb + B_E1 + 8 * st, par);
          REL_TS(76 + i);
          mbar_expect_tx(fb, P1_BYTES);
          tma5d(sw, &mp.wd, fb, j2 * 128, kb * 2, HINT_W); tma5d(sw + 8192, &mp.wd, fb, j2 * 128 + 64, kb * 2, HINT_W);
          tma5d(sw + 16384, &mp.wd, fb, (j2 ^ 1) * 128, kb * 2, HINT_W); tma5d(sw + 24576, &mp.wd, fb, (j2 ^ 1) * 128 + 64, kb * 2, HINT_W);
          if (i == 0 || i == 6 || i == 10 || i == 18) { mbar_wait(sb + B_DEP + 8 * (1 + ((i + 6) >> 3)), 0); }
          bulk_load(sa, gs->h + (m2 * 56 + kb) * 1024, 16384, fb, HINT_H);
          if (st == 3) par ^= 1;
        }
        int st = 0; uint32_t par2 = 1;
#pragma unroll 1
        for (int t = 0; t < 16; t++) {
          const uint32_t sa = sb + p2_a(st), sw = sb + p2_b(st), fb = sb + B_F2 + 8 * st;
          if (t < 5) mbar_wait(sb + B_E1 + 8 * (((2 * t + 1) / 3 + 2) & 3), t < 3); else mbar_wait(sb + B_E2 + 8 * st, par2);
          REL_TS(102 + t);
          mbar_expect_tx(fb, P2_BYTES);
          bulk_load_mc(sa + rank * 8192, gs->o + (m2 * 16 + t) * 1024 + rank * 512, 8192, fb, HINT_H);
          tma2d(sw, &mp.wo, fb, j2 * 128, t * 64, HINT_W); tma2d(sw + 8192, &mp.wo, fb, j2 * 128 + 64, t * 64, HINT_W);
          if (++st == 5) { st = 0; par2 ^= 1; }
        }
      }
    } else if (warp == 9) {
#pragma unroll 1
      for (int e = 0; e < 7; e++) {
        const bool halo = e == 2 || e == 3;
        bar_sync(BAR_EV + e, halo ? 96 : 288);
        if (lane == 0) {
          const int f = e == 0 ? FL_XN + m : (halo ? FL_HALO + (e - 2) * 128 + bid : FL_H + m * 4 + (e == 1 ? 0 : e - 3));
          TS(10 + 2 * e); TG(52 + e);
          flag_add(&gs->flags[f * 32]);
          if (e < 6) TS(11 + 2 * e);
        }
        __syncwarp();
      }
      unsigned other;
      asm volatile("ld.shared::cluster.b32 %0, [%1];" : "=r"(other) : "r"(mapa(sb + OFF_EPOCH + 4, rank ^ 1)) : "memory");
      if (other != (bid ^ 1)) asm volatile("trap;");
      mbar_wait(sb + B_DONE, 0);
    } else {
      unsigned e = 0;
      if (lane == 0) {
        unsigned* ep = &gs->epoch[bid * 2 + warp - 10];
        e = *ep + 1; *ep = e;
        if (warp == 10) { asm volatile("st.shared.b32 [%0], %1;" ::"r"(sb + OFF_EPOCH), "r"(e) : "memory"); mbar_arrive(sb + B_EP); }
      }
      e = __shfl_sync(~0u, e, 0);
      mbar_wait(sb + B_CS + 8 * (warp - 10), 0);
      if (lane == 0 && warp == 11) TS(6);
      col_sums(sb + OFF_X + (warp - 10) * 16384, gs->cspart + (j * 16 + m) * 128 + (warp - 10) * 16, e);
      if (lane == 0 && warp == 11) TS(9);
      if (warp == 10) {
        if (lane == 0) {
#pragma unroll 1
          for (int g = 0; g < 6; g++) {
            flag_wait(&gs->flags[(g == 5 ? FL_P + m2 : (g ? FL_H + m2 * 4 + g - 1 : FL_XN + m)) * 32], e * (g == 5 ? 4u : 8u));
            fence_async();
            mbar_arrive(sb + B_DEP + 8 * g);
            if (g == 0) TS(8);
          }
        }
      } else
      if (elect_one()) {
#pragma unroll 1
        for (int r = 0; r < 2; r++) {
          const uint32_t hb = sb + B_HALO + 8 * r;
          if (r) mbar_wait(sb + B_HALO, 0);
          if (m) {
            flag_wait(&gs->flags[(FL_HALO + r * 128 + bid - 1) * 32], e);
            fence_async();
            mbar_expect_tx(hb, 4096);
            for (int g = 0; g < 2; g++) bulk_load(sb + OFF_X + g * AT_WG + AT_REM + r * 2048, gs->halo + ((r * 128 + bid - 1) * 2 + g) * 128, 2048, hb, EVICT_FIRST);
          } else {
            mbar_arrive(hb);
          }
          TS(34 + r);
        }
      }
    }
  } else {
    asm volatile("barrier.cluster.arrive.relaxed.aligned;" ::: "memory");
    asm volatile("setmaxnreg.inc.sync.aligned.u32 232;");
    const int wg = warp >> 2, w = warp & 3;
    Cons c;
    c.sb = sb; c.wg = wg; c.zero = warp >> 8;
    c.a = 0x4000004000010000ull + ((SM_BASE + OFF_A + wg * 8192) >> 4); c.k1 = 2 + c.zero; c.k2 = 2; c.k4 = 1024 - 6; c.k4w = -3072 - 6; c.b1 = 128 + c.zero;
    c.b = 0x4000004000000000ull + DB_LO + c.zero;
    c.rel = mapa(sb, threadIdx.x & 1);
    c.do_rel = (threadIdx.x & 127) < 2;
    constexpr bool t0 = false;
    float acc[128];
    uint32_t pk[64];
    float rs[2];
    const int q = lane & 3;

    if (helper) {
      asm volatile("barrier.cluster.wait.aligned;" ::: "memory");
      c.a = 0x8000002000010000ull + ((SM_BASE + OFF_A + wg * 4096) >> 4); c.k2 = 510; c.k4 = 1024 - 514; c.k4w = -3072 - 514;
      c.rel = sb;
      uint4* dst = gs->dpart + (bid - NMAIN) * 4096 + threadIdx.x;
      auto put = [&](int p) {
#pragma unroll
        for (int i = 4 * p; i < 4 * p + 4; i++) stg128(dst + i * 256, pk[4 * i], pk[4 * i + 1], pk[4 * i + 2], pk[4 * i + 3]);
      };
#pragma unroll 1
      for (int t = 0; t < 16; t++) {
        p1_issue<0, 0>(acc, c, t & 1);
        if (t) put(0);
        p1_issue<1, 1>(acc, c, t & 1); wg_wait<1>(); release(c, B_E1);
        if (t) put(1);
        p1_issue<2, 1>(acc, c, t & 1); wg_wait<1>(); release(c, B_E1 + 8);
        if (t) put(2);
        if (wg == 1) { wg_wait<0>(); release(c, B_E1 + 16); bar_sync(BAR_LAG, 256); }
        p1_issue<3, 1>(acc, c, t & 1);
        if (wg == 0) bar_arrive(BAR_LAG, 256);
        if (t) { put(3); bar_arrive(BAR_EV + (~t & 1), 288); dst += 8 * 2048; }
        wg_wait<1>(); if (wg == 0) release(c, B_E1 + 16);
        wg_wait<0>(); release(c, B_E1 + 24);
#pragma unroll
        for (int i = 0; i < 64; i++) pk[i] = pack2(acc[2 * i], acc[2 * i + 1]);
      }
      put(0); put(1); put(2); put(3);
      bar_arrive(BAR_EV + 1, 288);
      return;
    }
    {
      const int prow = 16 * j + 2 * warp;
      const uint4* xr = x + (size_t)(128 * m + 2 * (prow & 63) + (prow >> 6)) * 128 + lane;
      uint4* xo = gs->xn + (size_t)(128 * m + prow) * 128 + lane;
      float c0[2], mo[4];
      uint32_t st[2];
      uint32_t e;
      asm volatile("" : "+l"(xr), "+l"(xo));
      asm volatile("cp.async.wait_all;\nfence.proxy.async.shared::cta;" ::: "memory");
      bar_sync(BAR_MMA, 256);
      if (threadIdx.x == 0) TS(39);
      p1_step<0, false>(acc, c);
      asm volatile("barrier.cluster.wait.aligned;" ::: "memory");
      unsigned long long part[18];
      auto gather = [&](int from, int to) {
        const int lane = lane_here();
        const unsigned long long* cp = (const unsigned long long*)gs->cspart + j * 4096 + warp * 32 + lane;
        const unsigned long long* sp = gs->stats + 128 * m + warp * 16 + (lane >> 2);
#pragma unroll
        for (int i = from; i < to; i++) asm volatile("ld.relaxed.gpu.global.b64 %0, [%1];" : "=l"(part[i]) : "l"(i < 16 ? cp + i * 256 : sp + (i - 16) * 8) : "memory");
      };
      auto row_load = [&](int r) {
#pragma unroll
        for (int i = 4 * r; i < 4 * r + 4; i++)
          asm volatile("ld.global.nc.L1::no_allocate.v4.b32 {%0,%1,%2,%3}, [%4];" : "=r"(pk[4 * i]), "=r"(pk[4 * i + 1]), "=r"(pk[4 * i + 2]), "=r"(pk[4 * i + 3]) : "l"(xr + r * 256 + (i & 3) * 32));
      };
      p1_step<1>(acc, c); row_load(0);
      p1_step<2>(acc, c); row_load(1);
      p1_loop(acc, c, 3, LN_KB + 1, [](int) {});
      pin<16>(pk); ln_moments(pk, c0[0], mo[0], mo[1]); pin<2>(mo);
      p1_step<LN_KB + 1>(acc, c);
      sched_fence(c.zero);
      pin<16>(pk + 16); ln_moments(pk + 16, c0[1], mo[2], mo[3]); ln_reduce(mo[0], mo[1]); pin<4>(mo);
      p1_step<LN_KB + 2>(acc, c);
      mbar_spin(sb + B_EP, 0, c.zero);
      asm volatile("ld.shared.b32 %0, [%1];" : "=r"(e) : "r"(sb + OFF_EPOCH) : "memory");
      pin<2>(mo); st[0] = ln_finish(c0[0], mo[0], mo[1]); ln_reduce(mo[2], mo[3]); pin<1>(st); pin<2>(mo + 2);
      p1_step<LN_KB + 3>(acc, c);
      sched_fence(c.zero);
      pin<1>(st); pin<2>(mo + 2);
      st[1] = ln_finish(c0[1], mo[2], mo[3]);
      ln_store(pk, st[0], xo);
      if (lane == 0)
        asm volatile("{\n.reg .b64 a, b;\nmov.b64 a, {%1, %3};\nmov.b64 b, {%2, %3};\nst.relaxed.gpu.global.v2.b64 [%0], {a, b};\n}" ::"l"(gs->stats + 128 * m + prow), "r"(st[0]), "r"(st[1]), "r"(e) : "memory");
      p1_step<LN_KB + 4>(acc, c);
      sched_fence(c.zero);
      pin<1>(st + 1);
      ln_store(pk + 16, st[1], xo + 128);
      bar_arrive(BAR_EV, 288);
      p1_loop(acc, c, LN_KB + 5, 13, [](int) {});
      gather(0, 9);
      p1_step<13>(acc, c);
      gather(9, 18);
      p1_step<14>(acc, c);
      auto validate = [&]() {
        float csum;
        for (int tries = 0;; tries++) {
          uint32_t bad = 0;
          csum = 0.f;
#pragma unroll
          for (int i = 0; i < 18; i++) { bad |= (uint32_t)(part[i] >> 32) ^ e; if (i < 16) csum += __uint_as_float((uint32_t)part[i]); }
          if (!__any_sync(~0u, bad != 0) || tries > (1 << 20)) break;
          gather(0, 18);
        }
        const float hi = bf16r(csum), mid = bf16r(csum - hi);
        sts128(sb + OFF_CS + ((threadIdx.x & 62) * 4 + (threadIdx.x >> 6) * 2 + (threadIdx.x & 1)) * 16, make_uint4(pack2(hi, mid), pack2(csum - hi - mid, 0.f), 0, 0));
        asm volatile("fence.proxy.async.shared::cta;" ::: "memory");
        __syncwarp();
        if (lane == 0) mbar_arrive(sb + B_AUX);
      };
#pragma unroll 1
      for (int ph = 1; ph >= 0; ph--) {
        if (wg == ph) validate();
        if (ph) {
          if (wg == 1) { wg_wait<0>(); release(c, B_E1 + 16); bar_sync(BAR_LAG, 256); }
          p1_issue<3, 1>(acc, c, 1);
        }
      }
      const uint32_t keep = q == 0 ? 0xffffffffu : (q == 1 ? 0xffffu : 0u);
      const uint32_t a0 = (__byte_perm((uint32_t)part[16], 0, 0x1010) ^ 0x80008000u) & keep, a1 = (__byte_perm((uint32_t)part[17], 0, 0x1010) ^ 0x80008000u) & keep;
      mbar_spin(sb + B_AUX, 0, c.zero);
      wg_fence();
      wgmma256_rs(acc, a0, a1, 0, 0, (SM_BASE + OFF_CS) >> 4);
      wg_commit();
      if (wg == 0) bar_arrive(BAR_LAG, 256);
      rs[0] = rcpf(hi_f((uint32_t)part[16])); rs[1] = rcpf(hi_f((uint32_t)part[17]));
      wg_wait<2>(); if (wg == 0) release(c, B_E1 + 16);
      wg_wait<0>(); release(c, B_E1 + 24);
    }
#pragma unroll 1
    for (int R = 1;; R++) {
#pragma unroll
      for (int i = 0; i < 64; i++) pk[i] = pack2(acc[2 * i], acc[2 * i + 1]);
      if (t0) TS(24 + R + wg * 16);
      uint8_t* hb = (uint8_t*)gs->h + (size_t)m * 56 * 16384 + warp * 1024;
      if (R == 5) { c.a = 0x8000002000010000ull + ((SM_BASE + OFF_A + wg * 4096) >> 4); c.k2 = 510; c.k4 = 1024 - 514; c.k4w = -3072 - 514; }
      p1_step<0>(acc, c);
      if (R == 2 || R == 3) {
        attn_tile(acc, pk, c, R - 2, warp, m, bid, gs, hb + (16 + j) * 16384, (uint8_t*)gs->o + (m * 16 + j + 8 * (R - 2)) * 16384 + warp * 1024);
      } else {
        geglu_tile(acc, pk, c, R == 5 ? 24 : 14, hb + (2 * j + (R == 1 ? 0 : 16 * R - 40)) * 16384, BAR_EV + (R == 1 ? 1 : R + 1), rs);
        rs[0] = rs[1] = 1.0f;
        if (R == 5) break;
      }
      p1_step<14>(acc, c); p1_step<15>(acc, c);
    }
    auto fetch = [&](int p) {
      asm volatile("ld.global.cg.v4.b32 {%0,%1,%2,%3}, [%4];" : "=r"(pk[4 * p]), "=r"(pk[4 * p + 1]), "=r"(pk[4 * p + 2]), "=r"(pk[4 * p + 3]) : "l"(gs->dpart + bid * 2048 + p * 256 + threadIdx.x) : "memory");
    };
    mbar_spin(sb + B_DEP + 40, 0, c.zero);
    fetch(0); fetch(1); fetch(2);
    p1_step<8>(acc, c);
    fetch(3); fetch(4); fetch(5);
    p1_step<9>(acc, c);
    fetch(6); fetch(7);
    {
      float accs[64];
      const uint32_t peer = mapa(sb, rank ^ 1);
      auto send_piece = [&](int p) {
        asm volatile("st.async.weak.shared::cluster.mbarrier::complete_tx::bytes.v4.b32 [%0], {%1,%2,%3,%4}, [%5];" ::"r"(peer + OFF_LAND + p * 4096 + threadIdx.x * 16),
                     "r"(pack2(acc[64 + 8 * p], acc[65 + 8 * p])), "r"(pack2(acc[66 + 8 * p], acc[67 + 8 * p])), "r"(pack2(acc[68 + 8 * p], acc[69 + 8 * p])), "r"(pack2(acc[70 + 8 * p], acc[71 + 8 * p])),
                     "r"(peer + B_EX + 16 * wg + 8 * (p >> 2)) : "memory");
      };
      auto silu_piece = [&](int p) {
        const uint4 r = lds128(sb + OFF_LAND + p * 4096 + threadIdx.x * 16);
        const uint32_t rr[4] = {add2(r.x, pk[4 * p]), add2(r.y, pk[4 * p + 1]), add2(r.z, pk[4 * p + 2]), add2(r.w, pk[4 * p + 3])};
#pragma unroll
        for (int i = 0; i < 4; i++) {
          const float a = acc[8 * p + 2 * i] + lo_f(rr[i]), b = acc[8 * p + 2 * i + 1] + hi_f(rr[i]);
          pk[4 * p + i] = pack2(silu_half(a), silu_half(b));
        }
        pin<4>(pk + 4 * p);
      };
      const uint32_t xa = sb + OFF_X + (warp * 16 + (lane & 7)) * 128 + (((lane >> 3) ^ (lane & 7)) << 4);
      auto x_addr = [&](int i) { return (xa ^ ((i & 1) << 6)) + ((i >> 1) & 1) * 1024 + (i >> 2) * 16384; };
      auto x_piece = [&](int i) { const uint4 v = ldsm(x_addr(i)); pk[32 + 4 * i] = v.x; pk[33 + 4 * i] = v.y; pk[34 + 4 * i] = v.z; pk[35 + 4 * i] = v.w; };
      p2_step<0>(accs, c);
      p2_step<1>(accs, c);
      mbar_spin(sb + B_E1 + 8, 0, c.zero);
      send_piece(0); send_piece(1);
      p2_step<2>(accs, c); sched_fence(c.zero); send_piece(2); send_piece(3);
      p2_step<3>(accs, c); sched_fence(c.zero); send_piece(4); send_piece(5);
      p2_step<4>(accs, c); mbar_spin(sb + B_XT, 0, c.zero); send_piece(6); send_piece(7);
      p2_step<5>(accs, c); mbar_spin(sb + B_EX + 16 * wg, 0, c.zero); silu_piece(0); x_piece(0);
      p2_step<6>(accs, c); sched_fence(c.zero); silu_piece(1); x_piece(1);
      p2_step<7>(accs, c); sched_fence(c.zero); silu_piece(2); x_piece(2);
      p2_step<8>(accs, c); sched_fence(c.zero); silu_piece(3); x_piece(3);
      p2_step<9>(accs, c); mbar_spin(sb + B_EX + 16 * wg + 8, 0, c.zero); silu_piece(4); x_piece(4);
      p2_step<10>(accs, c); sched_fence(c.zero); silu_piece(5); x_piece(5);
      p2_step<11>(accs, c); sched_fence(c.zero); silu_piece(6); x_piece(6); x_piece(7);
      auto out_half = [&](const float* a, int h) {
#pragma unroll
        for (int i = 4 * h; i < 4 * h + 4; i++) {
          uint32_t v[4];
#pragma unroll
          for (int k = 0; k < 4; k++) { const int o = 2 * (4 * (i & 1) + k) + ((i >> 1) & 1); v[k] = fma2(pack2(a[2 * o], a[2 * o + 1]), pk[16 * h + o], pk[32 + 4 * i + k]); }
          asm volatile("stmatrix.sync.aligned.m8n8.x4.shared.b16 [%0], {%1,%2,%3,%4};" ::"r"(x_addr(i)), "r"(v[0]), "r"(v[1]), "r"(v[2]), "r"(v[3]) : "memory");
          if (i & 1) {
            asm volatile("fence.proxy.async.shared::cta;" ::: "memory");
            __syncwarp();
            if (elect_one()) tma3d_store(&mp.out, sb + OFF_X + h * 16384 + warp * 2048 + (i & 2) * 512, j2 * 128 + h * 64, m2 * 64 + w * 16 + (i & 2) * 4, wg);
          }
        }
      };
      if (wg == 1) silu_piece(7);
      p2_step<12>(accs, c); p2_step<13>(accs, c); p2_step<14>(accs, c); p2_step<15>(accs, c);
      if (c.do_rel) mbar_arrive(sb + B_DONE);
      if (wg == 0) silu_piece(7);
      wg_wait<0>();
      out_half(accs, 0); out_half(accs + 32, 1);
      if (elect_one()) { asm volatile("cp.async.bulk.commit_group;\ncp.async.bulk.wait_group.read 0;" ::: "memory"); }
      if ((threadIdx.x & 127) == 0) { TS(33 + wg * 16); if (wg) { TG(59); unsigned id; asm volatile("mov.u32 %0, %%smid;" : "=r"(id)); TSV(60, id); } }
    }
  }
}

typedef CUresult (*EncodeFn)(CUtensorMap*, CUtensorMapDataType, cuuint32_t, void*, const cuuint64_t*, const cuuint64_t*, const cuuint32_t*, const cuuint32_t*,
                             CUtensorMapInterleave, CUtensorMapSwizzle, CUtensorMapL2promotion, CUtensorMapFloatOOBfill);

void encode(EncodeFn fn, CUtensorMap* tm, const void* p, int rank, const cuuint64_t* dims, const cuuint64_t* strides, const cuuint32_t* box) {
  const cuuint32_t es[5] = {1, 1, 1, 1, 1};
  fn(tm, CU_TENSOR_MAP_DATA_TYPE_BFLOAT16, rank, const_cast<void*>(p), dims, strides, box, es, CU_TENSOR_MAP_INTERLEAVE_NONE, CU_TENSOR_MAP_SWIZZLE_128B,
     PROMO, CU_TENSOR_MAP_FLOAT_OOB_FILL_NONE);
}

}

extern "C" void kernel_launch(void* const* d_in, const int* in_sizes, int n_in, void* d_out, int out_size) {
  (void)in_sizes; (void)n_in; (void)out_size;
  static EncodeFn fn = nullptr;
  static Scratch* gs = nullptr;
  if (!fn) {
    void* p = nullptr;
    cudaDriverEntryPointQueryResult qr;
    cudaGetDriverEntryPoint("cuTensorMapEncodeTiled", &p, cudaEnableDefault, &qr);
    fn = (EncodeFn)p;
    cudaGetSymbolAddress((void**)&gs, g_scratch);
    cudaFuncSetAttribute(fused_kernel, cudaFuncAttributeMaxDynamicSharedMemorySize, SMEM_BYTES);
  }
  const void *x = d_in[0], *wqkv = d_in[1], *wo = d_in[2], *wg = d_in[4], *wu = d_in[5], *wd = d_in[6];
  Maps mp;
  {
    const cuuint64_t dims[3] = {DM, SEQ / 2, 2}, st[2] = {DM * 4, DM * 2};
    const cuuint32_t box_in[3] = {64, 64, 2}, box_out[3] = {64, 8, 1};
    encode(fn, &mp.x, x, 3, dims, st, box_in);
    encode(fn, &mp.out, d_out, 3, dims, st, box_out);
  }
  {
    const cuuint64_t dims[2] = {DM, SEQ}, st[1] = {DM * 2};
    const cuuint32_t box[2] = {64, 128};
    encode(fn, &mp.xn, gs->xn, 2, dims, st, box);
  }
  {
    const cuuint32_t box[2] = {64, 64};
    const cuuint64_t dq[2] = {3 * DM, DM}, sq[1] = {3 * DM * 2}, df[2] = {DFF, DM}, sf[1] = {DFF * 2}, dw[2] = {DM, DM}, sw[1] = {DM * 2};
    encode(fn, &mp.wqkv, wqkv, 2, dq, sq, box);
    encode(fn, &mp.wg, wg, 2, df, sf, box);
    encode(fn, &mp.wu, wu, 2, df, sf, box);
    encode(fn, &mp.wo, wo, 2, dw, sw, box);
  }
  {
    const cuuint32_t box[5] = {64, 2, 4, 4, 2};
    const cuuint64_t st[4] = {DM * 2, 8 * DM * 2, 2 * DM * 2, 32 * DM * 2};
    const cuuint64_t dd[5] = {DM, 2, 4, 4, DFF / 32};
    encode(fn, &mp.wd, wd, 5, dd, st, box);
  }
  fused_kernel<<<NCTA, 384, SMEM_BYTES>>>((const uint4*)x, (const uint4*)wg, (const uint4*)wu, gs, mp);
}
```

```cpp
#include <cuda_runtime.h>
#include <cuda_bf16.h>
#include <cuda.h>
#include <stdint.h>

#define CS_KB 8
#define LN_KB 4

namespace {

constexpr int SEQ = 2048, DM = 1024, DFF = 3584;
constexpr int NMAIN = 128, NCTA = 132;
constexpr uint64_t EVICT_FIRST = 0x12F0000000000000ull, EVICT_NORMAL = 0x1000000000000000ull;

constexpr uint32_t SM_BASE = 0x400;
constexpr uint32_t P1_BYTES = 49152, P2_BYTES = 32768;
constexpr uint32_t OFF_A = 131072;
__host__ __device__ constexpr uint32_t p2_a(int s) { return s == 0 ? OFF_A + 32768 : s == 1 ? OFF_A + 49152 : s == 2 ? 114688 : s == 3 ? 16384 : 49152; }
__host__ __device__ constexpr uint32_t p2_b(int s) { return s < 3 ? 65536 + s * 16384 : (s - 3) * 32768; }
constexpr uint32_t OFF_LAND = OFF_A;
constexpr uint32_t OFF_X = 196608;
constexpr uint32_t OFF_CS = OFF_X + 14336;
constexpr uint32_t OFF_BAR = 229376;
constexpr uint32_t B_F1 = OFF_BAR, B_E1 = B_F1 + 32, B_E2 = B_E1 + 32, B_DONE = B_E2 + 40, B_F2 = B_DONE + 8, B_DEP = B_F2 + 40, B_CS = B_DEP + 48,
                   B_XT = B_CS + 16, B_EP = B_XT + 8, B_EX = B_EP + 8, B_AUX = B_EX + 32, B_HALO = B_AUX + 8, OFF_EPOCH = B_HALO + 16;
constexpr uint32_t SMEM_BYTES = 232448;
constexpr uint32_t AT_V = 0, AT_K = 8192, AT_REM = 11264, AT_WG = 15360;

constexpr int FL_XN = 0, FL_H = 16, FL_P = 80, FL_HALO = 96, FL_N = FL_HALO + 256;
struct __align__(1024) Scratch {
  uint4 h[16 * 56 * 1024];
  uint4 o[16 * 16 * 1024];
  uint4 xn[SEQ * DM / 8];
  uint4 dpart[128 * 8 * 256];
  uint4 halo[2 * 128 * 2 * 128];
  ulonglong2 cspart[8 * 16 * 128];
  unsigned long long stats[SEQ];
  unsigned flags[FL_N * 32];
  unsigned epoch[NCTA * 2];
};
__device__ Scratch g_scratch;
#define TG(i) do {} while (0)
#define TSV(i, v) do {} while (0)
#define TS(i) do {} while (0)

__device__ __forceinline__ unsigned role_id() {
  unsigned sm, nsm;
  asm("mov.u32 %0, %%smid;\nmov.u32 %1, %%nsmid;" : "=r"(sm), "=r"(nsm));
  const unsigned t = (nsm == NCTA ? sm : blockIdx.x) >> 1;
  unsigned g = t & 7, i = t >> 3;
  if (t >= 32) { i = (t - 32) / 7; g = t - 31 - 7 * i; i += 4; }
  if (t >= 60) { g = t - 60; i = 8; }
  if (t >= 62) { g = 0; i = t - 58; }
  return 16 * i + 2 * g + (blockIdx.x & 1);
}

struct Maps { CUtensorMap x, xn, out, wqkv, wg, wu, wd, wo; };

__device__ __forceinline__ void mbar_init(uint32_t bar, uint32_t cnt) { asm volatile("mbarrier.init.shared::cta.b64 [%0], %1;" ::"r"(bar), "r"(cnt)); }
__device__ __forceinline__ void mbar_expect_tx(uint32_t bar, uint32_t bytes) { asm volatile("mbarrier.arrive.expect_tx.shared::cta.b64 _, [%0], %1;" ::"r"(bar), "r"(bytes) : "memory"); }
__device__ __forceinline__ void mbar_arrive(uint32_t bar) { asm volatile("mbarrier.arrive.shared::cta.b64 _, [%0];" ::"r"(bar) : "memory"); }
__device__ __forceinline__ void mbar_arrive_cl(uint32_t bar) { asm volatile("mbarrier.arrive.shared::cluster.b64 _, [%0];" ::"r"(bar) : "memory"); }
__device__ __forceinline__ uint32_t mapa(uint32_t a, uint32_t cta) { uint32_t r; asm("mapa.shared::cluster.u32 %0, %1, %2;" : "=r"(r) : "r"(a), "r"(cta)); return r; }
__device__ __forceinline__ void mbar_wait(uint32_t bar, uint32_t parity) {
  asm volatile("{\n.reg .pred p;\n.reg .u32 n;\nmov.u32 n, 0;\nLAB_WAIT:\nmbarrier.try_wait.parity.shared::cta.b64 p, [%0], %1;\n@p bra LAB_DONE;\n"
               "add.u32 n, n, 1;\nsetp.gt.u32 p, n, 4000000;\n@p trap;\nbra LAB_WAIT;\nLAB_DONE:\n}" ::"r"(bar), "r"(parity) : "memory");
}
__device__ __forceinline__ void mbar_spin(uint32_t bar, uint32_t parity, uint32_t zero) {
  asm volatile("{\n.reg .pred p, z;\nsetp.ne.u32 z, %2, 0;\nLAB_WAIT:\nmbarrier.try_wait.parity.shared::cta.b64 p, [%0], %1;\n@p bra LAB_DONE;\n@z trap;\nbra LAB_WAIT;\nLAB_DONE:\n}" ::"r"(bar), "r"(parity), "r"(zero) : "memory");
}
__device__ __forceinline__ void flag_wait(const unsigned* f, unsigned target) {
  asm volatile("{\n.reg .pred p;\n.reg .u32 n, v;\nmov.u32 n, 0;\nLAB_WAIT:\nld.relaxed.gpu.global.u32 v, [%0];\nsub.u32 v, v, %1;\nsetp.ge.s32 p, v, 0;\n@p bra LAB_DONE;\n"
               "nanosleep.u32 200;\nadd.u32 n, n, 1;\nsetp.gt.u32 p, n, 4000000;\n@p trap;\nbra LAB_WAIT;\nLAB_DONE:\nfence.acquire.gpu;\n}" ::"l"(f), "r"(target) : "memory");
}
__device__ __forceinline__ void flag_add(unsigned* f) { asm volatile("red.release.gpu.global.add.u32 [%0], 1;" ::"l"(f) : "memory"); }
__device__ __forceinline__ void fence_async() { asm volatile("fence.proxy.async.global;" ::: "memory"); }
__device__ __forceinline__ bool elect_one() { uint32_t p; asm volatile("{\n.reg .pred P;\nelect.sync _|P, 0xffffffff;\nselp.u32 %0, 1, 0, P;\n}" : "=r"(p)); return p; }
__device__ __forceinline__ void bar_sync(int id, int n) { asm volatile("bar.sync %0, %1;" ::"r"(id), "r"(n) : "memory"); }
__device__ __forceinline__ void bar_arrive(int id, int n) { asm volatile("bar.arrive %0, %1;" ::"r"(id), "r"(n) : "memory"); }

__device__ __forceinline__ void tma2d(uint32_t dst, const CUtensorMap* tm, uint32_t bar, int c0, int c1, uint64_t hint) {
  asm volatile("cp.async.bulk.tensor.2d.shared::cluster.global.mbarrier::complete_tx::bytes.L2::cache_hint [%0], [%1, {%3, %4}], [%2], %5;" ::"r"(dst), "l"(tm), "r"(bar), "r"(c0), "r"(c1), "l"(hint) : "memory");
}
__device__ __forceinline__ void tma2d_mc(uint32_t dst, const CUtensorMap* tm, uint32_t bar, int c0, int c1, uint64_t hint) {
  asm volatile("cp.async.bulk.tensor.2d.shared::cluster.global.mbarrier::complete_tx::bytes.multicast::cluster.L2::cache_hint [%0], [%1, {%3, %4}], [%2], %5, %6;" ::"r"(dst), "l"(tm), "r"(bar), "r"(c0), "r"(c1), "h"((uint16_t)3), "l"(hint) : "memory");
}
__device__ __forceinline__ void tma3d(uint32_t dst, const CUtensorMap* tm, uint32_t bar, int c0, int c1, int c2, uint64_t hint) {
  asm volatile("cp.async.bulk.tensor.3d.shared::cluster.global.mbarrier::complete_tx::bytes.L2::cache_hint [%0], [%1, {%3, %4, %5}], [%2], %6;" ::"r"(dst), "l"(tm), "r"(bar), "r"(c0), "r"(c1), "r"(c2), "l"(hint) : "memory");
}
__device__ __forceinline__ void tma5d(uint32_t dst, const CUtensorMap* tm, uint32_t bar, int c0, int c4, uint64_t hint) {
  asm volatile("cp.async.bulk.tensor.5d.shared::cluster.global.mbarrier::complete_tx::bytes.L2::cache_hint [%0], [%1, {%3, %5, %5, %5, %4}], [%2], %6;" ::"r"(dst), "l"(tm), "r"(bar), "r"(c0), "r"(c4), "r"(0), "l"(hint) : "memory");
}
__device__ __forceinline__ void tma3d_store(const CUtensorMap* tm, uint32_t src, int c0, int c1, int c2) {
  asm volatile("cp.async.bulk.tensor.3d.global.shared::cta.bulk_group.L2::cache_hint [%0, {%2, %3, %4}], [%1], %5;" ::"l"(tm), "r"(src), "r"(c0), "r"(c1), "r"(c2), "l"(EVICT_FIRST) : "memory");
}
__device__ __forceinline__ void bulk_load(uint32_t dst, const void* src, uint32_t bytes, uint32_t bar, uint64_t hint) {
  asm volatile("cp.async.bulk.shared::cluster.global.mbarrier::complete_tx::bytes.L2::cache_hint [%0], [%1], %2, [%3], %4;" ::"r"(dst), "l"(src), "r"(bytes), "r"(bar), "l"(hint) : "memory");
}
__device__ __forceinline__ void bulk_load_mc(uint32_t dst, const void* src, uint32_t bytes, uint32_t bar, uint64_t hint) {
  asm volatile("cp.async.bulk.shared::cluster.global.mbarrier::complete_tx::bytes.multicast::cluster.L2::cache_hint [%0], [%1], %2, [%3], %4, %5;" ::"r"(dst), "l"(src), "r"(bytes), "r"(bar), "h"((uint16_t)3), "l"(hint) : "memory");
}
__device__ __forceinline__ uint4 lds128(uint32_t a) { uint4 v; asm volatile("ld.shared.v4.b32 {%0,%1,%2,%3}, [%4];" : "=r"(v.x), "=r"(v.y), "=r"(v.z), "=r"(v.w) : "r"(a) : "memory"); return v; }
__device__ __forceinline__ void sts128(uint32_t a, uint4 v) { asm volatile("st.shared.v4.b32 [%0], {%1,%2,%3,%4};" ::"r"(a), "r"(v.x), "r"(v.y), "r"(v.z), "r"(v.w) : "memory"); }
__device__ __forceinline__ void stg128(void* p, uint32_t a, uint32_t b, uint32_t c, uint32_t d) { asm volatile("st.global.v4.b32 [%0], {%1,%2,%3,%4};" ::"l"(p), "r"(a), "r"(b), "r"(c), "r"(d) : "memory"); }

__device__ __forceinline__ uint32_t pack2(float lo, float hi) { uint32_t r; asm("cvt.rn.bf16x2.f32 %0, %1, %2;" : "=r"(r) : "f"(hi), "f"(lo)); return r; }
__device__ __forceinline__ float lo_f(uint32_t v) { return __uint_as_float(v << 16); }
__device__ __forceinline__ float hi_f(uint32_t v) { return __uint_as_float(v & 0xffff0000u); }
__device__ __forceinline__ float bf16r(float v) { return lo_f(pack2(v, 0.f)); }
__device__ __forceinline__ uint32_t mul2(uint32_t a, uint32_t b) { uint32_t r; asm("mul.rn.bf16x2 %0, %1, %2;" : "=r"(r) : "r"(a), "r"(b)); return r; }
__device__ __forceinline__ uint32_t add2(uint32_t a, uint32_t b) { uint32_t r; asm("add.rn.bf16x2 %0, %1, %2;" : "=r"(r) : "r"(a), "r"(b)); return r; }
__device__ __forceinline__ uint32_t sub2(uint32_t a, uint32_t b) { uint32_t r; asm("sub.rn.bf16x2 %0, %1, %2;" : "=r"(r) : "r"(a), "r"(b)); return r; }
__device__ __forceinline__ uint32_t fma2(uint32_t a, uint32_t b, uint32_t c) { uint32_t r; asm("fma.rn.bf16x2 %0, %1, %2, %3;" : "=r"(r) : "r"(a), "r"(b), "r"(c)); return r; }
__device__ __forceinline__ uint32_t max2(uint32_t a, uint32_t b) { uint32_t r; asm("max.bf16x2 %0, %1, %2;" : "=r"(r) : "r"(a), "r"(b)); return r; }
__device__ __forceinline__ float ex2f(float x) { float y; asm("ex2.approx.ftz.f32 %0, %1;" : "=f"(y) : "f"(x)); return y; }
__device__ __forceinline__ float rcpf(float x) { float y; asm("rcp.approx.ftz.f32 %0, %1;" : "=f"(y) : "f"(x)); return y; }
constexpr float GELU_C1 = 0.7978845608028654f, GELU_C3 = 0.035677408136300125f;
__device__ __forceinline__ float gelu_k(float g, float c1, float c3, float k) {
  float t;
  asm("tanh.approx.f32 %0, %1;" : "=f"(t) : "f"(g * fmaf(g * g, c3, c1)));
  g *= k;
  return fmaf(g, t, g);
}
__device__ __forceinline__ float silu_half(float z) { float t; asm("tanh.approx.f32 %0, %1;" : "=f"(t) : "f"(z)); return fmaf(z, t, z); }

__device__ __forceinline__ void wg_fence() { asm volatile("wgmma.fence.sync.aligned;" ::: "memory"); }
__device__ __forceinline__ void wg_commit() { asm volatile("wgmma.commit_group.sync.aligned;" ::: "memory"); }
template <int N> __device__ __forceinline__ void wg_wait() { asm volatile("wgmma.wait_group.sync.aligned %0;" ::"n"(N) : "memory"); }
#define A8(o) "+f"(d[(o)]), "+f"(d[(o) + 1]), "+f"(d[(o) + 2]), "+f"(d[(o) + 3]), "+f"(d[(o) + 4]), "+f"(d[(o) + 5]), "+f"(d[(o) + 6]), "+f"(d[(o) + 7])
#define A64(o) A8(o), A8((o) + 8), A8((o) + 16), A8((o) + 24), A8((o) + 32), A8((o) + 40), A8((o) + 48), A8((o) + 56)
#define REGS0_63 "%0,%1,%2,%3,%4,%5,%6,%7,%8,%9,%10,%11,%12,%13,%14,%15,%16,%17,%18,%19,%20,%21,%22,%23,%24,%25,%26,%27,%28,%29,%30,%31," \
                 "%32,%33,%34,%35,%36,%37,%38,%39,%40,%41,%42,%43,%44,%45,%46,%47,%48,%49,%50,%51,%52,%53,%54,%55,%56,%57,%58,%59,%60,%61,%62,%63"
#define REGS64_127 "%64,%65,%66,%67,%68,%69,%70,%71,%72,%73,%74,%75,%76,%77,%78,%79,%80,%81,%82,%83,%84,%85,%86,%87,%88,%89,%90,%91,%92,%93,%94,%95," \
                   "%96,%97,%98,%99,%100,%101,%102,%103,%104,%105,%106,%107,%108,%109,%110,%111,%112,%113,%114,%115,%116,%117,%118,%119,%120,%121,%122,%123,%124,%125,%126,%127"
__device__ __forceinline__ void desc_add(uint64_t& x, int v) { asm volatile("{\n.reg .b32 lo, hi;\nmov.b64 {lo, hi}, %0;\nadd.s32 lo, lo, %1;\nmov.b64 %0, {lo, hi};\n}" : "+l"(x) : "r"(v)); }
template <int ACCUM> __device__ __forceinline__ void wgmma256(float (&d)[128], uint64_t& a, uint64_t& b, int da, int db) {
  asm volatile("{\n.reg .pred p;\nsetp.ne.b32 p, %130, 0;\n"
               "wgmma.mma_async.sync.aligned.m64n256k16.f32.bf16.bf16 {" REGS0_63 "," REGS64_127 "}, %128, %129, p, 1, 1, 0, 1;\n}"
               : A64(0), A64(64) : "l"(a), "l"(b), "n"(ACCUM));
  desc_add(a, da); desc_add(b, db);
}
__device__ __forceinline__ void wgmma256_rs(float (&d)[128], uint32_t a0, uint32_t a1, uint32_t z0, uint32_t z1, uint32_t b_lo) {
  asm volatile("{\n.reg .b64 db;\nmov.b64 db, {%132, 0x00000008};\n"
               "wgmma.mma_async.sync.aligned.m64n256k16.f32.bf16.bf16 {" REGS0_63 "," REGS64_127 "}, {%128,%129,%130,%131}, db, 1, 1, 1, 0;\n}"
               : A64(0), A64(64) : "r"(a0), "r"(a1), "r"(z0), "r"(z1), "r"(b_lo));
}
template <int ACCUM> __device__ __forceinline__ void wgmma128(float (&d)[64], uint64_t& a, uint64_t& b, int da, int db) {
  asm volatile("{\n.reg .pred p;\nsetp.ne.b32 p, %66, 0;\n"
               "wgmma.mma_async.sync.aligned.m64n128k16.f32.bf16.bf16 {" REGS0_63 "}, %64, %65, p, 1, 1, 0, 1;\n}"
               : A64(0) : "l"(a), "l"(b), "n"(ACCUM));
  desc_add(a, da); desc_add(b, db);
}
template <int ACCUM> __device__ __forceinline__ void hmma(float (&c)[4], uint32_t a0, uint32_t a1, uint32_t a2, uint32_t a3, uint32_t b0, uint32_t b1) {
  if (ACCUM)
    asm volatile("mma.sync.aligned.m16n8k16.row.col.f32.bf16.bf16.f32 {%0,%1,%2,%3}, {%4,%5,%6,%7}, {%8,%9}, {%0,%1,%2,%3};"
                 : "+f"(c[0]), "+f"(c[1]), "+f"(c[2]), "+f"(c[3]) : "r"(a0), "r"(a1), "r"(a2), "r"(a3), "r"(b0), "r"(b1));
  else
    asm volatile("mma.sync.aligned.m16n8k16.row.col.f32.bf16.bf16.f32 {%0,%1,%2,%3}, {%4,%5,%6,%7}, {%8,%9}, {%10,%10,%10,%10};"
                 : "=f"(c[0]), "=f"(c[1]), "=f"(c[2]), "=f"(c[3]) : "r"(a0), "r"(a1), "r"(a2), "r"(a3), "r"(b0), "r"(b1), "f"(0.f));
}
__device__ __forceinline__ uint32_t movm(uint32_t a) { uint32_t d; asm volatile("movmatrix.sync.aligned.m8n8.trans.b16 %0, %1;" : "=r"(d) : "r"(a)); return d; }
__device__ __forceinline__ int lane_here() { int v; asm volatile("mov.u32 %0, %%laneid;" : "=r"(v)); return v; }
template <int N> __device__ __forceinline__ void pin(uint32_t* r) {
#pragma unroll
  for (int i = 0; i < N; i++) asm volatile("" : "+r"(r[i]));
}
template <int N> __device__ __forceinline__ void pin(float* r) {
#pragma unroll
  for (int i = 0; i < N; i++) asm volatile("" : "+f"(r[i]));
}
__device__ __forceinline__ void sched_fence(uint32_t zero) {
  asm volatile("{\n.reg .pred p;\nsetp.eq.u32 p, %0, 0;\nLAB_F:\n@p bra.uni LAB_D;\nnanosleep.u32 0;\nbra.uni LAB_F;\nLAB_D:\n}" ::"r"(zero) : "memory");
}
__device__ __forceinline__ uint4 ldsm(uint32_t a) { uint4 v; asm volatile("ldmatrix.sync.aligned.m8n8.x4.shared.b16 {%0,%1,%2,%3}, [%4];" : "=r"(v.x), "=r"(v.y), "=r"(v.z), "=r"(v.w) : "r"(a) : "memory"); return v; }
__device__ __forceinline__ uint4 ldsm_t(uint32_t a) { uint4 v; asm volatile("ldmatrix.sync.aligned.m8n8.x4.trans.shared.b16 {%0,%1,%2,%3}, [%4];" : "=r"(v.x), "=r"(v.y), "=r"(v.z), "=r"(v.w) : "r"(a) : "memory"); return v; }

constexpr int BAR_LAG = 1, BAR_MMA = 2, BAR_EV = 3;

struct Cons {
  uint32_t sb;
  mutable uint64_t a, b;
  int k1, k2, k4, k4w, b1;
  uint32_t rel;
  bool do_rel;
  int wg;
  uint32_t zero;
};
#define REL_TS(n) TS(64 + (n))
constexpr uint32_t DB_LO = (SM_BASE >> 4) | ((8192 >> 4) << 16);

template <int ST, int ACCUM, bool WAIT = true> __device__ __forceinline__ void p1_issue(float (&acc)[128], const Cons& c, uint32_t parity) {
  if (WAIT) mbar_spin(c.sb + B_F1 + 8 * ST, parity, c.zero);
  wg_fence();
  wgmma256<ACCUM>(acc, c.a, c.b, c.k1, c.b1);
  wgmma256<1>(acc, c.a, c.b, c.k2, c.b1);
  wgmma256<1>(acc, c.a, c.b, c.k1, c.b1);
  wgmma256<1>(acc, c.a, c.b, ST == 3 ? c.k4w : c.k4, ST == 3 ? -6144 - 384 : 2048 - 384);
  wg_commit();
}
__device__ __forceinline__ void release(const Cons& c, uint32_t bar) { if (c.do_rel) mbar_arrive_cl(c.rel + bar); }
template <int KB, bool WAIT = true> __device__ __forceinline__ void p1_step(float (&acc)[128], const Cons& c) {
  if (KB == 15) { if (c.wg == 1) { wg_wait<0>(); release(c, B_E1 + 16); bar_sync(BAR_LAG, 256); } }
  p1_issue<KB & 3, KB != 0, WAIT>(acc, c, (KB >> 2) & 1);
  if (KB == 15) { if (c.wg == 0) bar_arrive(BAR_LAG, 256); }
  if (KB > 0) { wg_wait<1>(); if (KB != 15 || c.wg == 0) release(c, B_E1 + 8 * ((KB - 1) & 3)); }
  if (KB == 15) { wg_wait<0>(); release(c, B_E1 + 24); }
}
template <class F> __device__ __forceinline__ void p1_loop(float (&acc)[128], const Cons& c, int from, int to, F&& shadow) {
#pragma unroll 1
  for (int kb = from; kb < to; kb++) {
    const bool wrap = (kb & 3) == 3;
    mbar_spin(c.sb + B_F1 + 8 * (kb & 3), (kb >> 2) & 1, c.zero);
    wg_fence();
    wgmma256<1>(acc, c.a, c.b, c.k1, c.b1);
    wgmma256<1>(acc, c.a, c.b, c.k2, c.b1);
    wgmma256<1>(acc, c.a, c.b, c.k1, c.b1);
    wgmma256<1>(acc, c.a, c.b, wrap ? c.k4w : c.k4, wrap ? -6144 - 384 : 2048 - 384);
    wg_commit();
    wg_wait<1>();
    release(c, B_E1 + 8 * ((kb - 1) & 3));
    shadow(kb);
  }
}
template <int T> __device__ __forceinline__ void p2_step(float (&acc)[64], const Cons& c) {
  if (T == 12) { if (c.wg == 1) bar_sync(BAR_LAG, 256); }
  mbar_spin(c.sb + B_F2 + 8 * (T % 5), (T / 5) & 1, c.zero);
  wg_fence();
  wgmma128<T != 0>(acc, c.a, c.b, c.k1, c.b1);
  wgmma128<1>(acc, c.a, c.b, c.k2, c.b1);
  wgmma128<1>(acc, c.a, c.b, c.k1, c.b1);
  wgmma128<1>(acc, c.a, c.b, ((int)p2_a((T + 1) % 5) - (int)p2_a(T % 5)) / 16 - 514, ((int)p2_b((T + 1) % 5) - (int)p2_b(T % 5)) / 16 - 384);
  wg_commit();
  if (T == 15) { if (c.wg == 0) bar_arrive(BAR_LAG, 256); }
  if (T <= 11) { wg_wait<1>(); release(c, T ? B_E2 + 8 * ((T + 4) % 5) : B_E1 + 8); }
}

template <int P> __device__ __forceinline__ void geglu_piece(uint32_t (&pk)[64], uint8_t* dst, float (&rs)[2]) {
  constexpr int cg = P >> 1, r = P & 1;
  pin<1>(rs + r);
#pragma unroll
  for (int i = 0; i < 4; i++) pin<1>(pk + 2 * (4 * cg + i) + r);
  const float r2 = rs[r] * rs[r], c1 = GELU_C1 * rs[r], c3 = GELU_C3 * r2 * rs[r], k = 0.25f * r2;
  uint32_t v[4];
#pragma unroll
  for (int i = 0; i < 4; i++) {
    const uint32_t g = pk[2 * (4 * cg + i) + r];
    v[i] = mul2(pack2(gelu_k(lo_f(g), c1, c3, k), gelu_k(hi_f(g), c1, c3, k)), pk[32 + 2 * (4 * cg + i) + r]);
  }
  stg128(dst + cg * 8192 + r * 512, v[0], v[1], v[2], v[3]);
}
__device__ __forceinline__ void geglu_tile(float (&acc)[128], uint32_t (&pk)[64], const Cons& c, int to, uint8_t* dst, int ev, float (&rs)[2]) {
  const int lane = lane_here();
  dst += (lane ^ (lane >> 3)) << 4;
  p1_loop(acc, c, 1, to, [&](int kb) {
    if (kb <= 4) {
      if (kb <= 2) { if (kb == 1) geglu_piece<0>(pk, dst, rs); else geglu_piece<1>(pk, dst, rs); }
      else { if (kb == 3) geglu_piece<2>(pk, dst, rs); else geglu_piece<3>(pk, dst, rs); }
    } else if (kb <= 8) {
      if (kb <= 6) { if (kb == 5) geglu_piece<4>(pk, dst, rs); else geglu_piece<5>(pk, dst, rs); }
      else { if (kb == 7) geglu_piece<6>(pk, dst, rs); else { geglu_piece<7>(pk, dst, rs); bar_arrive(ev, 288); } }
    }
  });
}

__device__ __forceinline__ void attn_tile(float (&acc)[128], uint32_t (&pk)[64], const Cons& c, int round, int warp, int m, unsigned bid, Scratch* gs, uint8_t* hdst, uint8_t* odst) {
  const int w = warp & 3;
  const uint32_t at = c.sb + OFF_X + c.wg * AT_WG;
  int lane = lane_here();
  hdst += (lane ^ (lane >> 3)) << 4;
  auto scatter = [&]() {
    const int lane = lane_here();
    const uint32_t swz = (lane ^ (lane >> 3)) << 4;
#pragma unroll
    for (int i = 0; i < 4; i++) {
      const int h = i & 1, r = i >> 1;
      sts128(at + AT_V + (2 * w + r) * 1024 + h * 512 + swz, make_uint4(pk[32 + 8 * h + r], pk[34 + 8 * h + r], pk[36 + 8 * h + r], pk[38 + 8 * h + r]));
    }
    if (w < 3) {
#pragma unroll
      for (int i = 0; i < 8; i++) asm volatile("st.shared.b32 [%0], %1;" ::"r"(at + AT_K + w * 1024 + i * 128 + lane * 4), "r"(pk[17 + 2 * i]) : "memory");
    } else {
      uint8_t* g = (uint8_t*)gs->halo + ((round * 128 + bid) * 2 + c.wg) * 2048;
#pragma unroll
      for (int i = 0; i < 8; i++) asm volatile("st.global.b32 [%0], %1;" ::"l"(g + i * 128 + lane * 4), "r"(pk[17 + 2 * i]) : "memory");
#pragma unroll
      for (int h = 0; h < 2; h++) stg128(g + 1024 + h * 512 + swz, pk[33 + 8 * h], pk[35 + 8 * h], pk[37 + 8 * h], pk[39 + 8 * h]);
      bar_arrive(BAR_EV + 2 + round, 96);
    }
    __syncwarp();
    if (lane == 0) mbar_arrive(c.sb + B_HALO + 8 * round);
    if (round) {
#pragma unroll
      for (int p = 0; p < 4; p++) {
        const int o = 32 + 8 * (p >> 1) + (p & 1);
        asm volatile("ld.global.cg.v4.b32 {%0,%1,%2,%3}, [%4];" : "=r"(pk[o]), "=r"(pk[o + 2]), "=r"(pk[o + 4]), "=r"(pk[o + 6]) : "l"(hdst + (p >> 1) * 8192 + (p & 1) * 512) : "memory");
      }
    }
  };
  auto gu_piece = [&](int p) {
    uint32_t v[4];
#pragma unroll
    for (int i = 0; i < 4; i++) {
      const int o = 8 * (p >> 1) + 2 * i + (p & 1);
      pin<1>(pk + 48 + o);
      const uint32_t g = pk[48 + o];
      v[i] = mul2(round ? pk[32 + o] : 0x3e803e80u, round ? g : pack2(gelu_k(lo_f(g), GELU_C1, GELU_C3, 1.0f), gelu_k(hi_f(g), GELU_C1, GELU_C3, 1.0f)));
    }
    stg128(hdst + (p >> 1) * 8192 + (p & 1) * 512, v[0], v[1], v[2], v[3]);
  };
  p1_step<1>(acc, c);
  scatter();
  p1_loop(acc, c, 2, 9, [&](int kb) {
    if (kb <= 4) { if (kb == 3) gu_piece(0); else if (kb == 4) gu_piece(1); }
    else if (kb == 5) gu_piece(2); else if (kb == 6) gu_piece(3);
  });
  const bool first = m == 0 && w == 0;
  uint32_t kl[16];
  mbar_spin(c.sb + B_HALO + 8 * round, 0, c.zero);
  lane = lane_here();
  {
    const uint32_t ka = at + lane * 4 + (w ? AT_K + (w - 1) * 1024 : (first ? AT_K : AT_REM + round * 2048));
#pragma unroll
    for (int i = 0; i < 8; i++) {
      asm volatile("ld.shared.b32 %0, [%1];" : "=r"(kl[2 * i]) : "r"(ka + i * 128) : "memory");
      kl[2 * i + 1] = pk[16 + 2 * i] | c.zero;
    }
  }
  float st[4][4];
  pin<16>(kl);
  bar_sync(BAR_MMA, 256);
  mbar_spin(c.sb + B_F1 + 8 * 1, 0, c.zero);
#pragma unroll
  for (int ks = 0; ks < 2; ks++) {
#pragma unroll
    for (int h = 0; h < 2; h++) {
      const int o = 8 * h + 4 * ks;
      if (ks == 0) { hmma<0>(st[2 * h], kl[o], kl[o + 1], kl[o + 2], kl[o + 3], pk[o], pk[o + 2]); hmma<0>(st[2 * h + 1], pk[16 + o], pk[17 + o], pk[18 + o], pk[19 + o], pk[o + 1], pk[o + 3]); }
      else { hmma<1>(st[2 * h], kl[o], kl[o + 1], kl[o + 2], kl[o + 3], pk[o], pk[o + 2]); hmma<1>(st[2 * h + 1], pk[16 + o], pk[17 + o], pk[18 + o], pk[19 + o], pk[o + 1], pk[o + 3]); }
    }
  }
  sched_fence(c.zero);
  bar_sync(BAR_MMA, 256);
  p1_step<9, false>(acc, c);
  sched_fence(c.zero);
  pin<16>(&st[0][0]);
  lane = lane_here();
  const int rho = lane >> 2, q = lane & 3;
  const bool le0 = 2 * q <= rho, le1 = 2 * q + 1 <= rho;
  uint32_t la[2], lb[2], mx[2];
#pragma unroll
  for (int h = 0; h < 2; h++) {
    uint32_t l[2];
#pragma unroll
    for (int r = 0; r < 2; r++) {
      const float (&t)[4] = st[2 * h + r];
      l[r] = movm(pack2(rho <= 2 * q ? t[2] : t[0], rho <= 2 * q + 1 ? t[3] : t[1]));
      l[r] = fma2(l[r], 0x3e353e35u, mul2(l[r], 0x379e379eu));
    }
    la[h] = __byte_perm(l[0], l[1], 0x5410); lb[h] = __byte_perm(l[0], l[1], 0x7632);
    if (first && !le0) la[h] = (la[h] & 0xffff0000u) | 0xce6eu;
    if (first && !le1) lb[h] = (lb[h] & 0xffff0000u) | 0xce6eu;
    mx[h] = max2(la[h], lb[h]);
  }
#pragma unroll
  for (int o = 1; o <= 2; o++) { mx[0] = max2(mx[0], __shfl_xor_sync(~0u, mx[0], o)); mx[1] = max2(mx[1], __shfl_xor_sync(~0u, mx[1], o)); }
  const float L2E = 1.4426950408889634f;
  float pr[2][4], z[4];
#pragma unroll
  for (int h = 0; h < 2; h++) {
    pr[h][0] = ex2f((lo_f(la[h]) - lo_f(mx[h])) * L2E); pr[h][1] = ex2f((lo_f(lb[h]) - lo_f(mx[h])) * L2E);
    pr[h][2] = ex2f((hi_f(la[h]) - hi_f(mx[h])) * L2E); pr[h][3] = ex2f((hi_f(lb[h]) - hi_f(mx[h])) * L2E);
    z[2 * h] = pr[h][0] + pr[h][1]; z[2 * h + 1] = pr[h][2] + pr[h][3];
  }
  p1_step<10>(acc, c);
#pragma unroll
  for (int o = 1; o <= 2; o++) {
#pragma unroll
    for (int i = 0; i < 4; i++) z[i] += __shfl_xor_sync(~0u, z[i], o);
  }
  const uint32_t LE = (le0 ? 0xffffu : 0u) | (le1 ? 0xffff0000u : 0u);
  uint32_t P[4][2];
  uint4 vt[4][2];
  {
    const uint32_t row = (lane & 7) * 64 + ((((lane >> 3) & 1) ^ ((lane & 7) >> 1)) << 4);
    const uint32_t v1 = at + AT_V + (2 * w + (lane >> 4)) * 1024 + row;
    const uint32_t v0 = (w || lane >= 16) ? v1 - 1024 : (first ? v1 : at + AT_REM + round * 2048 + 1024 + row);
#pragma unroll
    for (int i = 0; i < 4; i++) {
      const float rz = rcpf(z[i]);
      const uint32_t p = pack2(pr[i >> 1][2 * (i & 1)] * rz, pr[i >> 1][2 * (i & 1) + 1] * rz);
      P[i][0] = p & ~LE; P[i][1] = p & LE;
      const uint32_t a = ((i & 1) ? v1 : v0) + (i >> 1) * 512;
      vt[i][0] = ldsm_t(a); vt[i][1] = ldsm_t(a ^ 32);
    }
  }
  float ot[4][2][4];
  pin<8>(&P[0][0]);
  bar_sync(BAR_MMA, 256);
  mbar_spin(c.sb + B_F1 + 8 * 3, 0, c.zero);
#pragma unroll
  for (int i = 0; i < 8; i++) { const uint4& v = vt[i >> 1][i & 1]; hmma<0>(ot[i >> 1][i & 1], v.x, v.y, v.z, v.w, P[i >> 1][0], P[i >> 1][1]); }
  sched_fence(c.zero);
  bar_sync(BAR_MMA, 256);
  p1_step<11, false>(acc, c);
  sched_fence(c.zero);
  pin<32>(&ot[0][0][0]);
  lane = lane_here();
  odst += (lane ^ (lane >> 3)) << 4;
  auto o_piece = [&](int i) {
    stg128(odst + (i >> 1) * 8192 + (i & 1) * 512, movm(pack2(ot[i][0][0], ot[i][0][1])), movm(pack2(ot[i][0][2], ot[i][0][3])), movm(pack2(ot[i][1][0], ot[i][1][1])), movm(pack2(ot[i][1][2], ot[i][1][3])));
  };
  o_piece(0); o_piece(1);
  p1_step<12>(acc, c);
  o_piece(2); o_piece(3);
  if (round) bar_arrive(BAR_EV + 4, 288);
  p1_step<13>(acc, c);
}

__device__ __forceinline__ void ln_moments(const uint32_t* raw, float& c0, float& s, float& v) {
  c0 = lo_f(__shfl_sync(~0u, raw[0], 0));
  float ss[4] = {0.f, 0.f, 0.f, 0.f}, vv[4] = {0.f, 0.f, 0.f, 0.f};
#pragma unroll
  for (int i = 0; i < 16; i++) {
    const float a = lo_f(raw[i]) - c0, b = hi_f(raw[i]) - c0;
    ss[(2 * i) & 3] += a; ss[(2 * i + 1) & 3] += b;
    vv[(2 * i) & 3] = fmaf(a, a, vv[(2 * i) & 3]); vv[(2 * i + 1) & 3] = fmaf(b, b, vv[(2 * i + 1) & 3]);
  }
  s = (ss[0] + ss[1]) + (ss[2] + ss[3]); v = (vv[0] + vv[1]) + (vv[2] + vv[3]);
}
__device__ __forceinline__ void ln_reduce(float& s, float& v) {
#pragma unroll
  for (int o = 16; o; o >>= 1) { s += __shfl_xor_sync(~0u, s, o); v += __shfl_xor_sync(~0u, v, o); }
}
__device__ __forceinline__ uint32_t ln_finish(float c0, float s, float v) {
  s *= 1.0f / DM;
  float sd;
  asm("sqrt.approx.ftz.f32 %0, %1;" : "=f"(sd) : "f"(bf16r(bf16r(fmaxf(fmaf(v, 1.0f / DM, -s * s), 0.f)) + 1e-5f)));
  return pack2(c0 + s, sd);
}
__device__ __forceinline__ void ln_store(const uint32_t* raw, uint32_t st, uint4* dst) {
  const uint32_t m2 = __byte_perm(st, st, 0x1010);
  const float rinv = rcpf(hi_f(st));
  const uint32_t rh = pack2(rinv, rinv), rl = pack2(rinv - hi_f(rh), rinv - hi_f(rh));
#pragma unroll
  for (int c = 0; c < 4; c++) {
    uint32_t v[4];
#pragma unroll
    for (int i = 0; i < 4; i++) { const uint32_t t = sub2(raw[4 * c + i], m2); v[i] = fma2(t, rh, mul2(t, rl)); }
    stg128(dst + 32 * c, v[0], v[1], v[2], v[3]);
  }
}
__device__ __forceinline__ void col_sums(uint32_t tile, ulonglong2* part, uint32_t tag) {
  const int lane = threadIdx.x & 31;
  float cs[8] = {0, 0, 0, 0, 0, 0, 0, 0};
  uint32_t base = tile + ((lane >> 3) & 1) * 8192 + (lane >> 4) * 4096 + ((lane & 7) << 4);
#pragma unroll 1
  for (int k0 = 0; k0 < 8; k0++, base = (base ^ ((k0 ^ (k0 - 1)) << 4)) + 128) {
    uint4 v[4];
#pragma unroll
    for (int k = 0; k < 4; k++) v[k] = lds128(base + k * 1024);
#pragma unroll
    for (int k = 0; k < 4; k++) {
      cs[0] += lo_f(v[k].x); cs[1] += hi_f(v[k].x); cs[2] += lo_f(v[k].y); cs[3] += hi_f(v[k].y);
      cs[4] += lo_f(v[k].z); cs[5] += hi_f(v[k].z); cs[6] += lo_f(v[k].w); cs[7] += hi_f(v[k].w);
    }
  }
  const bool up = lane >= 16;
#pragma unroll
  for (int i = 0; i < 2; i++) {
    const float a = (up ? cs[4 + 2 * i] : cs[2 * i]) + __shfl_xor_sync(~0u, up ? cs[2 * i] : cs[4 + 2 * i], 16);
    const float b = (up ? cs[5 + 2 * i] : cs[1 + 2 * i]) + __shfl_xor_sync(~0u, up ? cs[1 + 2 * i] : cs[5 + 2 * i], 16);
    asm volatile("{\n.reg .b64 a, b;\nmov.b64 a, {%1, %3};\nmov.b64 b, {%2, %3};\nst.relaxed.gpu.global.v2.b64 [%0], {a, b};\n}"
                 ::"l"(part + 32 * (i + (up ? 2 : 0)) + (lane & 15)), "r"(__float_as_uint(a)), "r"(__float_as_uint(b)), "r"(tag) : "memory");
  }
  asm volatile("fence.proxy.async.shared::cta;" ::: "memory");
}

__global__ void __cluster_dims__(2, 1, 1) __launch_bounds__(384, 1)
fused_kernel(const uint4* __restrict__ x, const uint4* __restrict__ wgate, const uint4* __restrict__ wup, Scratch* gs, const __grid_constant__ Maps mp) {
  extern __shared__ __align__(1024) uint8_t smem_raw[];
  const uint32_t sb = (uint32_t)__cvta_generic_to_shared(smem_raw);
  const unsigned bid = role_id();
  if (threadIdx.x == 352) TS(63);
  if (threadIdx.x < 256 && bid < NMAIN) {
    const uint32_t r = threadIdx.x >> 3, ch = threadIdx.x & 7;
    const uint32_t d = sb + r * 128 + ((ch ^ (r & 7)) << 4);
    const uint8_t* xa = (const uint8_t*)x + ((bid & 15) * 262144 + r * 4096 + ch * 16);
    const uint32_t wo = r * (DFF * 2) + (bid >> 4) * 256 + ch * 16;
    const uint8_t *wa = (const uint8_t*)wgate + wo, *wb = (const uint8_t*)wup + wo;
#pragma unroll
    for (int i = 0; i < 12; i++) {
      const int h = i >= 8;
      const uint8_t* src = (i >> 2) == 1 ? xa + (i & 1) * 131072 + ((i >> 1) & 1) * 2048 : ((i & 2) ? wb : wa) + h * 32 * (DFF * 2) + (i & 1) * 128;
      asm volatile("cp.async.cg.shared.global [%0], [%1], 16;" ::"r"(d + ((i >> 2) == 1 ? OFF_A + (i & 3) * 4096 : (i & 3) * 8192 + h * 4096)), "l"(src) : "memory");
    }
    if (threadIdx.x == 0) TS(23);
  }
  const int warp = __shfl_sync(~0u, threadIdx.x >> 5, 0), lane = threadIdx.x & 31;
  const int m = bid & 15, j = bid >> 4, rank = bid & 1;
  const int m2 = bid >> 3, j2 = bid & 7;
  const bool helper = bid >= NMAIN;
  if (warp >= 8) {
    asm volatile("setmaxnreg.dec.sync.aligned.u32 40;");
    if (warp == 8) {
      if (elect_one()) {
        asm volatile("prefetch.tensormap [%0];\nprefetch.tensormap [%1];\nprefetch.tensormap [%2];" ::"l"(&mp.x), "l"(&mp.wg), "l"(&mp.wu) : "memory");
        for (int s = 0; s < 4; s++) mbar_init(sb + B_F1 + 8 * s, 1);
        if (!helper) mbar_arrive(sb + B_F1);
        asm volatile("fence.mbarrier_init.release.cluster;" ::: "memory");
      }
      __syncwarp();
    } else if (warp == 9) {
      if (elect_one()) {
        if ((sb & 0xffffff) != SM_BASE) asm volatile("trap;");
        for (uint32_t b = B_E1; b < B_F2; b += 8) mbar_init(sb + b, 4);
        for (uint32_t b = B_F2; b < B_AUX; b += 8) mbar_init(sb + b, 1);
        for (uint32_t b = B_EX; b < B_AUX; b += 8) mbar_expect_tx(sb + b, 8192);
        mbar_init(sb + B_AUX, 8); mbar_init(sb + B_HALO, 9); mbar_init(sb + B_HALO + 8, 9);
        asm volatile("st.shared.b32 [%0], %1;" ::"r"(sb + OFF_EPOCH + 4), "r"(bid) : "memory");
        asm volatile("fence.mbarrier_init.release.cluster;" ::: "memory");
      }
      __syncwarp();
    }
    asm volatile("barrier.cluster.arrive.relaxed.aligned;" ::: "memory");
    if (warp == 8 && !helper) {
      if (elect_one()) {
        TS(0); TG(51);
#pragma unroll 1
        for (int kb = 1; kb < 4; kb++) {
          const uint32_t sa = sb + OFF_A + kb * 16384, sw = sb + kb * 32768, fb = sb + B_F1 + 8 * kb;
          mbar_expect_tx(fb, P1_BYTES);
          tma3d(sa, &mp.x, fb, kb * 64, m * 64, 0, EVICT_NORMAL);
          tma2d(sw, &mp.wg, fb, j * 128, kb * 64, EVICT_NORMAL); tma2d(sw + 16384, &mp.wu, fb, j * 128, kb * 64, EVICT_NORMAL);
          tma2d(sw + 8192, &mp.wg, fb, j * 128 + 64, kb * 64, EVICT_NORMAL); tma2d(sw + 24576, &mp.wu, fb, j * 128 + 64, kb * 64, EVICT_NORMAL);
        }
        TS(7);
      }
      __syncwarp();
    }
    asm volatile("barrier.cluster.wait.aligned;" ::: "memory");
    if (helper) {
      if (warp == 8) {
        unsigned e = 0;
        if (elect_one()) {
#pragma unroll 1
          for (int i = 0; i < 16; i++) {
            const uint32_t fb = sb + B_F1 + 8 * (i >> 2);
            if (!(i & 3)) mbar_expect_tx(fb, P1_BYTES);
            tma5d(sb + i * 8192, &mp.wd, fb, (bid - NMAIN) * 256 + (i & 3) * 64, (i >> 2) * 2, EVICT_FIRST);
          }
        }
        if (lane == 0) { unsigned* ep = &gs->epoch[bid * 2]; e = *ep + 1; *ep = e; }
        e = __shfl_sync(~0u, e, 0);
        if (lane < 16) flag_wait(&gs->flags[(FL_H + lane * 4) * 32], e * 8u);
        __syncwarp();
        if (elect_one()) {
          fence_async();
          TS(0);
#pragma unroll 1
          for (int i = 0; i < 64; i++) {
            const uint32_t fb = sb + B_F1 + 8 * (i & 3);
            if (i >= 4) { mbar_wait(sb + B_E1 + 8 * (i & 3), ~(i >> 2) & 1); mbar_expect_tx(fb, 16384); }
            bulk_load(sb + OFF_A + (i & 3) * 16384, gs->h + ((i >> 2) * 56 + (i & 3)) * 1024, 16384, fb, EVICT_NORMAL);
          }
        }
      } else if (warp == 9) {
#pragma unroll 1
        for (int t = 0; t < 16; t++) {
          bar_sync(BAR_EV + (t & 1), 288);
          if (lane == 0) { flag_add(&gs->flags[(FL_P + t) * 32]); TS(64 + t); }
          __syncwarp();
        }
      }
    } else if (warp == 8) {
      if (elect_one()) {
        uint32_t par = 0;

        auto x_load = [&]() {
          mbar_expect_tx(sb + B_XT, 32768);
          tma3d(sb + OFF_X, &mp.x, sb + B_XT, j2 * 128, m2 * 64, 0, EVICT_FIRST); tma3d(sb + OFF_X + 16384, &mp.x, sb + B_XT, j2 * 128 + 64, m2 * 64, 0, EVICT_FIRST);
        };
        auto w_tile = [&](int R, const CUtensorMap*& mb0, const CUtensorMap*& mb1, int& n0, int& n1) {
          if (R == 1 || R == 2) {
            mb0 = &mp.wqkv; n0 = 64 * (j + 8 * (R - 1)) + rank * 2048;
            mb1 = rank ? (R == 1 ? &mp.wg : &mp.wu) : &mp.wqkv; n1 = rank ? 1024 + 64 * j : n0 + 1024;
          } else {
            mb0 = mb1 = rank ? &mp.wu : &mp.wg;
            n0 = 128 * j + (R ? 1024 * R - 1536 : 0); n1 = n0 + 64;
          }
        };
        for (int R = 0; R < 5; R++) {
          const CUtensorMap *mb0, *mb1;
          int n0, n1;
          w_tile(R, mb0, mb1, n0, n1);
#pragma unroll 1
          for (int kb = R ? 0 : 4; kb < 16; kb++) {
            if (R == 0 && kb == 14) { asm volatile("prefetch.tensormap [%0];\nprefetch.tensormap [%1];" ::"l"(&mp.xn), "l"(&mp.wqkv) : "memory"); }
            if (R == 4 && kb == 2) { asm volatile("prefetch.tensormap [%0];\nprefetch.tensormap [%1];\nprefetch.tensormap [%2];" ::"l"(&mp.wd), "l"(&mp.wo), "l"(&mp.out) : "memory"); }
            if (R == 0 && kb == CS_KB) {
#pragma unroll 1
              for (int h = 0; h < 2; h++) {
                const uint32_t cb = sb + B_CS + 8 * h, d = sb + OFF_X + 16384 * h;
                mbar_expect_tx(cb, 16384);
                tma2d(d, h ? &mp.wu : &mp.wg, cb, n0, m * 64, EVICT_NORMAL); tma2d(d + 8192, h ? &mp.wu : &mp.wg, cb, n1, m * 64, EVICT_NORMAL);
              }
            }
            const int st = kb & 3;
            const uint32_t sa = sb + OFF_A + st * 16384, sw = sb + st * 32768, fb = sb + B_F1 + 8 * st;
            mbar_wait(sb + B_E1 + 8 * st, par);
            if (R * 16 + kb >= 4) REL_TS(R * 16 + kb - 4);
            mbar_expect_tx(fb, P1_BYTES);
            tma2d_mc(sw + rank * 16384, mb0, fb, n0, kb * 64, EVICT_FIRST);
            tma2d_mc(sw + 8192 + rank * 16384, mb1, fb, n1, kb * 64, EVICT_FIRST);
            if (R == 0) {
              tma3d(sa, &mp.x, fb, kb * 64, m * 64, 0, EVICT_NORMAL);
            } else {
              if (R == 1 && kb == 0) { mbar_wait(sb + B_DEP, 0); TS(1); }
              tma2d(sa, &mp.xn, fb, kb * 64, m * 128, R == 4 ? EVICT_FIRST : EVICT_NORMAL);
            }
            if (R == 4 && kb == 4 + j2) x_load();
            if (st == 3) par ^= 1;
          }
        }
#pragma unroll 1
        for (int i = 0; i < 26; i++) {
          const int st = i & 3, kb = 2 * i + 4 + rank;
          const uint32_t sa = sb + OFF_A + st * 16384, sw = sb + st * 32768, fb = sb + B_F1 + 8 * st;
          mbar_wait(sb + B_E1 + 8 * st, par);
          REL_TS(76 + i);
          mbar_expect_tx(fb, P1_BYTES);
          tma5d(sw, &mp.wd, fb, j2 * 128, kb * 2, EVICT_FIRST); tma5d(sw + 8192, &mp.wd, fb, j2 * 128 + 64, kb * 2, EVICT_FIRST);
          tma5d(sw + 16384, &mp.wd, fb, (j2 ^ 1) * 128, kb * 2, EVICT_FIRST); tma5d(sw + 24576, &mp.wd, fb, (j2 ^ 1) * 128 + 64, kb * 2, EVICT_FIRST);
          if (i == 0 || i == 6 || i == 10 || i == 18) { mbar_wait(sb + B_DEP + 8 * (1 + ((i + 6) >> 3)), 0); }
          bulk_load(sa, gs->h + (m2 * 56 + kb) * 1024, 16384, fb, EVICT_FIRST);
          if (st == 3) par ^= 1;
        }
        int st = 0; uint32_t par2 = 1;
#pragma unroll 1
        for (int t = 0; t < 16; t++) {
          const uint32_t sa = sb + p2_a(st), sw = sb + p2_b(st), fb = sb + B_F2 + 8 * st;
          if (t < 5) mbar_wait(sb + B_E1 + 8 * (((2 * t + 1) / 3 + 2) & 3), t < 3); else mbar_wait(sb + B_E2 + 8 * st, par2);
          REL_TS(102 + t);
          mbar_expect_tx(fb, P2_BYTES);
          bulk_load_mc(sa + rank * 8192, gs->o + (m2 * 16 + t) * 1024 + rank * 512, 8192, fb, EVICT_FIRST);
          tma2d(sw, &mp.wo, fb, j2 * 128, t * 64, EVICT_FIRST); tma2d(sw + 8192, &mp.wo, fb, j2 * 128 + 64, t * 64, EVICT_FIRST);
          if (++st == 5) { st = 0; par2 ^= 1; }
        }
      }
    } else if (warp == 9) {
#pragma unroll 1
      for (int e = 0; e < 7; e++) {
        const bool halo = e == 2 || e == 3;
        bar_sync(BAR_EV + e, halo ? 96 : 288);
        if (lane == 0) {
          const int f = e == 0 ? FL_XN + m : (halo ? FL_HALO + (e - 2) * 128 + bid : FL_H + m * 4 + (e == 1 ? 0 : e - 3));
          TS(10 + 2 * e); TG(52 + e);
          flag_add(&gs->flags[f * 32]);
          if (e < 6) TS(11 + 2 * e);
        }
        __syncwarp();
      }
      unsigned other;
      asm volatile("ld.shared::cluster.b32 %0, [%1];" : "=r"(other) : "r"(mapa(sb + OFF_EPOCH + 4, rank ^ 1)) : "memory");
      if (other != (bid ^ 1)) asm volatile("trap;");
      mbar_wait(sb + B_DONE, 0);
    } else {
      unsigned e = 0;
      if (lane == 0) {
        unsigned* ep = &gs->epoch[bid * 2 + warp - 10];
        e = *ep + 1; *ep = e;
        if (warp == 10) { asm volatile("st.shared.b32 [%0], %1;" ::"r"(sb + OFF_EPOCH), "r"(e) : "memory"); mbar_arrive(sb + B_EP); }
      }
      e = __shfl_sync(~0u, e, 0);
      mbar_wait(sb + B_CS + 8 * (warp - 10), 0);
      if (lane == 0 && warp == 11) TS(6);
      col_sums(sb + OFF_X + (warp - 10) * 16384, gs->cspart + (j * 16 + m) * 128 + (warp - 10) * 16, e);
      if (lane == 0 && warp == 11) TS(9);
      if (warp == 10) {
        if (lane == 0) {
#pragma unroll 1
          for (int g = 0; g < 6; g++) {
            flag_wait(&gs->flags[(g == 5 ? FL_P + m2 : (g ? FL_H + m2 * 4 + g - 1 : FL_XN + m)) * 32], e * (g == 5 ? 4u : 8u));
            fence_async();
            mbar_arrive(sb + B_DEP + 8 * g);
            if (g == 0) TS(8);
          }
        }
      } else
      if (elect_one()) {
#pragma unroll 1
        for (int r = 0; r < 2; r++) {
          const uint32_t hb = sb + B_HALO + 8 * r;
          if (r) mbar_wait(sb + B_HALO, 0);
          if (m) {
            flag_wait(&gs->flags[(FL_HALO + r * 128 + bid - 1) * 32], e);
            fence_async();
            mbar_expect_tx(hb, 4096);
            for (int g = 0; g < 2; g++) bulk_load(sb + OFF_X + g * AT_WG + AT_REM + r * 2048, gs->halo + ((r * 128 + bid - 1) * 2 + g) * 128, 2048, hb, EVICT_FIRST);
          } else {
            mbar_arrive(hb);
          }
          TS(34 + r);
        }
      }
    }
  } else {
    asm volatile("barrier.cluster.arrive.relaxed.aligned;" ::: "memory");
    asm volatile("setmaxnreg.inc.sync.aligned.u32 232;");
    const int wg = warp >> 2, w = warp & 3;
    Cons c;
    c.sb = sb; c.wg = wg; c.zero = warp >> 8;
    c.a = 0x4000004000010000ull + ((SM_BASE + OFF_A + wg * 8192) >> 4); c.k1 = 2 + c.zero; c.k2 = 2; c.k4 = 1024 - 6; c.k4w = -3072 - 6; c.b1 = 128 + c.zero;
    c.b = 0x4000004000000000ull + DB_LO + c.zero;
    c.rel = mapa(sb, threadIdx.x & 1);
    c.do_rel = (threadIdx.x & 127) < 2;
    float acc[128];
    uint32_t pk[64];
    float rs[2];
    const int q = lane & 3;

    if (helper) {
      asm volatile("barrier.cluster.wait.aligned;" ::: "memory");
      c.a = 0x8000002000010000ull + ((SM_BASE + OFF_A + wg * 4096) >> 4); c.k2 = 510; c.k4 = 1024 - 514; c.k4w = -3072 - 514;
      c.rel = sb;
      uint4* dst = gs->dpart + (bid - NMAIN) * 4096 + threadIdx.x;
      auto put = [&](int p) {
#pragma unroll
        for (int i = 4 * p; i < 4 * p + 4; i++) stg128(dst + i * 256, pk[4 * i], pk[4 * i + 1], pk[4 * i + 2], pk[4 * i + 3]);
      };
#pragma unroll 1
      for (int t = 0; t < 16; t++) {
        p1_issue<0, 0>(acc, c, t & 1);
        if (t) put(0);
        p1_issue<1, 1>(acc, c, t & 1); wg_wait<1>(); release(c, B_E1);
        if (t) put(1);
        p1_issue<2, 1>(acc, c, t & 1); wg_wait<1>(); release(c, B_E1 + 8);
        if (t) put(2);
        if (wg == 1) { wg_wait<0>(); release(c, B_E1 + 16); bar_sync(BAR_LAG, 256); }
        p1_issue<3, 1>(acc, c, t & 1);
        if (wg == 0) bar_arrive(BAR_LAG, 256);
        if (t) { put(3); bar_arrive(BAR_EV + (~t & 1), 288); dst += 8 * 2048; }
        wg_wait<1>(); if (wg == 0) release(c, B_E1 + 16);
        wg_wait<0>(); release(c, B_E1 + 24);
#pragma unroll
        for (int i = 0; i < 64; i++) pk[i] = pack2(acc[2 * i], acc[2 * i + 1]);
      }
      put(0); put(1); put(2); put(3);
      bar_arrive(BAR_EV + 1, 288);
      return;
    }
    {
      const int prow = 16 * j + 2 * warp;
      const uint4* xr = x + (size_t)(128 * m + 2 * (prow & 63) + (prow >> 6)) * 128 + lane;
      uint4* xo = gs->xn + (size_t)(128 * m + prow) * 128 + lane;
      float c0[2], mo[4];
      uint32_t st[2];
      uint32_t e;
      asm volatile("" : "+l"(xr), "+l"(xo));
      asm volatile("cp.async.wait_all;\nfence.proxy.async.shared::cta;" ::: "memory");
      bar_sync(BAR_MMA, 256);
      if (threadIdx.x == 0) TS(39);
      p1_step<0, false>(acc, c);
      asm volatile("barrier.cluster.wait.aligned;" ::: "memory");
      unsigned long long part[18];
      auto gather = [&](int from, int to) {
        const int lane = lane_here();
        const unsigned long long* cp = (const unsigned long long*)gs->cspart + j * 4096 + warp * 32 + lane;
        const unsigned long long* sp = gs->stats + 128 * m + warp * 16 + (lane >> 2);
#pragma unroll
        for (int i = from; i < to; i++) asm volatile("ld.relaxed.gpu.global.b64 %0, [%1];" : "=l"(part[i]) : "l"(i < 16 ? cp + i * 256 : sp + (i - 16) * 8) : "memory");
      };
      auto row_load = [&](int r) {
#pragma unroll
        for (int i = 4 * r; i < 4 * r + 4; i++)
          asm volatile("ld.global.nc.L1::no_allocate.v4.b32 {%0,%1,%2,%3}, [%4];" : "=r"(pk[4 * i]), "=r"(pk[4 * i + 1]), "=r"(pk[4 * i + 2]), "=r"(pk[4 * i + 3]) : "l"(xr + r * 256 + (i & 3) * 32));
      };
      p1_step<1>(acc, c); row_load(0);
      p1_step<2>(acc, c); row_load(1);
      p1_loop(acc, c, 3, LN_KB + 1, [](int) {});
      pin<16>(pk); ln_moments(pk, c0[0], mo[0], mo[1]); pin<2>(mo);
      p1_step<LN_KB + 1>(acc, c);
      sched_fence(c.zero);
      pin<16>(pk + 16); ln_moments(pk + 16, c0[1], mo[2], mo[3]); ln_reduce(mo[0], mo[1]); pin<4>(mo);
      p1_step<LN_KB + 2>(acc, c);
      mbar_spin(sb + B_EP, 0, c.zero);
      asm volatile("ld.shared.b32 %0, [%1];" : "=r"(e) : "r"(sb + OFF_EPOCH) : "memory");
      pin<2>(mo); st[0] = ln_finish(c0[0], mo[0], mo[1]); ln_reduce(mo[2], mo[3]); pin<1>(st); pin<2>(mo + 2);
      p1_step<LN_KB + 3>(acc, c);
      sched_fence(c.zero);
      pin<1>(st); pin<2>(mo + 2);
      st[1] = ln_finish(c0[1], mo[2], mo[3]);
      ln_store(pk, st[0], xo);
      if (lane == 0)
        asm volatile("{\n.reg .b64 a, b;\nmov.b64 a, {%1, %3};\nmov.b64 b, {%2, %3};\nst.relaxed.gpu.global.v2.b64 [%0], {a, b};\n}" ::"l"(gs->stats + 128 * m + prow), "r"(st[0]), "r"(st[1]), "r"(e) : "memory");
      p1_step<LN_KB + 4>(acc, c);
      sched_fence(c.zero);
      pin<1>(st + 1);
      ln_store(pk + 16, st[1], xo + 128);
      bar_arrive(BAR_EV, 288);
      p1_loop(acc, c, LN_KB + 5, 13, [](int) {});
      gather(0, 9);
      p1_step<13>(acc, c);
      gather(9, 18);
      p1_step<14>(acc, c);
      auto validate = [&]() {
        float csum;
        for (int tries = 0;; tries++) {
          uint32_t bad = 0;
          csum = 0.f;
#pragma unroll
          for (int i = 0; i < 18; i++) { bad |= (uint32_t)(part[i] >> 32) ^ e; if (i < 16) csum += __uint_as_float((uint32_t)part[i]); }
          if (!__any_sync(~0u, bad != 0) || tries > (1 << 20)) break;
          gather(0, 18);
        }
        const float hi = bf16r(csum), mid = bf16r(csum - hi);
        sts128(sb + OFF_CS + ((threadIdx.x & 62) * 4 + (threadIdx.x >> 6) * 2 + (threadIdx.x & 1)) * 16, make_uint4(pack2(hi, mid), pack2(csum - hi - mid, 0.f), 0, 0));
        asm volatile("fence.proxy.async.shared::cta;" ::: "memory");
        __syncwarp();
        if (lane == 0) mbar_arrive(sb + B_AUX);
      };
#pragma unroll 1
      for (int ph = 1; ph >= 0; ph--) {
        if (wg == ph) validate();
        if (ph) {
          if (wg == 1) { wg_wait<0>(); release(c, B_E1 + 16); bar_sync(BAR_LAG, 256); }
          p1_issue<3, 1>(acc, c, 1);
        }
      }
      const uint32_t keep = q == 0 ? 0xffffffffu : (q == 1 ? 0xffffu : 0u);
      const uint32_t a0 = (__byte_perm((uint32_t)part[16], 0, 0x1010) ^ 0x80008000u) & keep, a1 = (__byte_perm((uint32_t)part[17], 0, 0x1010) ^ 0x80008000u) & keep;
      mbar_spin(sb + B_AUX, 0, c.zero);
      wg_fence();
      wgmma256_rs(acc, a0, a1, 0, 0, (SM_BASE + OFF_CS) >> 4);
      wg_commit();
      if (wg == 0) bar_arrive(BAR_LAG, 256);
      rs[0] = rcpf(hi_f((uint32_t)part[16])); rs[1] = rcpf(hi_f((uint32_t)part[17]));
      wg_wait<2>(); if (wg == 0) release(c, B_E1 + 16);
      wg_wait<0>(); release(c, B_E1 + 24);
    }
#pragma unroll 1
    for (int R = 1;; R++) {
#pragma unroll
      for (int i = 0; i < 64; i++) pk[i] = pack2(acc[2 * i], acc[2 * i + 1]);
      uint8_t* hb = (uint8_t*)gs->h + (size_t)m * 56 * 16384 + warp * 1024;
      if (R == 5) { c.a = 0x8000002000010000ull + ((SM_BASE + OFF_A + wg * 4096) >> 4); c.k2 = 510; c.k4 = 1024 - 514; c.k4w = -3072 - 514; }
      p1_step<0>(acc, c);
      if (R == 2 || R == 3) {
        attn_tile(acc, pk, c, R - 2, warp, m, bid, gs, hb + (16 + j) * 16384, (uint8_t*)gs->o + (m * 16 + j + 8 * (R - 2)) * 16384 + warp * 1024);
      } else {
        geglu_tile(acc, pk, c, R == 5 ? 24 : 14, hb + (2 * j + (R == 1 ? 0 : 16 * R - 40)) * 16384, BAR_EV + (R == 1 ? 1 : R + 1), rs);
        rs[0] = rs[1] = 1.0f;
        if (R == 5) break;
      }
      p1_step<14>(acc, c); p1_step<15>(acc, c);
    }
    auto fetch = [&](int p) {
      asm volatile("ld.global.cg.v4.b32 {%0,%1,%2,%3}, [%4];" : "=r"(pk[4 * p]), "=r"(pk[4 * p + 1]), "=r"(pk[4 * p + 2]), "=r"(pk[4 * p + 3]) : "l"(gs->dpart + bid * 2048 + p * 256 + threadIdx.x) : "memory");
    };
    mbar_spin(sb + B_DEP + 40, 0, c.zero);
    fetch(0); fetch(1); fetch(2);
    p1_step<8>(acc, c);
    fetch(3); fetch(4); fetch(5);
    p1_step<9>(acc, c);
    fetch(6); fetch(7);
    {
      float accs[64];
      const uint32_t peer = mapa(sb, rank ^ 1);
      auto send_piece = [&](int p) {
        asm volatile("st.async.weak.shared::cluster.mbarrier::complete_tx::bytes.v4.b32 [%0], {%1,%2,%3,%4}, [%5];" ::"r"(peer + OFF_LAND + p * 4096 + threadIdx.x * 16),
                     "r"(pack2(acc[64 + 8 * p], acc[65 + 8 * p])), "r"(pack2(acc[66 + 8 * p], acc[67 + 8 * p])), "r"(pack2(acc[68 + 8 * p], acc[69 + 8 * p])), "r"(pack2(acc[70 + 8 * p], acc[71 + 8 * p])),
                     "r"(peer + B_EX + 16 * wg + 8 * (p >> 2)) : "memory");
      };
      auto silu_piece = [&](int p) {
        const uint4 r = lds128(sb + OFF_LAND + p * 4096 + threadIdx.x * 16);
        const uint32_t rr[4] = {add2(r.x, pk[4 * p]), add2(r.y, pk[4 * p + 1]), add2(r.z, pk[4 * p + 2]), add2(r.w, pk[4 * p + 3])};
#pragma unroll
        for (int i = 0; i < 4; i++) {
          const float a = acc[8 * p + 2 * i] + lo_f(rr[i]), b = acc[8 * p + 2 * i + 1] + hi_f(rr[i]);
          pk[4 * p + i] = pack2(silu_half(a), silu_half(b));
        }
        pin<4>(pk + 4 * p);
      };
      const uint32_t xa = sb + OFF_X + (warp * 16 + (lane & 7)) * 128 + (((lane >> 3) ^ (lane & 7)) << 4);
      auto x_addr = [&](int i) { return (xa ^ ((i & 1) << 6)) + ((i >> 1) & 1) * 1024 + (i >> 2) * 16384; };
      auto x_piece = [&](int i) { const uint4 v = ldsm(x_addr(i)); pk[32 + 4 * i] = v.x; pk[33 + 4 * i] = v.y; pk[34 + 4 * i] = v.z; pk[35 + 4 * i] = v.w; };
      p2_step<0>(accs, c);
      p2_step<1>(accs, c);
      mbar_spin(sb + B_E1 + 8, 0, c.zero);
      send_piece(0); send_piece(1);
      p2_step<2>(accs, c); sched_fence(c.zero); send_piece(2); send_piece(3);
      p2_step<3>(accs, c); sched_fence(c.zero); send_piece(4); send_piece(5);
      p2_step<4>(accs, c); mbar_spin(sb + B_XT, 0, c.zero); send_piece(6); send_piece(7);
      p2_step<5>(accs, c); mbar_spin(sb + B_EX + 16 * wg, 0, c.zero); silu_piece(0); x_piece(0);
      p2_step<6>(accs, c); sched_fence(c.zero); silu_piece(1); x_piece(1);
      p2_step<7>(accs, c); sched_fence(c.zero); silu_piece(2); x_piece(2);
      p2_step<8>(accs, c); sched_fence(c.zero); silu_piece(3); x_piece(3);
      p2_step<9>(accs, c); mbar_spin(sb + B_EX + 16 * wg + 8, 0, c.zero); silu_piece(4); x_piece(4);
      p2_step<10>(accs, c); sched_fence(c.zero); silu_piece(5); x_piece(5);
      p2_step<11>(accs, c); sched_fence(c.zero); silu_piece(6); x_piece(6); x_piece(7);
      auto out_half = [&](const float* a, int h) {
#pragma unroll
        for (int i = 4 * h; i < 4 * h + 4; i++) {
          uint32_t v[4];
#pragma unroll
          for (int k = 0; k < 4; k++) { const int o = 2 * (4 * (i & 1) + k) + ((i >> 1) & 1); v[k] = fma2(pack2(a[2 * o], a[2 * o + 1]), pk[16 * h + o], pk[32 + 4 * i + k]); }
          asm volatile("stmatrix.sync.aligned.m8n8.x4.shared.b16 [%0], {%1,%2,%3,%4};" ::"r"(x_addr(i)), "r"(v[0]), "r"(v[1]), "r"(v[2]), "r"(v[3]) : "memory");
          if (i & 1) {
            asm volatile("fence.proxy.async.shared::cta;" ::: "memory");
            __syncwarp();
            if (elect_one()) tma3d_store(&mp.out, sb + OFF_X + h * 16384 + warp * 2048 + (i & 2) * 512, j2 * 128 + h * 64, m2 * 64 + w * 16 + (i & 2) * 4, wg);
          }
        }
      };
      if (wg == 1) silu_piece(7);
      p2_step<12>(accs, c); p2_step<13>(accs, c); p2_step<14>(accs, c); p2_step<15>(accs, c);
      if (c.do_rel) mbar_arrive(sb + B_DONE);
      if (wg == 0) silu_piece(7);
      wg_wait<0>();
      out_half(accs, 0); out_half(accs + 32, 1);
      if (elect_one()) { asm volatile("cp.async.bulk.commit_group;\ncp.async.bulk.wait_group.read 0;" ::: "memory"); }
      if ((threadIdx.x & 127) == 0) { TS(33 + wg * 16); if (wg) { TG(59); unsigned id; asm volatile("mov.u32 %0, %%smid;" : "=r"(id)); TSV(60, id); } }
    }
  }
}

typedef CUresult (*EncodeFn)(CUtensorMap*, CUtensorMapDataType, cuuint32_t, void*, const cuuint64_t*, const cuuint64_t*, const cuuint32_t*, const cuuint32_t*,
                             CUtensorMapInterleave, CUtensorMapSwizzle, CUtensorMapL2promotion, CUtensorMapFloatOOBfill);

void encode(EncodeFn fn, CUtensorMap* tm, const void* p, int rank, const cuuint64_t* dims, const cuuint64_t* strides, const cuuint32_t* box) {
  const cuuint32_t es[5] = {1, 1, 1, 1, 1};
  fn(tm, CU_TENSOR_MAP_DATA_TYPE_BFLOAT16, rank, const_cast<void*>(p), dims, strides, box, es, CU_TENSOR_MAP_INTERLEAVE_NONE, CU_TENSOR_MAP_SWIZZLE_128B,
     CU_TENSOR_MAP_L2_PROMOTION_L2_128B, CU_TENSOR_MAP_FLOAT_OOB_FILL_NONE);
}

}

extern "C" void kernel_launch(void* const* d_in, const int* in_sizes, int n_in, void* d_out, int out_size) {
  (void)in_sizes; (void)n_in; (void)out_size;
  static EncodeFn fn = nullptr;
  static Scratch* gs = nullptr;
  if (!fn) {
    void* p = nullptr;
    cudaDriverEntryPointQueryResult qr;
    cudaGetDriverEntryPoint("cuTensorMapEncodeTiled", &p, cudaEnableDefault, &qr);
    fn = (EncodeFn)p;
    cudaGetSymbolAddress((void**)&gs, g_scratch);
    cudaFuncSetAttribute(fused_kernel, cudaFuncAttributeMaxDynamicSharedMemorySize, SMEM_BYTES);
  }
  const void *x = d_in[0], *wqkv = d_in[1], *wo = d_in[2], *wg = d_in[4], *wu = d_in[5], *wd = d_in[6];
  Maps mp;
  {
    const cuuint64_t dims[3] = {DM, SEQ / 2, 2}, st[2] = {DM * 4, DM * 2};
    const cuuint32_t box_in[3] = {64, 64, 2}, box_out[3] = {64, 8, 1};
    encode(fn, &mp.x, x, 3, dims, st, box_in);
    encode(fn, &mp.out, d_out, 3, dims, st, box_out);
  }
  {
    const cuuint64_t dims[2] = {DM, SEQ}, st[1] = {DM * 2};
    const cuuint32_t box[2] = {64, 128};
    encode(fn, &mp.xn, gs->xn, 2, dims, st, box);
  }
  {
    const cuuint32_t box[2] = {64, 64};
    const cuuint64_t dq[2] = {3 * DM, DM}, sq[1] = {3 * DM * 2}, df[2] = {DFF, DM}, sf[1] = {DFF * 2}, dw[2] = {DM, DM}, sw[1] = {DM * 2};
    encode(fn, &mp.wqkv, wqkv, 2, dq, sq, box);
    encode(fn, &mp.wg, wg, 2, df, sf, box);
    encode(fn, &mp.wu, wu, 2, df, sf, box);
    encode(fn, &mp.wo, wo, 2, dw, sw, box);
  }
  {
    const cuuint32_t box[5] = {64, 2, 4, 4, 2};
    const cuuint64_t st[4] = {DM * 2, 8 * DM * 2, 2 * DM * 2, 32 * DM * 2};
    const cuuint64_t dd[5] = {DM, 2, 4, 4, DFF / 32};
    encode(fn, &mp.wd, wd, 5, dd, st, box);
  }
  fused_kernel<<<NCTA, 384, SMEM_BYTES>>>((const uint4*)x, (const uint4*)wg, (const uint4*)wu, gs, mp);
}
```

```cpp
#include <cuda_runtime.h>
#include <cuda_bf16.h>
#include <cuda.h>
#include <stdint.h>

#define CS_KB 8
#define LN_KB 4

namespace {

constexpr int SEQ = 2048, DM = 1024, DFF = 3584;
constexpr int NMAIN = 128, NCTA = 132;
constexpr uint64_t EVICT_FIRST = 0x12F0000000000000ull, EVICT_NORMAL = 0x1000000000000000ull;

constexpr uint32_t SM_BASE = 0x400;
constexpr uint32_t P1_BYTES = 49152, P2_BYTES = 32768;
constexpr uint32_t OFF_A = 131072;
__host__ __device__ constexpr uint32_t p2_a(int s) { return s == 0 ? OFF_A + 32768 : s == 1 ? OFF_A + 49152 : s == 2 ? 114688 : s == 3 ? 16384 : 49152; }
__host__ __device__ constexpr uint32_t p2_b(int s) { return s < 3 ? 65536 + s * 16384 : (s - 3) * 32768; }
constexpr uint32_t OFF_LAND = OFF_A;
constexpr uint32_t OFF_X = 196608;
constexpr uint32_t OFF_CS = OFF_X + 14336;
constexpr uint32_t OFF_BAR = 229376;
constexpr uint32_t B_F1 = OFF_BAR, B_E1 = B_F1 + 32, B_E2 = B_E1 + 32, B_DONE = B_E2 + 40, B_F2 = B_DONE + 8, B_DEP = B_F2 + 40, B_CS = B_DEP + 48,
                   B_XT = B_CS + 16, B_EP = B_XT + 8, B_EX = B_EP + 8, B_AUX = B_EX + 32, B_HALO = B_AUX + 8, OFF_EPOCH = B_HALO + 16;
constexpr uint32_t SMEM_BYTES = 232448;
constexpr uint32_t AT_V = 0, AT_K = 8192, AT_REM = 11264, AT_WG = 15360;

constexpr int FL_XN = 0, FL_H = 16, FL_P = 80, FL_HALO = 96, FL_N = FL_HALO + 256;
struct __align__(1024) Scratch {
  uint4 h[16 * 56 * 1024];
  uint4 o[16 * 16 * 1024];
  uint4 xn[SEQ * DM / 8];
  uint4 dpart[128 * 8 * 256];
  uint4 halo[2 * 128 * 2 * 128];
  ulonglong2 cspart[8 * 16 * 128];
  unsigned long long stats[SEQ];
  unsigned flags[FL_N * 32];
  unsigned epoch[NCTA * 2];
};
__device__ Scratch g_scratch;
#define TG(i) do {} while (0)
#define TSV(i, v) do {} while (0)
#define TS(i) do {} while (0)

__device__ __forceinline__ unsigned role_id(bool by_sm) {
  unsigned sm;
  asm volatile("mov.u32 %0, %%smid;" : "=r"(sm));
  const unsigned t = sm >> 1;
  const unsigned c = t < 60 ? (t < 32 ? t : t + 1 + ((t - 32) * 37 >> 8)) : (t < 62 ? t + 4 : 8 * t - 464);
  return by_sm ? 2 * c + (blockIdx.x & 1) : blockIdx.x;
}

struct Maps { CUtensorMap x, xn, out, wqkv, wg, wu, wd, wo; };

__device__ __forceinline__ void mbar_init(uint32_t bar, uint32_t cnt) { asm volatile("mbarrier.init.shared::cta.b64 [%0], %1;" ::"r"(bar), "r"(cnt)); }
__device__ __forceinline__ void mbar_expect_tx(uint32_t bar, uint32_t bytes) { asm volatile("mbarrier.arrive.expect_tx.shared::cta.b64 _, [%0], %1;" ::"r"(bar), "r"(bytes) : "memory"); }
__device__ __forceinline__ void mbar_arrive(uint32_t bar) { asm volatile("mbarrier.arrive.shared::cta.b64 _, [%0];" ::"r"(bar) : "memory"); }
__device__ __forceinline__ void mbar_arrive_cl(uint32_t bar) { asm volatile("mbarrier.arrive.shared::cluster.b64 _, [%0];" ::"r"(bar) : "memory"); }
__device__ __forceinline__ uint32_t mapa(uint32_t a, uint32_t cta) { uint32_t r; asm("mapa.shared::cluster.u32 %0, %1, %2;" : "=r"(r) : "r"(a), "r"(cta)); return r; }
__device__ __forceinline__ void mbar_wait(uint32_t bar, uint32_t parity) {
  asm volatile("{\n.reg .pred p;\n.reg .u32 n;\nmov.u32 n, 0;\nLAB_WAIT:\nmbarrier.try_wait.parity.shared::cta.b64 p, [%0], %1;\n@p bra LAB_DONE;\n"
               "add.u32 n, n, 1;\nsetp.gt.u32 p, n, 4000000;\n@p trap;\nbra LAB_WAIT;\nLAB_DONE:\n}" ::"r"(bar), "r"(parity) : "memory");
}
__device__ __forceinline__ void mbar_spin(uint32_t bar, uint32_t parity, uint32_t zero) {
  asm volatile("{\n.reg .pred p, z;\nsetp.ne.u32 z, %2, 0;\nLAB_WAIT:\nmbarrier.try_wait.parity.shared::cta.b64 p, [%0], %1;\n@p bra LAB_DONE;\n@z trap;\nbra LAB_WAIT;\nLAB_DONE:\n}" ::"r"(bar), "r"(parity), "r"(zero) : "memory");
}
__device__ __forceinline__ void flag_wait(const unsigned* f, unsigned target) {
  asm volatile("{\n.reg .pred p;\n.reg .u32 n, v;\nmov.u32 n, 0;\nLAB_WAIT:\nld.relaxed.gpu.global.u32 v, [%0];\nsub.u32 v, v, %1;\nsetp.ge.s32 p, v, 0;\n@p bra LAB_DONE;\n"
               "nanosleep.u32 200;\nadd.u32 n, n, 1;\nsetp.gt.u32 p, n, 4000000;\n@p trap;\nbra LAB_WAIT;\nLAB_DONE:\nfence.acquire.gpu;\n}" ::"l"(f), "r"(target) : "memory");
}
__device__ __forceinline__ void flag_add(unsigned* f) { asm volatile("red.release.gpu.global.add.u32 [%0], 1;" ::"l"(f) : "memory"); }
__device__ __forceinline__ void fence_async() { asm volatile("fence.proxy.async.global;" ::: "memory"); }
__device__ __forceinline__ bool elect_one() { uint32_t p; asm volatile("{\n.reg .pred P;\nelect.sync _|P, 0xffffffff;\nselp.u32 %0, 1, 0, P;\n}" : "=r"(p)); return p; }
__device__ __forceinline__ void bar_sync(int id, int n) { asm volatile("bar.sync %0, %1;" ::"r"(id), "r"(n) : "memory"); }
__device__ __forceinline__ void bar_arrive(int id, int n) { asm volatile("bar.arrive %0, %1;" ::"r"(id), "r"(n) : "memory"); }

__device__ __forceinline__ void tma2d(uint32_t dst, const CUtensorMap* tm, uint32_t bar, int c0, int c1, uint64_t hint) {
  asm volatile("cp.async.bulk.tensor.2d.shared::cluster.global.mbarrier::complete_tx::bytes.L2::cache_hint [%0], [%1, {%3, %4}], [%2], %5;" ::"r"(dst), "l"(tm), "r"(bar), "r"(c0), "r"(c1), "l"(hint) : "memory");
}
__device__ __forceinline__ void tma2d_mc(uint32_t dst, const CUtensorMap* tm, uint32_t bar, int c0, int c1, uint64_t hint) {
  asm volatile("cp.async.bulk.tensor.2d.shared::cluster.global.mbarrier::complete_tx::bytes.multicast::cluster.L2::cache_hint [%0], [%1, {%3, %4}], [%2], %5, %6;" ::"r"(dst), "l"(tm), "r"(bar), "r"(c0), "r"(c1), "h"((uint16_t)3), "l"(hint) : "memory");
}
__device__ __forceinline__ void tma3d(uint32_t dst, const CUtensorMap* tm, uint32_t bar, int c0, int c1, int c2, uint64_t hint) {
  asm volatile("cp.async.bulk.tensor.3d.shared::cluster.global.mbarrier::complete_tx::bytes.L2::cache_hint [%0], [%1, {%3, %4, %5}], [%2], %6;" ::"r"(dst), "l"(tm), "r"(bar), "r"(c0), "r"(c1), "r"(c2), "l"(hint) : "memory");
}
__device__ __forceinline__ void tma5d(uint32_t dst, const CUtensorMap* tm, uint32_t bar, int c0, int c4, uint64_t hint) {
  asm volatile("cp.async.bulk.tensor.5d.shared::cluster.global.mbarrier::complete_tx::bytes.L2::cache_hint [%0], [%1, {%3, %5, %5, %5, %4}], [%2], %6;" ::"r"(dst), "l"(tm), "r"(bar), "r"(c0), "r"(c4), "r"(0), "l"(hint) : "memory");
}
__device__ __forceinline__ void tma3d_store(const CUtensorMap* tm, uint32_t src, int c0, int c1, int c2) {
  asm volatile("cp.async.bulk.tensor.3d.global.shared::cta.bulk_group.L2::cache_hint [%0, {%2, %3, %4}], [%1], %5;" ::"l"(tm), "r"(src), "r"(c0), "r"(c1), "r"(c2), "l"(EVICT_FIRST) : "memory");
}
__device__ __forceinline__ void bulk_load(uint32_t dst, const void* src, uint32_t bytes, uint32_t bar, uint64_t hint) {
  asm volatile("cp.async.bulk.shared::cluster.global.mbarrier::complete_tx::bytes.L2::cache_hint [%0], [%1], %2, [%3], %4;" ::"r"(dst), "l"(src), "r"(bytes), "r"(bar), "l"(hint) : "memory");
}
__device__ __forceinline__ void bulk_load_mc(uint32_t dst, const void* src, uint32_t bytes, uint32_t bar, uint64_t hint) {
  asm volatile("cp.async.bulk.shared::cluster.global.mbarrier::complete_tx::bytes.multicast::cluster.L2::cache_hint [%0], [%1], %2, [%3], %4, %5;" ::"r"(dst), "l"(src), "r"(bytes), "r"(bar), "h"((uint16_t)3), "l"(hint) : "memory");
}
__device__ __forceinline__ uint4 lds128(uint32_t a) { uint4 v; asm volatile("ld.shared.v4.b32 {%0,%1,%2,%3}, [%4];" : "=r"(v.x), "=r"(v.y), "=r"(v.z), "=r"(v.w) : "r"(a) : "memory"); return v; }
__device__ __forceinline__ void sts128(uint32_t a, uint4 v) { asm volatile("st.shared.v4.b32 [%0], {%1,%2,%3,%4};" ::"r"(a), "r"(v.x), "r"(v.y), "r"(v.z), "r"(v.w) : "memory"); }
__device__ __forceinline__ void stg128(void* p, uint32_t a, uint32_t b, uint32_t c, uint32_t d) { asm volatile("st.global.v4.b32 [%0], {%1,%2,%3,%4};" ::"l"(p), "r"(a), "r"(b), "r"(c), "r"(d) : "memory"); }

__device__ __forceinline__ uint32_t pack2(float lo, float hi) { uint32_t r; asm("cvt.rn.bf16x2.f32 %0, %1, %2;" : "=r"(r) : "f"(hi), "f"(lo)); return r; }
__device__ __forceinline__ float lo_f(uint32_t v) { return __uint_as_float(v << 16); }
__device__ __forceinline__ float hi_f(uint32_t v) { return __uint_as_float(v & 0xffff0000u); }
__device__ __forceinline__ float bf16r(float v) { return lo_f(pack2(v, 0.f)); }
__device__ __forceinline__ uint32_t mul2(uint32_t a, uint32_t b) { uint32_t r; asm("mul.rn.bf16x2 %0, %1, %2;" : "=r"(r) : "r"(a), "r"(b)); return r; }
__device__ __forceinline__ uint32_t add2(uint32_t a, uint32_t b) { uint32_t r; asm("add.rn.bf16x2 %0, %1, %2;" : "=r"(r) : "r"(a), "r"(b)); return r; }
__device__ __forceinline__ uint32_t sub2(uint32_t a, uint32_t b) { uint32_t r; asm("sub.rn.bf16x2 %0, %1, %2;" : "=r"(r) : "r"(a), "r"(b)); return r; }
__device__ __forceinline__ uint32_t fma2(uint32_t a, uint32_t b, uint32_t c) { uint32_t r; asm("fma.rn.bf16x2 %0, %1, %2, %3;" : "=r"(r) : "r"(a), "r"(b), "r"(c)); return r; }
__device__ __forceinline__ uint32_t max2(uint32_t a, uint32_t b) { uint32_t r; asm("max.bf16x2 %0, %1, %2;" : "=r"(r) : "r"(a), "r"(b)); return r; }
__device__ __forceinline__ float ex2f(float x) { float y; asm("ex2.approx.ftz.f32 %0, %1;" : "=f"(y) : "f"(x)); return y; }
__device__ __forceinline__ float rcpf(float x) { float y; asm("rcp.approx.ftz.f32 %0, %1;" : "=f"(y) : "f"(x)); return y; }
constexpr float GELU_C1 = 0.7978845608028654f, GELU_C3 = 0.035677408136300125f;
__device__ __forceinline__ float gelu_k(float g, float c1, float c3, float k) {
  float t;
  asm("tanh.approx.f32 %0, %1;" : "=f"(t) : "f"(g * fmaf(g * g, c3, c1)));
  g *= k;
  return fmaf(g, t, g);
}
__device__ __forceinline__ float silu_half(float z) { float t; asm("tanh.approx.f32 %0, %1;" : "=f"(t) : "f"(z)); return fmaf(z, t, z); }

__device__ __forceinline__ void wg_fence() { asm volatile("wgmma.fence.sync.aligned;" ::: "memory"); }
__device__ __forceinline__ void wg_commit() { asm volatile("wgmma.commit_group.sync.aligned;" ::: "memory"); }
template <int N> __device__ __forceinline__ void wg_wait() { asm volatile("wgmma.wait_group.sync.aligned %0;" ::"n"(N) : "memory"); }
#define A8(o) "+f"(d[(o)]), "+f"(d[(o) + 1]), "+f"(d[(o) + 2]), "+f"(d[(o) + 3]), "+f"(d[(o) + 4]), "+f"(d[(o) + 5]), "+f"(d[(o) + 6]), "+f"(d[(o) + 7])
#define A64(o) A8(o), A8((o) + 8), A8((o) + 16), A8((o) + 24), A8((o) + 32), A8((o) + 40), A8((o) + 48), A8((o) + 56)
#define REGS0_63 "%0,%1,%2,%3,%4,%5,%6,%7,%8,%9,%10,%11,%12,%13,%14,%15,%16,%17,%18,%19,%20,%21,%22,%23,%24,%25,%26,%27,%28,%29,%30,%31," \
                 "%32,%33,%34,%35,%36,%37,%38,%39,%40,%41,%42,%43,%44,%45,%46,%47,%48,%49,%50,%51,%52,%53,%54,%55,%56,%57,%58,%59,%60,%61,%62,%63"
#define REGS64_127 "%64,%65,%66,%67,%68,%69,%70,%71,%72,%73,%74,%75,%76,%77,%78,%79,%80,%81,%82,%83,%84,%85,%86,%87,%88,%89,%90,%91,%92,%93,%94,%95," \
                   "%96,%97,%98,%99,%100,%101,%102,%103,%104,%105,%106,%107,%108,%109,%110,%111,%112,%113,%114,%115,%116,%117,%118,%119,%120,%121,%122,%123,%124,%125,%126,%127"
__device__ __forceinline__ void desc_add(uint64_t& x, int v) { asm volatile("{\n.reg .b32 lo, hi;\nmov.b64 {lo, hi}, %0;\nadd.s32 lo, lo, %1;\nmov.b64 %0, {lo, hi};\n}" : "+l"(x) : "r"(v)); }
template <int ACCUM> __device__ __forceinline__ void wgmma256(float (&d)[128], uint64_t& a, uint64_t& b, int da, int db) {
  asm volatile("{\n.reg .pred p;\nsetp.ne.b32 p, %130, 0;\n"
               "wgmma.mma_async.sync.aligned.m64n256k16.f32.bf16.bf16 {" REGS0_63 "," REGS64_127 "}, %128, %129, p, 1, 1, 0, 1;\n}"
               : A64(0), A64(64) : "l"(a), "l"(b), "n"(ACCUM));
  desc_add(a, da); desc_add(b, db);
}
__device__ __forceinline__ void wgmma256_rs(float (&d)[128], uint32_t a0, uint32_t a1, uint32_t z0, uint32_t z1, uint32_t b_lo) {
  asm volatile("{\n.reg .b64 db;\nmov.b64 db, {%132, 0x00000008};\n"
               "wgmma.mma_async.sync.aligned.m64n256k16.f32.bf16.bf16 {" REGS0_63 "," REGS64_127 "}, {%128,%129,%130,%131}, db, 1, 1, 1, 0;\n}"
               : A64(0), A64(64) : "r"(a0), "r"(a1), "r"(z0), "r"(z1), "r"(b_lo));
}
template <int ACCUM> __device__ __forceinline__ void wgmma128(float (&d)[64], uint64_t& a, uint64_t& b, int da, int db) {
  asm volatile("{\n.reg .pred p;\nsetp.ne.b32 p, %66, 0;\n"
               "wgmma.mma_async.sync.aligned.m64n128k16.f32.bf16.bf16 {" REGS0_63 "}, %64, %65, p, 1, 1, 0, 1;\n}"
               : A64(0) : "l"(a), "l"(b), "n"(ACCUM));
  desc_add(a, da); desc_add(b, db);
}
template <int ACCUM> __device__ __forceinline__ void hmma(float (&c)[4], uint32_t a0, uint32_t a1, uint32_t a2, uint32_t a3, uint32_t b0, uint32_t b1) {
  if (ACCUM)
    asm volatile("mma.sync.aligned.m16n8k16.row.col.f32.bf16.bf16.f32 {%0,%1,%2,%3}, {%4,%5,%6,%7}, {%8,%9}, {%0,%1,%2,%3};"
                 : "+f"(c[0]), "+f"(c[1]), "+f"(c[2]), "+f"(c[3]) : "r"(a0), "r"(a1), "r"(a2), "r"(a3), "r"(b0), "r"(b1));
  else
    asm volatile("mma.sync.aligned.m16n8k16.row.col.f32.bf16.bf16.f32 {%0,%1,%2,%3}, {%4,%5,%6,%7}, {%8,%9}, {%10,%10,%10,%10};"
                 : "=f"(c[0]), "=f"(c[1]), "=f"(c[2]), "=f"(c[3]) : "r"(a0), "r"(a1), "r"(a2), "r"(a3), "r"(b0), "r"(b1), "f"(0.f));
}
__device__ __forceinline__ uint32_t movm(uint32_t a) { uint32_t d; asm volatile("movmatrix.sync.aligned.m8n8.trans.b16 %0, %1;" : "=r"(d) : "r"(a)); return d; }
__device__ __forceinline__ int lane_here() { int v; asm volatile("mov.u32 %0, %%laneid;" : "=r"(v)); return v; }
template <int N> __device__ __forceinline__ void pin(uint32_t* r) {
#pragma unroll
  for (int i = 0; i < N; i++) asm volatile("" : "+r"(r[i]));
}
template <int N> __device__ __forceinline__ void pin(float* r) {
#pragma unroll
  for (int i = 0; i < N; i++) asm volatile("" : "+f"(r[i]));
}
__device__ __forceinline__ void sched_fence(uint32_t zero) {
  asm volatile("{\n.reg .pred p;\nsetp.eq.u32 p, %0, 0;\nLAB_F:\n@p bra.uni LAB_D;\nnanosleep.u32 0;\nbra.uni LAB_F;\nLAB_D:\n}" ::"r"(zero) : "memory");
}
__device__ __forceinline__ uint4 ldsm(uint32_t a) { uint4 v; asm volatile("ldmatrix.sync.aligned.m8n8.x4.shared.b16 {%0,%1,%2,%3}, [%4];" : "=r"(v.x), "=r"(v.y), "=r"(v.z), "=r"(v.w) : "r"(a) : "memory"); return v; }
__device__ __forceinline__ uint4 ldsm_t(uint32_t a) { uint4 v; asm volatile("ldmatrix.sync.aligned.m8n8.x4.trans.shared.b16 {%0,%1,%2,%3}, [%4];" : "=r"(v.x), "=r"(v.y), "=r"(v.z), "=r"(v.w) : "r"(a) : "memory"); return v; }

constexpr int BAR_LAG = 1, BAR_MMA = 2, BAR_EV = 3;

struct Cons {
  uint32_t sb;
  mutable uint64_t a, b;
  int k1, k2, k4, k4w, b1;
  uint32_t rel;
  bool do_rel;
  int wg;
  uint32_t zero;
};
#define REL_TS(n) TS(64 + (n))
constexpr uint32_t DB_LO = (SM_BASE >> 4) | ((8192 >> 4) << 16);

template <int ST, int ACCUM, bool WAIT = true> __device__ __forceinline__ void p1_issue(float (&acc)[128], const Cons& c, uint32_t parity) {
  if (WAIT) mbar_spin(c.sb + B_F1 + 8 * ST, parity, c.zero);
  wg_fence();
  wgmma256<ACCUM>(acc, c.a, c.b, c.k1, c.b1);
  wgmma256<1>(acc, c.a, c.b, c.k2, c.b1);
  wgmma256<1>(acc, c.a, c.b, c.k1, c.b1);
  wgmma256<1>(acc, c.a, c.b, ST == 3 ? c.k4w : c.k4, ST == 3 ? -6144 - 384 : 2048 - 384);
  wg_commit();
}
__device__ __forceinline__ void release(const Cons& c, uint32_t bar) { if (c.do_rel) mbar_arrive_cl(c.rel + bar); }
template <int KB, bool WAIT = true> __device__ __forceinline__ void p1_step(float (&acc)[128], const Cons& c) {
  if (KB == 15) { if (c.wg == 1) { wg_wait<0>(); release(c, B_E1 + 16); bar_sync(BAR_LAG, 256); } }
  p1_issue<KB & 3, KB != 0, WAIT>(acc, c, (KB >> 2) & 1);
  if (KB == 15) { if (c.wg == 0) bar_arrive(BAR_LAG, 256); }
  if (KB > 0) { wg_wait<1>(); if (KB != 15 || c.wg == 0) release(c, B_E1 + 8 * ((KB - 1) & 3)); }
  if (KB == 15) { wg_wait<0>(); release(c, B_E1 + 24); }
}
template <class F> __device__ __forceinline__ void p1_loop(float (&acc)[128], const Cons& c, int from, int to, F&& shadow) {
#pragma unroll 1
  for (int kb = from; kb < to; kb++) {
    const bool wrap = (kb & 3) == 3;
    mbar_spin(c.sb + B_F1 + 8 * (kb & 3), (kb >> 2) & 1, c.zero);
    wg_fence();
    wgmma256<1>(acc, c.a, c.b, c.k1, c.b1);
    wgmma256<1>(acc, c.a, c.b, c.k2, c.b1);
    wgmma256<1>(acc, c.a, c.b, c.k1, c.b1);
    wgmma256<1>(acc, c.a, c.b, wrap ? c.k4w : c.k4, wrap ? -6144 - 384 : 2048 - 384);
    wg_commit();
    wg_wait<1>();
    release(c, B_E1 + 8 * ((kb - 1) & 3));
    shadow(kb);
  }
}
template <int T> __device__ __forceinline__ void p2_step(float (&acc)[64], const Cons& c) {
  if (T == 12) { if (c.wg == 1) bar_sync(BAR_LAG, 256); }
  mbar_spin(c.sb + B_F2 + 8 * (T % 5), (T / 5) & 1, c.zero);
  wg_fence();
  wgmma128<T != 0>(acc, c.a, c.b, c.k1, c.b1);
  wgmma128<1>(acc, c.a, c.b, c.k2, c.b1);
  wgmma128<1>(acc, c.a, c.b, c.k1, c.b1);
  wgmma128<1>(acc, c.a, c.b, ((int)p2_a((T + 1) % 5) - (int)p2_a(T % 5)) / 16 - 514, ((int)p2_b((T + 1) % 5) - (int)p2_b(T % 5)) / 16 - 384);
  wg_commit();
  if (T == 15) { if (c.wg == 0) bar_arrive(BAR_LAG, 256); }
  if (T <= 11) { wg_wait<1>(); release(c, T ? B_E2 + 8 * ((T + 4) % 5) : B_E1 + 8); }
}

template <int P> __device__ __forceinline__ void geglu_piece(uint32_t (&pk)[64], uint8_t* dst, float (&rs)[2]) {
  constexpr int cg = P >> 1, r = P & 1;
  pin<1>(rs + r);
#pragma unroll
  for (int i = 0; i < 4; i++) pin<1>(pk + 2 * (4 * cg + i) + r);
  const float r2 = rs[r] * rs[r], c1 = GELU_C1 * rs[r], c3 = GELU_C3 * r2 * rs[r], k = 0.25f * r2;
  uint32_t v[4];
#pragma unroll
  for (int i = 0; i < 4; i++) {
    const uint32_t g = pk[2 * (4 * cg + i) + r];
    v[i] = mul2(pack2(gelu_k(lo_f(g), c1, c3, k), gelu_k(hi_f(g), c1, c3, k)), pk[32 + 2 * (4 * cg + i) + r]);
  }
  stg128(dst + cg * 8192 + r * 512, v[0], v[1], v[2], v[3]);
}
__device__ __forceinline__ void geglu_tile(float (&acc)[128], uint32_t (&pk)[64], const Cons& c, int to, uint8_t* dst, int ev, float (&rs)[2]) {
  const int lane = lane_here();
  dst += (lane ^ (lane >> 3)) << 4;
  p1_loop(acc, c, 1, to, [&](int kb) {
    if (kb <= 4) {
      if (kb <= 2) { if (kb == 1) geglu_piece<0>(pk, dst, rs); else geglu_piece<1>(pk, dst, rs); }
      else { if (kb == 3) geglu_piece<2>(pk, dst, rs); else geglu_piece<3>(pk, dst, rs); }
    } else if (kb <= 8) {
      if (kb <= 6) { if (kb == 5) geglu_piece<4>(pk, dst, rs); else geglu_piece<5>(pk, dst, rs); }
      else { if (kb == 7) geglu_piece<6>(pk, dst, rs); else { geglu_piece<7>(pk, dst, rs); bar_arrive(ev, 288); } }
    }
  });
}

__device__ __forceinline__ void attn_tile(float (&acc)[128], uint32_t (&pk)[64], const Cons& c, int round, int warp, int m, unsigned bid, Scratch* gs, uint8_t* hdst, uint8_t* odst) {
  const int w = warp & 3;
  const uint32_t at = c.sb + OFF_X + c.wg * AT_WG;
  int lane = lane_here();
  hdst += (lane ^ (lane >> 3)) << 4;
  auto scatter = [&]() {
    const int lane = lane_here();
    const uint32_t swz = (lane ^ (lane >> 3)) << 4;
#pragma unroll
    for (int i = 0; i < 4; i++) {
      const int h = i & 1, r = i >> 1;
      sts128(at + AT_V + (2 * w + r) * 1024 + h * 512 + swz, make_uint4(pk[32 + 8 * h + r], pk[34 + 8 * h + r], pk[36 + 8 * h + r], pk[38 + 8 * h + r]));
    }
    if (w < 3) {
#pragma unroll
      for (int i = 0; i < 8; i++) asm volatile("st.shared.b32 [%0], %1;" ::"r"(at + AT_K + w * 1024 + i * 128 + lane * 4), "r"(pk[17 + 2 * i]) : "memory");
    } else {
      uint8_t* g = (uint8_t*)gs->halo + ((round * 128 + bid) * 2 + c.wg) * 2048;
#pragma unroll
      for (int i = 0; i < 8; i++) asm volatile("st.global.b32 [%0], %1;" ::"l"(g + i * 128 + lane * 4), "r"(pk[17 + 2 * i]) : "memory");
#pragma unroll
      for (int h = 0; h < 2; h++) stg128(g + 1024 + h * 512 + swz, pk[33 + 8 * h], pk[35 + 8 * h], pk[37 + 8 * h], pk[39 + 8 * h]);
      bar_arrive(BAR_EV + 2 + round, 96);
    }
    __syncwarp();
    if (lane == 0) mbar_arrive(c.sb + B_HALO + 8 * round);
    if (round) {
#pragma unroll
      for (int p = 0; p < 4; p++) {
        const int o = 32 + 8 * (p >> 1) + (p & 1);
        asm volatile("ld.global.cg.v4.b32 {%0,%1,%2,%3}, [%4];" : "=r"(pk[o]), "=r"(pk[o + 2]), "=r"(pk[o + 4]), "=r"(pk[o + 6]) : "l"(hdst + (p >> 1) * 8192 + (p & 1) * 512) : "memory");
      }
    }
  };
  auto gu_piece = [&](int p) {
    uint32_t v[4];
#pragma unroll
    for (int i = 0; i < 4; i++) {
      const int o = 8 * (p >> 1) + 2 * i + (p & 1);
      pin<1>(pk + 48 + o);
      const uint32_t g = pk[48 + o];
      v[i] = mul2(round ? pk[32 + o] : 0x3e803e80u, round ? g : pack2(gelu_k(lo_f(g), GELU_C1, GELU_C3, 1.0f), gelu_k(hi_f(g), GELU_C1, GELU_C3, 1.0f)));
    }
    stg128(hdst + (p >> 1) * 8192 + (p & 1) * 512, v[0], v[1], v[2], v[3]);
  };
  p1_step<1>(acc, c);
  scatter();
  p1_loop(acc, c, 2, 9, [&](int kb) {
    if (kb <= 4) { if (kb == 3) gu_piece(0); else if (kb == 4) gu_piece(1); }
    else if (kb == 5) gu_piece(2); else if (kb == 6) gu_piece(3);
  });
  const bool first = m == 0 && w == 0;
  uint32_t kl[16];
  mbar_spin(c.sb + B_HALO + 8 * round, 0, c.zero);
  lane = lane_here();
  {
    const uint32_t ka = at + lane * 4 + (w ? AT_K + (w - 1) * 1024 : (first ? AT_K : AT_REM + round * 2048));
#pragma unroll
    for (int i = 0; i < 8; i++) {
      asm volatile("ld.shared.b32 %0, [%1];" : "=r"(kl[2 * i]) : "r"(ka + i * 128) : "memory");
      kl[2 * i + 1] = pk[16 + 2 * i] | c.zero;
    }
  }
  float st[4][4];
  pin<16>(kl);
  bar_sync(BAR_MMA, 256);
  mbar_spin(c.sb + B_F1 + 8 * 1, 0, c.zero);
#pragma unroll
  for (int ks = 0; ks < 2; ks++) {
#pragma unroll
    for (int h = 0; h < 2; h++) {
      const int o = 8 * h + 4 * ks;
      if (ks == 0) { hmma<0>(st[2 * h], kl[o], kl[o + 1], kl[o + 2], kl[o + 3], pk[o], pk[o + 2]); hmma<0>(st[2 * h + 1], pk[16 + o], pk[17 + o], pk[18 + o], pk[19 + o], pk[o + 1], pk[o + 3]); }
      else { hmma<1>(st[2 * h], kl[o], kl[o + 1], kl[o + 2], kl[o + 3], pk[o], pk[o + 2]); hmma<1>(st[2 * h + 1], pk[16 + o], pk[17 + o], pk[18 + o], pk[19 + o], pk[o + 1], pk[o + 3]); }
    }
  }
  sched_fence(c.zero);
  bar_sync(BAR_MMA, 256);
  p1_step<9, false>(acc, c);
  sched_fence(c.zero);
  pin<16>(&st[0][0]);
  lane = lane_here();
  const int rho = lane >> 2, q = lane & 3;
  const bool le0 = 2 * q <= rho, le1 = 2 * q + 1 <= rho;
  uint32_t la[2], lb[2], mx[2];
#pragma unroll
  for (int h = 0; h < 2; h++) {
    uint32_t l[2];
#pragma unroll
    for (int r = 0; r < 2; r++) {
      const float (&t)[4] = st[2 * h + r];
      l[r] = movm(pack2(rho <= 2 * q ? t[2] : t[0], rho <= 2 * q + 1 ? t[3] : t[1]));
      l[r] = fma2(l[r], 0x3e353e35u, mul2(l[r], 0x379e379eu));
    }
    la[h] = __byte_perm(l[0], l[1], 0x5410); lb[h] = __byte_perm(l[0], l[1], 0x7632);
    if (first && !le0) la[h] = (la[h] & 0xffff0000u) | 0xce6eu;
    if (first && !le1) lb[h] = (lb[h] & 0xffff0000u) | 0xce6eu;
    mx[h] = max2(la[h], lb[h]);
  }
#pragma unroll
  for (int o = 1; o <= 2; o++) { mx[0] = max2(mx[0], __shfl_xor_sync(~0u, mx[0], o)); mx[1] = max2(mx[1], __shfl_xor_sync(~0u, mx[1], o)); }
  const float L2E = 1.4426950408889634f;
  float pr[2][4], z[4];
#pragma unroll
  for (int h = 0; h < 2; h++) {
    pr[h][0] = ex2f((lo_f(la[h]) - lo_f(mx[h])) * L2E); pr[h][1] = ex2f((lo_f(lb[h]) - lo_f(mx[h])) * L2E);
    pr[h][2] = ex2f((hi_f(la[h]) - hi_f(mx[h])) * L2E); pr[h][3] = ex2f((hi_f(lb[h]) - hi_f(mx[h])) * L2E);
    z[2 * h] = pr[h][0] + pr[h][1]; z[2 * h + 1] = pr[h][2] + pr[h][3];
  }
  p1_step<10>(acc, c);
#pragma unroll
  for (int o = 1; o <= 2; o++) {
#pragma unroll
    for (int i = 0; i < 4; i++) z[i] += __shfl_xor_sync(~0u, z[i], o);
  }
  const uint32_t LE = (le0 ? 0xffffu : 0u) | (le1 ? 0xffff0000u : 0u);
  uint32_t P[4][2];
  uint4 vt[4][2];
  {
    const uint32_t row = (lane & 7) * 64 + ((((lane >> 3) & 1) ^ ((lane & 7) >> 1)) << 4);
    const uint32_t v1 = at + AT_V + (2 * w + (lane >> 4)) * 1024 + row;
    const uint32_t v0 = (w || lane >= 16) ? v1 - 1024 : (first ? v1 : at + AT_REM + round * 2048 + 1024 + row);
#pragma unroll
    for (int i = 0; i < 4; i++) {
      const float rz = rcpf(z[i]);
      const uint32_t p = pack2(pr[i >> 1][2 * (i & 1)] * rz, pr[i >> 1][2 * (i & 1) + 1] * rz);
      P[i][0] = p & ~LE; P[i][1] = p & LE;
      const uint32_t a = ((i & 1) ? v1 : v0) + (i >> 1) * 512;
      vt[i][0] = ldsm_t(a); vt[i][1] = ldsm_t(a ^ 32);
    }
  }
  float ot[4][2][4];
  pin<8>(&P[0][0]);
  bar_sync(BAR_MMA, 256);
  mbar_spin(c.sb + B_F1 + 8 * 3, 0, c.zero);
#pragma unroll
  for (int i = 0; i < 8; i++) { const uint4& v = vt[i >> 1][i & 1]; hmma<0>(ot[i >> 1][i & 1], v.x, v.y, v.z, v.w, P[i >> 1][0], P[i >> 1][1]); }
  sched_fence(c.zero);
  bar_sync(BAR_MMA, 256);
  p1_step<11, false>(acc, c);
  sched_fence(c.zero);
  pin<32>(&ot[0][0][0]);
  lane = lane_here();
  odst += (lane ^ (lane >> 3)) << 4;
  auto o_piece = [&](int i) {
    stg128(odst + (i >> 1) * 8192 + (i & 1) * 512, movm(pack2(ot[i][0][0], ot[i][0][1])), movm(pack2(ot[i][0][2], ot[i][0][3])), movm(pack2(ot[i][1][0], ot[i][1][1])), movm(pack2(ot[i][1][2], ot[i][1][3])));
  };
  o_piece(0); o_piece(1);
  p1_step<12>(acc, c);
  o_piece(2); o_piece(3);
  if (round) bar_arrive(BAR_EV + 4, 288);
  p1_step<13>(acc, c);
}

__device__ __forceinline__ void ln_moments(const uint32_t* raw, float& c0, float& s, float& v) {
  c0 = lo_f(__shfl_sync(~0u, raw[0], 0));
  float ss[4] = {0.f, 0.f, 0.f, 0.f}, vv[4] = {0.f, 0.f, 0.f, 0.f};
#pragma unroll
  for (int i = 0; i < 16; i++) {
    const float a = lo_f(raw[i]) - c0, b = hi_f(raw[i]) - c0;
    ss[(2 * i) & 3] += a; ss[(2 * i + 1) & 3] += b;
    vv[(2 * i) & 3] = fmaf(a, a, vv[(2 * i) & 3]); vv[(2 * i + 1) & 3] = fmaf(b, b, vv[(2 * i + 1) & 3]);
  }
  s = (ss[0] + ss[1]) + (ss[2] + ss[3]); v = (vv[0] + vv[1]) + (vv[2] + vv[3]);
}
__device__ __forceinline__ void ln_reduce(float& s, float& v) {
#pragma unroll
  for (int o = 16; o; o >>= 1) { s += __shfl_xor_sync(~0u, s, o); v += __shfl_xor_sync(~0u, v, o); }
}
__device__ __forceinline__ uint32_t ln_finish(float c0, float s, float v) {
  s *= 1.0f / DM;
  float sd;
  asm("sqrt.approx.ftz.f32 %0, %1;" : "=f"(sd) : "f"(bf16r(bf16r(fmaxf(fmaf(v, 1.0f / DM, -s * s), 0.f)) + 1e-5f)));
  return pack2(c0 + s, sd);
}
__device__ __forceinline__ void ln_store(const uint32_t* raw, uint32_t st, uint4* dst) {
  const uint32_t m2 = __byte_perm(st, st, 0x1010);
  const float rinv = rcpf(hi_f(st));
  const uint32_t rh = pack2(rinv, rinv), rl = pack2(rinv - hi_f(rh), rinv - hi_f(rh));
#pragma unroll
  for (int c = 0; c < 4; c++) {
    uint32_t v[4];
#pragma unroll
    for (int i = 0; i < 4; i++) { const uint32_t t = sub2(raw[4 * c + i], m2); v[i] = fma2(t, rh, mul2(t, rl)); }
    stg128(dst + 32 * c, v[0], v[1], v[2], v[3]);
  }
}
__device__ __forceinline__ void col_sums(uint32_t tile, ulonglong2* part, uint32_t tag) {
  const int lane = threadIdx.x & 31;
  float cs[8] = {0, 0, 0, 0, 0, 0, 0, 0};
  uint32_t base = tile + ((lane >> 3) & 1) * 8192 + (lane >> 4) * 4096 + ((lane & 7) << 4);
#pragma unroll 1
  for (int k0 = 0; k0 < 8; k0++, base = (base ^ ((k0 ^ (k0 - 1)) << 4)) + 128) {
    uint4 v[4];
#pragma unroll
    for (int k = 0; k < 4; k++) v[k] = lds128(base + k * 1024);
#pragma unroll
    for (int k = 0; k < 4; k++) {
      cs[0] += lo_f(v[k].x); cs[1] += hi_f(v[k].x); cs[2] += lo_f(v[k].y); cs[3] += hi_f(v[k].y);
      cs[4] += lo_f(v[k].z); cs[5] += hi_f(v[k].z); cs[6] += lo_f(v[k].w); cs[7] += hi_f(v[k].w);
    }
  }
  const bool up = lane >= 16;
#pragma unroll
  for (int i = 0; i < 2; i++) {
    const float a = (up ? cs[4 + 2 * i] : cs[2 * i]) + __shfl_xor_sync(~0u, up ? cs[2 * i] : cs[4 + 2 * i], 16);
    const float b = (up ? cs[5 + 2 * i] : cs[1 + 2 * i]) + __shfl_xor_sync(~0u, up ? cs[1 + 2 * i] : cs[5 + 2 * i], 16);
    asm volatile("{\n.reg .b64 a, b;\nmov.b64 a, {%1, %3};\nmov.b64 b, {%2, %3};\nst.relaxed.gpu.global.v2.b64 [%0], {a, b};\n}"
                 ::"l"(part + 32 * (i + (up ? 2 : 0)) + (lane & 15)), "r"(__float_as_uint(a)), "r"(__float_as_uint(b)), "r"(tag) : "memory");
  }
  asm volatile("fence.proxy.async.shared::cta;" ::: "memory");
}

__global__ void __cluster_dims__(2, 1, 1) __launch_bounds__(384, 1)
fused_kernel(const uint4* __restrict__ x, const uint4* __restrict__ wgate, const uint4* __restrict__ wup, Scratch* gs, int by_sm, const __grid_constant__ Maps mp) {
  extern __shared__ __align__(1024) uint8_t smem_raw[];
  const uint32_t sb = (uint32_t)__cvta_generic_to_shared(smem_raw);
  const unsigned bid = role_id(by_sm);
  if (threadIdx.x == 352) TS(63);
  if (threadIdx.x < 256 && bid < NMAIN) {
    const uint32_t r = threadIdx.x >> 3, ch = threadIdx.x & 7;
    const uint32_t d = sb + r * 128 + ((ch ^ (r & 7)) << 4);
    const uint8_t* xa = (const uint8_t*)x + ((bid & 15) * 262144 + r * 4096 + ch * 16);
    const uint32_t wo = r * (DFF * 2) + (bid >> 4) * 256 + ch * 16;
    const uint8_t *wa = (const uint8_t*)wgate + wo, *wb = (const uint8_t*)wup + wo;
#pragma unroll
    for (int i = 0; i < 12; i++) {
      const int h = i >= 8;
      const uint8_t* src = (i >> 2) == 1 ? xa + (i & 1) * 131072 + ((i >> 1) & 1) * 2048 : ((i & 2) ? wb : wa) + h * 32 * (DFF * 2) + (i & 1) * 128;
      asm volatile("cp.async.cg.shared.global [%0], [%1], 16;" ::"r"(d + ((i >> 2) == 1 ? OFF_A + (i & 3) * 4096 : (i & 3) * 8192 + h * 4096)), "l"(src) : "memory");
    }
    if (threadIdx.x == 0) TS(23);
  }
  const int warp = __shfl_sync(~0u, threadIdx.x >> 5, 0), lane = threadIdx.x & 31;
  const int m = bid & 15, j = bid >> 4, rank = bid & 1;
  const int m2 = bid >> 3, j2 = bid & 7;
  const bool helper = bid >= NMAIN;
  if (warp >= 8) {
    asm volatile("setmaxnreg.dec.sync.aligned.u32 40;");
    if (warp == 8) {
      if (elect_one()) {
        asm volatile("prefetch.tensormap [%0];\nprefetch.tensormap [%1];\nprefetch.tensormap [%2];" ::"l"(&mp.x), "l"(&mp.wg), "l"(&mp.wu) : "memory");
        for (int s = 0; s < 4; s++) mbar_init(sb + B_F1 + 8 * s, 1);
        if (!helper) mbar_arrive(sb + B_F1);
        asm volatile("fence.mbarrier_init.release.cluster;" ::: "memory");
      }
      __syncwarp();
    } else if (warp == 9) {
      if (elect_one()) {
        unsigned nsmid;
        asm("mov.u32 %0, %%nsmid;" : "=r"(nsmid));
        if ((sb & 0xffffff) != SM_BASE || (by_sm && nsmid != NCTA)) asm volatile("trap;");
        for (uint32_t b = B_E1; b < B_F2; b += 8) mbar_init(sb + b, 4);
        for (uint32_t b = B_F2; b < B_AUX; b += 8) mbar_init(sb + b, 1);
        for (uint32_t b = B_EX; b < B_AUX; b += 8) mbar_expect_tx(sb + b, 8192);
        mbar_init(sb + B_AUX, 8); mbar_init(sb + B_HALO, 9); mbar_init(sb + B_HALO + 8, 9);
        asm volatile("st.shared.b32 [%0], %1;" ::"r"(sb + OFF_EPOCH + 4), "r"(bid) : "memory");
        asm volatile("fence.mbarrier_init.release.cluster;" ::: "memory");
      }
      __syncwarp();
    }
    asm volatile("barrier.cluster.arrive.relaxed.aligned;" ::: "memory");
    if (warp == 8 && !helper) {
      if (elect_one()) {
        TS(0); TG(51);
#pragma unroll 1
        for (int kb = 1; kb < 4; kb++) {
          const uint32_t sa = sb + OFF_A + kb * 16384, sw = sb + kb * 32768, fb = sb + B_F1 + 8 * kb;
          mbar_expect_tx(fb, P1_BYTES);
          tma3d(sa, &mp.x, fb, kb * 64, m * 64, 0, EVICT_NORMAL);
          tma2d(sw, &mp.wg, fb, j * 128, kb * 64, EVICT_NORMAL); tma2d(sw + 16384, &mp.wu, fb, j * 128, kb * 64, EVICT_NORMAL);
          tma2d(sw + 8192, &mp.wg, fb, j * 128 + 64, kb * 64, EVICT_NORMAL); tma2d(sw + 24576, &mp.wu, fb, j * 128 + 64, kb * 64, EVICT_NORMAL);
        }
        TS(7);
      }
      __syncwarp();
    }
    asm volatile("barrier.cluster.wait.aligned;" ::: "memory");
    if (helper) {
      if (warp == 8) {
        unsigned e = 0;
        if (elect_one()) {
#pragma unroll 1
          for (int i = 0; i < 16; i++) {
            const uint32_t fb = sb + B_F1 + 8 * (i >> 2);
            if (!(i & 3)) mbar_expect_tx(fb, P1_BYTES);
            tma5d(sb + i * 8192, &mp.wd, fb, (bid - NMAIN) * 256 + (i & 3) * 64, (i >> 2) * 2, EVICT_FIRST);
          }
        }
        if (lane == 0) { unsigned* ep = &gs->epoch[bid * 2]; e = *ep + 1; *ep = e; }
        e = __shfl_sync(~0u, e, 0);
        if (lane < 16) flag_wait(&gs->flags[(FL_H + lane * 4) * 32], e * 8u);
        __syncwarp();
        if (elect_one()) {
          fence_async();
          TS(0);
#pragma unroll 1
          for (int i = 0; i < 64; i++) {
            const uint32_t fb = sb + B_F1 + 8 * (i & 3);
            if (i >= 4) { mbar_wait(sb + B_E1 + 8 * (i & 3), ~(i >> 2) & 1); mbar_expect_tx(fb, 16384); }
            bulk_load(sb + OFF_A + (i & 3) * 16384, gs->h + ((i >> 2) * 56 + (i & 3)) * 1024, 16384, fb, EVICT_NORMAL);
          }
        }
      } else if (warp == 9) {
#pragma unroll 1
        for (int t = 0; t < 16; t++) {
          bar_sync(BAR_EV + (t & 1), 288);
          if (lane == 0) { flag_add(&gs->flags[(FL_P + t) * 32]); TS(64 + t); }
          __syncwarp();
        }
      }
    } else if (warp == 8) {
      if (elect_one()) {
        uint32_t par = 0;

        auto x_load = [&]() {
          mbar_expect_tx(sb + B_XT, 32768);
          tma3d(sb + OFF_X, &mp.x, sb + B_XT, j2 * 128, m2 * 64, 0, EVICT_FIRST); tma3d(sb + OFF_X + 16384, &mp.x, sb + B_XT, j2 * 128 + 64, m2 * 64, 0, EVICT_FIRST);
        };
        auto w_tile = [&](int R, const CUtensorMap*& mb0, const CUtensorMap*& mb1, int& n0, int& n1) {
          if (R == 1 || R == 2) {
            mb0 = &mp.wqkv; n0 = 64 * (j + 8 * (R - 1)) + rank * 2048;
            mb1 = rank ? (R == 1 ? &mp.wg : &mp.wu) : &mp.wqkv; n1 = rank ? 1024 + 64 * j : n0 + 1024;
          } else {
            mb0 = mb1 = rank ? &mp.wu : &mp.wg;
            n0 = 128 * j + (R ? 1024 * R - 1536 : 0); n1 = n0 + 64;
          }
        };
        for (int R = 0; R < 5; R++) {
          const CUtensorMap *mb0, *mb1;
          int n0, n1;
          w_tile(R, mb0, mb1, n0, n1);
#pragma unroll 1
          for (int kb = R ? 0 : 4; kb < 16; kb++) {
            if (R == 0 && kb == 14) { asm volatile("prefetch.tensormap [%0];\nprefetch.tensormap [%1];" ::"l"(&mp.xn), "l"(&mp.wqkv) : "memory"); }
            if (R == 4 && kb == 2) { asm volatile("prefetch.tensormap [%0];\nprefetch.tensormap [%1];\nprefetch.tensormap [%2];" ::"l"(&mp.wd), "l"(&mp.wo), "l"(&mp.out) : "memory"); }
            if (R == 0 && kb == CS_KB) {
#pragma unroll 1
              for (int h = 0; h < 2; h++) {
                const uint32_t cb = sb + B_CS + 8 * h, d = sb + OFF_X + 16384 * h;
                mbar_expect_tx(cb, 16384);
                tma2d(d, h ? &mp.wu : &mp.wg, cb, n0, m * 64, EVICT_NORMAL); tma2d(d + 8192, h ? &mp.wu : &mp.wg, cb, n1, m * 64, EVICT_NORMAL);
              }
            }
            const int st = kb & 3;
            const uint32_t sa = sb + OFF_A + st * 16384, sw = sb + st * 32768, fb = sb + B_F1 + 8 * st;
            mbar_wait(sb + B_E1 + 8 * st, par);
            if (R * 16 + kb >= 4) REL_TS(R * 16 + kb - 4);
            mbar_expect_tx(fb, P1_BYTES);
            tma2d_mc(sw + rank * 16384, mb0, fb, n0, kb * 64, EVICT_FIRST);
            tma2d_mc(sw + 8192 + rank * 16384, mb1, fb, n1, kb * 64, EVICT_FIRST);
            if (R == 0) {
              tma3d(sa, &mp.x, fb, kb * 64, m * 64, 0, EVICT_NORMAL);
            } else {
              if (R == 1 && kb == 0) { mbar_wait(sb + B_DEP, 0); TS(1); }
              tma2d(sa, &mp.xn, fb, kb * 64, m * 128, R == 4 ? EVICT_FIRST : EVICT_NORMAL);
            }
            if (R == 4 && kb == 4 + j2) x_load();
            if (st == 3) par ^= 1;
          }
        }
#pragma unroll 1
        for (int i = 0; i < 26; i++) {
          const int st = i & 3, kb = 2 * i + 4 + rank;
          const uint32_t sa = sb + OFF_A + st * 16384, sw = sb + st * 32768, fb = sb + B_F1 + 8 * st;
          mbar_wait(sb + B_E1 + 8 * st, par);
          REL_TS(76 + i);
          mbar_expect_tx(fb, P1_BYTES);
          tma5d(sw, &mp.wd, fb, j2 * 128, kb * 2, EVICT_FIRST); tma5d(sw + 8192, &mp.wd, fb, j2 * 128 + 64, kb * 2, EVICT_FIRST);
          tma5d(sw + 16384, &mp.wd, fb, (j2 ^ 1) * 128, kb * 2, EVICT_FIRST); tma5d(sw + 24576, &mp.wd, fb, (j2 ^ 1) * 128 + 64, kb * 2, EVICT_FIRST);
          if (i == 0 || i == 6 || i == 10 || i == 18) { mbar_wait(sb + B_DEP + 8 * (1 + ((i + 6) >> 3)), 0); }
          bulk_load(sa, gs->h + (m2 * 56 + kb) * 1024, 16384, fb, EVICT_FIRST);
          if (st == 3) par ^= 1;
        }
        int st = 0; uint32_t par2 = 1;
#pragma unroll 1
        for (int t = 0; t < 16; t++) {
          const uint32_t sa = sb + p2_a(st), sw = sb + p2_b(st), fb = sb + B_F2 + 8 * st;
          if (t < 5) mbar_wait(sb + B_E1 + 8 * (((2 * t + 1) / 3 + 2) & 3), t < 3); else mbar_wait(sb + B_E2 + 8 * st, par2);
          REL_TS(102 + t);
          mbar_expect_tx(fb, P2_BYTES);
          bulk_load_mc(sa + rank * 8192, gs->o + (m2 * 16 + t) * 1024 + rank * 512, 8192, fb, EVICT_FIRST);
          tma2d(sw, &mp.wo, fb, j2 * 128, t * 64, EVICT_FIRST); tma2d(sw + 8192, &mp.wo, fb, j2 * 128 + 64, t * 64, EVICT_FIRST);
          if (++st == 5) { st = 0; par2 ^= 1; }
        }
      }
    } else if (warp == 9) {
#pragma unroll 1
      for (int e = 0; e < 7; e++) {
        const bool halo = e == 2 || e == 3;
        bar_sync(BAR_EV + e, halo ? 96 : 288);
        if (lane == 0) {
          const int f = e == 0 ? FL_XN + m : (halo ? FL_HALO + (e - 2) * 128 + bid : FL_H + m * 4 + (e == 1 ? 0 : e - 3));
          TS(10 + 2 * e); TG(52 + e);
          flag_add(&gs->flags[f * 32]);
          if (e < 6) TS(11 + 2 * e);
        }
        __syncwarp();
      }
      unsigned other;
      asm volatile("ld.shared::cluster.b32 %0, [%1];" : "=r"(other) : "r"(mapa(sb + OFF_EPOCH + 4, rank ^ 1)) : "memory");
      if (other != (bid ^ 1)) asm volatile("trap;");
      mbar_wait(sb + B_DONE, 0);
    } else {
      unsigned e = 0;
      if (lane == 0) {
        unsigned* ep = &gs->epoch[bid * 2 + warp - 10];
        e = *ep + 1; *ep = e;
        if (warp == 10) { asm volatile("st.shared.b32 [%0], %1;" ::"r"(sb + OFF_EPOCH), "r"(e) : "memory"); mbar_arrive(sb + B_EP); }
      }
      e = __shfl_sync(~0u, e, 0);
      mbar_wait(sb + B_CS + 8 * (warp - 10), 0);
      if (lane == 0 && warp == 11) TS(6);
      col_sums(sb + OFF_X + (warp - 10) * 16384, gs->cspart + (j * 16 + m) * 128 + (warp - 10) * 16, e);
      if (lane == 0 && warp == 11) TS(9);
      if (warp == 10) {
        if (lane == 0) {
#pragma unroll 1
          for (int g = 0; g < 6; g++) {
            flag_wait(&gs->flags[(g == 5 ? FL_P + m2 : (g ? FL_H + m2 * 4 + g - 1 : FL_XN + m)) * 32], e * (g == 5 ? 4u : 8u));
            fence_async();
            mbar_arrive(sb + B_DEP + 8 * g);
            if (g == 0) TS(8);
          }
        }
      } else
      if (elect_one()) {
#pragma unroll 1
        for (int r = 0; r < 2; r++) {
          const uint32_t hb = sb + B_HALO + 8 * r;
          if (r) mbar_wait(sb + B_HALO, 0);
          if (m) {
            flag_wait(&gs->flags[(FL_HALO + r * 128 + bid - 1) * 32], e);
            fence_async();
            mbar_expect_tx(hb, 4096);
            for (int g = 0; g < 2; g++) bulk_load(sb + OFF_X + g * AT_WG + AT_REM + r * 2048, gs->halo + ((r * 128 + bid - 1) * 2 + g) * 128, 2048, hb, EVICT_FIRST);
          } else {
            mbar_arrive(hb);
          }
          TS(34 + r);
        }
      }
    }
  } else {
    asm volatile("barrier.cluster.arrive.relaxed.aligned;" ::: "memory");
    asm volatile("setmaxnreg.inc.sync.aligned.u32 232;");
    const int wg = warp >> 2, w = warp & 3;
    Cons c;
    c.sb = sb; c.wg = wg; c.zero = warp >> 8;
    c.a = 0x4000004000010000ull + ((SM_BASE + OFF_A + wg * 8192) >> 4); c.k1 = 2 + c.zero; c.k2 = 2; c.k4 = 1024 - 6; c.k4w = -3072 - 6; c.b1 = 128 + c.zero;
    c.b = 0x4000004000000000ull + DB_LO + c.zero;
    c.rel = mapa(sb, threadIdx.x & 1);
    c.do_rel = (threadIdx.x & 127) < 2;
    float acc[128];
    uint32_t pk[64];
    float rs[2];
    const int q = lane & 3;

    if (helper) {
      asm volatile("barrier.cluster.wait.aligned;" ::: "memory");
      c.a = 0x8000002000010000ull + ((SM_BASE + OFF_A + wg * 4096) >> 4); c.k2 = 510; c.k4 = 1024 - 514; c.k4w = -3072 - 514;
      c.rel = sb;
      uint4* dst = gs->dpart + (bid - NMAIN) * 4096 + threadIdx.x;
      auto put = [&](int p) {
#pragma unroll
        for (int i = 4 * p; i < 4 * p + 4; i++) stg128(dst + i * 256, pk[4 * i], pk[4 * i + 1], pk[4 * i + 2], pk[4 * i + 3]);
      };
#pragma unroll 1
      for (int t = 0; t < 16; t++) {
        p1_issue<0, 0>(acc, c, t & 1);
        if (t) put(0);
        p1_issue<1, 1>(acc, c, t & 1); wg_wait<1>(); release(c, B_E1);
        if (t) put(1);
        p1_issue<2, 1>(acc, c, t & 1); wg_wait<1>(); release(c, B_E1 + 8);
        if (t) put(2);
        if (wg == 1) { wg_wait<0>(); release(c, B_E1 + 16); bar_sync(BAR_LAG, 256); }
        p1_issue<3, 1>(acc, c, t & 1);
        if (wg == 0) bar_arrive(BAR_LAG, 256);
        if (t) { put(3); bar_arrive(BAR_EV + (~t & 1), 288); dst += 8 * 2048; }
        wg_wait<1>(); if (wg == 0) release(c, B_E1 + 16);
        wg_wait<0>(); release(c, B_E1 + 24);
#pragma unroll
        for (int i = 0; i < 64; i++) pk[i] = pack2(acc[2 * i], acc[2 * i + 1]);
      }
      put(0); put(1); put(2); put(3);
      bar_arrive(BAR_EV + 1, 288);
      return;
    }
    {
      const int prow = 16 * j + 2 * warp;
      const uint4* xr = x + (size_t)(128 * m + 2 * (prow & 63) + (prow >> 6)) * 128 + lane;
      uint4* xo = gs->xn + (size_t)(128 * m + prow) * 128 + lane;
      float c0[2], mo[4];
      uint32_t st[2];
      uint32_t e;
      asm volatile("" : "+l"(xr), "+l"(xo));
      asm volatile("cp.async.wait_all;\nfence.proxy.async.shared::cta;" ::: "memory");
      bar_sync(BAR_MMA, 256);
      if (threadIdx.x == 0) TS(39);
      p1_step<0, false>(acc, c);
      asm volatile("barrier.cluster.wait.aligned;" ::: "memory");
      unsigned long long part[18];
      auto gather = [&](int from, int to) {
        const int lane = lane_here();
        const unsigned long long* cp = (const unsigned long long*)gs->cspart + j * 4096 + warp * 32 + lane;
        const unsigned long long* sp = gs->stats + 128 * m + warp * 16 + (lane >> 2);
#pragma unroll
        for (int i = from; i < to; i++) asm volatile("ld.relaxed.gpu.global.b64 %0, [%1];" : "=l"(part[i]) : "l"(i < 16 ? cp + i * 256 : sp + (i - 16) * 8) : "memory");
      };
      auto row_load = [&](int r) {
#pragma unroll
        for (int i = 4 * r; i < 4 * r + 4; i++)
          asm volatile("ld.global.nc.L1::no_allocate.v4.b32 {%0,%1,%2,%3}, [%4];" : "=r"(pk[4 * i]), "=r"(pk[4 * i + 1]), "=r"(pk[4 * i + 2]), "=r"(pk[4 * i + 3]) : "l"(xr + r * 256 + (i & 3) * 32));
      };
      p1_step<1>(acc, c); row_load(0);
      p1_step<2>(acc, c); row_load(1);
      p1_loop(acc, c, 3, LN_KB + 1, [](int) {});
      pin<16>(pk); ln_moments(pk, c0[0], mo[0], mo[1]); pin<2>(mo);
      p1_step<LN_KB + 1>(acc, c);
      sched_fence(c.zero);
      pin<16>(pk + 16); ln_moments(pk + 16, c0[1], mo[2], mo[3]); ln_reduce(mo[0], mo[1]); pin<4>(mo);
      p1_step<LN_KB + 2>(acc, c);
      mbar_spin(sb + B_EP, 0, c.zero);
      asm volatile("ld.shared.b32 %0, [%1];" : "=r"(e) : "r"(sb + OFF_EPOCH) : "memory");
      pin<2>(mo); st[0] = ln_finish(c0[0], mo[0], mo[1]); ln_reduce(mo[2], mo[3]); pin<1>(st); pin<2>(mo + 2);
      p1_step<LN_KB + 3>(acc, c);
      sched_fence(c.zero);
      pin<1>(st); pin<2>(mo + 2);
      st[1] = ln_finish(c0[1], mo[2], mo[3]);
      ln_store(pk, st[0], xo);
      if (lane == 0)
        asm volatile("{\n.reg .b64 a, b;\nmov.b64 a, {%1, %3};\nmov.b64 b, {%2, %3};\nst.relaxed.gpu.global.v2.b64 [%0], {a, b};\n}" ::"l"(gs->stats + 128 * m + prow), "r"(st[0]), "r"(st[1]), "r"(e) : "memory");
      p1_step<LN_KB + 4>(acc, c);
      sched_fence(c.zero);
      pin<1>(st + 1);
      ln_store(pk + 16, st[1], xo + 128);
      bar_arrive(BAR_EV, 288);
      p1_loop(acc, c, LN_KB + 5, 13, [](int) {});
      gather(0, 9);
      p1_step<13>(acc, c);
      gather(9, 18);
      p1_step<14>(acc, c);
      auto validate = [&]() {
        float csum;
        for (int tries = 0;; tries++) {
          uint32_t bad = 0;
          csum = 0.f;
#pragma unroll
          for (int i = 0; i < 18; i++) { bad |= (uint32_t)(part[i] >> 32) ^ e; if (i < 16) csum += __uint_as_float((uint32_t)part[i]); }
          if (!__any_sync(~0u, bad != 0) || tries > (1 << 20)) break;
          gather(0, 18);
        }
        const float hi = bf16r(csum), mid = bf16r(csum - hi);
        sts128(sb + OFF_CS + ((threadIdx.x & 62) * 4 + (threadIdx.x >> 6) * 2 + (threadIdx.x & 1)) * 16, make_uint4(pack2(hi, mid), pack2(csum - hi - mid, 0.f), 0, 0));
        asm volatile("fence.proxy.async.shared::cta;" ::: "memory");
        __syncwarp();
        if (lane == 0) mbar_arrive(sb + B_AUX);
      };
#pragma unroll 1
      for (int ph = 1; ph >= 0; ph--) {
        if (wg == ph) validate();
        if (ph) {
          if (wg == 1) { wg_wait<0>(); release(c, B_E1 + 16); bar_sync(BAR_LAG, 256); }
          p1_issue<3, 1>(acc, c, 1);
        }
      }
      const uint32_t keep = q == 0 ? 0xffffffffu : (q == 1 ? 0xffffu : 0u);
      const uint32_t a0 = (__byte_perm((uint32_t)part[16], 0, 0x1010) ^ 0x80008000u) & keep, a1 = (__byte_perm((uint32_t)part[17], 0, 0x1010) ^ 0x80008000u) & keep;
      mbar_spin(sb + B_AUX, 0, c.zero);
      wg_fence();
      wgmma256_rs(acc, a0, a1, 0, 0, (SM_BASE + OFF_CS) >> 4);
      wg_commit();
      if (wg == 0) bar_arrive(BAR_LAG, 256);
      rs[0] = rcpf(hi_f((uint32_t)part[16])); rs[1] = rcpf(hi_f((uint32_t)part[17]));
      wg_wait<2>(); if (wg == 0) release(c, B_E1 + 16);
      wg_wait<0>(); release(c, B_E1 + 24);
    }
#pragma unroll 1
    for (int R = 1;; R++) {
#pragma unroll
      for (int i = 0; i < 64; i++) pk[i] = pack2(acc[2 * i], acc[2 * i + 1]);
      uint8_t* hb = (uint8_t*)gs->h + (size_t)m * 56 * 16384 + warp * 1024;
      if (R == 5) { c.a = 0x8000002000010000ull + ((SM_BASE + OFF_A + wg * 4096) >> 4); c.k2 = 510; c.k4 = 1024 - 514; c.k4w = -3072 - 514; }
      p1_step<0>(acc, c);
      if (R == 2 || R == 3) {
        attn_tile(acc, pk, c, R - 2, warp, m, bid, gs, hb + (16 + j) * 16384, (uint8_t*)gs->o + (m * 16 + j + 8 * (R - 2)) * 16384 + warp * 1024);
      } else {
        geglu_tile(acc, pk, c, R == 5 ? 24 : 14, hb + (2 * j + (R == 1 ? 0 : 16 * R - 40)) * 16384, BAR_EV + (R == 1 ? 1 : R + 1), rs);
        rs[0] = rs[1] = 1.0f;
        if (R == 5) break;
      }
      p1_step<14>(acc, c); p1_step<15>(acc, c);
    }
    auto fetch = [&](int p) {
      asm volatile("ld.global.cg.v4.b32 {%0,%1,%2,%3}, [%4];" : "=r"(pk[4 * p]), "=r"(pk[4 * p + 1]), "=r"(pk[4 * p + 2]), "=r"(pk[4 * p + 3]) : "l"(gs->dpart + bid * 2048 + p * 256 + threadIdx.x) : "memory");
    };
    mbar_spin(sb + B_DEP + 40, 0, c.zero);
    fetch(0); fetch(1); fetch(2);
    p1_step<8>(acc, c);
    fetch(3); fetch(4); fetch(5);
    p1_step<9>(acc, c);
    fetch(6); fetch(7);
    {
      float accs[64];
      const uint32_t peer = mapa(sb, rank ^ 1);
      auto send_piece = [&](int p) {
        asm volatile("st.async.weak.shared::cluster.mbarrier::complete_tx::bytes.v4.b32 [%0], {%1,%2,%3,%4}, [%5];" ::"r"(peer + OFF_LAND + p * 4096 + threadIdx.x * 16),
                     "r"(pack2(acc[64 + 8 * p], acc[65 + 8 * p])), "r"(pack2(acc[66 + 8 * p], acc[67 + 8 * p])), "r"(pack2(acc[68 + 8 * p], acc[69 + 8 * p])), "r"(pack2(acc[70 + 8 * p], acc[71 + 8 * p])),
                     "r"(peer + B_EX + 16 * wg + 8 * (p >> 2)) : "memory");
      };
      auto silu_piece = [&](int p) {
        const uint4 r = lds128(sb + OFF_LAND + p * 4096 + threadIdx.x * 16);
        const uint32_t rr[4] = {add2(r.x, pk[4 * p]), add2(r.y, pk[4 * p + 1]), add2(r.z, pk[4 * p + 2]), add2(r.w, pk[4 * p + 3])};
#pragma unroll
        for (int i = 0; i < 4; i++) {
          const float a = acc[8 * p + 2 * i] + lo_f(rr[i]), b = acc[8 * p + 2 * i + 1] + hi_f(rr[i]);
          pk[4 * p + i] = pack2(silu_half(a), silu_half(b));
        }
        pin<4>(pk + 4 * p);
      };
      const uint32_t xa = sb + OFF_X + (warp * 16 + (lane & 7)) * 128 + (((lane >> 3) ^ (lane & 7)) << 4);
      auto x_addr = [&](int i) { return (xa ^ ((i & 1) << 6)) + ((i >> 1) & 1) * 1024 + (i >> 2) * 16384; };
      auto x_piece = [&](int i) { const uint4 v = ldsm(x_addr(i)); pk[32 + 4 * i] = v.x; pk[33 + 4 * i] = v.y; pk[34 + 4 * i] = v.z; pk[35 + 4 * i] = v.w; };
      p2_step<0>(accs, c);
      p2_step<1>(accs, c);
      mbar_spin(sb + B_E1 + 8, 0, c.zero);
      send_piece(0); send_piece(1);
      p2_step<2>(accs, c); sched_fence(c.zero); send_piece(2); send_piece(3);
      p2_step<3>(accs, c); sched_fence(c.zero); send_piece(4); send_piece(5);
      p2_step<4>(accs, c); mbar_spin(sb + B_XT, 0, c.zero); send_piece(6); send_piece(7);
      p2_step<5>(accs, c); mbar_spin(sb + B_EX + 16 * wg, 0, c.zero); silu_piece(0); x_piece(0);
      p2_step<6>(accs, c); sched_fence(c.zero); silu_piece(1); x_piece(1);
      p2_step<7>(accs, c); sched_fence(c.zero); silu_piece(2); x_piece(2);
      p2_step<8>(accs, c); sched_fence(c.zero); silu_piece(3); x_piece(3);
      p2_step<9>(accs, c); mbar_spin(sb + B_EX + 16 * wg + 8, 0, c.zero); silu_piece(4); x_piece(4);
      p2_step<10>(accs, c); sched_fence(c.zero); silu_piece(5); x_piece(5);
      p2_step<11>(accs, c); sched_fence(c.zero); silu_piece(6); x_piece(6); x_piece(7);
      auto out_half = [&](const float* a, int h) {
#pragma unroll
        for (int i = 4 * h; i < 4 * h + 4; i++) {
          uint32_t v[4];
#pragma unroll
          for (int k = 0; k < 4; k++) { const int o = 2 * (4 * (i & 1) + k) + ((i >> 1) & 1); v[k] = fma2(pack2(a[2 * o], a[2 * o + 1]), pk[16 * h + o], pk[32 + 4 * i + k]); }
          asm volatile("stmatrix.sync.aligned.m8n8.x4.shared.b16 [%0], {%1,%2,%3,%4};" ::"r"(x_addr(i)), "r"(v[0]), "r"(v[1]), "r"(v[2]), "r"(v[3]) : "memory");
          if (i & 1) {
            asm volatile("fence.proxy.async.shared::cta;" ::: "memory");
            __syncwarp();
            if (elect_one()) tma3d_store(&mp.out, sb + OFF_X + h * 16384 + warp * 2048 + (i & 2) * 512, j2 * 128 + h * 64, m2 * 64 + w * 16 + (i & 2) * 4, wg);
          }
        }
      };
      if (wg == 1) silu_piece(7);
      p2_step<12>(accs, c); p2_step<13>(accs, c); p2_step<14>(accs, c); p2_step<15>(accs, c);
      if (c.do_rel) mbar_arrive(sb + B_DONE);
      if (wg == 0) silu_piece(7);
      wg_wait<0>();
      out_half(accs, 0); out_half(accs + 32, 1);
      if (elect_one()) { asm volatile("cp.async.bulk.commit_group;\ncp.async.bulk.wait_group.read 0;" ::: "memory"); }
      if ((threadIdx.x & 127) == 0) { TS(33 + wg * 16); if (wg) { TG(59); unsigned id; asm volatile("mov.u32 %0, %%smid;" : "=r"(id)); TSV(60, id); } }
    }
  }
}

typedef CUresult (*EncodeFn)(CUtensorMap*, CUtensorMapDataType, cuuint32_t, void*, const cuuint64_t*, const cuuint64_t*, const cuuint32_t*, const cuuint32_t*,
                             CUtensorMapInterleave, CUtensorMapSwizzle, CUtensorMapL2promotion, CUtensorMapFloatOOBfill);

void encode(EncodeFn fn, CUtensorMap* tm, const void* p, int rank, const cuuint64_t* dims, const cuuint64_t* strides, const cuuint32_t* box) {
  const cuuint32_t es[5] = {1, 1, 1, 1, 1};
  fn(tm, CU_TENSOR_MAP_DATA_TYPE_BFLOAT16, rank, const_cast<void*>(p), dims, strides, box, es, CU_TENSOR_MAP_INTERLEAVE_NONE, CU_TENSOR_MAP_SWIZZLE_128B,
     CU_TENSOR_MAP_L2_PROMOTION_L2_128B, CU_TENSOR_MAP_FLOAT_OOB_FILL_NONE);
}

}

extern "C" void kernel_launch(void* const* d_in, const int* in_sizes, int n_in, void* d_out, int out_size) {
  (void)in_sizes; (void)n_in; (void)out_size;
  static EncodeFn fn = nullptr;
  static Scratch* gs = nullptr;
  static int nsm = 0;
  if (!fn) {
    void* p = nullptr;
    cudaDriverEntryPointQueryResult qr;
    cudaGetDriverEntryPoint("cuTensorMapEncodeTiled", &p, cudaEnableDefault, &qr);
    fn = (EncodeFn)p;
    cudaGetSymbolAddress((void**)&gs, g_scratch);
    int dev = 0;
    cudaGetDevice(&dev);
    cudaDeviceGetAttribute(&nsm, cudaDevAttrMultiProcessorCount, dev);
    cudaFuncSetAttribute(fused_kernel, cudaFuncAttributeMaxDynamicSharedMemorySize, SMEM_BYTES);
  }
  const void *x = d_in[0], *wqkv = d_in[1], *wo = d_in[2], *wg = d_in[4], *wu = d_in[5], *wd = d_in[6];
  Maps mp;
  {
    const cuuint64_t dims[3] = {DM, SEQ / 2, 2}, st[2] = {DM * 4, DM * 2};
    const cuuint32_t box_in[3] = {64, 64, 2}, box_out[3] = {64, 8, 1};
    encode(fn, &mp.x, x, 3, dims, st, box_in);
    encode(fn, &mp.out, d_out, 3, dims, st, box_out);
  }
  {
    const cuuint64_t dims[2] = {DM, SEQ}, st[1] = {DM * 2};
    const cuuint32_t box[2] = {64, 128};
    encode(fn, &mp.xn, gs->xn, 2, dims, st, box);
  }
  {
    const cuuint32_t box[2] = {64, 64};
    const cuuint64_t dq[2] = {3 * DM, DM}, sq[1] = {3 * DM * 2}, df[2] = {DFF, DM}, sf[1] = {DFF * 2}, dw[2] = {DM, DM}, sw[1] = {DM * 2};
    encode(fn, &mp.wqkv, wqkv, 2, dq, sq, box);
    encode(fn, &mp.wg, wg, 2, df, sf, box);
    encode(fn, &mp.wu, wu, 2, df, sf, box);
    encode(fn, &mp.wo, wo, 2, dw, sw, box);
  }
  {
    const cuuint32_t box[5] = {64, 2, 4, 4, 2};
    const cuuint64_t st[4] = {DM * 2, 8 * DM * 2, 2 * DM * 2, 32 * DM * 2};
    const cuuint64_t dd[5] = {DM, 2, 4, 4, DFF / 32};
    encode(fn, &mp.wd, wd, 5, dd, st, box);
  }
  fused_kernel<<<NCTA, 384, SMEM_BYTES>>>((const uint4*)x, (const uint4*)wg, (const uint4*)wu, gs, nsm == NCTA, mp);
}
```

```cpp
#include <cuda_runtime.h>
#include <cuda_bf16.h>
#include <cuda.h>
#include <stdint.h>

#define CS_KB 8
#define LN_KB 4

namespace {

constexpr int SEQ = 2048, DM = 1024, DFF = 3584;
constexpr int NMAIN = 128, NCTA = 132;
constexpr uint64_t EVICT_FIRST = 0x12F0000000000000ull, EVICT_NORMAL = 0x1000000000000000ull;

constexpr uint32_t SM_BASE = 0x400;
constexpr uint32_t P1_BYTES = 49152, P2_BYTES = 32768;
constexpr uint32_t OFF_A = 131072;
__host__ __device__ constexpr uint32_t p2_a(int s) { return s == 0 ? OFF_A + 32768 : s == 1 ? OFF_A + 49152 : s == 2 ? 114688 : s == 3 ? 16384 : 49152; }
__host__ __device__ constexpr uint32_t p2_b(int s) { return s < 3 ? 65536 + s * 16384 : (s - 3) * 32768; }
constexpr uint32_t OFF_LAND = OFF_A;
constexpr uint32_t OFF_X = 196608;
constexpr uint32_t OFF_CS = OFF_X + 14336;
constexpr uint32_t OFF_BAR = 229376;
constexpr uint32_t B_F1 = OFF_BAR, B_E1 = B_F1 + 32, B_E2 = B_E1 + 32, B_DONE = B_E2 + 40, B_F2 = B_DONE + 8, B_DEP = B_F2 + 40, B_CS = B_DEP + 48,
                   B_XT = B_CS + 16, B_EP = B_XT + 8, B_EX = B_EP + 8, B_AUX = B_EX + 32, B_HALO = B_AUX + 8, OFF_EPOCH = B_HALO + 16;
constexpr uint32_t SMEM_BYTES = 232448;
constexpr uint32_t AT_V = 0, AT_K = 8192, AT_REM = 11264, AT_WG = 15360;

constexpr int FL_XN = 0, FL_H = 16, FL_P = 80, FL_HALO = 96, FL_N = FL_HALO + 256;
struct __align__(1024) Scratch {
  uint4 h[16 * 56 * 1024];
  uint4 o[16 * 16 * 1024];
  uint4 xn[SEQ * DM / 8];
  uint4 dpart[128 * 8 * 256];
  uint4 halo[2 * 128 * 2 * 128];
  ulonglong2 cspart[8 * 16 * 128];
  unsigned long long stats[SEQ];
  unsigned flags[FL_N * 32];
  unsigned epoch[NCTA * 2];
};
__device__ Scratch g_scratch;
#define TG(i) do {} while (0)
#define TSV(i, v) do {} while (0)
#define TS(i) do {} while (0)

__device__ __forceinline__ unsigned role_id(bool by_sm) {
  unsigned sm;
  asm volatile("mov.u32 %0, %%smid;" : "=r"(sm));
  const unsigned t = sm >> 1;
  const unsigned c = t < 60 ? (t < 32 ? t : t + 1 + ((t - 32) * 37 >> 8)) : (t < 62 ? t + 4 : 8 * t - 464);
  return by_sm ? 2 * c + (blockIdx.x & 1) : blockIdx.x;
}

struct Maps { CUtensorMap x, xn, out, wqkv, wg, wu, wd, wo; };

__device__ __forceinline__ void mbar_init(uint32_t bar, uint32_t cnt) { asm volatile("mbarrier.init.shared::cta.b64 [%0], %1;" ::"r"(bar), "r"(cnt)); }
__device__ __forceinline__ void mbar_expect_tx(uint32_t bar, uint32_t bytes) { asm volatile("mbarrier.arrive.expect_tx.shared::cta.b64 _, [%0], %1;" ::"r"(bar), "r"(bytes) : "memory"); }
__device__ __forceinline__ void mbar_arrive(uint32_t bar) { asm volatile("mbarrier.arrive.shared::cta.b64 _, [%0];" ::"r"(bar) : "memory"); }
__device__ __forceinline__ void mbar_arrive_cl(uint32_t bar) { asm volatile("mbarrier.arrive.shared::cluster.b64 _, [%0];" ::"r"(bar) : "memory"); }
__device__ __forceinline__ uint32_t mapa(uint32_t a, uint32_t cta) { uint32_t r; asm("mapa.shared::cluster.u32 %0, %1, %2;" : "=r"(r) : "r"(a), "r"(cta)); return r; }
__device__ __forceinline__ void mbar_wait(uint32_t bar, uint32_t parity) {
  asm volatile("{\n.reg .pred p;\n.reg .u32 n;\nmov.u32 n, 0;\nLAB_WAIT:\nmbarrier.try_wait.parity.shared::cta.b64 p, [%0], %1;\n@p bra LAB_DONE;\n"
               "add.u32 n, n, 1;\nsetp.gt.u32 p, n, 4000000;\n@p trap;\nbra LAB_WAIT;\nLAB_DONE:\n}" ::"r"(bar), "r"(parity) : "memory");
}
__device__ __forceinline__ void mbar_spin(uint32_t bar, uint32_t parity, uint32_t zero) {
  asm volatile("{\n.reg .pred p, z;\nsetp.ne.u32 z, %2, 0;\nLAB_WAIT:\nmbarrier.try_wait.parity.shared::cta.b64 p, [%0], %1;\n@p bra LAB_DONE;\n@z trap;\nbra LAB_WAIT;\nLAB_DONE:\n}" ::"r"(bar), "r"(parity), "r"(zero) : "memory");
}
__device__ __forceinline__ void flag_wait(const unsigned* f, unsigned target) {
  asm volatile("{\n.reg .pred p;\n.reg .u32 n, v;\nmov.u32 n, 0;\nLAB_WAIT:\nld.relaxed.gpu.global.u32 v, [%0];\nsub.u32 v, v, %1;\nsetp.ge.s32 p, v, 0;\n@p bra LAB_DONE;\n"
               "nanosleep.u32 200;\nadd.u32 n, n, 1;\nsetp.gt.u32 p, n, 4000000;\n@p trap;\nbra LAB_WAIT;\nLAB_DONE:\nfence.acquire.gpu;\n}" ::"l"(f), "r"(target) : "memory");
}
__device__ __forceinline__ void flag_add(unsigned* f) { asm volatile("red.release.gpu.global.add.u32 [%0], 1;" ::"l"(f) : "memory"); }
__device__ __forceinline__ void fence_async() { asm volatile("fence.proxy.async.global;" ::: "memory"); }
__device__ __forceinline__ bool elect_one() { uint32_t p; asm volatile("{\n.reg .pred P;\nelect.sync _|P, 0xffffffff;\nselp.u32 %0, 1, 0, P;\n}" : "=r"(p)); return p; }
__device__ __forceinline__ void bar_sync(int id, int n) { asm volatile("bar.sync %0, %1;" ::"r"(id), "r"(n) : "memory"); }
__device__ __forceinline__ void bar_arrive(int id, int n) { asm volatile("bar.arrive %0, %1;" ::"r"(id), "r"(n) : "memory"); }

__device__ __forceinline__ void tma2d(uint32_t dst, const CUtensorMap* tm, uint32_t bar, int c0, int c1, uint64_t hint) {
  asm volatile("cp.async.bulk.tensor.2d.shared::cluster.global.mbarrier::complete_tx::bytes.L2::cache_hint [%0], [%1, {%3, %4}], [%2], %5;" ::"r"(dst), "l"(tm), "r"(bar), "r"(c0), "r"(c1), "l"(hint) : "memory");
}
__device__ __forceinline__ void tma2d_mc(uint32_t dst, const CUtensorMap* tm, uint32_t bar, int c0, int c1, uint64_t hint) {
  asm volatile("cp.async.bulk.tensor.2d.shared::cluster.global.mbarrier::complete_tx::bytes.multicast::cluster.L2::cache_hint [%0], [%1, {%3, %4}], [%2], %5, %6;" ::"r"(dst), "l"(tm), "r"(bar), "r"(c0), "r"(c1), "h"((uint16_t)3), "l"(hint) : "memory");
}
__device__ __forceinline__ void tma3d(uint32_t dst, const CUtensorMap* tm, uint32_t bar, int c0, int c1, int c2, uint64_t hint) {
  asm volatile("cp.async.bulk.tensor.3d.shared::cluster.global.mbarrier::complete_tx::bytes.L2::cache_hint [%0], [%1, {%3, %4, %5}], [%2], %6;" ::"r"(dst), "l"(tm), "r"(bar), "r"(c0), "r"(c1), "r"(c2), "l"(hint) : "memory");
}
__device__ __forceinline__ void tma5d(uint32_t dst, const CUtensorMap* tm, uint32_t bar, int c0, int c4, uint64_t hint) {
  asm volatile("cp.async.bulk.tensor.5d.shared::cluster.global.mbarrier::complete_tx::bytes.L2::cache_hint [%0], [%1, {%3, %5, %5, %5, %4}], [%2], %6;" ::"r"(dst), "l"(tm), "r"(bar), "r"(c0), "r"(c4), "r"(0), "l"(hint) : "memory");
}
__device__ __forceinline__ void tma3d_store(const CUtensorMap* tm, uint32_t src, int c0, int c1, int c2) {
  asm volatile("cp.async.bulk.tensor.3d.global.shared::cta.bulk_group.L2::cache_hint [%0, {%2, %3, %4}], [%1], %5;" ::"l"(tm), "r"(src), "r"(c0), "r"(c1), "r"(c2), "l"(EVICT_FIRST) : "memory");
}
__device__ __forceinline__ void bulk_load(uint32_t dst, const void* src, uint32_t bytes, uint32_t bar, uint64_t hint) {
  asm volatile("cp.async.bulk.shared::cluster.global.mbarrier::complete_tx::bytes.L2::cache_hint [%0], [%1], %2, [%3], %4;" ::"r"(dst), "l"(src), "r"(bytes), "r"(bar), "l"(hint) : "memory");
}
__device__ __forceinline__ void bulk_load_mc(uint32_t dst, const void* src, uint32_t bytes, uint32_t bar, uint64_t hint) {
  asm volatile("cp.async.bulk.shared::cluster.global.mbarrier::complete_tx::bytes.multicast::cluster.L2::cache_hint [%0], [%1], %2, [%3], %4, %5;" ::"r"(dst), "l"(src), "r"(bytes), "r"(bar), "h"((uint16_t)3), "l"(hint) : "memory");
}
__device__ __forceinline__ uint4 lds128(uint32_t a) { uint4 v; asm volatile("ld.shared.v4.b32 {%0,%1,%2,%3}, [%4];" : "=r"(v.x), "=r"(v.y), "=r"(v.z), "=r"(v.w) : "r"(a) : "memory"); return v; }
__device__ __forceinline__ void sts128(uint32_t a, uint4 v) { asm volatile("st.shared.v4.b32 [%0], {%1,%2,%3,%4};" ::"r"(a), "r"(v.x), "r"(v.y), "r"(v.z), "r"(v.w) : "memory"); }
__device__ __forceinline__ void stg128(void* p, uint32_t a, uint32_t b, uint32_t c, uint32_t d) { asm volatile("st.global.v4.b32 [%0], {%1,%2,%3,%4};" ::"l"(p), "r"(a), "r"(b), "r"(c), "r"(d) : "memory"); }

__device__ __forceinline__ uint32_t pack2(float lo, float hi) { uint32_t r; asm("cvt.rn.bf16x2.f32 %0, %1, %2;" : "=r"(r) : "f"(hi), "f"(lo)); return r; }
__device__ __forceinline__ float lo_f(uint32_t v) { return __uint_as_float(v << 16); }
__device__ __forceinline__ float hi_f(uint32_t v) { return __uint_as_float(v & 0xffff0000u); }
__device__ __forceinline__ float bf16r(float v) { return lo_f(pack2(v, 0.f)); }
__device__ __forceinline__ uint32_t mul2(uint32_t a, uint32_t b) { uint32_t r; asm("mul.rn.bf16x2 %0, %1, %2;" : "=r"(r) : "r"(a), "r"(b)); return r; }
__device__ __forceinline__ uint32_t add2(uint32_t a, uint32_t b) { uint32_t r; asm("add.rn.bf16x2 %0, %1, %2;" : "=r"(r) : "r"(a), "r"(b)); return r; }
__device__ __forceinline__ uint32_t sub2(uint32_t a, uint32_t b) { uint32_t r; asm("sub.rn.bf16x2 %0, %1, %2;" : "=r"(r) : "r"(a), "r"(b)); return r; }
__device__ __forceinline__ uint32_t fma2(uint32_t a, uint32_t b, uint32_t c) { uint32_t r; asm("fma.rn.bf16x2 %0, %1, %2, %3;" : "=r"(r) : "r"(a), "r"(b), "r"(c)); return r; }
__device__ __forceinline__ uint32_t max2(uint32_t a, uint32_t b) { uint32_t r; asm("max.bf16x2 %0, %1, %2;" : "=r"(r) : "r"(a), "r"(b)); return r; }
__device__ __forceinline__ float ex2f(float x) { float y; asm("ex2.approx.ftz.f32 %0, %1;" : "=f"(y) : "f"(x)); return y; }
__device__ __forceinline__ float rcpf(float x) { float y; asm("rcp.approx.ftz.f32 %0, %1;" : "=f"(y) : "f"(x)); return y; }
constexpr float GELU_C1 = 0.7978845608028654f, GELU_C3 = 0.035677408136300125f;
__device__ __forceinline__ float gelu_k(float g, float c1, float c3, float k) {
  float t;
  asm("tanh.approx.f32 %0, %1;" : "=f"(t) : "f"(g * fmaf(g * g, c3, c1)));
  g *= k;
  return fmaf(g, t, g);
}
__device__ __forceinline__ float silu_half(float z) { float t; asm("tanh.approx.f32 %0, %1;" : "=f"(t) : "f"(z)); return fmaf(z, t, z); }

__device__ __forceinline__ void wg_fence() { asm volatile("wgmma.fence.sync.aligned;" ::: "memory"); }
__device__ __forceinline__ void wg_commit() { asm volatile("wgmma.commit_group.sync.aligned;" ::: "memory"); }
template <int N> __device__ __forceinline__ void wg_wait() { asm volatile("wgmma.wait_group.sync.aligned %0;" ::"n"(N) : "memory"); }
#define A8(o) "+f"(d[(o)]), "+f"(d[(o) + 1]), "+f"(d[(o) + 2]), "+f"(d[(o) + 3]), "+f"(d[(o) + 4]), "+f"(d[(o) + 5]), "+f"(d[(o) + 6]), "+f"(d[(o) + 7])
#define A64(o) A8(o), A8((o) + 8), A8((o) + 16), A8((o) + 24), A8((o) + 32), A8((o) + 40), A8((o) + 48), A8((o) + 56)
#define REGS0_63 "%0,%1,%2,%3,%4,%5,%6,%7,%8,%9,%10,%11,%12,%13,%14,%15,%16,%17,%18,%19,%20,%21,%22,%23,%24,%25,%26,%27,%28,%29,%30,%31," \
                 "%32,%33,%34,%35,%36,%37,%38,%39,%40,%41,%42,%43,%44,%45,%46,%47,%48,%49,%50,%51,%52,%53,%54,%55,%56,%57,%58,%59,%60,%61,%62,%63"
#define REGS64_127 "%64,%65,%66,%67,%68,%69,%70,%71,%72,%73,%74,%75,%76,%77,%78,%79,%80,%81,%82,%83,%84,%85,%86,%87,%88,%89,%90,%91,%92,%93,%94,%95," \
                   "%96,%97,%98,%99,%100,%101,%102,%103,%104,%105,%106,%107,%108,%109,%110,%111,%112,%113,%114,%115,%116,%117,%118,%119,%120,%121,%122,%123,%124,%125,%126,%127"
__device__ __forceinline__ void desc_add(uint64_t& x, int v) { asm volatile("{\n.reg .b32 lo, hi;\nmov.b64 {lo, hi}, %0;\nadd.s32 lo, lo, %1;\nmov.b64 %0, {lo, hi};\n}" : "+l"(x) : "r"(v)); }
template <int ACCUM> __device__ __forceinline__ void wgmma256(float (&d)[128], uint64_t& a, uint64_t& b, int da, int db) {
  asm volatile("{\n.reg .pred p;\nsetp.ne.b32 p, %130, 0;\n"
               "wgmma.mma_async.sync.aligned.m64n256k16.f32.bf16.bf16 {" REGS0_63 "," REGS64_127 "}, %128, %129, p, 1, 1, 0, 1;\n}"
               : A64(0), A64(64) : "l"(a), "l"(b), "n"(ACCUM));
  desc_add(a, da); desc_add(b, db);
}
__device__ __forceinline__ void wgmma256_rs(float (&d)[128], uint32_t a0, uint32_t a1, uint32_t z0, uint32_t z1, uint32_t b_lo) {
  asm volatile("{\n.reg .b64 db;\nmov.b64 db, {%132, 0x00000008};\n"
               "wgmma.mma_async.sync.aligned.m64n256k16.f32.bf16.bf16 {" REGS0_63 "," REGS64_127 "}, {%128,%129,%130,%131}, db, 1, 1, 1, 0;\n}"
               : A64(0), A64(64) : "r"(a0), "r"(a1), "r"(z0), "r"(z1), "r"(b_lo));
}
template <int ACCUM> __device__ __forceinline__ void wgmma128(float (&d)[64], uint64_t& a, uint64_t& b, int da, int db) {
  asm volatile("{\n.reg .pred p;\nsetp.ne.b32 p, %66, 0;\n"
               "wgmma.mma_async.sync.aligned.m64n128k16.f32.bf16.bf16 {" REGS0_63 "}, %64, %65, p, 1, 1, 0, 1;\n}"
               : A64(0) : "l"(a), "l"(b), "n"(ACCUM));
  desc_add(a, da); desc_add(b, db);
}
template <int ACCUM> __device__ __forceinline__ void hmma(float (&c)[4], uint32_t a0, uint32_t a1, uint32_t a2, uint32_t a3, uint32_t b0, uint32_t b1) {
  if (ACCUM)
    asm volatile("mma.sync.aligned.m16n8k16.row.col.f32.bf16.bf16.f32 {%0,%1,%2,%3}, {%4,%5,%6,%7}, {%8,%9}, {%0,%1,%2,%3};"
                 : "+f"(c[0]), "+f"(c[1]), "+f"(c[2]), "+f"(c[3]) : "r"(a0), "r"(a1), "r"(a2), "r"(a3), "r"(b0), "r"(b1));
  else
    asm volatile("mma.sync.aligned.m16n8k16.row.col.f32.bf16.bf16.f32 {%0,%1,%2,%3}, {%4,%5,%6,%7}, {%8,%9}, {%10,%10,%10,%10};"
                 : "=f"(c[0]), "=f"(c[1]), "=f"(c[2]), "=f"(c[3]) : "r"(a0), "r"(a1), "r"(a2), "r"(a3), "r"(b0), "r"(b1), "f"(0.f));
}
__device__ __forceinline__ uint32_t movm(uint32_t a) { uint32_t d; asm volatile("movmatrix.sync.aligned.m8n8.trans.b16 %0, %1;" : "=r"(d) : "r"(a)); return d; }
__device__ __forceinline__ int lane_here() { int v; asm volatile("mov.u32 %0, %%laneid;" : "=r"(v)); return v; }
template <int N> __device__ __forceinline__ void pin(uint32_t* r) {
#pragma unroll
  for (int i = 0; i < N; i++) asm volatile("" : "+r"(r[i]));
}
template <int N> __device__ __forceinline__ void pin(float* r) {
#pragma unroll
  for (int i = 0; i < N; i++) asm volatile("" : "+f"(r[i]));
}
__device__ __forceinline__ void sched_fence(uint32_t zero) {
  asm volatile("{\n.reg .pred p;\nsetp.eq.u32 p, %0, 0;\nLAB_F:\n@p bra.uni LAB_D;\nnanosleep.u32 0;\nbra.uni LAB_F;\nLAB_D:\n}" ::"r"(zero) : "memory");
}
__device__ __forceinline__ uint4 ldsm(uint32_t a) { uint4 v; asm volatile("ldmatrix.sync.aligned.m8n8.x4.shared.b16 {%0,%1,%2,%3}, [%4];" : "=r"(v.x), "=r"(v.y), "=r"(v.z), "=r"(v.w) : "r"(a) : "memory"); return v; }
__device__ __forceinline__ uint4 ldsm_t(uint32_t a) { uint4 v; asm volatile("ldmatrix.sync.aligned.m8n8.x4.trans.shared.b16 {%0,%1,%2,%3}, [%4];" : "=r"(v.x), "=r"(v.y), "=r"(v.z), "=r"(v.w) : "r"(a) : "memory"); return v; }

constexpr int BAR_LAG = 1, BAR_MMA = 2, BAR_EV = 3;

struct Cons {
  uint32_t sb;
  mutable uint64_t a, b;
  int k1, k2, k4, k4w, b1;
  uint32_t rel;
  bool do_rel;
  int wg;
  uint32_t zero;
};
#define REL_TS(n) TS(64 + (n))
constexpr uint32_t DB_LO = (SM_BASE >> 4) | ((8192 >> 4) << 16);

template <int ST, int ACCUM, bool WAIT = true> __device__ __forceinline__ void p1_issue(float (&acc)[128], const Cons& c, uint32_t parity) {
  if (WAIT) mbar_spin(c.sb + B_F1 + 8 * ST, parity, c.zero);
  wg_fence();
  wgmma256<ACCUM>(acc, c.a, c.b, c.k1, c.b1);
  wgmma256<1>(acc, c.a, c.b, c.k2, c.b1);
  wgmma256<1>(acc, c.a, c.b, c.k1, c.b1);
  wgmma256<1>(acc, c.a, c.b, ST == 3 ? c.k4w : c.k4, ST == 3 ? -6144 - 384 : 2048 - 384);
  wg_commit();
}
__device__ __forceinline__ void release(const Cons& c, uint32_t bar) { if (c.do_rel) mbar_arrive_cl(c.rel + bar); }
template <int KB, bool WAIT = true> __device__ __forceinline__ void p1_step(float (&acc)[128], const Cons& c) {
  if (KB == 15) { if (c.wg == 1) { wg_wait<0>(); release(c, B_E1 + 16); bar_sync(BAR_LAG, 256); } }
  p1_issue<KB & 3, KB != 0, WAIT>(acc, c, (KB >> 2) & 1);
  if (KB == 15) { if (c.wg == 0) bar_arrive(BAR_LAG, 256); }
  if (KB > 0) { wg_wait<1>(); if (KB != 15 || c.wg == 0) release(c, B_E1 + 8 * ((KB - 1) & 3)); }
  if (KB == 15) { wg_wait<0>(); release(c, B_E1 + 24); }
}
template <class F> __device__ __forceinline__ void p1_loop(float (&acc)[128], const Cons& c, int from, int to, F&& shadow) {
#pragma unroll 1
  for (int kb = from; kb < to; kb++) {
    const bool wrap = (kb & 3) == 3;
    mbar_spin(c.sb + B_F1 + 8 * (kb & 3), (kb >> 2) & 1, c.zero);
    wg_fence();
    wgmma256<1>(acc, c.a, c.b, c.k1, c.b1);
    wgmma256<1>(acc, c.a, c.b, c.k2, c.b1);
    wgmma256<1>(acc, c.a, c.b, c.k1, c.b1);
    wgmma256<1>(acc, c.a, c.b, wrap ? c.k4w : c.k4, wrap ? -6144 - 384 : 2048 - 384);
    wg_commit();
    wg_wait<1>();
    release(c, B_E1 + 8 * ((kb - 1) & 3));
    shadow(kb);
  }
}
template <int T> __device__ __forceinline__ void p2_step(float (&acc)[64], const Cons& c) {
  if (T == 12) { if (c.wg == 1) bar_sync(BAR_LAG, 256); }
  mbar_spin(c.sb + B_F2 + 8 * (T % 5), (T / 5) & 1, c.zero);
  wg_fence();
  wgmma128<T != 0>(acc, c.a, c.b, c.k1, c.b1);
  wgmma128<1>(acc, c.a, c.b, c.k2, c.b1);
  wgmma128<1>(acc, c.a, c.b, c.k1, c.b1);
  wgmma128<1>(acc, c.a, c.b, ((int)p2_a((T + 1) % 5) - (int)p2_a(T % 5)) / 16 - 514, ((int)p2_b((T + 1) % 5) - (int)p2_b(T % 5)) / 16 - 384);
  wg_commit();
  if (T == 15) { if (c.wg == 0) bar_arrive(BAR_LAG, 256); }
  if (T <= 11) { wg_wait<1>(); release(c, T ? B_E2 + 8 * ((T + 4) % 5) : B_E1 + 8); }
}

template <int P> __device__ __forceinline__ void geglu_piece(uint32_t (&pk)[64], uint8_t* dst, float (&rs)[2]) {
  constexpr int cg = P >> 1, r = P & 1;
  pin<1>(rs + r);
#pragma unroll
  for (int i = 0; i < 4; i++) pin<1>(pk + 2 * (4 * cg + i) + r);
  const float r2 = rs[r] * rs[r], c1 = GELU_C1 * rs[r], c3 = GELU_C3 * r2 * rs[r], k = 0.25f * r2;
  uint32_t v[4];
#pragma unroll
  for (int i = 0; i < 4; i++) {
    const uint32_t g = pk[2 * (4 * cg + i) + r];
    v[i] = mul2(pack2(gelu_k(lo_f(g), c1, c3, k), gelu_k(hi_f(g), c1, c3, k)), pk[32 + 2 * (4 * cg + i) + r]);
  }
  stg128(dst + cg * 8192 + r * 512, v[0], v[1], v[2], v[3]);
}
__device__ __forceinline__ void geglu_tile(float (&acc)[128], uint32_t (&pk)[64], const Cons& c, int to, uint8_t* dst, int ev, float (&rs)[2]) {
  const int lane = lane_here();
  dst += (lane ^ (lane >> 3)) << 4;
  p1_loop(acc, c, 1, to, [&](int kb) {
    if (kb <= 4) {
      if (kb <= 2) { if (kb == 1) geglu_piece<0>(pk, dst, rs); else geglu_piece<1>(pk, dst, rs); }
      else { if (kb == 3) geglu_piece<2>(pk, dst, rs); else geglu_piece<3>(pk, dst, rs); }
    } else if (kb <= 8) {
      if (kb <= 6) { if (kb == 5) geglu_piece<4>(pk, dst, rs); else geglu_piece<5>(pk, dst, rs); }
      else { if (kb == 7) geglu_piece<6>(pk, dst, rs); else { geglu_piece<7>(pk, dst, rs); bar_arrive(ev, 288); } }
    }
  });
}

__device__ __forceinline__ void attn_tile(float (&acc)[128], uint32_t (&pk)[64], const Cons& c, int round, int warp, int m, unsigned bid, Scratch* gs, uint8_t* hdst, uint8_t* odst) {
  const int w = warp & 3;
  const uint32_t at = c.sb + OFF_X + c.wg * AT_WG;
  int lane = lane_here();
  hdst += (lane ^ (lane >> 3)) << 4;
  auto scatter = [&]() {
    const int lane = lane_here();
    const uint32_t swz = (lane ^ (lane >> 3)) << 4;
#pragma unroll
    for (int i = 0; i < 4; i++) {
      const int h = i & 1, r = i >> 1;
      sts128(at + AT_V + (2 * w + r) * 1024 + h * 512 + swz, make_uint4(pk[32 + 8 * h + r], pk[34 + 8 * h + r], pk[36 + 8 * h + r], pk[38 + 8 * h + r]));
    }
    if (w < 3) {
#pragma unroll
      for (int i = 0; i < 8; i++) asm volatile("st.shared.b32 [%0], %1;" ::"r"(at + AT_K + w * 1024 + i * 128 + lane * 4), "r"(pk[17 + 2 * i]) : "memory");
    } else {
      uint8_t* g = (uint8_t*)gs->halo + ((round * 128 + bid) * 2 + c.wg) * 2048;
#pragma unroll
      for (int i = 0; i < 8; i++) asm volatile("st.global.b32 [%0], %1;" ::"l"(g + i * 128 + lane * 4), "r"(pk[17 + 2 * i]) : "memory");
#pragma unroll
      for (int h = 0; h < 2; h++) stg128(g + 1024 + h * 512 + swz, pk[33 + 8 * h], pk[35 + 8 * h], pk[37 + 8 * h], pk[39 + 8 * h]);
      bar_arrive(BAR_EV + 2 + round, 96);
    }
    __syncwarp();
    if (lane == 0) mbar_arrive(c.sb + B_HALO + 8 * round);
    if (round) {
#pragma unroll
      for (int p = 0; p < 4; p++) {
        const int o = 32 + 8 * (p >> 1) + (p & 1);
        asm volatile("ld.global.cg.v4.b32 {%0,%1,%2,%3}, [%4];" : "=r"(pk[o]), "=r"(pk[o + 2]), "=r"(pk[o + 4]), "=r"(pk[o + 6]) : "l"(hdst + (p >> 1) * 8192 + (p & 1) * 512) : "memory");
      }
    }
  };
  auto gu_piece = [&](int p) {
    uint32_t v[4];
#pragma unroll
    for (int i = 0; i < 4; i++) {
      const int o = 8 * (p >> 1) + 2 * i + (p & 1);
      pin<1>(pk + 48 + o);
      const uint32_t g = pk[48 + o];
      v[i] = mul2(round ? pk[32 + o] : 0x3e803e80u, round ? g : pack2(gelu_k(lo_f(g), GELU_C1, GELU_C3, 1.0f), gelu_k(hi_f(g), GELU_C1, GELU_C3, 1.0f)));
    }
    stg128(hdst + (p >> 1) * 8192 + (p & 1) * 512, v[0], v[1], v[2], v[3]);
  };
  p1_step<1>(acc, c);
  scatter();
  p1_loop(acc, c, 2, 9, [&](int kb) {
    if (kb <= 4) { if (kb == 3) gu_piece(0); else if (kb == 4) gu_piece(1); }
    else if (kb == 5) gu_piece(2); else if (kb == 6) gu_piece(3);
  });
  const bool first = m == 0 && w == 0;
  uint32_t kl[16];
  mbar_spin(c.sb + B_HALO + 8 * round, 0, c.zero);
  lane = lane_here();
  {
    const uint32_t ka = at + lane * 4 + (w ? AT_K + (w - 1) * 1024 : (first ? AT_K : AT_REM + round * 2048));
#pragma unroll
    for (int i = 0; i < 8; i++) {
      asm volatile("ld.shared.b32 %0, [%1];" : "=r"(kl[2 * i]) : "r"(ka + i * 128) : "memory");
      kl[2 * i + 1] = pk[16 + 2 * i] | c.zero;
    }
  }
  float st[4][4];
  pin<16>(kl);
  bar_sync(BAR_MMA, 256);
  mbar_spin(c.sb + B_F1 + 8 * 1, 0, c.zero);
#pragma unroll
  for (int ks = 0; ks < 2; ks++) {
#pragma unroll
    for (int h = 0; h < 2; h++) {
      const int o = 8 * h + 4 * ks;
      if (ks == 0) { hmma<0>(st[2 * h], kl[o], kl[o + 1], kl[o + 2], kl[o + 3], pk[o], pk[o + 2]); hmma<0>(st[2 * h + 1], pk[16 + o], pk[17 + o], pk[18 + o], pk[19 + o], pk[o + 1], pk[o + 3]); }
      else { hmma<1>(st[2 * h], kl[o], kl[o + 1], kl[o + 2], kl[o + 3], pk[o], pk[o + 2]); hmma<1>(st[2 * h + 1], pk[16 + o], pk[17 + o], pk[18 + o], pk[19 + o], pk[o + 1], pk[o + 3]); }
    }
  }
  sched_fence(c.zero);
  bar_sync(BAR_MMA, 256);
  p1_step<9, false>(acc, c);
  sched_fence(c.zero);
  pin<16>(&st[0][0]);
  lane = lane_here();
  const int rho = lane >> 2, q = lane & 3;
  const bool le0 = 2 * q <= rho, le1 = 2 * q + 1 <= rho;
  uint32_t la[2], lb[2], mx[2];
#pragma unroll
  for (int h = 0; h < 2; h++) {
    uint32_t l[2];
#pragma unroll
    for (int r = 0; r < 2; r++) {
      const float (&t)[4] = st[2 * h + r];
      l[r] = movm(pack2(rho <= 2 * q ? t[2] : t[0], rho <= 2 * q + 1 ? t[3] : t[1]));
      l[r] = fma2(l[r], 0x3e353e35u, mul2(l[r], 0x379e379eu));
    }
    la[h] = __byte_perm(l[0], l[1], 0x5410); lb[h] = __byte_perm(l[0], l[1], 0x7632);
    if (first && !le0) la[h] = (la[h] & 0xffff0000u) | 0xce6eu;
    if (first && !le1) lb[h] = (lb[h] & 0xffff0000u) | 0xce6eu;
    mx[h] = max2(la[h], lb[h]);
  }
#pragma unroll
  for (int o = 1; o <= 2; o++) { mx[0] = max2(mx[0], __shfl_xor_sync(~0u, mx[0], o)); mx[1] = max2(mx[1], __shfl_xor_sync(~0u, mx[1], o)); }
  const float L2E = 1.4426950408889634f;
  float pr[2][4], z[4];
#pragma unroll
  for (int h = 0; h < 2; h++) {
    pr[h][0] = ex2f((lo_f(la[h]) - lo_f(mx[h])) * L2E); pr[h][1] = ex2f((lo_f(lb[h]) - lo_f(mx[h])) * L2E);
    pr[h][2] = ex2f((hi_f(la[h]) - hi_f(mx[h])) * L2E); pr[h][3] = ex2f((hi_f(lb[h]) - hi_f(mx[h])) * L2E);
    z[2 * h] = pr[h][0] + pr[h][1]; z[2 * h + 1] = pr[h][2] + pr[h][3];
  }
  p1_step<10>(acc, c);
#pragma unroll
  for (int o = 1; o <= 2; o++) {
#pragma unroll
    for (int i = 0; i < 4; i++) z[i] += __shfl_xor_sync(~0u, z[i], o);
  }
  const uint32_t LE = (le0 ? 0xffffu : 0u) | (le1 ? 0xffff0000u : 0u);
  uint32_t P[4][2];
  uint4 vt[4][2];
  {
    const uint32_t row = (lane & 7) * 64 + ((((lane >> 3) & 1) ^ ((lane & 7) >> 1)) << 4);
    const uint32_t v1 = at + AT_V + (2 * w + (lane >> 4)) * 1024 + row;
    const uint32_t v0 = (w || lane >= 16) ? v1 - 1024 : (first ? v1 : at + AT_REM + round * 2048 + 1024 + row);
#pragma unroll
    for (int i = 0; i < 4; i++) {
      const float rz = rcpf(z[i]);
      const uint32_t p = pack2(pr[i >> 1][2 * (i & 1)] * rz, pr[i >> 1][2 * (i & 1) + 1] * rz);
      P[i][0] = p & ~LE; P[i][1] = p & LE;
      const uint32_t a = ((i & 1) ? v1 : v0) + (i >> 1) * 512;
      vt[i][0] = ldsm_t(a); vt[i][1] = ldsm_t(a ^ 32);
    }
  }
  float ot[4][2][4];
  pin<8>(&P[0][0]);
  bar_sync(BAR_MMA, 256);
  mbar_spin(c.sb + B_F1 + 8 * 3, 0, c.zero);
#pragma unroll
  for (int i = 0; i < 8; i++) { const uint4& v = vt[i >> 1][i & 1]; hmma<0>(ot[i >> 1][i & 1], v.x, v.y, v.z, v.w, P[i >> 1][0], P[i >> 1][1]); }
  sched_fence(c.zero);
  bar_sync(BAR_MMA, 256);
  p1_step<11, false>(acc, c);
  sched_fence(c.zero);
  pin<32>(&ot[0][0][0]);
  lane = lane_here();
  odst += (lane ^ (lane >> 3)) << 4;
  auto o_piece = [&](int i) {
    stg128(odst + (i >> 1) * 8192 + (i & 1) * 512, movm(pack2(ot[i][0][0], ot[i][0][1])), movm(pack2(ot[i][0][2], ot[i][0][3])), movm(pack2(ot[i][1][0], ot[i][1][1])), movm(pack2(ot[i][1][2], ot[i][1][3])));
  };
  o_piece(0); o_piece(1);
  p1_step<12>(acc, c);
  o_piece(2); o_piece(3);
  if (round) bar_arrive(BAR_EV + 4, 288);
  p1_step<13>(acc, c);
}

__device__ __forceinline__ void ln_moments(const uint32_t* raw, float& c0, float& s, float& v) {
  c0 = lo_f(__shfl_sync(~0u, raw[0], 0));
  float ss[4] = {0.f, 0.f, 0.f, 0.f}, vv[4] = {0.f, 0.f, 0.f, 0.f};
#pragma unroll
  for (int i = 0; i < 16; i++) {
    const float a = lo_f(raw[i]) - c0, b = hi_f(raw[i]) - c0;
    ss[(2 * i) & 3] += a; ss[(2 * i + 1) & 3] += b;
    vv[(2 * i) & 3] = fmaf(a, a, vv[(2 * i) & 3]); vv[(2 * i + 1) & 3] = fmaf(b, b, vv[(2 * i + 1) & 3]);
  }
  s = (ss[0] + ss[1]) + (ss[2] + ss[3]); v = (vv[0] + vv[1]) + (vv[2] + vv[3]);
}
__device__ __forceinline__ void ln_reduce(float& s, float& v) {
#pragma unroll
  for (int o = 16; o; o >>= 1) { s += __shfl_xor_sync(~0u, s, o); v += __shfl_xor_sync(~0u, v, o); }
}
__device__ __forceinline__ uint32_t ln_finish(float c0, float s, float v) {
  s *= 1.0f / DM;
  float sd;
  asm("sqrt.approx.ftz.f32 %0, %1;" : "=f"(sd) : "f"(bf16r(bf16r(fmaxf(fmaf(v, 1.0f / DM, -s * s), 0.f)) + 1e-5f)));
  return pack2(c0 + s, sd);
}
__device__ __forceinline__ void ln_store(const uint32_t* raw, uint32_t st, uint4* dst) {
  const uint32_t m2 = __byte_perm(st, st, 0x1010);
  const float rinv = rcpf(hi_f(st));
  const uint32_t rh = pack2(rinv, rinv), rl = pack2(rinv - hi_f(rh), rinv - hi_f(rh));
#pragma unroll
  for (int c = 0; c < 4; c++) {
    uint32_t v[4];
#pragma unroll
    for (int i = 0; i < 4; i++) { const uint32_t t = sub2(raw[4 * c + i], m2); v[i] = fma2(t, rh, mul2(t, rl)); }
    stg128(dst + 32 * c, v[0], v[1], v[2], v[3]);
  }
}
__device__ __forceinline__ void col_sums(uint32_t tile, ulonglong2* part, uint32_t tag) {
  const int lane = threadIdx.x & 31;
  float cs[8] = {0, 0, 0, 0, 0, 0, 0, 0};
  uint32_t base = tile + ((lane >> 3) & 1) * 8192 + (lane >> 4) * 4096 + ((lane & 7) << 4);
#pragma unroll 1
  for (int k0 = 0; k0 < 8; k0++, base = (base ^ ((k0 ^ (k0 - 1)) << 4)) + 128) {
    uint4 v[4];
#pragma unroll
    for (int k = 0; k < 4; k++) v[k] = lds128(base + k * 1024);
#pragma unroll
    for (int k = 0; k < 4; k++) {
      cs[0] += lo_f(v[k].x); cs[1] += hi_f(v[k].x); cs[2] += lo_f(v[k].y); cs[3] += hi_f(v[k].y);
      cs[4] += lo_f(v[k].z); cs[5] += hi_f(v[k].z); cs[6] += lo_f(v[k].w); cs[7] += hi_f(v[k].w);
    }
  }
  const bool up = lane >= 16;
#pragma unroll
  for (int i = 0; i < 2; i++) {
    const float a = (up ? cs[4 + 2 * i] : cs[2 * i]) + __shfl_xor_sync(~0u, up ? cs[2 * i] : cs[4 + 2 * i], 16);
    const float b = (up ? cs[5 + 2 * i] : cs[1 + 2 * i]) + __shfl_xor_sync(~0u, up ? cs[1 + 2 * i] : cs[5 + 2 * i], 16);
    asm volatile("{\n.reg .b64 a, b;\nmov.b64 a, {%1, %3};\nmov.b64 b, {%2, %3};\nst.relaxed.gpu.global.v2.b64 [%0], {a, b};\n}"
                 ::"l"(part + 32 * (i + (up ? 2 : 0)) + (lane & 15)), "r"(__float_as_uint(a)), "r"(__float_as_uint(b)), "r"(tag) : "memory");
  }
  asm volatile("fence.proxy.async.shared::cta;" ::: "memory");
}

__global__ void __cluster_dims__(2, 1, 1) __launch_bounds__(384, 1)
fused_kernel(const uint4* __restrict__ x, const uint4* __restrict__ wgate, const uint4* __restrict__ wup, Scratch* gs, int by_sm, const __grid_constant__ Maps mp) {
  extern __shared__ __align__(1024) uint8_t smem_raw[];
  const uint32_t sb = (uint32_t)__cvta_generic_to_shared(smem_raw);
  const unsigned bid = role_id(by_sm);
  if (threadIdx.x == 352) TS(63);
  if (threadIdx.x < 256 && bid < NMAIN) {
    const uint32_t r = threadIdx.x >> 3, ch = threadIdx.x & 7;
    const uint32_t d = sb + r * 128 + ((ch ^ (r & 7)) << 4);
    const uint8_t* xa = (const uint8_t*)x + ((bid & 15) * 262144 + r * 4096 + ch * 16);
    const uint32_t wo = r * (DFF * 2) + (bid >> 4) * 256 + ch * 16;
    const uint8_t *wa = (const uint8_t*)wgate + wo, *wb = (const uint8_t*)wup + wo;
#pragma unroll
    for (int i = 0; i < 12; i++) {
      const int h = i >= 8;
      const uint8_t* src = (i >> 2) == 1 ? xa + (i & 1) * 131072 + ((i >> 1) & 1) * 2048 : ((i & 2) ? wb : wa) + h * 32 * (DFF * 2) + (i & 1) * 128;
      asm volatile("cp.async.cg.shared.global [%0], [%1], 16;" ::"r"(d + ((i >> 2) == 1 ? OFF_A + (i & 3) * 4096 : (i & 3) * 8192 + h * 4096)), "l"(src) : "memory");
    }
    if (threadIdx.x == 0) TS(23);
  }
  const int warp = __shfl_sync(~0u, threadIdx.x >> 5, 0), lane = threadIdx.x & 31;
  const int m = bid & 15, j = bid >> 4, rank = bid & 1;
  const int m2 = bid >> 3, j2 = bid & 7;
  const bool helper = bid >= NMAIN;
  if (warp >= 8) {
    asm volatile("setmaxnreg.dec.sync.aligned.u32 40;");
    if (warp == 8) {
      if (elect_one()) {
        asm volatile("prefetch.tensormap [%0];\nprefetch.tensormap [%1];\nprefetch.tensormap [%2];" ::"l"(&mp.x), "l"(&mp.wg), "l"(&mp.wu) : "memory");
        for (int s = 0; s < 4; s++) mbar_init(sb + B_F1 + 8 * s, 1);
        if (!helper) mbar_arrive(sb + B_F1);
        asm volatile("fence.mbarrier_init.release.cluster;" ::: "memory");
      }
      __syncwarp();
    } else if (warp == 9) {
      if (elect_one()) {
        unsigned nsmid;
        asm("mov.u32 %0, %%nsmid;" : "=r"(nsmid));
        if ((sb & 0xffffff) != SM_BASE || (by_sm && nsmid != NCTA)) asm volatile("trap;");
        for (uint32_t b = B_E1; b < B_F2; b += 8) mbar_init(sb + b, 4);
        for (uint32_t b = B_F2; b < B_AUX; b += 8) mbar_init(sb + b, 1);
        for (uint32_t b = B_EX; b < B_AUX; b += 8) mbar_expect_tx(sb + b, 8192);
        mbar_init(sb + B_AUX, 8); mbar_init(sb + B_HALO, 9); mbar_init(sb + B_HALO + 8, 9);
        asm volatile("st.shared.b32 [%0], %1;" ::"r"(sb + OFF_EPOCH + 4), "r"(bid) : "memory");
        asm volatile("fence.mbarrier_init.release.cluster;" ::: "memory");
      }
      __syncwarp();
    }
    asm volatile("barrier.cluster.arrive.relaxed.aligned;" ::: "memory");
    if (warp == 8 && !helper) {
      if (elect_one()) {
        TS(0); TG(51);
#pragma unroll 1
        for (int kb = 1; kb < 4; kb++) {
          const uint32_t sa = sb + OFF_A + kb * 16384, sw = sb + kb * 32768, fb = sb + B_F1 + 8 * kb;
          mbar_expect_tx(fb, P1_BYTES);
          tma3d(sa, &mp.x, fb, kb * 64, m * 64, 0, EVICT_NORMAL);
          tma2d(sw, &mp.wg, fb, j * 128, kb * 64, EVICT_NORMAL); tma2d(sw + 16384, &mp.wu, fb, j * 128, kb * 64, EVICT_NORMAL);
          tma2d(sw + 8192, &mp.wg, fb, j * 128 + 64, kb * 64, EVICT_NORMAL); tma2d(sw + 24576, &mp.wu, fb, j * 128 + 64, kb * 64, EVICT_NORMAL);
        }
        TS(7);
      }
      __syncwarp();
    }
    asm volatile("barrier.cluster.wait.aligned;" ::: "memory");
    if (helper) {
      if (warp == 8) {
        if (elect_one()) {
          unsigned* ep = &gs->epoch[bid * 2];
          const unsigned e = *ep + 1;
          *ep = e;
#pragma unroll 1
          for (int i = 0; i < 20; i++) {
            const uint32_t fb = sb + (i < 16 ? B_F1 + 8 * (i >> 2) : B_XT);
            if (!(i & 3)) mbar_expect_tx(fb, i < 16 ? P1_BYTES : 32768);
            tma5d(sb + (i < 16 ? i : i + 8) * 8192, &mp.wd, fb, (bid - NMAIN) * 256 + (i & 3) * 64, (i >> 2) * 2, EVICT_FIRST);
          }
          mbar_wait(sb + B_XT, 0);
#pragma unroll 1
          for (int t = 0; t < 16; t++) {
            flag_wait(&gs->flags[(FL_H + t * 4) * 32], e * 8u);
            fence_async();
            if (t == 0) TS(0);
#pragma unroll 1
            for (int n = 0; n < 5; n++) {
              const int i = n ? n - 1 : 4;
              const uint32_t fb = sb + (i < 4 ? B_F1 + 8 * i : B_F2);
              if (t) mbar_wait(sb + B_E1 + 8 * i, ~t & 1);
              if (t || i == 4) mbar_expect_tx(fb, i < 4 ? 16384 : 8192);
              const uint4* src = gs->h + (t * 56 + i) * 1024;
              bulk_load(sb + (i < 4 ? OFF_A + i * 16384 : OFF_X + 4096), src, i < 4 ? 16384 : 4096, fb, EVICT_NORMAL);
              if (i == 4) bulk_load(sb + OFF_X + 12288, src + 256, 4096, fb, EVICT_NORMAL);
            }
          }
        }
      } else if (warp == 9) {
#pragma unroll 1
        for (int t = 0; t < 16; t++) {
          bar_sync(BAR_EV + (t & 1), 288);
          if (lane == 0) { flag_add(&gs->flags[(FL_P + t) * 32]); TS(64 + t); }
          __syncwarp();
        }
      }
    } else if (warp == 8) {
      if (elect_one()) {
        uint32_t par = 0;

        auto x_load = [&]() {
          mbar_expect_tx(sb + B_XT, 32768);
          tma3d(sb + OFF_X, &mp.x, sb + B_XT, j2 * 128, m2 * 64, 0, EVICT_FIRST); tma3d(sb + OFF_X + 16384, &mp.x, sb + B_XT, j2 * 128 + 64, m2 * 64, 0, EVICT_FIRST);
        };
        auto w_tile = [&](int R, const CUtensorMap*& mb0, const CUtensorMap*& mb1, int& n0, int& n1) {
          if (R == 1 || R == 2) {
            mb0 = &mp.wqkv; n0 = 64 * (j + 8 * (R - 1)) + rank * 2048;
            mb1 = rank ? (R == 1 ? &mp.wg : &mp.wu) : &mp.wqkv; n1 = rank ? 1024 + 64 * j : n0 + 1024;
          } else {
            mb0 = mb1 = rank ? &mp.wu : &mp.wg;
            n0 = 128 * j + (R ? 1024 * R - 1536 : 0); n1 = n0 + 64;
          }
        };
        for (int R = 0; R < 5; R++) {
          const CUtensorMap *mb0, *mb1;
          int n0, n1;
          w_tile(R, mb0, mb1, n0, n1);
#pragma unroll 1
          for (int kb = R ? 0 : 4; kb < 16; kb++) {
            if (R == 0 && kb == 14) { asm volatile("prefetch.tensormap [%0];\nprefetch.tensormap [%1];" ::"l"(&mp.xn), "l"(&mp.wqkv) : "memory"); }
            if (R == 4 && kb == 2) { asm volatile("prefetch.tensormap [%0];\nprefetch.tensormap [%1];\nprefetch.tensormap [%2];" ::"l"(&mp.wd), "l"(&mp.wo), "l"(&mp.out) : "memory"); }
            if (R == 0 && kb == CS_KB) {
#pragma unroll 1
              for (int h = 0; h < 2; h++) {
                const uint32_t cb = sb + B_CS + 8 * h, d = sb + OFF_X + 16384 * h;
                mbar_expect_tx(cb, 16384);
                tma2d(d, h ? &mp.wu : &mp.wg, cb, n0, m * 64, EVICT_NORMAL); tma2d(d + 8192, h ? &mp.wu : &mp.wg, cb, n1, m * 64, EVICT_NORMAL);
              }
            }
            const int st = kb & 3;
            const uint32_t sa = sb + OFF_A + st * 16384, sw = sb + st * 32768, fb = sb + B_F1 + 8 * st;
            mbar_wait(sb + B_E1 + 8 * st, par);
            if (R * 16 + kb >= 4) REL_TS(R * 16 + kb - 4);
            mbar_expect_tx(fb, P1_BYTES);
            tma2d_mc(sw + rank * 16384, mb0, fb, n0, kb * 64, EVICT_FIRST);
            tma2d_mc(sw + 8192 + rank * 16384, mb1, fb, n1, kb * 64, EVICT_FIRST);
            if (R == 0) {
              tma3d(sa, &mp.x, fb, kb * 64, m * 64, 0, EVICT_NORMAL);
            } else {
              if (R == 1 && kb == 0) { mbar_wait(sb + B_DEP, 0); TS(1); }
              tma2d(sa, &mp.xn, fb, kb * 64, m * 128, R == 4 ? EVICT_FIRST : EVICT_NORMAL);
            }
            if (R == 4 && kb == 4 + j2) x_load();
            if (st == 3) par ^= 1;
          }
        }
#pragma unroll 1
        for (int i = 0; i < 26; i++) {
          const int st = i & 3, kh = i < 25 ? 9 + 4 * i + 2 * rank : 109 + rank;
          const uint32_t sa = sb + OFF_A + st * 16384, sw = sb + st * 32768, fb = sb + B_F1 + 8 * st;
          mbar_wait(sb + B_E1 + 8 * st, par);
          REL_TS(76 + i);
          mbar_expect_tx(fb, P1_BYTES);
          tma5d(sw, &mp.wd, fb, j2 * 128, kh, EVICT_FIRST); tma5d(sw + 8192, &mp.wd, fb, j2 * 128 + 64, kh, EVICT_FIRST);
          tma5d(sw + 16384, &mp.wd, fb, (j2 ^ 1) * 128, kh, EVICT_FIRST); tma5d(sw + 24576, &mp.wd, fb, (j2 ^ 1) * 128 + 64, kh, EVICT_FIRST);
          if (i == 0 || i == 5 || i == 9 || i == 17) mbar_wait(sb + B_DEP + 8 * (1 + ((i + 7) >> 3)), 0);
          bulk_load(sa, gs->h + (m2 * 112 + kh) * 512, 16384, fb, EVICT_FIRST);
          if (st == 3) par ^= 1;
        }
        int st = 0; uint32_t par2 = 1;
#pragma unroll 1
        for (int t = 0; t < 16; t++) {
          const uint32_t sa = sb + p2_a(st), sw = sb + p2_b(st), fb = sb + B_F2 + 8 * st;
          if (t < 5) mbar_wait(sb + B_E1 + 8 * (((2 * t + 1) / 3 + 2) & 3), t < 3); else mbar_wait(sb + B_E2 + 8 * st, par2);
          REL_TS(102 + t);
          mbar_expect_tx(fb, P2_BYTES);
          bulk_load_mc(sa + rank * 8192, gs->o + (m2 * 16 + t) * 1024 + rank * 512, 8192, fb, EVICT_FIRST);
          tma2d(sw, &mp.wo, fb, j2 * 128, t * 64, EVICT_FIRST); tma2d(sw + 8192, &mp.wo, fb, j2 * 128 + 64, t * 64, EVICT_FIRST);
          if (++st == 5) { st = 0; par2 ^= 1; }
        }
      }
    } else if (warp == 9) {
#pragma unroll 1
      for (int e = 0; e < 7; e++) {
        const bool halo = e == 2 || e == 3;
        bar_sync(BAR_EV + e, halo ? 96 : 288);
        if (lane == 0) {
          const int f = e == 0 ? FL_XN + m : (halo ? FL_HALO + (e - 2) * 128 + bid : FL_H + m * 4 + (e == 1 ? 0 : e - 3));
          TS(10 + 2 * e); TG(52 + e);
          flag_add(&gs->flags[f * 32]);
          if (e < 6) TS(11 + 2 * e);
        }
        __syncwarp();
      }
      unsigned other;
      asm volatile("ld.shared::cluster.b32 %0, [%1];" : "=r"(other) : "r"(mapa(sb + OFF_EPOCH + 4, rank ^ 1)) : "memory");
      if (other != (bid ^ 1)) asm volatile("trap;");
      mbar_wait(sb + B_DONE, 0);
    } else {
      unsigned e = 0;
      if (lane == 0) {
        unsigned* ep = &gs->epoch[bid * 2 + warp - 10];
        e = *ep + 1; *ep = e;
        if (warp == 10) { asm volatile("st.shared.b32 [%0], %1;" ::"r"(sb + OFF_EPOCH), "r"(e) : "memory"); mbar_arrive(sb + B_EP); }
      }
      e = __shfl_sync(~0u, e, 0);
      mbar_wait(sb + B_CS + 8 * (warp - 10), 0);
      if (lane == 0 && warp == 11) TS(6);
      col_sums(sb + OFF_X + (warp - 10) * 16384, gs->cspart + (j * 16 + m) * 128 + (warp - 10) * 16, e);
      if (lane == 0 && warp == 11) TS(9);
      if (warp == 10) {
        if (lane == 0) {
#pragma unroll 1
          for (int g = 0; g < 6; g++) {
            flag_wait(&gs->flags[(g == 5 ? FL_P + m2 : (g ? FL_H + m2 * 4 + g - 1 : FL_XN + m)) * 32], e * (g == 5 ? 4u : 8u));
            fence_async();
            mbar_arrive(sb + B_DEP + 8 * g);
            if (g == 0) TS(8);
          }
        }
      } else
      if (elect_one()) {
#pragma unroll 1
        for (int r = 0; r < 2; r++) {
          const uint32_t hb = sb + B_HALO + 8 * r;
          if (r) mbar_wait(sb + B_HALO, 0);
          if (m) {
            flag_wait(&gs->flags[(FL_HALO + r * 128 + bid - 1) * 32], e);
            fence_async();
            mbar_expect_tx(hb, 4096);
            for (int g = 0; g < 2; g++) bulk_load(sb + OFF_X + g * AT_WG + AT_REM + r * 2048, gs->halo + ((r * 128 + bid - 1) * 2 + g) * 128, 2048, hb, EVICT_FIRST);
          } else {
            mbar_arrive(hb);
          }
          TS(34 + r);
        }
      }
    }
  } else {
    asm volatile("barrier.cluster.arrive.relaxed.aligned;" ::: "memory");
    asm volatile("setmaxnreg.inc.sync.aligned.u32 232;");
    const int wg = warp >> 2, w = warp & 3;
    Cons c;
    c.sb = sb; c.wg = wg; c.zero = warp >> 8;
    c.a = 0x4000004000010000ull + ((SM_BASE + OFF_A + wg * 8192) >> 4); c.k1 = 2 + c.zero; c.k2 = 2; c.k4 = 1024 - 6; c.k4w = -3072 - 6; c.b1 = 128 + c.zero;
    c.b = 0x4000004000000000ull + DB_LO + c.zero;
    c.rel = mapa(sb, threadIdx.x & 1);
    c.do_rel = (threadIdx.x & 127) < 2;
    float acc[128];
    uint32_t pk[64];
    float rs[2];
    const int q = lane & 3;

    if (helper) {
      asm volatile("barrier.cluster.wait.aligned;" ::: "memory");
      c.a = 0x8000002000010000ull + ((SM_BASE + OFF_A + wg * 4096) >> 4); c.k2 = 510; c.k4 = 1024 - 514; c.k4w = -3072 - 514;
      c.rel = sb;
      uint4* dst = gs->dpart + (bid - NMAIN) * 4096 + threadIdx.x;
      auto put = [&](int p) {
#pragma unroll
        for (int i = 4 * p; i < 4 * p + 4; i++) stg128(dst + i * 256, pk[4 * i], pk[4 * i + 1], pk[4 * i + 2], pk[4 * i + 3]);
      };
#pragma unroll 1
      for (int t = 0; t < 16; t++) {
        {
          uint64_t a = c.a, b = c.b;
          desc_add(a, (OFF_X + 4096 - OFF_A + wg * 4096) >> 4); desc_add(b, OFF_X >> 4);
          mbar_spin(sb + B_F2, t & 1, c.zero);
          wg_fence();
          wgmma256<0>(acc, a, b, 2, 128); wgmma256<1>(acc, a, b, 0, 0);
          wg_commit();
        }
        p1_issue<0, 1>(acc, c, t & 1); wg_wait<1>(); release(c, B_E2);
        if (t) put(0);
        p1_issue<1, 1>(acc, c, t & 1); wg_wait<1>(); release(c, B_E1);
        if (t) put(1);
        p1_issue<2, 1>(acc, c, t & 1); wg_wait<1>(); release(c, B_E1 + 8);
        if (t) put(2);
        if (wg == 1) { wg_wait<0>(); release(c, B_E1 + 16); bar_sync(BAR_LAG, 256); }
        p1_issue<3, 1>(acc, c, t & 1);
        if (wg == 0) bar_arrive(BAR_LAG, 256);
        if (t) { put(3); bar_arrive(BAR_EV + (~t & 1), 288); dst += 8 * 2048; }
        wg_wait<1>(); if (wg == 0) release(c, B_E1 + 16);
        wg_wait<0>(); release(c, B_E1 + 24);
#pragma unroll
        for (int i = 0; i < 64; i++) pk[i] = pack2(acc[2 * i], acc[2 * i + 1]);
      }
      put(0); put(1); put(2); put(3);
      bar_arrive(BAR_EV + 1, 288);
      return;
    }
    {
      const int prow = 16 * j + 2 * warp;
      const uint4* xr = x + (size_t)(128 * m + 2 * (prow & 63) + (prow >> 6)) * 128 + lane;
      uint4* xo = gs->xn + (size_t)(128 * m + prow) * 128 + lane;
      float c0[2], mo[4];
      uint32_t st[2];
      uint32_t e;
      asm volatile("" : "+l"(xr), "+l"(xo));
      wg_fence(); wgmma256<0>(acc, c.a, c.b, 0, 0); wg_commit(); wg_wait<0>();
      asm volatile("barrier.cluster.wait.aligned;" ::: "memory");
      asm volatile("cp.async.wait_all;\nfence.proxy.async.shared::cta;" ::: "memory");
      bar_sync(BAR_MMA, 256);
      if (threadIdx.x == 0) TS(39);
      p1_step<0, false>(acc, c);
      unsigned long long part[18];
      auto gather = [&](int from, int to) {
        const int lane = lane_here();
        const unsigned long long* cp = (const unsigned long long*)gs->cspart + j * 4096 + warp * 32 + lane;
        const unsigned long long* sp = gs->stats + 128 * m + warp * 16 + (lane >> 2);
#pragma unroll
        for (int i = from; i < to; i++) asm volatile("ld.relaxed.gpu.global.b64 %0, [%1];" : "=l"(part[i]) : "l"(i < 16 ? cp + i * 256 : sp + (i - 16) * 8) : "memory");
      };
      auto row_load = [&](int r) {
#pragma unroll
        for (int i = 4 * r; i < 4 * r + 4; i++)
          asm volatile("ld.global.nc.L1::no_allocate.v4.b32 {%0,%1,%2,%3}, [%4];" : "=r"(pk[4 * i]), "=r"(pk[4 * i + 1]), "=r"(pk[4 * i + 2]), "=r"(pk[4 * i + 3]) : "l"(xr + r * 256 + (i & 3) * 32));
      };
      p1_step<1>(acc, c); row_load(0);
      p1_step<2>(acc, c); row_load(1);
      p1_loop(acc, c, 3, LN_KB + 1, [](int) {});
      pin<16>(pk); ln_moments(pk, c0[0], mo[0], mo[1]); pin<2>(mo);
      p1_step<LN_KB + 1>(acc, c);
      sched_fence(c.zero);
      pin<16>(pk + 16); ln_moments(pk + 16, c0[1], mo[2], mo[3]); ln_reduce(mo[0], mo[1]); pin<4>(mo);
      p1_step<LN_KB + 2>(acc, c);
      mbar_spin(sb + B_EP, 0, c.zero);
      asm volatile("ld.shared.b32 %0, [%1];" : "=r"(e) : "r"(sb + OFF_EPOCH) : "memory");
      pin<2>(mo); st[0] = ln_finish(c0[0], mo[0], mo[1]); ln_reduce(mo[2], mo[3]); pin<1>(st); pin<2>(mo + 2);
      p1_step<LN_KB + 3>(acc, c);
      sched_fence(c.zero);
      pin<1>(st); pin<2>(mo + 2);
      st[1] = ln_finish(c0[1], mo[2], mo[3]);
      ln_store(pk, st[0], xo);
      if (lane == 0)
        asm volatile("{\n.reg .b64 a, b;\nmov.b64 a, {%1, %3};\nmov.b64 b, {%2, %3};\nst.relaxed.gpu.global.v2.b64 [%0], {a, b};\n}" ::"l"(gs->stats + 128 * m + prow), "r"(st[0]), "r"(st[1]), "r"(e) : "memory");
      p1_step<LN_KB + 4>(acc, c);
      sched_fence(c.zero);
      pin<1>(st + 1);
      ln_store(pk + 16, st[1], xo + 128);
      bar_arrive(BAR_EV, 288);
      p1_loop(acc, c, LN_KB + 5, 13, [](int) {});
      gather(0, 9);
      p1_step<13>(acc, c);
      gather(9, 18);
      p1_step<14>(acc, c);
      auto validate = [&]() {
        float csum;
        for (int tries = 0;; tries++) {
          uint32_t bad = 0;
          csum = 0.f;
#pragma unroll
          for (int i = 0; i < 18; i++) { bad |= (uint32_t)(part[i] >> 32) ^ e; if (i < 16) csum += __uint_as_float((uint32_t)part[i]); }
          if (!__any_sync(~0u, bad != 0) || tries > (1 << 20)) break;
          gather(0, 18);
        }
        const float hi = bf16r(csum), mid = bf16r(csum - hi);
        sts128(sb + OFF_CS + ((threadIdx.x & 62) * 4 + (threadIdx.x >> 6) * 2 + (threadIdx.x & 1)) * 16, make_uint4(pack2(hi, mid), pack2(csum - hi - mid, 0.f), 0, 0));
        asm volatile("fence.proxy.async.shared::cta;" ::: "memory");
        __syncwarp();
        if (lane == 0) mbar_arrive(sb + B_AUX);
      };
#pragma unroll 1
      for (int ph = 1; ph >= 0; ph--) {
        if (wg == ph) validate();
        if (ph) {
          if (wg == 1) { wg_wait<0>(); release(c, B_E1 + 16); bar_sync(BAR_LAG, 256); }
          p1_issue<3, 1>(acc, c, 1);
        }
      }
      const uint32_t keep = q == 0 ? 0xffffffffu : (q == 1 ? 0xffffu : 0u);
      const uint32_t a0 = (__byte_perm((uint32_t)part[16], 0, 0x1010) ^ 0x80008000u) & keep, a1 = (__byte_perm((uint32_t)part[17], 0, 0x1010) ^ 0x80008000u) & keep;
      mbar_spin(sb + B_AUX, 0, c.zero);
      wg_fence();
      wgmma256_rs(acc, a0, a1, 0, 0, (SM_BASE + OFF_CS) >> 4);
      wg_commit();
      if (wg == 0) bar_arrive(BAR_LAG, 256);
      rs[0] = rcpf(hi_f((uint32_t)part[16])); rs[1] = rcpf(hi_f((uint32_t)part[17]));
      wg_wait<2>(); if (wg == 0) release(c, B_E1 + 16);
      wg_wait<0>(); release(c, B_E1 + 24);
    }
#pragma unroll 1
    for (int R = 1;; R++) {
#pragma unroll
      for (int i = 0; i < 64; i++) pk[i] = pack2(acc[2 * i], acc[2 * i + 1]);
      uint8_t* hb = (uint8_t*)gs->h + (size_t)m * 56 * 16384 + warp * 1024;
      if (R == 5) { c.a = 0x8000002000010000ull + ((SM_BASE + OFF_A + wg * 4096) >> 4); c.k2 = 510; c.k4 = 1024 - 514; c.k4w = -3072 - 514; }
      p1_step<0>(acc, c);
      if (R == 2 || R == 3) {
        attn_tile(acc, pk, c, R - 2, warp, m, bid, gs, hb + (16 + j) * 16384, (uint8_t*)gs->o + (m * 16 + j + 8 * (R - 2)) * 16384 + warp * 1024);
      } else {
        geglu_tile(acc, pk, c, R == 5 ? 24 : 14, hb + (2 * j + (R == 1 ? 0 : 16 * R - 40)) * 16384, BAR_EV + (R == 1 ? 1 : R + 1), rs);
        rs[0] = rs[1] = 1.0f;
        if (R == 5) break;
      }
      p1_step<14>(acc, c); p1_step<15>(acc, c);
    }
    auto fetch = [&](int p) {
      asm volatile("ld.global.cg.v4.b32 {%0,%1,%2,%3}, [%4];" : "=r"(pk[4 * p]), "=r"(pk[4 * p + 1]), "=r"(pk[4 * p + 2]), "=r"(pk[4 * p + 3]) : "l"(gs->dpart + bid * 2048 + p * 256 + threadIdx.x) : "memory");
    };
    mbar_spin(sb + B_DEP + 40, 0, c.zero);
    fetch(0); fetch(1); fetch(2);
    p1_step<8>(acc, c);
    fetch(3); fetch(4); fetch(5);
    desc_add(c.a, 2 * rank); desc_add(c.b, 128 * rank);
    mbar_spin(sb + B_F1 + 8, 0, c.zero);
    wg_fence();
    wgmma256<1>(acc, c.a, c.b, rank ? 510 : 2, c.b1);
    wgmma256<1>(acc, c.a, c.b, rank ? 2 : 510, c.b1);
    wgmma256<1>(acc, c.a, c.b, 512 - 2 * rank, 1792 - 128 * rank);
    wg_commit();
    wg_wait<1>(); release(c, B_E1);
    fetch(6); fetch(7);
    {
      float accs[64];
      const uint32_t peer = mapa(sb, rank ^ 1);
      auto send_piece = [&](int p) {
        asm volatile("st.async.weak.shared::cluster.mbarrier::complete_tx::bytes.v4.b32 [%0], {%1,%2,%3,%4}, [%5];" ::"r"(peer + OFF_LAND + p * 4096 + threadIdx.x * 16),
                     "r"(pack2(acc[64 + 8 * p], acc[65 + 8 * p])), "r"(pack2(acc[66 + 8 * p], acc[67 + 8 * p])), "r"(pack2(acc[68 + 8 * p], acc[69 + 8 * p])), "r"(pack2(acc[70 + 8 * p], acc[71 + 8 * p])),
                     "r"(peer + B_EX + 16 * wg + 8 * (p >> 2)) : "memory");
      };
      auto silu_piece = [&](int p) {
        const uint4 r = lds128(sb + OFF_LAND + p * 4096 + threadIdx.x * 16);
        const uint32_t rr[4] = {add2(r.x, pk[4 * p]), add2(r.y, pk[4 * p + 1]), add2(r.z, pk[4 * p + 2]), add2(r.w, pk[4 * p + 3])};
#pragma unroll
        for (int i = 0; i < 4; i++) {
          const float a = acc[8 * p + 2 * i] + lo_f(rr[i]), b = acc[8 * p + 2 * i + 1] + hi_f(rr[i]);
          pk[4 * p + i] = pack2(silu_half(a), silu_half(b));
        }
        pin<4>(pk + 4 * p);
      };
      const uint32_t xa = sb + OFF_X + (warp * 16 + (lane & 7)) * 128 + (((lane >> 3) ^ (lane & 7)) << 4);
      auto x_addr = [&](int i) { return (xa ^ ((i & 1) << 6)) + ((i >> 1) & 1) * 1024 + (i >> 2) * 16384; };
      auto x_piece = [&](int i) { const uint4 v = ldsm(x_addr(i)); pk[32 + 4 * i] = v.x; pk[33 + 4 * i] = v.y; pk[34 + 4 * i] = v.z; pk[35 + 4 * i] = v.w; };
      p2_step<0>(accs, c);
      p2_step<1>(accs, c);
      mbar_spin(sb + B_E1 + 8, 0, c.zero);
      send_piece(0); send_piece(1);
      p2_step<2>(accs, c); sched_fence(c.zero); send_piece(2); send_piece(3);
      p2_step<3>(accs, c); sched_fence(c.zero); send_piece(4); send_piece(5);
      p2_step<4>(accs, c); mbar_spin(sb + B_XT, 0, c.zero); send_piece(6); send_piece(7);
      p2_step<5>(accs, c); mbar_spin(sb + B_EX + 16 * wg, 0, c.zero); silu_piece(0); x_piece(0);
      p2_step<6>(accs, c); sched_fence(c.zero); silu_piece(1); x_piece(1);
      p2_step<7>(accs, c); sched_fence(c.zero); silu_piece(2); x_piece(2);
      p2_step<8>(accs, c); sched_fence(c.zero); silu_piece(3); x_piece(3);
      p2_step<9>(accs, c); mbar_spin(sb + B_EX + 16 * wg + 8, 0, c.zero); silu_piece(4); x_piece(4);
      p2_step<10>(accs, c); sched_fence(c.zero); silu_piece(5); x_piece(5);
      p2_step<11>(accs, c); sched_fence(c.zero); silu_piece(6); x_piece(6); x_piece(7);
      auto out_half = [&](const float* a, int h) {
#pragma unroll
        for (int i = 4 * h; i < 4 * h + 4; i++) {
          uint32_t v[4];
#pragma unroll
          for (int k = 0; k < 4; k++) { const int o = 2 * (4 * (i & 1) + k) + ((i >> 1) & 1); v[k] = fma2(pack2(a[2 * o], a[2 * o + 1]), pk[16 * h + o], pk[32 + 4 * i + k]); }
          asm volatile("stmatrix.sync.aligned.m8n8.x4.shared.b16 [%0], {%1,%2,%3,%4};" ::"r"(x_addr(i)), "r"(v[0]), "r"(v[1]), "r"(v[2]), "r"(v[3]) : "memory");
          if (i & 1) {
            asm volatile("fence.proxy.async.shared::cta;" ::: "memory");
            __syncwarp();
            if (elect_one()) tma3d_store(&mp.out, sb + OFF_X + h * 16384 + warp * 2048 + (i & 2) * 512, j2 * 128 + h * 64, m2 * 64 + w * 16 + (i & 2) * 4, wg);
          }
        }
      };
      if (wg == 1) silu_piece(7);
      p2_step<12>(accs, c); p2_step<13>(accs, c); p2_step<14>(accs, c); p2_step<15>(accs, c);
      if (c.do_rel) mbar_arrive(sb + B_DONE);
      if (wg == 0) silu_piece(7);
      wg_wait<0>();
      out_half(accs, 0); out_half(accs + 32, 1);
      if (elect_one()) { asm volatile("cp.async.bulk.commit_group;\ncp.async.bulk.wait_group.read 0;" ::: "memory"); }
      if ((threadIdx.x & 127) == 0) { TS(33 + wg * 16); if (wg) { TG(59); unsigned id; asm volatile("mov.u32 %0, %%smid;" : "=r"(id)); TSV(60, id); } }
    }
  }
}

typedef CUresult (*EncodeFn)(CUtensorMap*, CUtensorMapDataType, cuuint32_t, void*, const cuuint64_t*, const cuuint64_t*, const cuuint32_t*, const cuuint32_t*,
                             CUtensorMapInterleave, CUtensorMapSwizzle, CUtensorMapL2promotion, CUtensorMapFloatOOBfill);

void encode(EncodeFn fn, CUtensorMap* tm, const void* p, int rank, const cuuint64_t* dims, const cuuint64_t* strides, const cuuint32_t* box) {
  const cuuint32_t es[5] = {1, 1, 1, 1, 1};
  fn(tm, CU_TENSOR_MAP_DATA_TYPE_BFLOAT16, rank, const_cast<void*>(p), dims, strides, box, es, CU_TENSOR_MAP_INTERLEAVE_NONE, CU_TENSOR_MAP_SWIZZLE_128B,
     CU_TENSOR_MAP_L2_PROMOTION_L2_128B, CU_TENSOR_MAP_FLOAT_OOB_FILL_NONE);
}

}

extern "C" void kernel_launch(void* const* d_in, const int* in_sizes, int n_in, void* d_out, int out_size) {
  (void)in_sizes; (void)n_in; (void)out_size;
  static EncodeFn fn = nullptr;
  static Scratch* gs = nullptr;
  static int nsm = 0;
  if (!fn) {
    void* p = nullptr;
    cudaDriverEntryPointQueryResult qr;
    cudaGetDriverEntryPoint("cuTensorMapEncodeTiled", &p, cudaEnableDefault, &qr);
    fn = (EncodeFn)p;
    cudaGetSymbolAddress((void**)&gs, g_scratch);
    int dev = 0;
    cudaGetDevice(&dev);
    cudaDeviceGetAttribute(&nsm, cudaDevAttrMultiProcessorCount, dev);
    cudaFuncSetAttribute(fused_kernel, cudaFuncAttributeMaxDynamicSharedMemorySize, SMEM_BYTES);
  }
  const void *x = d_in[0], *wqkv = d_in[1], *wo = d_in[2], *wg = d_in[4], *wu = d_in[5], *wd = d_in[6];
  Maps mp;
  {
    const cuuint64_t dims[3] = {DM, SEQ / 2, 2}, st[2] = {DM * 4, DM * 2};
    const cuuint32_t box_in[3] = {64, 64, 2}, box_out[3] = {64, 8, 1};
    encode(fn, &mp.x, x, 3, dims, st, box_in);
    encode(fn, &mp.out, d_out, 3, dims, st, box_out);
  }
  {
    const cuuint64_t dims[2] = {DM, SEQ}, st[1] = {DM * 2};
    const cuuint32_t box[2] = {64, 128};
    encode(fn, &mp.xn, gs->xn, 2, dims, st, box);
  }
  {
    const cuuint32_t box[2] = {64, 64};
    const cuuint64_t dq[2] = {3 * DM, DM}, sq[1] = {3 * DM * 2}, df[2] = {DFF, DM}, sf[1] = {DFF * 2}, dw[2] = {DM, DM}, sw[1] = {DM * 2};
    encode(fn, &mp.wqkv, wqkv, 2, dq, sq, box);
    encode(fn, &mp.wg, wg, 2, df, sf, box);
    encode(fn, &mp.wu, wu, 2, df, sf, box);
    encode(fn, &mp.wo, wo, 2, dw, sw, box);
  }
  {
    const cuuint32_t box[5] = {64, 2, 4, 4, 2};
    const cuuint64_t st[4] = {DM * 2, 8 * DM * 2, 2 * DM * 2, 32 * DM * 2};
    const cuuint64_t dd[5] = {DM, 2, 4, 4, DFF / 32};
    encode(fn, &mp.wd, wd, 5, dd, st, box);
  }
  fused_kernel<<<NCTA, 384, SMEM_BYTES>>>((const uint4*)x, (const uint4*)wg, (const uint4*)wu, gs, nsm == NCTA, mp);
}
```

```cpp
#include <cuda_runtime.h>
#include <cuda_bf16.h>
#include <cuda.h>
#include <stdint.h>

#define CS_KB 8
#define LN_KB 4

namespace {

constexpr int SEQ = 2048, DM = 1024, DFF = 3584;
constexpr int NMAIN = 128, NCTA = 132;
constexpr uint64_t EVICT_FIRST = 0x12F0000000000000ull, EVICT_NORMAL = 0x1000000000000000ull;

constexpr uint32_t SM_BASE = 0x400;
constexpr uint32_t P1_BYTES = 49152, P2_BYTES = 32768;
constexpr uint32_t OFF_A = 131072;
__host__ __device__ constexpr uint32_t p2_a(int s) { return s == 0 ? OFF_A + 32768 : s == 1 ? OFF_A + 49152 : s == 2 ? 114688 : s == 3 ? 16384 : 49152; }
__host__ __device__ constexpr uint32_t p2_b(int s) { return s < 3 ? 65536 + s * 16384 : (s - 3) * 32768; }
constexpr uint32_t OFF_LAND = OFF_A;
constexpr uint32_t OFF_X = 196608;
constexpr uint32_t OFF_CS = OFF_X + 14336;
constexpr uint32_t OFF_BAR = 229376;
constexpr uint32_t B_F1 = OFF_BAR, B_E1 = B_F1 + 32, B_E2 = B_E1 + 32, B_DONE = B_E2 + 40, B_F2 = B_DONE + 8, B_DEP = B_F2 + 40, B_CS = B_DEP + 48,
                   B_XT = B_CS + 16, B_EP = B_XT + 8, B_EX = B_EP + 8, B_AUX = B_EX + 32, B_HALO = B_AUX + 8, OFF_EPOCH = B_HALO + 16;
constexpr uint32_t SMEM_BYTES = 232448;
constexpr uint32_t AT_V = 0, AT_K = 8192, AT_REM = 11264, AT_WG = 15360;

constexpr int FL_XN = 0, FL_H = 16, FL_P = 80, FL_HALO = 96, FL_N = FL_HALO + 256;
struct __align__(1024) Scratch {
  uint4 h[16 * 56 * 1024];
  uint4 o[16 * 16 * 1024];
  uint4 xn[SEQ * DM / 8];
  uint4 dpart[128 * 8 * 256];
  uint4 halo[2 * 128 * 2 * 128];
  ulonglong2 cspart[8 * 16 * 128];
  unsigned long long stats[SEQ];
  unsigned flags[FL_N * 32];
  unsigned epoch[NCTA * 2];
};
__device__ Scratch g_scratch;
#define TG(i) do {} while (0)
#define TSV(i, v) do {} while (0)
#define TS(i) do {} while (0)

__device__ __forceinline__ unsigned role_id(bool by_sm) {
  unsigned sm;
  asm volatile("mov.u32 %0, %%smid;" : "=r"(sm));
  const unsigned t = sm >> 1;
  const unsigned c = t < 60 ? (t < 32 ? t : t + 1 + ((t - 32) * 37 >> 8)) : (t < 62 ? t + 4 : 8 * t - 464);
  return by_sm ? 2 * c + (blockIdx.x & 1) : blockIdx.x;
}

struct Maps { CUtensorMap x, wg, wu, xn, wqkv, wd, wo, out; };

__device__ __forceinline__ void mbar_init(uint32_t bar, uint32_t cnt) { asm volatile("mbarrier.init.shared::cta.b64 [%0], %1;" ::"r"(bar), "r"(cnt)); }
__device__ __forceinline__ void mbar_expect_tx(uint32_t bar, uint32_t bytes) { asm volatile("mbarrier.arrive.expect_tx.shared::cta.b64 _, [%0], %1;" ::"r"(bar), "r"(bytes) : "memory"); }
__device__ __forceinline__ void mbar_arrive(uint32_t bar) { asm volatile("mbarrier.arrive.shared::cta.b64 _, [%0];" ::"r"(bar) : "memory"); }
__device__ __forceinline__ void mbar_arrive_cl(uint32_t bar) { asm volatile("mbarrier.arrive.shared::cluster.b64 _, [%0];" ::"r"(bar) : "memory"); }
__device__ __forceinline__ uint32_t mapa(uint32_t a, uint32_t cta) { uint32_t r; asm("mapa.shared::cluster.u32 %0, %1, %2;" : "=r"(r) : "r"(a), "r"(cta)); return r; }
__device__ __forceinline__ void mbar_wait(uint32_t bar, uint32_t parity) {
  asm volatile("{\n.reg .pred p;\n.reg .u32 n;\nmov.u32 n, 0;\nLAB_WAIT:\nmbarrier.try_wait.parity.shared::cta.b64 p, [%0], %1;\n@p bra LAB_DONE;\n"
               "add.u32 n, n, 1;\nsetp.gt.u32 p, n, 4000000;\n@p trap;\nbra LAB_WAIT;\nLAB_DONE:\n}" ::"r"(bar), "r"(parity) : "memory");
}
__device__ __forceinline__ void mbar_spin(uint32_t bar, uint32_t parity, uint32_t zero) {
  asm volatile("{\n.reg .pred p, z;\nsetp.ne.u32 z, %2, 0;\nLAB_WAIT:\nmbarrier.try_wait.parity.shared::cta.b64 p, [%0], %1;\n@p bra LAB_DONE;\n@z trap;\nbra LAB_WAIT;\nLAB_DONE:\n}" ::"r"(bar), "r"(parity), "r"(zero) : "memory");
}
__device__ __forceinline__ void flag_wait(const unsigned* f, unsigned target) {
  asm volatile("{\n.reg .pred p;\n.reg .u32 n, v;\nmov.u32 n, 0;\nLAB_WAIT:\nld.relaxed.gpu.global.u32 v, [%0];\nsub.u32 v, v, %1;\nsetp.ge.s32 p, v, 0;\n@p bra LAB_DONE;\n"
               "nanosleep.u32 200;\nadd.u32 n, n, 1;\nsetp.gt.u32 p, n, 4000000;\n@p trap;\nbra LAB_WAIT;\nLAB_DONE:\nfence.acquire.gpu;\n}" ::"l"(f), "r"(target) : "memory");
}
__device__ __forceinline__ void flag_add(unsigned* f) { asm volatile("red.release.gpu.global.add.u32 [%0], 1;" ::"l"(f) : "memory"); }
__device__ __forceinline__ void fence_async() { asm volatile("fence.proxy.async.global;" ::: "memory"); }
__device__ __forceinline__ bool elect_one() { uint32_t p; asm volatile("{\n.reg .pred P;\nelect.sync _|P, 0xffffffff;\nselp.u32 %0, 1, 0, P;\n}" : "=r"(p)); return p; }
__device__ __forceinline__ void bar_sync(int id, int n) { asm volatile("bar.sync %0, %1;" ::"r"(id), "r"(n) : "memory"); }
__device__ __forceinline__ void bar_arrive(int id, int n) { asm volatile("bar.arrive %0, %1;" ::"r"(id), "r"(n) : "memory"); }

__device__ __forceinline__ void tma2d(uint32_t dst, const CUtensorMap* tm, uint32_t bar, int c0, int c1, uint64_t hint) {
  asm volatile("cp.async.bulk.tensor.2d.shared::cluster.global.mbarrier::complete_tx::bytes.L2::cache_hint [%0], [%1, {%3, %4}], [%2], %5;" ::"r"(dst), "l"(tm), "r"(bar), "r"(c0), "r"(c1), "l"(hint) : "memory");
}
__device__ __forceinline__ void tma2d_mc(uint32_t dst, const CUtensorMap* tm, uint32_t bar, int c0, int c1, uint64_t hint) {
  asm volatile("cp.async.bulk.tensor.2d.shared::cluster.global.mbarrier::complete_tx::bytes.multicast::cluster.L2::cache_hint [%0], [%1, {%3, %4}], [%2], %5, %6;" ::"r"(dst), "l"(tm), "r"(bar), "r"(c0), "r"(c1), "h"((uint16_t)3), "l"(hint) : "memory");
}
__device__ __forceinline__ void tma3d(uint32_t dst, const CUtensorMap* tm, uint32_t bar, int c0, int c1, int c2, uint64_t hint) {
  asm volatile("cp.async.bulk.tensor.3d.shared::cluster.global.mbarrier::complete_tx::bytes.L2::cache_hint [%0], [%1, {%3, %4, %5}], [%2], %6;" ::"r"(dst), "l"(tm), "r"(bar), "r"(c0), "r"(c1), "r"(c2), "l"(hint) : "memory");
}
__device__ __forceinline__ void tma5d(uint32_t dst, const CUtensorMap* tm, uint32_t bar, int c0, int c4, uint64_t hint) {
  asm volatile("cp.async.bulk.tensor.5d.shared::cluster.global.mbarrier::complete_tx::bytes.L2::cache_hint [%0], [%1, {%3, %5, %5, %5, %4}], [%2], %6;" ::"r"(dst), "l"(tm), "r"(bar), "r"(c0), "r"(c4), "r"(0), "l"(hint) : "memory");
}
__device__ __forceinline__ void tma3d_store(const CUtensorMap* tm, uint32_t src, int c0, int c1, int c2) {
  asm volatile("cp.async.bulk.tensor.3d.global.shared::cta.bulk_group.L2::cache_hint [%0, {%2, %3, %4}], [%1], %5;" ::"l"(tm), "r"(src), "r"(c0), "r"(c1), "r"(c2), "l"(EVICT_FIRST) : "memory");
}
__device__ __forceinline__ void bulk_load(uint32_t dst, const void* src, uint32_t bytes, uint32_t bar, uint64_t hint) {
  asm volatile("cp.async.bulk.shared::cluster.global.mbarrier::complete_tx::bytes.L2::cache_hint [%0], [%1], %2, [%3], %4;" ::"r"(dst), "l"(src), "r"(bytes), "r"(bar), "l"(hint) : "memory");
}
__device__ __forceinline__ void bulk_load_mc(uint32_t dst, const void* src, uint32_t bytes, uint32_t bar, uint64_t hint) {
  asm volatile("cp.async.bulk.shared::cluster.global.mbarrier::complete_tx::bytes.multicast::cluster.L2::cache_hint [%0], [%1], %2, [%3], %4, %5;" ::"r"(dst), "l"(src), "r"(bytes), "r"(bar), "h"((uint16_t)3), "l"(hint) : "memory");
}
__device__ __forceinline__ uint4 lds128(uint32_t a) { uint4 v; asm volatile("ld.shared.v4.b32 {%0,%1,%2,%3}, [%4];" : "=r"(v.x), "=r"(v.y), "=r"(v.z), "=r"(v.w) : "r"(a) : "memory"); return v; }
__device__ __forceinline__ void sts128(uint32_t a, uint4 v) { asm volatile("st.shared.v4.b32 [%0], {%1,%2,%3,%4};" ::"r"(a), "r"(v.x), "r"(v.y), "r"(v.z), "r"(v.w) : "memory"); }
__device__ __forceinline__ void stg128(void* p, uint32_t a, uint32_t b, uint32_t c, uint32_t d) { asm volatile("st.global.v4.b32 [%0], {%1,%2,%3,%4};" ::"l"(p), "r"(a), "r"(b), "r"(c), "r"(d) : "memory"); }

__device__ __forceinline__ uint32_t pack2(float lo, float hi) { uint32_t r; asm("cvt.rn.bf16x2.f32 %0, %1, %2;" : "=r"(r) : "f"(hi), "f"(lo)); return r; }
__device__ __forceinline__ float lo_f(uint32_t v) { return __uint_as_float(v << 16); }
__device__ __forceinline__ float hi_f(uint32_t v) { return __uint_as_float(v & 0xffff0000u); }
__device__ __forceinline__ float bf16r(float v) { return lo_f(pack2(v, 0.f)); }
__device__ __forceinline__ uint32_t mul2(uint32_t a, uint32_t b) { uint32_t r; asm("mul.rn.bf16x2 %0, %1, %2;" : "=r"(r) : "r"(a), "r"(b)); return r; }
__device__ __forceinline__ uint32_t add2(uint32_t a, uint32_t b) { uint32_t r; asm("add.rn.bf16x2 %0, %1, %2;" : "=r"(r) : "r"(a), "r"(b)); return r; }
__device__ __forceinline__ uint32_t sub2(uint32_t a, uint32_t b) { uint32_t r; asm("sub.rn.bf16x2 %0, %1, %2;" : "=r"(r) : "r"(a), "r"(b)); return r; }
__device__ __forceinline__ uint32_t fma2(uint32_t a, uint32_t b, uint32_t c) { uint32_t r; asm("fma.rn.bf16x2 %0, %1, %2, %3;" : "=r"(r) : "r"(a), "r"(b), "r"(c)); return r; }
__device__ __forceinline__ uint32_t max2(uint32_t a, uint32_t b) { uint32_t r; asm("max.bf16x2 %0, %1, %2;" : "=r"(r) : "r"(a), "r"(b)); return r; }
__device__ __forceinline__ float ex2f(float x) { float y; asm("ex2.approx.ftz.f32 %0, %1;" : "=f"(y) : "f"(x)); return y; }
__device__ __forceinline__ float rcpf(float x) { float y; asm("rcp.approx.ftz.f32 %0, %1;" : "=f"(y) : "f"(x)); return y; }
constexpr float GELU_C1 = 0.7978845608028654f, GELU_C3 = 0.035677408136300125f;
__device__ __forceinline__ float gelu_k(float g, float c1, float c3, float k) {
  float t;
  asm("tanh.approx.f32 %0, %1;" : "=f"(t) : "f"(g * fmaf(g * g, c3, c1)));
  g *= k;
  return fmaf(g, t, g);
}
__device__ __forceinline__ float silu_half(float z) { float t; asm("tanh.approx.f32 %0, %1;" : "=f"(t) : "f"(z)); return fmaf(z, t, z); }

__device__ __forceinline__ void wg_fence() { asm volatile("wgmma.fence.sync.aligned;" ::: "memory"); }
__device__ __forceinline__ void wg_commit() { asm volatile("wgmma.commit_group.sync.aligned;" ::: "memory"); }
template <int N> __device__ __forceinline__ void wg_wait() { asm volatile("wgmma.wait_group.sync.aligned %0;" ::"n"(N) : "memory"); }
#define A8(o) "+f"(d[(o)]), "+f"(d[(o) + 1]), "+f"(d[(o) + 2]), "+f"(d[(o) + 3]), "+f"(d[(o) + 4]), "+f"(d[(o) + 5]), "+f"(d[(o) + 6]), "+f"(d[(o) + 7])
#define A64(o) A8(o), A8((o) + 8), A8((o) + 16), A8((o) + 24), A8((o) + 32), A8((o) + 40), A8((o) + 48), A8((o) + 56)
#define REGS0_63 "%0,%1,%2,%3,%4,%5,%6,%7,%8,%9,%10,%11,%12,%13,%14,%15,%16,%17,%18,%19,%20,%21,%22,%23,%24,%25,%26,%27,%28,%29,%30,%31," \
                 "%32,%33,%34,%35,%36,%37,%38,%39,%40,%41,%42,%43,%44,%45,%46,%47,%48,%49,%50,%51,%52,%53,%54,%55,%56,%57,%58,%59,%60,%61,%62,%63"
#define REGS64_127 "%64,%65,%66,%67,%68,%69,%70,%71,%72,%73,%74,%75,%76,%77,%78,%79,%80,%81,%82,%83,%84,%85,%86,%87,%88,%89,%90,%91,%92,%93,%94,%95," \
                   "%96,%97,%98,%99,%100,%101,%102,%103,%104,%105,%106,%107,%108,%109,%110,%111,%112,%113,%114,%115,%116,%117,%118,%119,%120,%121,%122,%123,%124,%125,%126,%127"
__device__ __forceinline__ void desc_add(uint64_t& x, int v) { asm volatile("{\n.reg .b32 lo, hi;\nmov.b64 {lo, hi}, %0;\nadd.s32 lo, lo, %1;\nmov.b64 %0, {lo, hi};\n}" : "+l"(x) : "r"(v)); }
template <int ACCUM> __device__ __forceinline__ void wgmma256(float (&d)[128], uint64_t& a, uint64_t& b, int da, int db) {
  asm volatile("{\n.reg .pred p;\nsetp.ne.b32 p, %130, 0;\n"
               "wgmma.mma_async.sync.aligned.m64n256k16.f32.bf16.bf16 {" REGS0_63 "," REGS64_127 "}, %128, %129, p, 1, 1, 0, 1;\n}"
               : A64(0), A64(64) : "l"(a), "l"(b), "n"(ACCUM));
  desc_add(a, da); desc_add(b, db);
}
__device__ __forceinline__ void wgmma256_rs(float (&d)[128], uint32_t a0, uint32_t a1, uint32_t z0, uint32_t z1, uint32_t b_lo) {
  asm volatile("{\n.reg .b64 db;\nmov.b64 db, {%132, 0x00000008};\n"
               "wgmma.mma_async.sync.aligned.m64n256k16.f32.bf16.bf16 {" REGS0_63 "," REGS64_127 "}, {%128,%129,%130,%131}, db, 1, 1, 1, 0;\n}"
               : A64(0), A64(64) : "r"(a0), "r"(a1), "r"(z0), "r"(z1), "r"(b_lo));
}
template <int ACCUM> __device__ __forceinline__ void wgmma128(float (&d)[64], uint64_t& a, uint64_t& b, int da, int db) {
  asm volatile("{\n.reg .pred p;\nsetp.ne.b32 p, %66, 0;\n"
               "wgmma.mma_async.sync.aligned.m64n128k16.f32.bf16.bf16 {" REGS0_63 "}, %64, %65, p, 1, 1, 0, 1;\n}"
               : A64(0) : "l"(a), "l"(b), "n"(ACCUM));
  desc_add(a, da); desc_add(b, db);
}
template <int ACCUM> __device__ __forceinline__ void hmma(float (&c)[4], uint32_t a0, uint32_t a1, uint32_t a2, uint32_t a3, uint32_t b0, uint32_t b1) {
  if (ACCUM)
    asm volatile("mma.sync.aligned.m16n8k16.row.col.f32.bf16.bf16.f32 {%0,%1,%2,%3}, {%4,%5,%6,%7}, {%8,%9}, {%0,%1,%2,%3};"
                 : "+f"(c[0]), "+f"(c[1]), "+f"(c[2]), "+f"(c[3]) : "r"(a0), "r"(a1), "r"(a2), "r"(a3), "r"(b0), "r"(b1));
  else
    asm volatile("mma.sync.aligned.m16n8k16.row.col.f32.bf16.bf16.f32 {%0,%1,%2,%3}, {%4,%5,%6,%7}, {%8,%9}, {%10,%10,%10,%10};"
                 : "=f"(c[0]), "=f"(c[1]), "=f"(c[2]), "=f"(c[3]) : "r"(a0), "r"(a1), "r"(a2), "r"(a3), "r"(b0), "r"(b1), "f"(0.f));
}
__device__ __forceinline__ uint32_t movm(uint32_t a) { uint32_t d; asm volatile("movmatrix.sync.aligned.m8n8.trans.b16 %0, %1;" : "=r"(d) : "r"(a)); return d; }
__device__ __forceinline__ int lane_here() { int v; asm volatile("mov.u32 %0, %%laneid;" : "=r"(v)); return v; }
template <int N> __device__ __forceinline__ void pin(uint32_t* r) {
#pragma unroll
  for (int i = 0; i < N; i++) asm volatile("" : "+r"(r[i]));
}
template <int N> __device__ __forceinline__ void pin(float* r) {
#pragma unroll
  for (int i = 0; i < N; i++) asm volatile("" : "+f"(r[i]));
}
__device__ __forceinline__ void sched_fence(uint32_t zero) {
  asm volatile("{\n.reg .pred p;\nsetp.eq.u32 p, %0, 0;\nLAB_F:\n@p bra.uni LAB_D;\nnanosleep.u32 0;\nbra.uni LAB_F;\nLAB_D:\n}" ::"r"(zero) : "memory");
}
__device__ __forceinline__ uint4 ldsm(uint32_t a) { uint4 v; asm volatile("ldmatrix.sync.aligned.m8n8.x4.shared.b16 {%0,%1,%2,%3}, [%4];" : "=r"(v.x), "=r"(v.y), "=r"(v.z), "=r"(v.w) : "r"(a) : "memory"); return v; }
__device__ __forceinline__ uint4 ldsm_t(uint32_t a) { uint4 v; asm volatile("ldmatrix.sync.aligned.m8n8.x4.trans.shared.b16 {%0,%1,%2,%3}, [%4];" : "=r"(v.x), "=r"(v.y), "=r"(v.z), "=r"(v.w) : "r"(a) : "memory"); return v; }

constexpr int BAR_LAG = 1, BAR_MMA = 2, BAR_EV = 3;

struct Cons {
  uint32_t sb;
  mutable uint64_t a, b;
  int k1, k2, k4, k4w, b1;
  uint32_t rel;
  bool do_rel;
  int wg;
  uint32_t zero;
};
#define REL_TS(n) TS(64 + (n))
constexpr uint32_t DB_LO = (SM_BASE >> 4) | ((8192 >> 4) << 16);

template <int ST, int ACCUM, bool WAIT = true> __device__ __forceinline__ void p1_issue(float (&acc)[128], const Cons& c, uint32_t parity) {
  if (WAIT) mbar_spin(c.sb + B_F1 + 8 * ST, parity, c.zero);
  wg_fence();
  wgmma256<ACCUM>(acc, c.a, c.b, c.k1, c.b1);
  wgmma256<1>(acc, c.a, c.b, c.k2, c.b1);
  wgmma256<1>(acc, c.a, c.b, c.k1, c.b1);
  wgmma256<1>(acc, c.a, c.b, ST == 3 ? c.k4w : c.k4, ST == 3 ? -6144 - 384 : 2048 - 384);
  wg_commit();
}
__device__ __forceinline__ void release(const Cons& c, uint32_t bar) { if (c.do_rel) mbar_arrive_cl(c.rel + bar); }
template <int KB, bool WAIT = true> __device__ __forceinline__ void p1_step(float (&acc)[128], const Cons& c) {
  if (KB == 15) { if (c.wg == 1) { wg_wait<0>(); release(c, B_E1 + 16); bar_sync(BAR_LAG, 256); } }
  p1_issue<KB & 3, KB != 0, WAIT>(acc, c, (KB >> 2) & 1);
  if (KB == 15) { if (c.wg == 0) bar_arrive(BAR_LAG, 256); }
  if (KB > 0) { wg_wait<1>(); if (KB != 15 || c.wg == 0) release(c, B_E1 + 8 * ((KB - 1) & 3)); }
  if (KB == 15) { wg_wait<0>(); release(c, B_E1 + 24); }
}
template <class F> __device__ __forceinline__ void p1_loop(float (&acc)[128], const Cons& c, int from, int to, F&& shadow) {
#pragma unroll 1
  for (int kb = from; kb < to; kb++) {
    const bool wrap = (kb & 3) == 3;
    mbar_spin(c.sb + B_F1 + 8 * (kb & 3), (kb >> 2) & 1, c.zero);
    wg_fence();
    wgmma256<1>(acc, c.a, c.b, c.k1, c.b1);
    wgmma256<1>(acc, c.a, c.b, c.k2, c.b1);
    wgmma256<1>(acc, c.a, c.b, c.k1, c.b1);
    wgmma256<1>(acc, c.a, c.b, wrap ? c.k4w : c.k4, wrap ? -6144 - 384 : 2048 - 384);
    wg_commit();
    wg_wait<1>();
    release(c, B_E1 + 8 * ((kb - 1) & 3));
    shadow(kb);
  }
}
template <int T> __device__ __forceinline__ void p2_step(float (&acc)[64], const Cons& c) {
  if (T == 12) { if (c.wg == 1) bar_sync(BAR_LAG, 256); }
  mbar_spin(c.sb + B_F2 + 8 * (T % 5), (T / 5) & 1, c.zero);
  wg_fence();
  wgmma128<T != 0>(acc, c.a, c.b, c.k1, c.b1);
  wgmma128<1>(acc, c.a, c.b, c.k2, c.b1);
  wgmma128<1>(acc, c.a, c.b, c.k1, c.b1);
  wgmma128<1>(acc, c.a, c.b, ((int)p2_a((T + 1) % 5) - (int)p2_a(T % 5)) / 16 - 514, ((int)p2_b((T + 1) % 5) - (int)p2_b(T % 5)) / 16 - 384);
  wg_commit();
  if (T == 15) { if (c.wg == 0) bar_arrive(BAR_LAG, 256); }
  if (T <= 11) { wg_wait<1>(); release(c, T ? B_E2 + 8 * ((T + 4) % 5) : B_E1 + 8); }
}

template <int P> __device__ __forceinline__ void geglu_piece(uint32_t (&pk)[64], uint8_t* dst, float (&rs)[2]) {
  constexpr int cg = P >> 1, r = P & 1;
  pin<1>(rs + r);
#pragma unroll
  for (int i = 0; i < 4; i++) pin<1>(pk + 2 * (4 * cg + i) + r);
  const float r2 = rs[r] * rs[r], c1 = GELU_C1 * rs[r], c3 = GELU_C3 * r2 * rs[r], k = 0.25f * r2;
  uint32_t v[4];
#pragma unroll
  for (int i = 0; i < 4; i++) {
    const uint32_t g = pk[2 * (4 * cg + i) + r];
    v[i] = mul2(pack2(gelu_k(lo_f(g), c1, c3, k), gelu_k(hi_f(g), c1, c3, k)), pk[32 + 2 * (4 * cg + i) + r]);
  }
  stg128(dst + cg * 8192 + r * 512, v[0], v[1], v[2], v[3]);
}
__device__ __forceinline__ void geglu_tile(float (&acc)[128], uint32_t (&pk)[64], const Cons& c, int to, uint8_t* dst, int ev, float (&rs)[2]) {
  const int lane = lane_here();
  dst += (lane ^ (lane >> 3)) << 4;
  p1_loop(acc, c, 1, to, [&](int kb) {
    if (kb <= 4) {
      if (kb <= 2) { if (kb == 1) geglu_piece<0>(pk, dst, rs); else geglu_piece<1>(pk, dst, rs); }
      else { if (kb == 3) geglu_piece<2>(pk, dst, rs); else geglu_piece<3>(pk, dst, rs); }
    } else if (kb <= 8) {
      if (kb <= 6) { if (kb == 5) geglu_piece<4>(pk, dst, rs); else geglu_piece<5>(pk, dst, rs); }
      else { if (kb == 7) geglu_piece<6>(pk, dst, rs); else { geglu_piece<7>(pk, dst, rs); bar_arrive(ev, 288); } }
    }
  });
}

__device__ __forceinline__ void attn_tile(float (&acc)[128], uint32_t (&pk)[64], const Cons& c, int round, int warp, int m, unsigned bid, Scratch* gs, uint8_t* hdst, uint8_t* odst) {
  const int w = warp & 3;
  const uint32_t at = c.sb + OFF_X + c.wg * AT_WG;
  int lane = lane_here();
  hdst += (lane ^ (lane >> 3)) << 4;
  auto scatter = [&]() {
    const int lane = lane_here();
    const uint32_t swz = (lane ^ (lane >> 3)) << 4;
#pragma unroll
    for (int i = 0; i < 4; i++) {
      const int h = i & 1, r = i >> 1;
      sts128(at + AT_V + (2 * w + r) * 1024 + h * 512 + swz, make_uint4(pk[32 + 8 * h + r], pk[34 + 8 * h + r], pk[36 + 8 * h + r], pk[38 + 8 * h + r]));
    }
    if (w < 3) {
#pragma unroll
      for (int i = 0; i < 8; i++) asm volatile("st.shared.b32 [%0], %1;" ::"r"(at + AT_K + w * 1024 + i * 128 + lane * 4), "r"(pk[17 + 2 * i]) : "memory");
    } else {
      uint8_t* g = (uint8_t*)gs->halo + ((round * 128 + bid) * 2 + c.wg) * 2048;
#pragma unroll
      for (int i = 0; i < 8; i++) asm volatile("st.global.b32 [%0], %1;" ::"l"(g + i * 128 + lane * 4), "r"(pk[17 + 2 * i]) : "memory");
#pragma unroll
      for (int h = 0; h < 2; h++) stg128(g + 1024 + h * 512 + swz, pk[33 + 8 * h], pk[35 + 8 * h], pk[37 + 8 * h], pk[39 + 8 * h]);
      bar_arrive(BAR_EV + 2 + round, 96);
    }
    __syncwarp();
    if (lane == 0) mbar_arrive(c.sb + B_HALO + 8 * round);
    if (round) {
#pragma unroll
      for (int p = 0; p < 4; p++) {
        const int o = 32 + 8 * (p >> 1) + (p & 1);
        asm volatile("ld.global.cg.v4.b32 {%0,%1,%2,%3}, [%4];" : "=r"(pk[o]), "=r"(pk[o + 2]), "=r"(pk[o + 4]), "=r"(pk[o + 6]) : "l"(hdst + (p >> 1) * 8192 + (p & 1) * 512) : "memory");
      }
    }
  };
  auto gu_piece = [&](int p) {
    uint32_t v[4];
#pragma unroll
    for (int i = 0; i < 4; i++) {
      const int o = 8 * (p >> 1) + 2 * i + (p & 1);
      pin<1>(pk + 48 + o);
      const uint32_t g = pk[48 + o];
      v[i] = mul2(round ? pk[32 + o] : 0x3e803e80u, round ? g : pack2(gelu_k(lo_f(g), GELU_C1, GELU_C3, 1.0f), gelu_k(hi_f(g), GELU_C1, GELU_C3, 1.0f)));
    }
    stg128(hdst + (p >> 1) * 8192 + (p & 1) * 512, v[0], v[1], v[2], v[3]);
  };
  p1_step<1>(acc, c);
  scatter();
  p1_loop(acc, c, 2, 9, [&](int kb) {
    if (kb <= 4) { if (kb == 3) gu_piece(0); else if (kb == 4) gu_piece(1); }
    else if (kb == 5) gu_piece(2); else if (kb == 6) gu_piece(3);
  });
  const bool first = m == 0 && w == 0;
  uint32_t kl[16];
  mbar_spin(c.sb + B_HALO + 8 * round, 0, c.zero);
  lane = lane_here();
  {
    const uint32_t ka = at + lane * 4 + (w ? AT_K + (w - 1) * 1024 : (first ? AT_K : AT_REM + round * 2048));
#pragma unroll
    for (int i = 0; i < 8; i++) {
      asm volatile("ld.shared.b32 %0, [%1];" : "=r"(kl[2 * i]) : "r"(ka + i * 128) : "memory");
      kl[2 * i + 1] = pk[16 + 2 * i] | c.zero;
    }
  }
  float st[4][4];
  pin<16>(kl);
  bar_sync(BAR_MMA, 256);
  mbar_spin(c.sb + B_F1 + 8 * 1, 0, c.zero);
#pragma unroll
  for (int ks = 0; ks < 2; ks++) {
#pragma unroll
    for (int h = 0; h < 2; h++) {
      const int o = 8 * h + 4 * ks;
      if (ks == 0) { hmma<0>(st[2 * h], kl[o], kl[o + 1], kl[o + 2], kl[o + 3], pk[o], pk[o + 2]); hmma<0>(st[2 * h + 1], pk[16 + o], pk[17 + o], pk[18 + o], pk[19 + o], pk[o + 1], pk[o + 3]); }
      else { hmma<1>(st[2 * h], kl[o], kl[o + 1], kl[o + 2], kl[o + 3], pk[o], pk[o + 2]); hmma<1>(st[2 * h + 1], pk[16 + o], pk[17 + o], pk[18 + o], pk[19 + o], pk[o + 1], pk[o + 3]); }
    }
  }
  sched_fence(c.zero);
  bar_sync(BAR_MMA, 256);
  p1_step<9, false>(acc, c);
  sched_fence(c.zero);
  pin<16>(&st[0][0]);
  lane = lane_here();
  const int rho = lane >> 2, q = lane & 3;
  const bool le0 = 2 * q <= rho, le1 = 2 * q + 1 <= rho;
  uint32_t la[2], lb[2], mx[2];
#pragma unroll
  for (int h = 0; h < 2; h++) {
    uint32_t l[2];
#pragma unroll
    for (int r = 0; r < 2; r++) {
      const float (&t)[4] = st[2 * h + r];
      l[r] = movm(pack2(rho <= 2 * q ? t[2] : t[0], rho <= 2 * q + 1 ? t[3] : t[1]));
      l[r] = fma2(l[r], 0x3e353e35u, mul2(l[r], 0x379e379eu));
    }
    la[h] = __byte_perm(l[0], l[1], 0x5410); lb[h] = __byte_perm(l[0], l[1], 0x7632);
    if (first && !le0) la[h] = (la[h] & 0xffff0000u) | 0xce6eu;
    if (first && !le1) lb[h] = (lb[h] & 0xffff0000u) | 0xce6eu;
    mx[h] = max2(la[h], lb[h]);
  }
#pragma unroll
  for (int o = 1; o <= 2; o++) { mx[0] = max2(mx[0], __shfl_xor_sync(~0u, mx[0], o)); mx[1] = max2(mx[1], __shfl_xor_sync(~0u, mx[1], o)); }
  const float L2E = 1.4426950408889634f;
  float pr[2][4], z[4];
#pragma unroll
  for (int h = 0; h < 2; h++) {
    pr[h][0] = ex2f((lo_f(la[h]) - lo_f(mx[h])) * L2E); pr[h][1] = ex2f((lo_f(lb[h]) - lo_f(mx[h])) * L2E);
    pr[h][2] = ex2f((hi_f(la[h]) - hi_f(mx[h])) * L2E); pr[h][3] = ex2f((hi_f(lb[h]) - hi_f(mx[h])) * L2E);
    z[2 * h] = pr[h][0] + pr[h][1]; z[2 * h + 1] = pr[h][2] + pr[h][3];
  }
  p1_step<10>(acc, c);
#pragma unroll
  for (int o = 1; o <= 2; o++) {
#pragma unroll
    for (int i = 0; i < 4; i++) z[i] += __shfl_xor_sync(~0u, z[i], o);
  }
  const uint32_t LE = (le0 ? 0xffffu : 0u) | (le1 ? 0xffff0000u : 0u);
  uint32_t P[4][2];
  uint4 vt[4][2];
  {
    const uint32_t row = (lane & 7) * 64 + ((((lane >> 3) & 1) ^ ((lane & 7) >> 1)) << 4);
    const uint32_t v1 = at + AT_V + (2 * w + (lane >> 4)) * 1024 + row;
    const uint32_t v0 = (w || lane >= 16) ? v1 - 1024 : (first ? v1 : at + AT_REM + round * 2048 + 1024 + row);
#pragma unroll
    for (int i = 0; i < 4; i++) {
      const float rz = rcpf(z[i]);
      const uint32_t p = pack2(pr[i >> 1][2 * (i & 1)] * rz, pr[i >> 1][2 * (i & 1) + 1] * rz);
      P[i][0] = p & ~LE; P[i][1] = p & LE;
      const uint32_t a = ((i & 1) ? v1 : v0) + (i >> 1) * 512;
      vt[i][0] = ldsm_t(a); vt[i][1] = ldsm_t(a ^ 32);
    }
  }
  float ot[4][2][4];
  pin<8>(&P[0][0]);
  bar_sync(BAR_MMA, 256);
  mbar_spin(c.sb + B_F1 + 8 * 3, 0, c.zero);
#pragma unroll
  for (int i = 0; i < 8; i++) { const uint4& v = vt[i >> 1][i & 1]; hmma<0>(ot[i >> 1][i & 1], v.x, v.y, v.z, v.w, P[i >> 1][0], P[i >> 1][1]); }
  sched_fence(c.zero);
  bar_sync(BAR_MMA, 256);
  p1_step<11, false>(acc, c);
  sched_fence(c.zero);
  pin<32>(&ot[0][0][0]);
  lane = lane_here();
  odst += (lane ^ (lane >> 3)) << 4;
  auto o_piece = [&](int i) {
    stg128(odst + (i >> 1) * 8192 + (i & 1) * 512, movm(pack2(ot[i][0][0], ot[i][0][1])), movm(pack2(ot[i][0][2], ot[i][0][3])), movm(pack2(ot[i][1][0], ot[i][1][1])), movm(pack2(ot[i][1][2], ot[i][1][3])));
  };
  o_piece(0); o_piece(1);
  p1_step<12>(acc, c);
  o_piece(2); o_piece(3);
  if (round) bar_arrive(BAR_EV + 4, 288);
  p1_loop(acc, c, 13, 15, [](int) {});
}

__device__ __forceinline__ void ln_moments(const uint32_t* raw, float& c0, float& s, float& v) {
  c0 = lo_f(__shfl_sync(~0u, raw[0], 0));
  float ss[4] = {0.f, 0.f, 0.f, 0.f}, vv[4] = {0.f, 0.f, 0.f, 0.f};
#pragma unroll
  for (int i = 0; i < 16; i++) {
    const float a = lo_f(raw[i]) - c0, b = hi_f(raw[i]) - c0;
    ss[(2 * i) & 3] += a; ss[(2 * i + 1) & 3] += b;
    vv[(2 * i) & 3] = fmaf(a, a, vv[(2 * i) & 3]); vv[(2 * i + 1) & 3] = fmaf(b, b, vv[(2 * i + 1) & 3]);
  }
  s = (ss[0] + ss[1]) + (ss[2] + ss[3]); v = (vv[0] + vv[1]) + (vv[2] + vv[3]);
}
__device__ __forceinline__ void ln_reduce(float& s, float& v) {
#pragma unroll
  for (int o = 16; o; o >>= 1) { s += __shfl_xor_sync(~0u, s, o); v += __shfl_xor_sync(~0u, v, o); }
}
__device__ __forceinline__ uint32_t ln_finish(float c0, float s, float v) {
  s *= 1.0f / DM;
  float sd;
  asm("sqrt.approx.ftz.f32 %0, %1;" : "=f"(sd) : "f"(bf16r(bf16r(fmaxf(fmaf(v, 1.0f / DM, -s * s), 0.f)) + 1e-5f)));
  return pack2(c0 + s, sd);
}
__device__ __forceinline__ void ln_store(const uint32_t* raw, uint32_t st, uint4* dst) {
  const uint32_t m2 = __byte_perm(st, st, 0x1010);
  const float rinv = rcpf(hi_f(st));
  const uint32_t rh = pack2(rinv, rinv), rl = pack2(rinv - hi_f(rh), rinv - hi_f(rh));
#pragma unroll
  for (int c = 0; c < 4; c++) {
    uint32_t v[4];
#pragma unroll
    for (int i = 0; i < 4; i++) { const uint32_t t = sub2(raw[4 * c + i], m2); v[i] = fma2(t, rh, mul2(t, rl)); }
    stg128(dst + 32 * c, v[0], v[1], v[2], v[3]);
  }
}
__device__ __forceinline__ void col_sums(uint32_t tile, ulonglong2* part, uint32_t tag) {
  const int lane = threadIdx.x & 31;
  float cs[8] = {0, 0, 0, 0, 0, 0, 0, 0};
  uint32_t base = tile + ((lane >> 3) & 1) * 8192 + (lane >> 4) * 4096 + ((lane & 7) << 4);
#pragma unroll 1
  for (int k0 = 0; k0 < 8; k0++, base = (base ^ ((k0 ^ (k0 - 1)) << 4)) + 128) {
    uint4 v[4];
#pragma unroll
    for (int k = 0; k < 4; k++) v[k] = lds128(base + k * 1024);
#pragma unroll
    for (int k = 0; k < 4; k++) {
      cs[0] += lo_f(v[k].x); cs[1] += hi_f(v[k].x); cs[2] += lo_f(v[k].y); cs[3] += hi_f(v[k].y);
      cs[4] += lo_f(v[k].z); cs[5] += hi_f(v[k].z); cs[6] += lo_f(v[k].w); cs[7] += hi_f(v[k].w);
    }
  }
  const bool up = lane >= 16;
#pragma unroll
  for (int i = 0; i < 2; i++) {
    const float a = (up ? cs[4 + 2 * i] : cs[2 * i]) + __shfl_xor_sync(~0u, up ? cs[2 * i] : cs[4 + 2 * i], 16);
    const float b = (up ? cs[5 + 2 * i] : cs[1 + 2 * i]) + __shfl_xor_sync(~0u, up ? cs[1 + 2 * i] : cs[5 + 2 * i], 16);
    asm volatile("{\n.reg .b64 a, b;\nmov.b64 a, {%1, %3};\nmov.b64 b, {%2, %3};\nst.relaxed.gpu.global.v2.b64 [%0], {a, b};\n}"
                 ::"l"(part + 32 * (i + (up ? 2 : 0)) + (lane & 15)), "r"(__float_as_uint(a)), "r"(__float_as_uint(b)), "r"(tag) : "memory");
  }
  asm volatile("fence.proxy.async.shared::cta;" ::: "memory");
}

__global__ void __cluster_dims__(2, 1, 1) __launch_bounds__(384, 1)
fused_kernel(const uint4* __restrict__ x, const uint4* __restrict__ wgate, const uint4* __restrict__ wup, Scratch* gs, int by_sm, const __grid_constant__ Maps mp) {
  extern __shared__ __align__(1024) uint8_t smem_raw[];
  const uint32_t sb = (uint32_t)__cvta_generic_to_shared(smem_raw);
  const unsigned bid = role_id(by_sm);
  if (threadIdx.x == 352) TS(63);
  if (threadIdx.x < 256 && bid < NMAIN) {
    const uint32_t r = threadIdx.x >> 3, ch = threadIdx.x & 7;
    const uint32_t d = sb + r * 128 + ((ch ^ (r & 7)) << 4);
    const uint8_t* xa = (const uint8_t*)x + ((bid & 15) * 262144 + r * 4096 + ch * 16);
    const uint32_t wo = r * (DFF * 2) + (bid >> 4) * 256 + ch * 16;
    const uint8_t *wa = (const uint8_t*)wgate + wo, *wb = (const uint8_t*)wup + wo;
#pragma unroll
    for (int i = 0; i < 12; i++) {
      const int h = i >= 8;
      const uint8_t* src = (i >> 2) == 1 ? xa + (i & 1) * 131072 + ((i >> 1) & 1) * 2048 : ((i & 2) ? wb : wa) + h * 32 * (DFF * 2) + (i & 1) * 128;
      asm volatile("cp.async.cg.shared.global [%0], [%1], 16;" ::"r"(d + ((i >> 2) == 1 ? OFF_A + (i & 3) * 4096 : (i & 3) * 8192 + h * 4096)), "l"(src) : "memory");
    }
    if (threadIdx.x == 0) TS(23);
  }
  const int warp = __shfl_sync(~0u, threadIdx.x >> 5, 0), lane = threadIdx.x & 31;
  const int m = bid & 15, j = bid >> 4, rank = bid & 1;
  const int m2 = bid >> 3, j2 = bid & 7;
  const uint32_t zero = warp >> 8;
  const bool helper = bid >= NMAIN;
  if (warp >= 8) {
    asm volatile("setmaxnreg.dec.sync.aligned.u32 40;");
    if (warp == 8) {
      if (elect_one()) {
        asm volatile("prefetch.tensormap [%0];\nprefetch.tensormap [%1];\nprefetch.tensormap [%2];" ::"l"(&mp.x), "l"(&mp.wg), "l"(&mp.wu) : "memory");
        for (int s = 0; s < 4; s++) mbar_init(sb + B_F1 + 8 * s, 1);
        if (!helper) mbar_arrive(sb + B_F1);
        asm volatile("fence.mbarrier_init.release.cluster;" ::: "memory");
      }
      __syncwarp();
    } else if (warp == 9) {
      if (elect_one()) {
        unsigned nsmid;
        asm("mov.u32 %0, %%nsmid;" : "=r"(nsmid));
        if ((sb & 0xffffff) != SM_BASE || (by_sm && nsmid != NCTA)) asm volatile("trap;");
        for (uint32_t b = B_E1; b < B_F2; b += 8) mbar_init(sb + b, 4);
        for (uint32_t b = B_F2; b < B_AUX; b += 8) mbar_init(sb + b, 1);
        for (uint32_t b = B_EX; b < B_AUX; b += 8) mbar_expect_tx(sb + b, 8192);
        mbar_init(sb + B_AUX, 8); mbar_init(sb + B_HALO, 9); mbar_init(sb + B_HALO + 8, 9);
        asm volatile("st.shared.b32 [%0], %1;" ::"r"(sb + OFF_EPOCH + 4), "r"(bid) : "memory");
        asm volatile("fence.mbarrier_init.release.cluster;" ::: "memory");
      }
      __syncwarp();
    }
    asm volatile("barrier.cluster.arrive.relaxed.aligned;" ::: "memory");
    if (warp == 8 && !helper) {
      if (elect_one()) {
        TS(0); TG(51);
#pragma unroll 1
        for (int kb = 1; kb < 4; kb++) {
          const uint32_t sa = sb + OFF_A + kb * 16384, sw = sb + kb * 32768, fb = sb + B_F1 + 8 * kb;
          mbar_expect_tx(fb, P1_BYTES);
          tma3d(sa, &mp.x, fb, kb * 64, m * 64, 0, EVICT_NORMAL);
          tma2d(sw, &mp.wg, fb, j * 128, kb * 64, EVICT_NORMAL); tma2d(sw + 16384, &mp.wu, fb, j * 128, kb * 64, EVICT_NORMAL);
          tma2d(sw + 8192, &mp.wg, fb, j * 128 + 64, kb * 64, EVICT_NORMAL); tma2d(sw + 24576, &mp.wu, fb, j * 128 + 64, kb * 64, EVICT_NORMAL);
        }
        TS(7);
      }
      __syncwarp();
    }
    asm volatile("barrier.cluster.wait.aligned;" ::: "memory");
    if (helper) {
      if (warp == 8) {
        if (elect_one()) {
          unsigned* ep = &gs->epoch[bid * 2];
          const unsigned e = *ep + 1;
          *ep = e;
#pragma unroll 1
          for (int i = 0; i < 20; i++) {
            const uint32_t fb = sb + (i < 16 ? B_F1 + 8 * (i >> 2) : B_XT);
            if (!(i & 3)) mbar_expect_tx(fb, i < 16 ? P1_BYTES : 32768);
            tma5d(sb + (i < 16 ? i : i + 8) * 8192, &mp.wd, fb, (bid - NMAIN) * 256 + (i & 3) * 64, (i >> 2) * 2, EVICT_FIRST);
          }
          mbar_spin(sb + B_XT, 0, zero);
#pragma unroll 1
          for (int t = 0; t < 16; t++) {
            flag_wait(&gs->flags[(FL_H + t * 4) * 32], e * 8u);
            fence_async();
            if (t == 0) TS(0);
#pragma unroll 1
            for (int n = 0; n < 5; n++) {
              const int i = n ? n - 1 : 4;
              const uint32_t fb = sb + (i < 4 ? B_F1 + 8 * i : B_F2);
              if (t) mbar_spin(sb + B_E1 + 8 * i, ~t & 1, zero);
              if (t || i == 4) mbar_expect_tx(fb, i < 4 ? 16384 : 8192);
              const uint4* src = gs->h + (t * 56 + i) * 1024;
              bulk_load(sb + (i < 4 ? OFF_A + i * 16384 : OFF_X + 4096), src, i < 4 ? 16384 : 4096, fb, EVICT_NORMAL);
              if (i == 4) bulk_load(sb + OFF_X + 12288, src + 256, 4096, fb, EVICT_NORMAL);
            }
          }
        }
      } else if (warp == 9) {
#pragma unroll 1
        for (int t = 0; t < 16; t++) {
          bar_sync(BAR_EV + (t & 1), 288);
          if (lane == 0) { flag_add(&gs->flags[(FL_P + t) * 32]); TS(64 + t); }
          __syncwarp();
        }
      }
    } else if (warp == 8) {
      if (elect_one()) {
        uint32_t par = 0;

        auto x_load = [&]() {
          mbar_expect_tx(sb + B_XT, 32768);
          tma3d(sb + OFF_X, &mp.x, sb + B_XT, j2 * 128, m2 * 64, 0, EVICT_FIRST); tma3d(sb + OFF_X + 16384, &mp.x, sb + B_XT, j2 * 128 + 64, m2 * 64, 0, EVICT_FIRST);
        };
        auto w_tile = [&](int R, const CUtensorMap*& mb0, const CUtensorMap*& mb1, int& n0, int& n1) {
          if (R == 1 || R == 2) {
            mb0 = &mp.wqkv; n0 = 64 * (j + 8 * (R - 1)) + rank * 2048;
            mb1 = rank ? (R == 1 ? &mp.wg : &mp.wu) : &mp.wqkv; n1 = rank ? 1024 + 64 * j : n0 + 1024;
          } else {
            mb0 = mb1 = rank ? &mp.wu : &mp.wg;
            n0 = 128 * j + (R ? 1024 * R - 1536 : 0); n1 = n0 + 64;
          }
        };
        for (int R = 0; R < 5; R++) {
          const CUtensorMap *mb0, *mb1;
          int n0, n1;
          w_tile(R, mb0, mb1, n0, n1);
#pragma unroll 1
          for (int kb = R ? 0 : 4; kb < 16; kb++) {
            if (R == 0 && kb == CS_KB) {
#pragma unroll 1
              for (int h = 0; h < 2; h++) {
                const uint32_t cb = sb + B_CS + 8 * h, d = sb + OFF_X + 16384 * h;
                mbar_expect_tx(cb, 16384);
                tma2d(d, h ? &mp.wu : &mp.wg, cb, n0, m * 64, EVICT_NORMAL); tma2d(d + 8192, h ? &mp.wu : &mp.wg, cb, n1, m * 64, EVICT_NORMAL);
              }
            }
            const int st = kb & 3;
            const uint32_t sa = sb + OFF_A + st * 16384, sw = sb + st * 32768, fb = sb + B_F1 + 8 * st;
            mbar_spin(sb + B_E1 + 8 * st, par, zero);
            if (R * 16 + kb >= 4) REL_TS(R * 16 + kb - 4);
            mbar_expect_tx(fb, P1_BYTES);
            tma2d_mc(sw + rank * 16384, mb0, fb, n0, kb * 64, EVICT_FIRST);
            tma2d_mc(sw + 8192 + rank * 16384, mb1, fb, n1, kb * 64, EVICT_FIRST);
            if (R == 0) {
              tma3d(sa, &mp.x, fb, kb * 64, m * 64, 0, EVICT_NORMAL);
            } else {
              if (R == 1 && kb == 0) { mbar_spin(sb + B_DEP, 0, zero); TS(1); }
              tma2d(sa, &mp.xn, fb, kb * 64, m * 128, R == 4 ? EVICT_FIRST : EVICT_NORMAL);
            }
            if (R == 4 && kb == 4 + j2) x_load();
            if (st == 3) par ^= 1;
          }
        }
#pragma unroll 1
        for (int i = 0; i < 26; i++) {
          const int st = i & 3, kh = i < 25 ? 9 + 4 * i + 2 * rank : 109 + rank;
          const uint32_t sa = sb + OFF_A + st * 16384, sw = sb + st * 32768, fb = sb + B_F1 + 8 * st;
          mbar_spin(sb + B_E1 + 8 * st, par, zero);
          REL_TS(76 + i);
          mbar_expect_tx(fb, P1_BYTES);
          tma5d(sw, &mp.wd, fb, j2 * 128, kh, EVICT_FIRST); tma5d(sw + 8192, &mp.wd, fb, j2 * 128 + 64, kh, EVICT_FIRST);
          tma5d(sw + 16384, &mp.wd, fb, (j2 ^ 1) * 128, kh, EVICT_FIRST); tma5d(sw + 24576, &mp.wd, fb, (j2 ^ 1) * 128 + 64, kh, EVICT_FIRST);
          if (i == 0 || i == 5 || i == 9 || i == 17) mbar_spin(sb + B_DEP + 8 * (1 + ((i + 7) >> 3)), 0, zero);
          bulk_load(sa, gs->h + (m2 * 112 + kh) * 512, 16384, fb, EVICT_FIRST);
          if (st == 3) par ^= 1;
        }
        int st = 0; uint32_t par2 = 1;
#pragma unroll 1
        for (int t = 0; t < 16; t++) {
          constexpr auto tab = [](auto f) { uint32_t v = 0; for (int s = 0; s < 5; s++) v |= f(s) / 16384 << (4 * s); return v; };
          const uint32_t sa = sb + (tab(p2_a) >> (4 * st) & 15) * 16384, sw = sb + (tab(p2_b) >> (4 * st) & 15) * 16384, fb = sb + B_F2 + 8 * st;
          mbar_spin(sb + (t < 5 ? B_E1 + 8 * (0x10332 >> (4 * t) & 3) : B_E2 + 8 * st), t < 5 ? t < 3 : par2, zero);
          REL_TS(102 + t);
          mbar_expect_tx(fb, P2_BYTES);
          bulk_load_mc(sa + rank * 8192, gs->o + (m2 * 16 + t) * 1024 + rank * 512, 8192, fb, EVICT_FIRST);
          tma2d(sw, &mp.wo, fb, j2 * 128, t * 64, EVICT_FIRST); tma2d(sw + 8192, &mp.wo, fb, j2 * 128 + 64, t * 64, EVICT_FIRST);
          if (++st == 5) { st = 0; par2 ^= 1; }
        }
      }
    } else if (warp == 9) {
#pragma unroll 1
      for (int e = 0; e < 7; e++) {
        const bool halo = e == 2 || e == 3;
        bar_sync(BAR_EV + e, halo ? 96 : 288);
        if (lane == 0) {
          const int f = e == 0 ? FL_XN + m : (halo ? FL_HALO + (e - 2) * 128 + bid : FL_H + m * 4 + (e == 1 ? 0 : e - 3));
          TS(10 + 2 * e); TG(52 + e);
          flag_add(&gs->flags[f * 32]);
          if (e < 6) TS(11 + 2 * e);
        }
        __syncwarp();
      }
      unsigned other;
      asm volatile("ld.shared::cluster.b32 %0, [%1];" : "=r"(other) : "r"(mapa(sb + OFF_EPOCH + 4, rank ^ 1)) : "memory");
      if (other != (bid ^ 1)) asm volatile("trap;");
      mbar_wait(sb + B_DONE, 0);
    } else {
      unsigned e = 0;
      if (lane == 0) {
        unsigned* ep = &gs->epoch[bid * 2 + warp - 10];
        e = *ep + 1; *ep = e;
        if (warp == 10) { asm volatile("st.shared.b32 [%0], %1;" ::"r"(sb + OFF_EPOCH), "r"(e) : "memory"); mbar_arrive(sb + B_EP); }
      }
      e = __shfl_sync(~0u, e, 0);
      mbar_spin(sb + B_CS + 8 * (warp - 10), 0, zero);
      if (lane == 0 && warp == 11) TS(6);
      col_sums(sb + OFF_X + (warp - 10) * 16384, gs->cspart + (j * 16 + m) * 128 + (warp - 10) * 16, e);
      if (lane == 0 && warp == 11) TS(9);
      if (warp == 10) {
        if (lane == 0) {
#pragma unroll 1
          for (int g = 0; g < 6; g++) {
            flag_wait(&gs->flags[(g == 5 ? FL_P + m2 : (g ? FL_H + m2 * 4 + g - 1 : FL_XN + m)) * 32], e * (g == 5 ? 4u : 8u));
            fence_async();
            mbar_arrive(sb + B_DEP + 8 * g);
            if (g == 0) TS(8);
          }
        }
      } else
      if (elect_one()) {
#pragma unroll 1
        for (int i = 3; i < 8; i++) asm volatile("prefetch.tensormap [%0];" ::"l"(&mp.x + i) : "memory");
#pragma unroll 1
        for (int r = 0; r < 2; r++) {
          const uint32_t hb = sb + B_HALO + 8 * r;
          if (r) mbar_spin(sb + B_HALO, 0, zero);
          if (m) {
            flag_wait(&gs->flags[(FL_HALO + r * 128 + bid - 1) * 32], e);
            fence_async();
            mbar_expect_tx(hb, 4096);
            for (int g = 0; g < 2; g++) bulk_load(sb + OFF_X + g * AT_WG + AT_REM + r * 2048, gs->halo + ((r * 128 + bid - 1) * 2 + g) * 128, 2048, hb, EVICT_FIRST);
          } else {
            mbar_arrive(hb);
          }
          TS(34 + r);
        }
      }
    }
  } else {
    asm volatile("barrier.cluster.arrive.relaxed.aligned;" ::: "memory");
    asm volatile("setmaxnreg.inc.sync.aligned.u32 232;");
    const int wg = warp >> 2, w = warp & 3;
    Cons c;
    c.sb = sb; c.wg = wg; c.zero = zero;
    c.a = 0x4000004000010000ull + ((SM_BASE + OFF_A + wg * 8192) >> 4); c.k1 = 2 + c.zero; c.k2 = 2; c.k4 = 1024 - 6; c.k4w = -3072 - 6; c.b1 = 128 + c.zero;
    c.b = 0x4000004000000000ull + DB_LO + c.zero;
    c.rel = mapa(sb, threadIdx.x & 1);
    c.do_rel = (threadIdx.x & 127) < 2;
    float acc[128];
    uint32_t pk[64];
    float rs[2];
    const int q = lane & 3;

    if (helper) {
      asm volatile("barrier.cluster.wait.aligned;" ::: "memory");
      c.a = 0x8000002000010000ull + ((SM_BASE + OFF_A + wg * 4096) >> 4); c.k2 = 510; c.k4 = 1024 - 514; c.k4w = -3072 - 514;
      c.rel = sb;
      uint4* dst = gs->dpart + (bid - NMAIN) * 4096 + threadIdx.x;
      auto put = [&](int p) {
#pragma unroll
        for (int i = 4 * p; i < 4 * p + 4; i++) stg128(dst + i * 256, pk[4 * i], pk[4 * i + 1], pk[4 * i + 2], pk[4 * i + 3]);
      };
#pragma unroll 1
      for (int t = 0; t < 16; t++) {
        {
          uint64_t a = c.a, b = c.b;
          desc_add(a, (OFF_X + 4096 - OFF_A + wg * 4096) >> 4); desc_add(b, OFF_X >> 4);
          mbar_spin(sb + B_F2, t & 1, c.zero);
          wg_fence();
          wgmma256<0>(acc, a, b, 2, 128); wgmma256<1>(acc, a, b, 0, 0);
          wg_commit();
        }
        p1_issue<0, 1>(acc, c, t & 1); wg_wait<1>(); release(c, B_E2);
        if (t) put(0);
        p1_issue<1, 1>(acc, c, t & 1); wg_wait<1>(); release(c, B_E1);
        if (t) put(1);
        p1_issue<2, 1>(acc, c, t & 1); wg_wait<1>(); release(c, B_E1 + 8);
        if (t) put(2);
        if (wg == 1) { wg_wait<0>(); release(c, B_E1 + 16); bar_sync(BAR_LAG, 256); }
        p1_issue<3, 1>(acc, c, t & 1);
        if (wg == 0) bar_arrive(BAR_LAG, 256);
        if (t) { put(3); bar_arrive(BAR_EV + (~t & 1), 288); dst += 8 * 2048; }
        wg_wait<1>(); if (wg == 0) release(c, B_E1 + 16);
        wg_wait<0>(); release(c, B_E1 + 24);
#pragma unroll
        for (int i = 0; i < 64; i++) pk[i] = pack2(acc[2 * i], acc[2 * i + 1]);
      }
      put(0); put(1); put(2); put(3);
      bar_arrive(BAR_EV + 1, 288);
      return;
    }
    {
      const int prow = 16 * j + 2 * warp;
      const uint4* xr = x + (size_t)(128 * m + 2 * (prow & 63) + (prow >> 6)) * 128 + lane;
      uint4* xo = gs->xn + (size_t)(128 * m + prow) * 128 + lane;
      float c0[2], mo[4];
      uint32_t st[2];
      uint32_t e;
      asm volatile("" : "+l"(xr), "+l"(xo));
      wg_fence(); wgmma256<0>(acc, c.a, c.b, 0, 0); wg_commit(); wg_wait<0>();
      asm volatile("barrier.cluster.wait.aligned;" ::: "memory");
      asm volatile("cp.async.wait_all;\nfence.proxy.async.shared::cta;" ::: "memory");
      bar_sync(BAR_MMA, 256);
      if (threadIdx.x == 0) TS(39);
      p1_step<0, false>(acc, c);
      unsigned long long part[18];
      auto gather = [&](int from, int to) {
        const int lane = lane_here();
        const unsigned long long* cp = (const unsigned long long*)gs->cspart + j * 4096 + warp * 32 + lane;
        const unsigned long long* sp = gs->stats + 128 * m + warp * 16 + (lane >> 2);
#pragma unroll
        for (int i = from; i < to; i++) asm volatile("ld.relaxed.gpu.global.b64 %0, [%1];" : "=l"(part[i]) : "l"(i < 16 ? cp + i * 256 : sp + (i - 16) * 8) : "memory");
      };
      auto row_load = [&](int r) {
#pragma unroll
        for (int i = 4 * r; i < 4 * r + 4; i++)
          asm volatile("ld.global.nc.L1::no_allocate.v4.b32 {%0,%1,%2,%3}, [%4];" : "=r"(pk[4 * i]), "=r"(pk[4 * i + 1]), "=r"(pk[4 * i + 2]), "=r"(pk[4 * i + 3]) : "l"(xr + r * 256 + (i & 3) * 32));
      };
      p1_step<1>(acc, c); row_load(0);
      p1_step<2>(acc, c); row_load(1);
      p1_loop(acc, c, 3, LN_KB + 1, [](int) {});
      pin<16>(pk); ln_moments(pk, c0[0], mo[0], mo[1]); pin<2>(mo);
      p1_step<LN_KB + 1>(acc, c);
      sched_fence(c.zero);
      pin<16>(pk + 16); ln_moments(pk + 16, c0[1], mo[2], mo[3]); ln_reduce(mo[0], mo[1]); pin<4>(mo);
      p1_step<LN_KB + 2>(acc, c);
      mbar_spin(sb + B_EP, 0, c.zero);
      asm volatile("ld.shared.b32 %0, [%1];" : "=r"(e) : "r"(sb + OFF_EPOCH) : "memory");
      pin<2>(mo); st[0] = ln_finish(c0[0], mo[0], mo[1]); ln_reduce(mo[2], mo[3]); pin<1>(st); pin<2>(mo + 2);
      p1_step<LN_KB + 3>(acc, c);
      sched_fence(c.zero);
      pin<1>(st); pin<2>(mo + 2);
      st[1] = ln_finish(c0[1], mo[2], mo[3]);
      ln_store(pk, st[0], xo);
      if (lane == 0)
        asm volatile("{\n.reg .b64 a, b;\nmov.b64 a, {%1, %3};\nmov.b64 b, {%2, %3};\nst.relaxed.gpu.global.v2.b64 [%0], {a, b};\n}" ::"l"(gs->stats + 128 * m + prow), "r"(st[0]), "r"(st[1]), "r"(e) : "memory");
      p1_step<LN_KB + 4>(acc, c);
      sched_fence(c.zero);
      pin<1>(st + 1);
      ln_store(pk + 16, st[1], xo + 128);
      bar_arrive(BAR_EV, 288);
      p1_loop(acc, c, LN_KB + 5, 13, [](int) {});
      gather(0, 9);
      p1_step<13>(acc, c);
      gather(9, 18);
      p1_step<14>(acc, c);
      auto validate = [&]() {
        float csum;
        for (int tries = 0;; tries++) {
          uint32_t bad = 0;
          csum = 0.f;
#pragma unroll
          for (int i = 0; i < 18; i++) { bad |= (uint32_t)(part[i] >> 32) ^ e; if (i < 16) csum += __uint_as_float((uint32_t)part[i]); }
          if (!__any_sync(~0u, bad != 0) || tries > (1 << 20)) break;
          gather(0, 18);
        }
        const float hi = bf16r(csum), mid = bf16r(csum - hi);
        sts128(sb + OFF_CS + ((threadIdx.x & 62) * 4 + (threadIdx.x >> 6) * 2 + (threadIdx.x & 1)) * 16, make_uint4(pack2(hi, mid), pack2(csum - hi - mid, 0.f), 0, 0));
        asm volatile("fence.proxy.async.shared::cta;" ::: "memory");
        __syncwarp();
        if (lane == 0) mbar_arrive(sb + B_AUX);
      };
#pragma unroll 1
      for (int ph = 1; ph >= 0; ph--) {
        if (wg == ph) validate();
        if (ph) {
          if (wg == 1) { wg_wait<0>(); release(c, B_E1 + 16); bar_sync(BAR_LAG, 256); }
          p1_issue<3, 1>(acc, c, 1);
        }
      }
      const uint32_t keep = q == 0 ? 0xffffffffu : (q == 1 ? 0xffffu : 0u);
      const uint32_t a0 = (__byte_perm((uint32_t)part[16], 0, 0x1010) ^ 0x80008000u) & keep, a1 = (__byte_perm((uint32_t)part[17], 0, 0x1010) ^ 0x80008000u) & keep;
      mbar_spin(sb + B_AUX, 0, c.zero);
      wg_fence();
      wgmma256_rs(acc, a0, a1, 0, 0, (SM_BASE + OFF_CS) >> 4);
      wg_commit();
      if (wg == 0) bar_arrive(BAR_LAG, 256);
      rs[0] = rcpf(hi_f((uint32_t)part[16])); rs[1] = rcpf(hi_f((uint32_t)part[17]));
      wg_wait<2>(); if (wg == 0) release(c, B_E1 + 16);
      wg_wait<0>(); release(c, B_E1 + 24);
    }
#pragma unroll 1
    for (int R = 1;; R++) {
#pragma unroll
      for (int i = 0; i < 64; i++) pk[i] = pack2(acc[2 * i], acc[2 * i + 1]);
      uint8_t* hb = (uint8_t*)gs->h + (size_t)m * 56 * 16384 + warp * 1024;
      if (R == 5) { c.a = 0x8000002000010000ull + ((SM_BASE + OFF_A + wg * 4096) >> 4); c.k2 = 510; c.k4 = 1024 - 514; c.k4w = -3072 - 514; }
      p1_step<0>(acc, c);
      if (R == 2 || R == 3) {
        attn_tile(acc, pk, c, R - 2, warp, m, bid, gs, hb + (16 + j) * 16384, (uint8_t*)gs->o + (m * 16 + j + 8 * (R - 2)) * 16384 + warp * 1024);
      } else {
        geglu_tile(acc, pk, c, R == 5 ? 24 : 15, hb + (2 * j + (R == 1 ? 0 : 16 * R - 40)) * 16384, BAR_EV + (R == 1 ? 1 : R + 1), rs);
        rs[0] = rs[1] = 1.0f;
        if (R == 5) break;
      }
      p1_step<15>(acc, c);
    }
    auto fetch = [&](int p) {
      asm volatile("ld.global.cg.v4.b32 {%0,%1,%2,%3}, [%4];" : "=r"(pk[4 * p]), "=r"(pk[4 * p + 1]), "=r"(pk[4 * p + 2]), "=r"(pk[4 * p + 3]) : "l"(gs->dpart + bid * 2048 + p * 256 + threadIdx.x) : "memory");
    };
    mbar_spin(sb + B_DEP + 40, 0, c.zero);
    fetch(0); fetch(1); fetch(2);
    p1_step<8>(acc, c);
    fetch(3); fetch(4); fetch(5);
    desc_add(c.a, 2 * rank); desc_add(c.b, 128 * rank);
    mbar_spin(sb + B_F1 + 8, 0, c.zero);
    wg_fence();
    wgmma256<1>(acc, c.a, c.b, rank ? 510 : 2, c.b1);
    wgmma256<1>(acc, c.a, c.b, rank ? 2 : 510, c.b1);
    wgmma256<1>(acc, c.a, c.b, 512 - 2 * rank, 1792 - 128 * rank);
    wg_commit();
    wg_wait<1>(); release(c, B_E1);
    fetch(6); fetch(7);
    {
      float accs[64];
      const uint32_t peer = mapa(sb, rank ^ 1);
      auto send_piece = [&](int p) {
        asm volatile("st.async.weak.shared::cluster.mbarrier::complete_tx::bytes.v4.b32 [%0], {%1,%2,%3,%4}, [%5];" ::"r"(peer + OFF_LAND + p * 4096 + threadIdx.x * 16),
                     "r"(pack2(acc[64 + 8 * p], acc[65 + 8 * p])), "r"(pack2(acc[66 + 8 * p], acc[67 + 8 * p])), "r"(pack2(acc[68 + 8 * p], acc[69 + 8 * p])), "r"(pack2(acc[70 + 8 * p], acc[71 + 8 * p])),
                     "r"(peer + B_EX + 16 * wg + 8 * (p >> 2)) : "memory");
      };
      auto silu_piece = [&](int p) {
        const uint4 r = lds128(sb + OFF_LAND + p * 4096 + threadIdx.x * 16);
        const uint32_t rr[4] = {add2(r.x, pk[4 * p]), add2(r.y, pk[4 * p + 1]), add2(r.z, pk[4 * p + 2]), add2(r.w, pk[4 * p + 3])};
#pragma unroll
        for (int i = 0; i < 4; i++) {
          const float a = acc[8 * p + 2 * i] + lo_f(rr[i]), b = acc[8 * p + 2 * i + 1] + hi_f(rr[i]);
          pk[4 * p + i] = pack2(silu_half(a), silu_half(b));
        }
        pin<4>(pk + 4 * p);
      };
      const uint32_t xa = sb + OFF_X + (warp * 16 + (lane & 7)) * 128 + (((lane >> 3) ^ (lane & 7)) << 4);
      auto x_addr = [&](int i) { return (xa ^ ((i & 1) << 6)) + ((i >> 1) & 1) * 1024 + (i >> 2) * 16384; };
      auto x_piece = [&](int i) { const uint4 v = ldsm(x_addr(i)); pk[32 + 4 * i] = v.x; pk[33 + 4 * i] = v.y; pk[34 + 4 * i] = v.z; pk[35 + 4 * i] = v.w; };
      p2_step<0>(accs, c);
      p2_step<1>(accs, c);
      mbar_spin(sb + B_E1 + 8, 0, c.zero);
      send_piece(0); send_piece(1);
      p2_step<2>(accs, c); sched_fence(c.zero); send_piece(2); send_piece(3);
      p2_step<3>(accs, c); sched_fence(c.zero); send_piece(4); send_piece(5);
      p2_step<4>(accs, c); mbar_spin(sb + B_XT, 0, c.zero); send_piece(6); send_piece(7);
      p2_step<5>(accs, c); mbar_spin(sb + B_EX + 16 * wg, 0, c.zero); silu_piece(0); x_piece(0);
      p2_step<6>(accs, c); sched_fence(c.zero); silu_piece(1); x_piece(1);
      p2_step<7>(accs, c); sched_fence(c.zero); silu_piece(2); x_piece(2);
      p2_step<8>(accs, c); sched_fence(c.zero); silu_piece(3); x_piece(3);
      p2_step<9>(accs, c); mbar_spin(sb + B_EX + 16 * wg + 8, 0, c.zero); silu_piece(4); x_piece(4);
      p2_step<10>(accs, c); sched_fence(c.zero); silu_piece(5); x_piece(5);
      p2_step<11>(accs, c); sched_fence(c.zero); silu_piece(6); x_piece(6); x_piece(7);
      auto out_half = [&](const float* a, int h) {
#pragma unroll
        for (int i = 4 * h; i < 4 * h + 4; i++) {
          uint32_t v[4];
#pragma unroll
          for (int k = 0; k < 4; k++) { const int o = 2 * (4 * (i & 1) + k) + ((i >> 1) & 1); v[k] = fma2(pack2(a[2 * o], a[2 * o + 1]), pk[16 * h + o], pk[32 + 4 * i + k]); }
          asm volatile("stmatrix.sync.aligned.m8n8.x4.shared.b16 [%0], {%1,%2,%3,%4};" ::"r"(x_addr(i)), "r"(v[0]), "r"(v[1]), "r"(v[2]), "r"(v[3]) : "memory");
          if (i & 1) {
            asm volatile("fence.proxy.async.shared::cta;" ::: "memory");
            __syncwarp();
            if (elect_one()) tma3d_store(&mp.out, sb + OFF_X + h * 16384 + warp * 2048 + (i & 2) * 512, j2 * 128 + h * 64, m2 * 64 + w * 16 + (i & 2) * 4, wg);
          }
        }
      };
      if (wg == 1) silu_piece(7);
      p2_step<12>(accs, c); p2_step<13>(accs, c); p2_step<14>(accs, c); p2_step<15>(accs, c);
      if (c.do_rel) mbar_arrive(sb + B_DONE);
      if (wg == 0) silu_piece(7);
      wg_wait<0>();
      out_half(accs, 0); out_half(accs + 32, 1);
      if (elect_one()) { asm volatile("cp.async.bulk.commit_group;\ncp.async.bulk.wait_group.read 0;" ::: "memory"); }
      if ((threadIdx.x & 127) == 0) { TS(33 + wg * 16); if (wg) { TG(59); unsigned id; asm volatile("mov.u32 %0, %%smid;" : "=r"(id)); TSV(60, id); } }
    }
  }
}

typedef CUresult (*EncodeFn)(CUtensorMap*, CUtensorMapDataType, cuuint32_t, void*, const cuuint64_t*, const cuuint64_t*, const cuuint32_t*, const cuuint32_t*,
                             CUtensorMapInterleave, CUtensorMapSwizzle, CUtensorMapL2promotion, CUtensorMapFloatOOBfill);

void encode(EncodeFn fn, CUtensorMap* tm, const void* p, int rank, const cuuint64_t* dims, const cuuint64_t* strides, const cuuint32_t* box) {
  const cuuint32_t es[5] = {1, 1, 1, 1, 1};
  fn(tm, CU_TENSOR_MAP_DATA_TYPE_BFLOAT16, rank, const_cast<void*>(p), dims, strides, box, es, CU_TENSOR_MAP_INTERLEAVE_NONE, CU_TENSOR_MAP_SWIZZLE_128B,
     CU_TENSOR_MAP_L2_PROMOTION_L2_128B, CU_TENSOR_MAP_FLOAT_OOB_FILL_NONE);
}

}

extern "C" void kernel_launch(void* const* d_in, const int* in_sizes, int n_in, void* d_out, int out_size) {
  (void)in_sizes; (void)n_in; (void)out_size;
  static EncodeFn fn = nullptr;
  static Scratch* gs = nullptr;
  static int nsm = 0;
  if (!fn) {
    void* p = nullptr;
    cudaDriverEntryPointQueryResult qr;
    cudaGetDriverEntryPoint("cuTensorMapEncodeTiled", &p, cudaEnableDefault, &qr);
    fn = (EncodeFn)p;
    cudaGetSymbolAddress((void**)&gs, g_scratch);
    int dev = 0;
    cudaGetDevice(&dev);
    cudaDeviceGetAttribute(&nsm, cudaDevAttrMultiProcessorCount, dev);
    cudaFuncSetAttribute(fused_kernel, cudaFuncAttributeMaxDynamicSharedMemorySize, SMEM_BYTES);
  }
  const void *x = d_in[0], *wqkv = d_in[1], *wo = d_in[2], *wg = d_in[4], *wu = d_in[5], *wd = d_in[6];
  Maps mp;
  {
    const cuuint64_t dims[3] = {DM, SEQ / 2, 2}, st[2] = {DM * 4, DM * 2};
    const cuuint32_t box_in[3] = {64, 64, 2}, box_out[3] = {64, 8, 1};
    encode(fn, &mp.x, x, 3, dims, st, box_in);
    encode(fn, &mp.out, d_out, 3, dims, st, box_out);
  }
  {
    const cuuint64_t dims[2] = {DM, SEQ}, st[1] = {DM * 2};
    const cuuint32_t box[2] = {64, 128};
    encode(fn, &mp.xn, gs->xn, 2, dims, st, box);
  }
  {
    const cuuint32_t box[2] = {64, 64};
    const cuuint64_t dq[2] = {3 * DM, DM}, sq[1] = {3 * DM * 2}, df[2] = {DFF, DM}, sf[1] = {DFF * 2}, dw[2] = {DM, DM}, sw[1] = {DM * 2};
    encode(fn, &mp.wqkv, wqkv, 2, dq, sq, box);
    encode(fn, &mp.wg, wg, 2, df, sf, box);
    encode(fn, &mp.wu, wu, 2, df, sf, box);
    encode(fn, &mp.wo, wo, 2, dw, sw, box);
  }
  {
    const cuuint32_t box[5] = {64, 2, 4, 4, 2};
    const cuuint64_t st[4] = {DM * 2, 8 * DM * 2, 2 * DM * 2, 32 * DM * 2};
    const cuuint64_t dd[5] = {DM, 2, 4, 4, DFF / 32};
    encode(fn, &mp.wd, wd, 5, dd, st, box);
  }
  fused_kernel<<<NCTA, 384, SMEM_BYTES>>>((const uint4*)x, (const uint4*)wg, (const uint4*)wu, gs, nsm == NCTA, mp);
}
```

```cpp
#include <cuda_runtime.h>
#include <cuda_bf16.h>
#include <cuda.h>
#include <stdint.h>

#define CS_KB 8
#define LN_KB 4

namespace {

constexpr int SEQ = 2048, DM = 1024, DFF = 3584;
constexpr int NMAIN = 128, NCTA = 132;
constexpr uint64_t EVICT_FIRST = 0x12F0000000000000ull, EVICT_NORMAL = 0x1000000000000000ull;

constexpr uint32_t SM_BASE = 0x400;
constexpr uint32_t P1_BYTES = 49152, P2_BYTES = 32768;
constexpr uint32_t OFF_A = 131072;
__host__ __device__ constexpr uint32_t p2_a(int s) { return s == 0 ? OFF_A + 32768 : s == 1 ? OFF_A + 49152 : s == 2 ? 114688 : s == 3 ? 16384 : 49152; }
__host__ __device__ constexpr uint32_t p2_b(int s) { return s < 3 ? 65536 + s * 16384 : (s - 3) * 32768; }
constexpr uint32_t OFF_LAND = OFF_A;
constexpr uint32_t OFF_X = 196608;
constexpr uint32_t OFF_CS = OFF_X + 14336;
constexpr uint32_t OFF_BAR = 229376;
constexpr uint32_t B_F1 = OFF_BAR, B_E1 = B_F1 + 32, B_E2 = B_E1 + 32, B_DONE = B_E2 + 40, B_F2 = B_DONE + 8, B_DEP = B_F2 + 40, B_CS = B_DEP + 48,
                   B_XT = B_CS + 16, B_EP = B_XT + 8, B_EX = B_EP + 8, B_AUX = B_EX + 32, B_HALO = B_AUX + 8, OFF_EPOCH = B_HALO + 16;
constexpr uint32_t SMEM_BYTES = 232448;
constexpr uint32_t AT_V = 0, AT_K = 8192, AT_REM = 11264, AT_WG = 15360;

constexpr int FL_XN = 0, FL_H = 16, FL_P = 80, FL_HALO = 96, FL_N = FL_HALO + 256;
struct __align__(1024) Scratch {
  uint4 h[16 * 56 * 1024];
  uint4 o[16 * 16 * 1024];
  uint4 xn[SEQ * DM / 8];
  uint4 dpart[128 * 8 * 256];
  uint4 halo[2 * 128 * 2 * 128];
  ulonglong2 cspart[8 * 16 * 128];
  unsigned long long stats[SEQ];
  unsigned flags[FL_N * 32];
  unsigned epoch[NCTA * 2];
};
__device__ Scratch g_scratch;
#define TG(i) do {} while (0)
#define TSV(i, v) do {} while (0)
#define TS(i) do {} while (0)

__device__ __forceinline__ unsigned role_id(bool by_sm) {
  unsigned sm;
  asm volatile("mov.u32 %0, %%smid;" : "=r"(sm));
  const unsigned t = sm >> 1;
  const unsigned c = t < 60 ? (t < 32 ? t : t + 1 + ((t - 32) * 37 >> 8)) : (t < 62 ? t + 4 : 8 * t - 464);
  return by_sm ? 2 * c + (blockIdx.x & 1) : blockIdx.x;
}

struct Maps { CUtensorMap x, wg, wu, xn, wqkv, wd, wo, out; };

__device__ __forceinline__ void mbar_init(uint32_t bar, uint32_t cnt) { asm volatile("mbarrier.init.shared::cta.b64 [%0], %1;" ::"r"(bar), "r"(cnt)); }
__device__ __forceinline__ void mbar_expect_tx(uint32_t bar, uint32_t bytes) { asm volatile("mbarrier.arrive.expect_tx.shared::cta.b64 _, [%0], %1;" ::"r"(bar), "r"(bytes) : "memory"); }
__device__ __forceinline__ void mbar_arrive(uint32_t bar) { asm volatile("mbarrier.arrive.shared::cta.b64 _, [%0];" ::"r"(bar) : "memory"); }
__device__ __forceinline__ void mbar_arrive_cl(uint32_t bar) { asm volatile("mbarrier.arrive.shared::cluster.b64 _, [%0];" ::"r"(bar) : "memory"); }
__device__ __forceinline__ uint32_t mapa(uint32_t a, uint32_t cta) { uint32_t r; asm("mapa.shared::cluster.u32 %0, %1, %2;" : "=r"(r) : "r"(a), "r"(cta)); return r; }
__device__ __forceinline__ void mbar_wait(uint32_t bar, uint32_t parity) {
  asm volatile("{\n.reg .pred p;\n.reg .u32 n;\nmov.u32 n, 0;\nLAB_WAIT:\nmbarrier.try_wait.parity.shared::cta.b64 p, [%0], %1;\n@p bra LAB_DONE;\n"
               "add.u32 n, n, 1;\nsetp.gt.u32 p, n, 4000000;\n@p trap;\nbra LAB_WAIT;\nLAB_DONE:\n}" ::"r"(bar), "r"(parity) : "memory");
}
__device__ __forceinline__ void mbar_spin(uint32_t bar, uint32_t parity, uint32_t zero) {
  asm volatile("{\n.reg .pred p, z;\nsetp.ne.u32 z, %2, 0;\nLAB_WAIT:\nmbarrier.try_wait.parity.shared::cta.b64 p, [%0], %1;\n@p bra LAB_DONE;\n@z trap;\nbra LAB_WAIT;\nLAB_DONE:\n}" ::"r"(bar), "r"(parity), "r"(zero) : "memory");
}
__device__ __forceinline__ void flag_wait(const unsigned* f, unsigned target) {
  asm volatile("{\n.reg .pred p;\n.reg .u32 n, v;\nmov.u32 n, 0;\nLAB_WAIT:\nld.relaxed.gpu.global.u32 v, [%0];\nsub.u32 v, v, %1;\nsetp.ge.s32 p, v, 0;\n@p bra LAB_DONE;\n"
               "nanosleep.u32 200;\nadd.u32 n, n, 1;\nsetp.gt.u32 p, n, 4000000;\n@p trap;\nbra LAB_WAIT;\nLAB_DONE:\nfence.acquire.gpu;\n}" ::"l"(f), "r"(target) : "memory");
}
__device__ __forceinline__ void flag_add(unsigned* f) { asm volatile("red.release.gpu.global.add.u32 [%0], 1;" ::"l"(f) : "memory"); }
__device__ __forceinline__ void fence_async() { asm volatile("fence.proxy.async.global;" ::: "memory"); }
__device__ __forceinline__ bool elect_one() { uint32_t p; asm volatile("{\n.reg .pred P;\nelect.sync _|P, 0xffffffff;\nselp.u32 %0, 1, 0, P;\n}" : "=r"(p)); return p; }
__device__ __forceinline__ void bar_sync(int id, int n) { asm volatile("bar.sync %0, %1;" ::"r"(id), "r"(n) : "memory"); }
__device__ __forceinline__ void bar_arrive(int id, int n) { asm volatile("bar.arrive %0, %1;" ::"r"(id), "r"(n) : "memory"); }

__device__ __forceinline__ void tma2d(uint32_t dst, const CUtensorMap* tm, uint32_t bar, int c0, int c1, uint64_t hint) {
  asm volatile("cp.async.bulk.tensor.2d.shared::cluster.global.mbarrier::complete_tx::bytes.L2::cache_hint [%0], [%1, {%3, %4}], [%2], %5;" ::"r"(dst), "l"(tm), "r"(bar), "r"(c0), "r"(c1), "l"(hint) : "memory");
}
__device__ __forceinline__ void tma2d_mc(uint32_t dst, const CUtensorMap* tm, uint32_t bar, int c0, int c1, uint64_t hint) {
  asm volatile("cp.async.bulk.tensor.2d.shared::cluster.global.mbarrier::complete_tx::bytes.multicast::cluster.L2::cache_hint [%0], [%1, {%3, %4}], [%2], %5, %6;" ::"r"(dst), "l"(tm), "r"(bar), "r"(c0), "r"(c1), "h"((uint16_t)3), "l"(hint) : "memory");
}
__device__ __forceinline__ void tma3d(uint32_t dst, const CUtensorMap* tm, uint32_t bar, int c0, int c1, int c2, uint64_t hint) {
  asm volatile("cp.async.bulk.tensor.3d.shared::cluster.global.mbarrier::complete_tx::bytes.L2::cache_hint [%0], [%1, {%3, %4, %5}], [%2], %6;" ::"r"(dst), "l"(tm), "r"(bar), "r"(c0), "r"(c1), "r"(c2), "l"(hint) : "memory");
}
__device__ __forceinline__ void tma5d(uint32_t dst, const CUtensorMap* tm, uint32_t bar, int c0, int c4, uint64_t hint) {
  asm volatile("cp.async.bulk.tensor.5d.shared::cluster.global.mbarrier::complete_tx::bytes.L2::cache_hint [%0], [%1, {%3, %5, %5, %5, %4}], [%2], %6;" ::"r"(dst), "l"(tm), "r"(bar), "r"(c0), "r"(c4), "r"(0), "l"(hint) : "memory");
}
__device__ __forceinline__ void tma3d_store(const CUtensorMap* tm, uint32_t src, int c0, int c1, int c2) {
  asm volatile("cp.async.bulk.tensor.3d.global.shared::cta.bulk_group.L2::cache_hint [%0, {%2, %3, %4}], [%1], %5;" ::"l"(tm), "r"(src), "r"(c0), "r"(c1), "r"(c2), "l"(EVICT_FIRST) : "memory");
}
__device__ __forceinline__ void bulk_load(uint32_t dst, const void* src, uint32_t bytes, uint32_t bar, uint64_t hint) {
  asm volatile("cp.async.bulk.shared::cluster.global.mbarrier::complete_tx::bytes.L2::cache_hint [%0], [%1], %2, [%3], %4;" ::"r"(dst), "l"(src), "r"(bytes), "r"(bar), "l"(hint) : "memory");
}
__device__ __forceinline__ void bulk_load_mc(uint32_t dst, const void* src, uint32_t bytes, uint32_t bar, uint64_t hint) {
  asm volatile("cp.async.bulk.shared::cluster.global.mbarrier::complete_tx::bytes.multicast::cluster.L2::cache_hint [%0], [%1], %2, [%3], %4, %5;" ::"r"(dst), "l"(src), "r"(bytes), "r"(bar), "h"((uint16_t)3), "l"(hint) : "memory");
}
__device__ __forceinline__ uint4 lds128(uint32_t a) { uint4 v; asm volatile("ld.shared.v4.b32 {%0,%1,%2,%3}, [%4];" : "=r"(v.x), "=r"(v.y), "=r"(v.z), "=r"(v.w) : "r"(a) : "memory"); return v; }
__device__ __forceinline__ void sts128(uint32_t a, uint4 v) { asm volatile("st.shared.v4.b32 [%0], {%1,%2,%3,%4};" ::"r"(a), "r"(v.x), "r"(v.y), "r"(v.z), "r"(v.w) : "memory"); }
__device__ __forceinline__ void stg128(void* p, uint32_t a, uint32_t b, uint32_t c, uint32_t d) { asm volatile("st.global.v4.b32 [%0], {%1,%2,%3,%4};" ::"l"(p), "r"(a), "r"(b), "r"(c), "r"(d) : "memory"); }

__device__ __forceinline__ uint32_t pack2(float lo, float hi) { uint32_t r; asm("cvt.rn.bf16x2.f32 %0, %1, %2;" : "=r"(r) : "f"(hi), "f"(lo)); return r; }
__device__ __forceinline__ float lo_f(uint32_t v) { return __uint_as_float(v << 16); }
__device__ __forceinline__ float hi_f(uint32_t v) { return __uint_as_float(v & 0xffff0000u); }
__device__ __forceinline__ float bf16r(float v) { return lo_f(pack2(v, 0.f)); }
__device__ __forceinline__ uint32_t mul2(uint32_t a, uint32_t b) { uint32_t r; asm("mul.rn.bf16x2 %0, %1, %2;" : "=r"(r) : "r"(a), "r"(b)); return r; }
__device__ __forceinline__ uint32_t add2(uint32_t a, uint32_t b) { uint32_t r; asm("add.rn.bf16x2 %0, %1, %2;" : "=r"(r) : "r"(a), "r"(b)); return r; }
__device__ __forceinline__ uint32_t sub2(uint32_t a, uint32_t b) { uint32_t r; asm("sub.rn.bf16x2 %0, %1, %2;" : "=r"(r) : "r"(a), "r"(b)); return r; }
__device__ __forceinline__ uint32_t fma2(uint32_t a, uint32_t b, uint32_t c) { uint32_t r; asm("fma.rn.bf16x2 %0, %1, %2, %3;" : "=r"(r) : "r"(a), "r"(b), "r"(c)); return r; }
__device__ __forceinline__ uint32_t max2(uint32_t a, uint32_t b) { uint32_t r; asm("max.bf16x2 %0, %1, %2;" : "=r"(r) : "r"(a), "r"(b)); return r; }
__device__ __forceinline__ float ex2f(float x) { float y; asm("ex2.approx.ftz.f32 %0, %1;" : "=f"(y) : "f"(x)); return y; }
__device__ __forceinline__ float rcpf(float x) { float y; asm("rcp.approx.ftz.f32 %0, %1;" : "=f"(y) : "f"(x)); return y; }
constexpr float GELU_C1 = 0.7978845608028654f, GELU_C3 = 0.035677408136300125f;
__device__ __forceinline__ float gelu_k(float g, float c1, float c3, float k) {
  float t;
  asm("tanh.approx.f32 %0, %1;" : "=f"(t) : "f"(g * fmaf(g * g, c3, c1)));
  g *= k;
  return fmaf(g, t, g);
}
__device__ __forceinline__ float silu_half(float z) { float t; asm("tanh.approx.f32 %0, %1;" : "=f"(t) : "f"(z)); return fmaf(z, t, z); }

__device__ __forceinline__ void wg_fence() { asm volatile("wgmma.fence.sync.aligned;" ::: "memory"); }
__device__ __forceinline__ void wg_commit() { asm volatile("wgmma.commit_group.sync.aligned;" ::: "memory"); }
template <int N> __device__ __forceinline__ void wg_wait() { asm volatile("wgmma.wait_group.sync.aligned %0;" ::"n"(N) : "memory"); }
#define A8(o) "+f"(d[(o)]), "+f"(d[(o) + 1]), "+f"(d[(o) + 2]), "+f"(d[(o) + 3]), "+f"(d[(o) + 4]), "+f"(d[(o) + 5]), "+f"(d[(o) + 6]), "+f"(d[(o) + 7])
#define A64(o) A8(o), A8((o) + 8), A8((o) + 16), A8((o) + 24), A8((o) + 32), A8((o) + 40), A8((o) + 48), A8((o) + 56)
#define REGS0_63 "%0,%1,%2,%3,%4,%5,%6,%7,%8,%9,%10,%11,%12,%13,%14,%15,%16,%17,%18,%19,%20,%21,%22,%23,%24,%25,%26,%27,%28,%29,%30,%31," \
                 "%32,%33,%34,%35,%36,%37,%38,%39,%40,%41,%42,%43,%44,%45,%46,%47,%48,%49,%50,%51,%52,%53,%54,%55,%56,%57,%58,%59,%60,%61,%62,%63"
#define REGS64_127 "%64,%65,%66,%67,%68,%69,%70,%71,%72,%73,%74,%75,%76,%77,%78,%79,%80,%81,%82,%83,%84,%85,%86,%87,%88,%89,%90,%91,%92,%93,%94,%95," \
                   "%96,%97,%98,%99,%100,%101,%102,%103,%104,%105,%106,%107,%108,%109,%110,%111,%112,%113,%114,%115,%116,%117,%118,%119,%120,%121,%122,%123,%124,%125,%126,%127"
__device__ __forceinline__ void desc_add(uint64_t& x, int v) { asm volatile("{\n.reg .b32 lo, hi;\nmov.b64 {lo, hi}, %0;\nadd.s32 lo, lo, %1;\nmov.b64 %0, {lo, hi};\n}" : "+l"(x) : "r"(v)); }
template <int ACCUM> __device__ __forceinline__ void wgmma256(float (&d)[128], uint64_t& a, uint64_t& b, int da, int db) {
  asm volatile("{\n.reg .pred p;\nsetp.ne.b32 p, %130, 0;\n"
               "wgmma.mma_async.sync.aligned.m64n256k16.f32.bf16.bf16 {" REGS0_63 "," REGS64_127 "}, %128, %129, p, 1, 1, 0, 1;\n}"
               : A64(0), A64(64) : "l"(a), "l"(b), "n"(ACCUM));
  desc_add(a, da); desc_add(b, db);
}
__device__ __forceinline__ void wgmma256_rs(float (&d)[128], uint32_t a0, uint32_t a1, uint32_t z0, uint32_t z1, uint32_t b_lo) {
  asm volatile("{\n.reg .b64 db;\nmov.b64 db, {%132, 0x00000008};\n"
               "wgmma.mma_async.sync.aligned.m64n256k16.f32.bf16.bf16 {" REGS0_63 "," REGS64_127 "}, {%128,%129,%130,%131}, db, 1, 1, 1, 0;\n}"
               : A64(0), A64(64) : "r"(a0), "r"(a1), "r"(z0), "r"(z1), "r"(b_lo));
}
template <int ACCUM> __device__ __forceinline__ void wgmma128(float (&d)[64], uint64_t& a, uint64_t& b, int da, int db) {
  asm volatile("{\n.reg .pred p;\nsetp.ne.b32 p, %66, 0;\n"
               "wgmma.mma_async.sync.aligned.m64n128k16.f32.bf16.bf16 {" REGS0_63 "}, %64, %65, p, 1, 1, 0, 1;\n}"
               : A64(0) : "l"(a), "l"(b), "n"(ACCUM));
  desc_add(a, da); desc_add(b, db);
}
template <int ACCUM> __device__ __forceinline__ void hmma(float (&c)[4], uint32_t a0, uint32_t a1, uint32_t a2, uint32_t a3, uint32_t b0, uint32_t b1) {
  if (ACCUM)
    asm volatile("mma.sync.aligned.m16n8k16.row.col.f32.bf16.bf16.f32 {%0,%1,%2,%3}, {%4,%5,%6,%7}, {%8,%9}, {%0,%1,%2,%3};"
                 : "+f"(c[0]), "+f"(c[1]), "+f"(c[2]), "+f"(c[3]) : "r"(a0), "r"(a1), "r"(a2), "r"(a3), "r"(b0), "r"(b1));
  else
    asm volatile("mma.sync.aligned.m16n8k16.row.col.f32.bf16.bf16.f32 {%0,%1,%2,%3}, {%4,%5,%6,%7}, {%8,%9}, {%10,%10,%10,%10};"
                 : "=f"(c[0]), "=f"(c[1]), "=f"(c[2]), "=f"(c[3]) : "r"(a0), "r"(a1), "r"(a2), "r"(a3), "r"(b0), "r"(b1), "f"(0.f));
}
__device__ __forceinline__ uint32_t movm(uint32_t a) { uint32_t d; asm volatile("movmatrix.sync.aligned.m8n8.trans.b16 %0, %1;" : "=r"(d) : "r"(a)); return d; }
__device__ __forceinline__ int lane_here() { int v; asm volatile("mov.u32 %0, %%laneid;" : "=r"(v)); return v; }
template <int N> __device__ __forceinline__ void pin(uint32_t* r) {
#pragma unroll
  for (int i = 0; i < N; i++) asm volatile("" : "+r"(r[i]));
}
template <int N> __device__ __forceinline__ void pin(float* r) {
#pragma unroll
  for (int i = 0; i < N; i++) asm volatile("" : "+f"(r[i]));
}
__device__ __forceinline__ void sched_fence(uint32_t zero) {
  asm volatile("{\n.reg .pred p;\nsetp.eq.u32 p, %0, 0;\nLAB_F:\n@p bra.uni LAB_D;\nnanosleep.u32 0;\nbra.uni LAB_F;\nLAB_D:\n}" ::"r"(zero) : "memory");
}
__device__ __forceinline__ uint4 ldsm(uint32_t a) { uint4 v; asm volatile("ldmatrix.sync.aligned.m8n8.x4.shared.b16 {%0,%1,%2,%3}, [%4];" : "=r"(v.x), "=r"(v.y), "=r"(v.z), "=r"(v.w) : "r"(a) : "memory"); return v; }
__device__ __forceinline__ uint4 ldsm_t(uint32_t a) { uint4 v; asm volatile("ldmatrix.sync.aligned.m8n8.x4.trans.shared.b16 {%0,%1,%2,%3}, [%4];" : "=r"(v.x), "=r"(v.y), "=r"(v.z), "=r"(v.w) : "r"(a) : "memory"); return v; }

constexpr int BAR_LAG = 1, BAR_MMA = 2, BAR_EV = 3;

struct Cons {
  uint32_t sb;
  mutable uint64_t a, b;
  int k1, k2, k4, k4w, b1;
  uint32_t rel;
  bool do_rel;
  int wg;
  uint32_t zero;
};
#define REL_TS(n) TS(64 + (n))
constexpr uint32_t DB_LO = (SM_BASE >> 4) | ((8192 >> 4) << 16);

template <int ST, int ACCUM, bool WAIT = true> __device__ __forceinline__ void p1_issue(float (&acc)[128], const Cons& c, uint32_t parity) {
  if (WAIT) mbar_spin(c.sb + B_F1 + 8 * ST, parity, c.zero);
  wg_fence();
  wgmma256<ACCUM>(acc, c.a, c.b, c.k1, c.b1);
  wgmma256<1>(acc, c.a, c.b, c.k2, c.b1);
  wgmma256<1>(acc, c.a, c.b, c.k1, c.b1);
  wgmma256<1>(acc, c.a, c.b, ST == 3 ? c.k4w : c.k4, ST == 3 ? -6144 - 384 : 2048 - 384);
  wg_commit();
}
__device__ __forceinline__ void release(const Cons& c, uint32_t bar) { if (c.do_rel) mbar_arrive_cl(c.rel + bar); }
template <int KB, bool WAIT = true> __device__ __forceinline__ void p1_step(float (&acc)[128], const Cons& c) {
  if (KB == 15) { if (c.wg == 1) { wg_wait<0>(); release(c, B_E1 + 16); bar_sync(BAR_LAG, 256); } }
  p1_issue<KB & 3, KB != 0, WAIT>(acc, c, (KB >> 2) & 1);
  if (KB == 15) { if (c.wg == 0) bar_arrive(BAR_LAG, 256); }
  if (KB > 0) { wg_wait<1>(); if (KB != 15 || c.wg == 0) release(c, B_E1 + 8 * ((KB - 1) & 3)); }
  if (KB == 15) { wg_wait<0>(); release(c, B_E1 + 24); }
}
template <class F> __device__ __forceinline__ void p1_loop(float (&acc)[128], const Cons& c, int from, int to, F&& shadow) {
#pragma unroll 1
  for (int kb = from; kb < to; kb++) {
    const bool wrap = (kb & 3) == 3;
    mbar_spin(c.sb + B_F1 + 8 * (kb & 3), (kb >> 2) & 1, c.zero);
    wg_fence();
    wgmma256<1>(acc, c.a, c.b, c.k1, c.b1);
    wgmma256<1>(acc, c.a, c.b, c.k2, c.b1);
    wgmma256<1>(acc, c.a, c.b, c.k1, c.b1);
    wgmma256<1>(acc, c.a, c.b, wrap ? c.k4w : c.k4, wrap ? -6144 - 384 : 2048 - 384);
    wg_commit();
    wg_wait<1>();
    release(c, B_E1 + 8 * ((kb - 1) & 3));
    shadow(kb);
  }
}
template <int T> __device__ __forceinline__ void p2_step(float (&acc)[64], const Cons& c) {
  if (T == 12) { if (c.wg == 1) bar_sync(BAR_LAG, 256); }
  mbar_spin(c.sb + B_F2 + 8 * (T % 5), (T / 5) & 1, c.zero);
  wg_fence();
  wgmma128<T != 0>(acc, c.a, c.b, c.k1, c.b1);
  wgmma128<1>(acc, c.a, c.b, c.k2, c.b1);
  wgmma128<1>(acc, c.a, c.b, c.k1, c.b1);
  wgmma128<1>(acc, c.a, c.b, ((int)p2_a((T + 1) % 5) - (int)p2_a(T % 5)) / 16 - 514, ((int)p2_b((T + 1) % 5) - (int)p2_b(T % 5)) / 16 - 384);
  wg_commit();
  if (T == 15) { if (c.wg == 0) bar_arrive(BAR_LAG, 256); }
  if (T <= 11) { wg_wait<1>(); release(c, T ? B_E2 + 8 * ((T + 4) % 5) : B_E1 + 8); }
}

template <int P> __device__ __forceinline__ void geglu_piece(uint32_t (&pk)[64], uint8_t* dst, float (&rs)[2]) {
  constexpr int cg = P >> 1, r = P & 1;
  pin<1>(rs + r);
#pragma unroll
  for (int i = 0; i < 4; i++) pin<1>(pk + 2 * (4 * cg + i) + r);
  const float r2 = rs[r] * rs[r], c1 = GELU_C1 * rs[r], c3 = GELU_C3 * r2 * rs[r], k = 0.25f * r2;
  uint32_t v[4];
#pragma unroll
  for (int i = 0; i < 4; i++) {
    const uint32_t g = pk[2 * (4 * cg + i) + r];
    v[i] = mul2(pack2(gelu_k(lo_f(g), c1, c3, k), gelu_k(hi_f(g), c1, c3, k)), pk[32 + 2 * (4 * cg + i) + r]);
  }
  stg128(dst + cg * 8192 + r * 512, v[0], v[1], v[2], v[3]);
#pragma unroll
  for (int i = 0; i < 4; i++) { const int o = 2 * (4 * cg + i) + r; pk[o] = pk[16 + o]; pk[32 + o] = pk[48 + o]; }
}
__device__ __forceinline__ void geglu_tile(float (&acc)[128], uint32_t (&pk)[64], const Cons& c, int to, uint8_t* dst, int ev, float (&rs)[2]) {
  const int lane = lane_here();
  dst += (lane ^ (lane >> 3)) << 4;
  p1_loop(acc, c, 1, to, [&](int kb) {
    if (kb <= 8) {
      if (kb & 1) { if (kb & 2) geglu_piece<2>(pk, dst, rs); else geglu_piece<0>(pk, dst, rs); }
      else if (kb & 2) geglu_piece<1>(pk, dst, rs);
      else {
        geglu_piece<3>(pk, dst, rs);
        if (kb == 8) bar_arrive(ev, 288);
        dst += 16384;
      }
    }
  });
}

__device__ __forceinline__ void attn_tile(float (&acc)[128], uint32_t (&pk)[64], const Cons& c, int round, int warp, int m, unsigned bid, Scratch* gs, uint8_t* hdst, uint8_t* odst) {
  const int w = warp & 3;
  const uint32_t at = c.sb + OFF_X + c.wg * AT_WG;
  int lane = lane_here();
  hdst += (lane ^ (lane >> 3)) << 4;
  auto scatter = [&]() {
    const int lane = lane_here();
    const uint32_t swz = (lane ^ (lane >> 3)) << 4;
#pragma unroll
    for (int i = 0; i < 4; i++) {
      const int h = i & 1, r = i >> 1;
      sts128(at + AT_V + (2 * w + r) * 1024 + h * 512 + swz, make_uint4(pk[32 + 8 * h + r], pk[34 + 8 * h + r], pk[36 + 8 * h + r], pk[38 + 8 * h + r]));
    }
    if (w < 3) {
#pragma unroll
      for (int i = 0; i < 8; i++) asm volatile("st.shared.b32 [%0], %1;" ::"r"(at + AT_K + w * 1024 + i * 128 + lane * 4), "r"(pk[17 + 2 * i]) : "memory");
    } else {
      uint8_t* g = (uint8_t*)gs->halo + ((round * 128 + bid) * 2 + c.wg) * 2048;
#pragma unroll
      for (int i = 0; i < 8; i++) asm volatile("st.global.b32 [%0], %1;" ::"l"(g + i * 128 + lane * 4), "r"(pk[17 + 2 * i]) : "memory");
#pragma unroll
      for (int h = 0; h < 2; h++) stg128(g + 1024 + h * 512 + swz, pk[33 + 8 * h], pk[35 + 8 * h], pk[37 + 8 * h], pk[39 + 8 * h]);
      bar_arrive(BAR_EV + 2 + round, 96);
    }
    __syncwarp();
    if (lane == 0) mbar_arrive(c.sb + B_HALO + 8 * round);
    if (round) {
#pragma unroll
      for (int p = 0; p < 4; p++) {
        const int o = 32 + 8 * (p >> 1) + (p & 1);
        asm volatile("ld.global.cg.v4.b32 {%0,%1,%2,%3}, [%4];" : "=r"(pk[o]), "=r"(pk[o + 2]), "=r"(pk[o + 4]), "=r"(pk[o + 6]) : "l"(hdst + (p >> 1) * 8192 + (p & 1) * 512) : "memory");
      }
    }
  };
  auto gu_piece = [&](int p) {
    uint32_t v[4];
#pragma unroll
    for (int i = 0; i < 4; i++) {
      const int o = 2 * i + p;
      pin<1>(pk + 48 + o);
      const uint32_t g = pk[48 + o];
      v[i] = mul2(round ? pk[32 + o] : 0x3e803e80u, round ? g : pack2(gelu_k(lo_f(g), GELU_C1, GELU_C3, 1.0f), gelu_k(hi_f(g), GELU_C1, GELU_C3, 1.0f)));
    }
    stg128(hdst + p * 512, v[0], v[1], v[2], v[3]);
#pragma unroll
    for (int i = 0; i < 4; i++) { pk[32 + 2 * i + p] = pk[40 + 2 * i + p]; pk[48 + 2 * i + p] = pk[56 + 2 * i + p]; }
  };
  p1_step<1>(acc, c);
  scatter();
  p1_loop(acc, c, 2, 9, [&](int kb) {
    if (kb >= 3 && kb <= 6) {
      if (kb & 1) gu_piece(0);
      else {
        gu_piece(1);
        hdst += 8192;
      }
    }
  });
  const bool first = m == 0 && w == 0;
  uint32_t kl[16];
  mbar_spin(c.sb + B_HALO + 8 * round, 0, c.zero);
  lane = lane_here();
  {
    const uint32_t ka = at + lane * 4 + (w ? AT_K + (w - 1) * 1024 : (first ? AT_K : AT_REM + round * 2048));
#pragma unroll
    for (int i = 0; i < 8; i++) {
      asm volatile("ld.shared.b32 %0, [%1];" : "=r"(kl[2 * i]) : "r"(ka + i * 128) : "memory");
      kl[2 * i + 1] = pk[16 + 2 * i] | c.zero;
    }
  }
  float st[4][4];
  pin<16>(kl);
  bar_sync(BAR_MMA, 256);
  mbar_spin(c.sb + B_F1 + 8 * 1, 0, c.zero);
#pragma unroll
  for (int ks = 0; ks < 2; ks++) {
#pragma unroll
    for (int h = 0; h < 2; h++) {
      const int o = 8 * h + 4 * ks;
      if (ks == 0) { hmma<0>(st[2 * h], kl[o], kl[o + 1], kl[o + 2], kl[o + 3], pk[o], pk[o + 2]); hmma<0>(st[2 * h + 1], pk[16 + o], pk[17 + o], pk[18 + o], pk[19 + o], pk[o + 1], pk[o + 3]); }
      else { hmma<1>(st[2 * h], kl[o], kl[o + 1], kl[o + 2], kl[o + 3], pk[o], pk[o + 2]); hmma<1>(st[2 * h + 1], pk[16 + o], pk[17 + o], pk[18 + o], pk[19 + o], pk[o + 1], pk[o + 3]); }
    }
  }
  sched_fence(c.zero);
  bar_sync(BAR_MMA, 256);
  p1_step<9, false>(acc, c);
  sched_fence(c.zero);
  pin<16>(&st[0][0]);
  lane = lane_here();
  const int rho = lane >> 2, q = lane & 3;
  const bool le0 = 2 * q <= rho, le1 = 2 * q + 1 <= rho;
  uint32_t la[2], lb[2], mx[2];
#pragma unroll
  for (int h = 0; h < 2; h++) {
    uint32_t l[2];
#pragma unroll
    for (int r = 0; r < 2; r++) {
      const float (&t)[4] = st[2 * h + r];
      l[r] = movm(pack2(rho <= 2 * q ? t[2] : t[0], rho <= 2 * q + 1 ? t[3] : t[1]));
      l[r] = fma2(l[r], 0x3e353e35u, mul2(l[r], 0x379e379eu));
    }
    la[h] = __byte_perm(l[0], l[1], 0x5410); lb[h] = __byte_perm(l[0], l[1], 0x7632);
    if (first && !le0) la[h] = (la[h] & 0xffff0000u) | 0xce6eu;
    if (first && !le1) lb[h] = (lb[h] & 0xffff0000u) | 0xce6eu;
    mx[h] = max2(la[h], lb[h]);
  }
#pragma unroll
  for (int o = 1; o <= 2; o++) { mx[0] = max2(mx[0], __shfl_xor_sync(~0u, mx[0], o)); mx[1] = max2(mx[1], __shfl_xor_sync(~0u, mx[1], o)); }
  const float L2E = 1.4426950408889634f;
  float pr[2][4], z[4];
#pragma unroll
  for (int h = 0; h < 2; h++) {
    pr[h][0] = ex2f((lo_f(la[h]) - lo_f(mx[h])) * L2E); pr[h][1] = ex2f((lo_f(lb[h]) - lo_f(mx[h])) * L2E);
    pr[h][2] = ex2f((hi_f(la[h]) - hi_f(mx[h])) * L2E); pr[h][3] = ex2f((hi_f(lb[h]) - hi_f(mx[h])) * L2E);
    z[2 * h] = pr[h][0] + pr[h][1]; z[2 * h + 1] = pr[h][2] + pr[h][3];
  }
  p1_step<10>(acc, c);
#pragma unroll
  for (int o = 1; o <= 2; o++) {
#pragma unroll
    for (int i = 0; i < 4; i++) z[i] += __shfl_xor_sync(~0u, z[i], o);
  }
  const uint32_t LE = (le0 ? 0xffffu : 0u) | (le1 ? 0xffff0000u : 0u);
  uint32_t P[4][2];
  uint4 vt[4][2];
  {
    const uint32_t row = (lane & 7) * 64 + ((((lane >> 3) & 1) ^ ((lane & 7) >> 1)) << 4);
    const uint32_t v1 = at + AT_V + (2 * w + (lane >> 4)) * 1024 + row;
    const uint32_t v0 = (w || lane >= 16) ? v1 - 1024 : (first ? v1 : at + AT_REM + round * 2048 + 1024 + row);
#pragma unroll
    for (int i = 0; i < 4; i++) {
      const float rz = rcpf(z[i]);
      const uint32_t p = pack2(pr[i >> 1][2 * (i & 1)] * rz, pr[i >> 1][2 * (i & 1) + 1] * rz);
      P[i][0] = p & ~LE; P[i][1] = p & LE;
      const uint32_t a = ((i & 1) ? v1 : v0) + (i >> 1) * 512;
      vt[i][0] = ldsm_t(a); vt[i][1] = ldsm_t(a ^ 32);
    }
  }
  float ot[4][2][4];
  pin<8>(&P[0][0]);
  bar_sync(BAR_MMA, 256);
  mbar_spin(c.sb + B_F1 + 8 * 3, 0, c.zero);
#pragma unroll
  for (int i = 0; i < 8; i++) { const uint4& v = vt[i >> 1][i & 1]; hmma<0>(ot[i >> 1][i & 1], v.x, v.y, v.z, v.w, P[i >> 1][0], P[i >> 1][1]); }
  sched_fence(c.zero);
  bar_sync(BAR_MMA, 256);
  p1_step<11, false>(acc, c);
  sched_fence(c.zero);
  pin<32>(&ot[0][0][0]);
  lane = lane_here();
  odst += (lane ^ (lane >> 3)) << 4;
  auto o_piece = [&](int i) {
    stg128(odst + (i >> 1) * 8192 + (i & 1) * 512, movm(pack2(ot[i][0][0], ot[i][0][1])), movm(pack2(ot[i][0][2], ot[i][0][3])), movm(pack2(ot[i][1][0], ot[i][1][1])), movm(pack2(ot[i][1][2], ot[i][1][3])));
  };
  o_piece(0); o_piece(1);
  p1_step<12>(acc, c);
  o_piece(2); o_piece(3);
  if (round) bar_arrive(BAR_EV + 4, 288);
  p1_loop(acc, c, 13, 15, [](int) {});
}

__device__ __forceinline__ void ln_moments(const uint32_t* raw, float& c0, float& s, float& v) {
  c0 = lo_f(__shfl_sync(~0u, raw[0], 0));
  float ss[4] = {0.f, 0.f, 0.f, 0.f}, vv[4] = {0.f, 0.f, 0.f, 0.f};
#pragma unroll
  for (int i = 0; i < 16; i++) {
    const float a = lo_f(raw[i]) - c0, b = hi_f(raw[i]) - c0;
    ss[(2 * i) & 3] += a; ss[(2 * i + 1) & 3] += b;
    vv[(2 * i) & 3] = fmaf(a, a, vv[(2 * i) & 3]); vv[(2 * i + 1) & 3] = fmaf(b, b, vv[(2 * i + 1) & 3]);
  }
  s = (ss[0] + ss[1]) + (ss[2] + ss[3]); v = (vv[0] + vv[1]) + (vv[2] + vv[3]);
}
__device__ __forceinline__ void ln_reduce(float& s, float& v) {
#pragma unroll
  for (int o = 16; o; o >>= 1) { s += __shfl_xor_sync(~0u, s, o); v += __shfl_xor_sync(~0u, v, o); }
}
__device__ __forceinline__ uint32_t ln_finish(float c0, float s, float v) {
  s *= 1.0f / DM;
  float sd;
  asm("sqrt.approx.ftz.f32 %0, %1;" : "=f"(sd) : "f"(bf16r(bf16r(fmaxf(fmaf(v, 1.0f / DM, -s * s), 0.f)) + 1e-5f)));
  return pack2(c0 + s, sd);
}
__device__ __forceinline__ void ln_store(const uint32_t* raw, uint32_t st, uint4* dst) {
  const uint32_t m2 = __byte_perm(st, st, 0x1010);
  const float rinv = rcpf(hi_f(st));
  const uint32_t rh = pack2(rinv, rinv), rl = pack2(rinv - hi_f(rh), rinv - hi_f(rh));
#pragma unroll
  for (int c = 0; c < 4; c++) {
    uint32_t v[4];
#pragma unroll
    for (int i = 0; i < 4; i++) { const uint32_t t = sub2(raw[4 * c + i], m2); v[i] = fma2(t, rh, mul2(t, rl)); }
    stg128(dst + 32 * c, v[0], v[1], v[2], v[3]);
  }
}
__device__ __forceinline__ void col_sums(uint32_t tile, ulonglong2* part, uint32_t tag) {
  const int lane = threadIdx.x & 31;
  float cs[8] = {0, 0, 0, 0, 0, 0, 0, 0};
  uint32_t base = tile + ((lane >> 3) & 1) * 8192 + (lane >> 4) * 4096 + ((lane & 7) << 4);
#pragma unroll 1
  for (int k0 = 0; k0 < 8; k0++, base = (base ^ ((k0 ^ (k0 - 1)) << 4)) + 128) {
    uint4 v[4];
#pragma unroll
    for (int k = 0; k < 4; k++) v[k] = lds128(base + k * 1024);
#pragma unroll
    for (int k = 0; k < 4; k++) {
      cs[0] += lo_f(v[k].x); cs[1] += hi_f(v[k].x); cs[2] += lo_f(v[k].y); cs[3] += hi_f(v[k].y);
      cs[4] += lo_f(v[k].z); cs[5] += hi_f(v[k].z); cs[6] += lo_f(v[k].w); cs[7] += hi_f(v[k].w);
    }
  }
  const bool up = lane >= 16;
#pragma unroll
  for (int i = 0; i < 2; i++) {
    const float a = (up ? cs[4 + 2 * i] : cs[2 * i]) + __shfl_xor_sync(~0u, up ? cs[2 * i] : cs[4 + 2 * i], 16);
    const float b = (up ? cs[5 + 2 * i] : cs[1 + 2 * i]) + __shfl_xor_sync(~0u, up ? cs[1 + 2 * i] : cs[5 + 2 * i], 16);
    asm volatile("{\n.reg .b64 a, b;\nmov.b64 a, {%1, %3};\nmov.b64 b, {%2, %3};\nst.relaxed.gpu.global.v2.b64 [%0], {a, b};\n}"
                 ::"l"(part + 32 * (i + (up ? 2 : 0)) + (lane & 15)), "r"(__float_as_uint(a)), "r"(__float_as_uint(b)), "r"(tag) : "memory");
  }
  asm volatile("fence.proxy.async.shared::cta;" ::: "memory");
}

__global__ void __cluster_dims__(2, 1, 1) __launch_bounds__(384, 1)
fused_kernel(const uint4* __restrict__ x, const uint4* __restrict__ wgate, const uint4* __restrict__ wup, Scratch* gs, int by_sm, const __grid_constant__ Maps mp) {
  extern __shared__ __align__(1024) uint8_t smem_raw[];
  const uint32_t sb = (uint32_t)__cvta_generic_to_shared(smem_raw);
  const unsigned bid = role_id(by_sm);
  if (threadIdx.x == 352) TS(63);
  if (threadIdx.x < 256 && bid < NMAIN) {
    const uint32_t r = threadIdx.x >> 3, ch = threadIdx.x & 7;
    const uint32_t d = sb + r * 128 + ((ch ^ (r & 7)) << 4);
    const uint8_t* xa = (const uint8_t*)x + ((bid & 15) * 262144 + r * 4096 + ch * 16);
    const uint32_t wo = r * (DFF * 2) + (bid >> 4) * 256 + ch * 16;
    const uint8_t *wa = (const uint8_t*)wgate + wo, *wb = (const uint8_t*)wup + wo;
#pragma unroll
    for (int i = 0; i < 12; i++) {
      const int h = i >= 8;
      const uint8_t* src = (i >> 2) == 1 ? xa + (i & 1) * 131072 + ((i >> 1) & 1) * 2048 : ((i & 2) ? wb : wa) + h * 32 * (DFF * 2) + (i & 1) * 128;
      asm volatile("cp.async.cg.shared.global [%0], [%1], 16;" ::"r"(d + ((i >> 2) == 1 ? OFF_A + (i & 3) * 4096 : (i & 3) * 8192 + h * 4096)), "l"(src) : "memory");
    }
    if (threadIdx.x == 0) TS(23);
  }
  const int warp = __shfl_sync(~0u, threadIdx.x >> 5, 0), lane = threadIdx.x & 31;
  const int m = bid & 15, j = bid >> 4, rank = bid & 1;
  const int m2 = bid >> 3, j2 = bid & 7;
  const uint32_t zero = warp >> 8;
  const bool helper = bid >= NMAIN;
  if (warp >= 8) {
    asm volatile("setmaxnreg.dec.sync.aligned.u32 40;");
    if (warp == 8) {
      if (elect_one()) {
        asm volatile("prefetch.tensormap [%0];\nprefetch.tensormap [%1];\nprefetch.tensormap [%2];" ::"l"(&mp.x), "l"(&mp.wg), "l"(&mp.wu) : "memory");
        for (int s = 0; s < 4; s++) mbar_init(sb + B_F1 + 8 * s, 1);
        if (!helper) mbar_arrive(sb + B_F1);
        asm volatile("fence.mbarrier_init.release.cluster;" ::: "memory");
      }
      __syncwarp();
    } else if (warp == 9) {
      if (elect_one()) {
        unsigned nsmid;
        asm("mov.u32 %0, %%nsmid;" : "=r"(nsmid));
        if ((sb & 0xffffff) != SM_BASE || (by_sm && nsmid != NCTA)) asm volatile("trap;");
        for (uint32_t b = B_E1; b < B_F2; b += 8) mbar_init(sb + b, 4);
        for (uint32_t b = B_F2; b < B_AUX; b += 8) mbar_init(sb + b, 1);
        for (uint32_t b = B_EX; b < B_AUX; b += 8) mbar_expect_tx(sb + b, 8192);
        mbar_init(sb + B_AUX, 8); mbar_init(sb + B_HALO, 9); mbar_init(sb + B_HALO + 8, 9);
        asm volatile("st.shared.b32 [%0], %1;" ::"r"(sb + OFF_EPOCH + 4), "r"(bid) : "memory");
        asm volatile("fence.mbarrier_init.release.cluster;" ::: "memory");
      }
      __syncwarp();
    }
    asm volatile("barrier.cluster.arrive.relaxed.aligned;" ::: "memory");
    if (warp == 8 && !helper) {
      if (elect_one()) {
        TS(0); TG(51);
#pragma unroll 1
        for (int kb = 1; kb < 4; kb++) {
          const uint32_t sa = sb + OFF_A + kb * 16384, sw = sb + kb * 32768, fb = sb + B_F1 + 8 * kb;
          mbar_expect_tx(fb, P1_BYTES);
          tma3d(sa, &mp.x, fb, kb * 64, m * 64, 0, EVICT_NORMAL);
          tma2d(sw, &mp.wg, fb, j * 128, kb * 64, EVICT_NORMAL); tma2d(sw + 16384, &mp.wu, fb, j * 128, kb * 64, EVICT_NORMAL);
          tma2d(sw + 8192, &mp.wg, fb, j * 128 + 64, kb * 64, EVICT_NORMAL); tma2d(sw + 24576, &mp.wu, fb, j * 128 + 64, kb * 64, EVICT_NORMAL);
        }
        TS(7);
      }
      __syncwarp();
    }
    asm volatile("barrier.cluster.wait.aligned;" ::: "memory");
    if (helper) {
      if (warp == 8) {
        if (elect_one()) {
          unsigned* ep = &gs->epoch[bid * 2];
          const unsigned e = *ep + 1;
          *ep = e;
#pragma unroll 1
          for (int i = 0; i < 20; i++) {
            const uint32_t fb = sb + (i < 16 ? B_F1 + 8 * (i >> 2) : B_XT);
            if (!(i & 3)) mbar_expect_tx(fb, i < 16 ? P1_BYTES : 32768);
            tma5d(sb + (i < 16 ? i : i + 8) * 8192, &mp.wd, fb, (bid - NMAIN) * 256 + (i & 3) * 64, (i >> 2) * 2, EVICT_FIRST);
          }
          mbar_spin(sb + B_XT, 0, zero);
#pragma unroll 1
          for (int t = 0; t < 16; t++) {
            flag_wait(&gs->flags[(FL_H + t * 4) * 32], e * 8u);
            fence_async();
            if (t == 0) TS(0);
#pragma unroll 1
            for (int n = 0; n < 5; n++) {
              const int i = n ? n - 1 : 4;
              const uint32_t fb = sb + (i < 4 ? B_F1 + 8 * i : B_F2);
              if (t) mbar_spin(sb + B_E1 + 8 * i, ~t & 1, zero);
              if (t || i == 4) mbar_expect_tx(fb, i < 4 ? 16384 : 8192);
              const uint4* src = gs->h + (t * 56 + i) * 1024;
              bulk_load(sb + (i < 4 ? OFF_A + i * 16384 : OFF_X + 4096), src, i < 4 ? 16384 : 4096, fb, EVICT_NORMAL);
              if (i == 4) bulk_load(sb + OFF_X + 12288, src + 256, 4096, fb, EVICT_NORMAL);
            }
          }
        }
      } else if (warp == 9) {
#pragma unroll 1
        for (int t = 0; t < 16; t++) {
          bar_sync(BAR_EV + (t & 1), 288);
          if (lane == 0) { flag_add(&gs->flags[(FL_P + t) * 32]); TS(64 + t); }
          __syncwarp();
        }
      }
    } else if (warp == 8) {
      if (elect_one()) {
        uint32_t par = 0;

        auto x_load = [&]() {
          mbar_expect_tx(sb + B_XT, 32768);
          tma3d(sb + OFF_X, &mp.x, sb + B_XT, j2 * 128, m2 * 64, 0, EVICT_FIRST); tma3d(sb + OFF_X + 16384, &mp.x, sb + B_XT, j2 * 128 + 64, m2 * 64, 0, EVICT_FIRST);
        };
        auto w_tile = [&](int R, const CUtensorMap*& mb0, const CUtensorMap*& mb1, int& n0, int& n1) {
          if (R == 1 || R == 2) {
            mb0 = &mp.wqkv; n0 = 64 * (j + 8 * (R - 1)) + rank * 2048;
            mb1 = rank ? (R == 1 ? &mp.wg : &mp.wu) : &mp.wqkv; n1 = rank ? 1024 + 64 * j : n0 + 1024;
          } else {
            mb0 = mb1 = rank ? &mp.wu : &mp.wg;
            n0 = 128 * j + (R ? 1024 * R - 1536 : 0); n1 = n0 + 64;
          }
        };
        for (int R = 0; R < 5; R++) {
          const CUtensorMap *mb0, *mb1;
          int n0, n1;
          w_tile(R, mb0, mb1, n0, n1);
#pragma unroll 1
          for (int kb = R ? 0 : 4; kb < 16; kb++) {
            if (R == 0 && kb == CS_KB) {
#pragma unroll 1
              for (int h = 0; h < 2; h++) {
                const uint32_t cb = sb + B_CS + 8 * h, d = sb + OFF_X + 16384 * h;
                mbar_expect_tx(cb, 16384);
                tma2d(d, h ? &mp.wu : &mp.wg, cb, n0, m * 64, EVICT_NORMAL); tma2d(d + 8192, h ? &mp.wu : &mp.wg, cb, n1, m * 64, EVICT_NORMAL);
              }
            }
            const int st = kb & 3;
            const uint32_t sa = sb + OFF_A + st * 16384, sw = sb + st * 32768, fb = sb + B_F1 + 8 * st;
            mbar_spin(sb + B_E1 + 8 * st, par, zero);
            if (R * 16 + kb >= 4) REL_TS(R * 16 + kb - 4);
            mbar_expect_tx(fb, P1_BYTES);
            tma2d_mc(sw + rank * 16384, mb0, fb, n0, kb * 64, EVICT_FIRST);
            tma2d_mc(sw + 8192 + rank * 16384, mb1, fb, n1, kb * 64, EVICT_FIRST);
            if (R == 0) {
              tma3d(sa, &mp.x, fb, kb * 64, m * 64, 0, EVICT_NORMAL);
            } else {
              if (R == 1 && kb == 0) { mbar_spin(sb + B_DEP, 0, zero); TS(1); }
              tma2d(sa, &mp.xn, fb, kb * 64, m * 128, R == 4 ? EVICT_FIRST : EVICT_NORMAL);
            }
            if (R == 4 && kb == 4 + j2) x_load();
            if (st == 3) par ^= 1;
          }
        }
#pragma unroll 1
        for (int i = 0; i < 26; i++) {
          const int st = i & 3, kh = i < 25 ? 9 + 4 * i + 2 * rank : 109 + rank;
          const uint32_t sa = sb + OFF_A + st * 16384, sw = sb + st * 32768, fb = sb + B_F1 + 8 * st;
          mbar_spin(sb + B_E1 + 8 * st, par, zero);
          REL_TS(76 + i);
          mbar_expect_tx(fb, P1_BYTES);
          tma5d(sw, &mp.wd, fb, j2 * 128, kh, EVICT_FIRST); tma5d(sw + 8192, &mp.wd, fb, j2 * 128 + 64, kh, EVICT_FIRST);
          tma5d(sw + 16384, &mp.wd, fb, (j2 ^ 1) * 128, kh, EVICT_FIRST); tma5d(sw + 24576, &mp.wd, fb, (j2 ^ 1) * 128 + 64, kh, EVICT_FIRST);
          if (i == 0 || i == 5 || i == 9 || i == 17) mbar_spin(sb + B_DEP + 8 * (1 + ((i + 7) >> 3)), 0, zero);
          bulk_load(sa, gs->h + (m2 * 112 + kh) * 512, 16384, fb, EVICT_FIRST);
          if (st == 3) par ^= 1;
        }
        int st = 0; uint32_t par2 = 1;
#pragma unroll 1
        for (int t = 0; t < 16; t++) {
          constexpr auto tab = [](auto f) { uint32_t v = 0; for (int s = 0; s < 5; s++) v |= f(s) / 16384 << (4 * s); return v; };
          const uint32_t sa = sb + (tab(p2_a) >> (4 * st) & 15) * 16384, sw = sb + (tab(p2_b) >> (4 * st) & 15) * 16384, fb = sb + B_F2 + 8 * st;
          mbar_spin(sb + (t < 5 ? B_E1 + 8 * (0x10332 >> (4 * t) & 3) : B_E2 + 8 * st), t < 5 ? t < 3 : par2, zero);
          REL_TS(102 + t);
          mbar_expect_tx(fb, P2_BYTES);
          bulk_load_mc(sa + rank * 8192, gs->o + (m2 * 16 + t) * 1024 + rank * 512, 8192, fb, EVICT_FIRST);
          tma2d(sw, &mp.wo, fb, j2 * 128, t * 64, EVICT_FIRST); tma2d(sw + 8192, &mp.wo, fb, j2 * 128 + 64, t * 64, EVICT_FIRST);
          if (++st == 5) { st = 0; par2 ^= 1; }
        }
      }
    } else if (warp == 9) {
#pragma unroll 1
      for (int e = 0; e < 7; e++) {
        const bool halo = e == 2 || e == 3;
        bar_sync(BAR_EV + e, halo ? 96 : 288);
        if (lane == 0) {
          const int f = e == 0 ? FL_XN + m : (halo ? FL_HALO + (e - 2) * 128 + bid : FL_H + m * 4 + (e == 1 ? 0 : e - 3));
          TS(10 + 2 * e); TG(52 + e);
          flag_add(&gs->flags[f * 32]);
          if (e < 6) TS(11 + 2 * e);
        }
        __syncwarp();
      }
      unsigned other;
      asm volatile("ld.shared::cluster.b32 %0, [%1];" : "=r"(other) : "r"(mapa(sb + OFF_EPOCH + 4, rank ^ 1)) : "memory");
      if (other != (bid ^ 1)) asm volatile("trap;");
      mbar_wait(sb + B_DONE, 0);
    } else {
      unsigned e = 0;
      if (lane == 0) {
        unsigned* ep = &gs->epoch[bid * 2 + warp - 10];
        e = *ep + 1; *ep = e;
        if (warp == 10) { asm volatile("st.shared.b32 [%0], %1;" ::"r"(sb + OFF_EPOCH), "r"(e) : "memory"); mbar_arrive(sb + B_EP); }
      }
      e = __shfl_sync(~0u, e, 0);
      mbar_spin(sb + B_CS + 8 * (warp - 10), 0, zero);
      if (lane == 0 && warp == 11) TS(6);
      col_sums(sb + OFF_X + (warp - 10) * 16384, gs->cspart + (j * 16 + m) * 128 + (warp - 10) * 16, e);
      if (lane == 0 && warp == 11) TS(9);
      if (warp == 10) {
        if (lane == 0) {
#pragma unroll 1
          for (int g = 0; g < 6; g++) {
            flag_wait(&gs->flags[(g == 5 ? FL_P + m2 : (g ? FL_H + m2 * 4 + g - 1 : FL_XN + m)) * 32], e * (g == 5 ? 4u : 8u));
            fence_async();
            mbar_arrive(sb + B_DEP + 8 * g);
            if (g == 0) TS(8);
          }
        }
      } else
      if (elect_one()) {
#pragma unroll 1
        for (int i = 3; i < 8; i++) asm volatile("prefetch.tensormap [%0];" ::"l"(&mp.x + i) : "memory");
#pragma unroll 1
        for (int r = 0; r < 2; r++) {
          const uint32_t hb = sb + B_HALO + 8 * r;
          if (r) mbar_spin(sb + B_HALO, 0, zero);
          if (m) {
            flag_wait(&gs->flags[(FL_HALO + r * 128 + bid - 1) * 32], e);
            fence_async();
            mbar_expect_tx(hb, 4096);
            for (int g = 0; g < 2; g++) bulk_load(sb + OFF_X + g * AT_WG + AT_REM + r * 2048, gs->halo + ((r * 128 + bid - 1) * 2 + g) * 128, 2048, hb, EVICT_FIRST);
          } else {
            mbar_arrive(hb);
          }
          TS(34 + r);
        }
      }
    }
  } else {
    asm volatile("barrier.cluster.arrive.relaxed.aligned;" ::: "memory");
    asm volatile("setmaxnreg.inc.sync.aligned.u32 232;");
    const int wg = warp >> 2, w = warp & 3;
    Cons c;
    c.sb = sb; c.wg = wg; c.zero = zero;
    c.a = 0x4000004000010000ull + ((SM_BASE + OFF_A + wg * 8192) >> 4); c.k1 = 2 + c.zero; c.k2 = 2; c.k4 = 1024 - 6; c.k4w = -3072 - 6; c.b1 = 128 + c.zero;
    c.b = 0x4000004000000000ull + DB_LO + c.zero;
    c.rel = mapa(sb, threadIdx.x & 1);
    c.do_rel = (threadIdx.x & 127) < 2;
    float acc[128];
    uint32_t pk[64];
    float rs[2];
    const int q = lane & 3;

    if (helper) {
      asm volatile("barrier.cluster.wait.aligned;" ::: "memory");
      c.a = 0x8000002000010000ull + ((SM_BASE + OFF_A + wg * 4096) >> 4); c.k2 = 510; c.k4 = 1024 - 514; c.k4w = -3072 - 514;
      c.rel = sb;
      uint4* dst = gs->dpart + (bid - NMAIN) * 4096 + threadIdx.x;
      auto put = [&](int p) {
#pragma unroll
        for (int i = 4 * p; i < 4 * p + 4; i++) stg128(dst + i * 256, pk[4 * i], pk[4 * i + 1], pk[4 * i + 2], pk[4 * i + 3]);
      };
#pragma unroll 1
      for (int t = 0; t < 16; t++) {
        {
          uint64_t a = c.a, b = c.b;
          desc_add(a, (OFF_X + 4096 - OFF_A + wg * 4096) >> 4); desc_add(b, OFF_X >> 4);
          mbar_spin(sb + B_F2, t & 1, c.zero);
          wg_fence();
          wgmma256<0>(acc, a, b, 2, 128); wgmma256<1>(acc, a, b, 0, 0);
          wg_commit();
        }
        p1_issue<0, 1>(acc, c, t & 1); wg_wait<1>(); release(c, B_E2);
        if (t) put(0);
        p1_issue<1, 1>(acc, c, t & 1); wg_wait<1>(); release(c, B_E1);
        if (t) put(1);
        p1_issue<2, 1>(acc, c, t & 1); wg_wait<1>(); release(c, B_E1 + 8);
        if (t) put(2);
        if (wg == 1) { wg_wait<0>(); release(c, B_E1 + 16); bar_sync(BAR_LAG, 256); }
        p1_issue<3, 1>(acc, c, t & 1);
        if (wg == 0) bar_arrive(BAR_LAG, 256);
        if (t) { put(3); bar_arrive(BAR_EV + (~t & 1), 288); dst += 8 * 2048; }
        wg_wait<1>(); if (wg == 0) release(c, B_E1 + 16);
        wg_wait<0>(); release(c, B_E1 + 24);
#pragma unroll
        for (int i = 0; i < 64; i++) pk[i] = pack2(acc[2 * i], acc[2 * i + 1]);
      }
      put(0); put(1); put(2); put(3);
      bar_arrive(BAR_EV + 1, 288);
      return;
    }
    {
      const int prow = 16 * j + 2 * warp;
      const uint4* xr = x + (size_t)(128 * m + 2 * (prow & 63) + (prow >> 6)) * 128 + lane;
      uint4* xo = gs->xn + (size_t)(128 * m + prow) * 128 + lane;
      float c0[2], mo[4];
      uint32_t st[2];
      uint32_t e;
      asm volatile("" : "+l"(xr), "+l"(xo));
      wg_fence(); wgmma256<0>(acc, c.a, c.b, 0, 0); wg_commit(); wg_wait<0>();
      asm volatile("barrier.cluster.wait.aligned;" ::: "memory");
      asm volatile("cp.async.wait_all;\nfence.proxy.async.shared::cta;" ::: "memory");
      bar_sync(BAR_MMA, 256);
      if (threadIdx.x == 0) TS(39);
      p1_step<0, false>(acc, c);
      unsigned long long part[18];
      auto gather = [&](int from, int to) {
        const int lane = lane_here();
        const unsigned long long* cp = (const unsigned long long*)gs->cspart + j * 4096 + warp * 32 + lane;
        const unsigned long long* sp = gs->stats + 128 * m + warp * 16 + (lane >> 2);
#pragma unroll
        for (int i = from; i < to; i++) asm volatile("ld.relaxed.gpu.global.b64 %0, [%1];" : "=l"(part[i]) : "l"(i < 16 ? cp + i * 256 : sp + (i - 16) * 8) : "memory");
      };
      auto row_load = [&](int r) {
#pragma unroll
        for (int i = 4 * r; i < 4 * r + 4; i++)
          asm volatile("ld.global.nc.L1::no_allocate.v4.b32 {%0,%1,%2,%3}, [%4];" : "=r"(pk[4 * i]), "=r"(pk[4 * i + 1]), "=r"(pk[4 * i + 2]), "=r"(pk[4 * i + 3]) : "l"(xr + r * 256 + (i & 3) * 32));
      };
      p1_step<1>(acc, c); row_load(0);
      p1_step<2>(acc, c); row_load(1);
      p1_loop(acc, c, 3, LN_KB + 1, [](int) {});
      pin<16>(pk); ln_moments(pk, c0[0], mo[0], mo[1]); pin<2>(mo);
      p1_step<LN_KB + 1>(acc, c);
      sched_fence(c.zero);
      pin<16>(pk + 16); ln_moments(pk + 16, c0[1], mo[2], mo[3]); ln_reduce(mo[0], mo[1]); pin<4>(mo);
      p1_step<LN_KB + 2>(acc, c);
      mbar_spin(sb + B_EP, 0, c.zero);
      asm volatile("ld.shared.b32 %0, [%1];" : "=r"(e) : "r"(sb + OFF_EPOCH) : "memory");
      pin<2>(mo); st[0] = ln_finish(c0[0], mo[0], mo[1]); ln_reduce(mo[2], mo[3]); pin<1>(st); pin<2>(mo + 2);
      p1_step<LN_KB + 3>(acc, c);
      sched_fence(c.zero);
      pin<1>(st); pin<2>(mo + 2);
      st[1] = ln_finish(c0[1], mo[2], mo[3]);
      ln_store(pk, st[0], xo);
      if (lane == 0)
        asm volatile("{\n.reg .b64 a, b;\nmov.b64 a, {%1, %3};\nmov.b64 b, {%2, %3};\nst.relaxed.gpu.global.v2.b64 [%0], {a, b};\n}" ::"l"(gs->stats + 128 * m + prow), "r"(st[0]), "r"(st[1]), "r"(e) : "memory");
      p1_step<LN_KB + 4>(acc, c);
      sched_fence(c.zero);
      pin<1>(st + 1);
      ln_store(pk + 16, st[1], xo + 128);
      bar_arrive(BAR_EV, 288);
      p1_loop(acc, c, LN_KB + 5, 13, [](int) {});
      gather(0, 9);
      p1_step<13>(acc, c);
      gather(9, 18);
      p1_step<14>(acc, c);
      auto validate = [&]() {
        float csum;
        for (int tries = 0;; tries++) {
          uint32_t bad = 0;
          csum = 0.f;
#pragma unroll
          for (int i = 0; i < 18; i++) { bad |= (uint32_t)(part[i] >> 32) ^ e; if (i < 16) csum += __uint_as_float((uint32_t)part[i]); }
          if (!__any_sync(~0u, bad != 0) || tries > (1 << 20)) break;
          gather(0, 18);
        }
        const float hi = bf16r(csum), mid = bf16r(csum - hi);
        sts128(sb + OFF_CS + ((threadIdx.x & 62) * 4 + (threadIdx.x >> 6) * 2 + (threadIdx.x & 1)) * 16, make_uint4(pack2(hi, mid), pack2(csum - hi - mid, 0.f), 0, 0));
        asm volatile("fence.proxy.async.shared::cta;" ::: "memory");
        __syncwarp();
        if (lane == 0) mbar_arrive(sb + B_AUX);
      };
#pragma unroll 1
      for (int ph = 1; ph >= 0; ph--) {
        if (wg == ph) validate();
        if (ph) {
          if (wg == 1) { wg_wait<0>(); release(c, B_E1 + 16); bar_sync(BAR_LAG, 256); }
          p1_issue<3, 1>(acc, c, 1);
        }
      }
      const uint32_t keep = q == 0 ? 0xffffffffu : (q == 1 ? 0xffffu : 0u);
      const uint32_t a0 = (__byte_perm((uint32_t)part[16], 0, 0x1010) ^ 0x80008000u) & keep, a1 = (__byte_perm((uint32_t)part[17], 0, 0x1010) ^ 0x80008000u) & keep;
      mbar_spin(sb + B_AUX, 0, c.zero);
      wg_fence();
      wgmma256_rs(acc, a0, a1, 0, 0, (SM_BASE + OFF_CS) >> 4);
      wg_commit();
      if (wg == 0) bar_arrive(BAR_LAG, 256);
      rs[0] = rcpf(hi_f((uint32_t)part[16])); rs[1] = rcpf(hi_f((uint32_t)part[17]));
      wg_wait<2>(); if (wg == 0) release(c, B_E1 + 16);
      wg_wait<0>(); release(c, B_E1 + 24);
    }
#pragma unroll 1
    for (int R = 1;; R++) {
#pragma unroll
      for (int i = 0; i < 64; i++) pk[i] = pack2(acc[2 * i], acc[2 * i + 1]);
      uint8_t* hb = (uint8_t*)gs->h + (size_t)m * 56 * 16384 + warp * 1024;
      if (R == 5) { c.a = 0x8000002000010000ull + ((SM_BASE + OFF_A + wg * 4096) >> 4); c.k2 = 510; c.k4 = 1024 - 514; c.k4w = -3072 - 514; }
      p1_step<0>(acc, c);
      if (R == 2 || R == 3) {
        attn_tile(acc, pk, c, R - 2, warp, m, bid, gs, hb + (16 + j) * 16384, (uint8_t*)gs->o + (m * 16 + j + 8 * (R - 2)) * 16384 + warp * 1024);
      } else {
        geglu_tile(acc, pk, c, R == 5 ? 24 : 15, hb + (2 * j + (R == 1 ? 0 : 16 * R - 40)) * 16384, BAR_EV + (R == 1 ? 1 : R + 1), rs);
        rs[0] = rs[1] = 1.0f;
        if (R == 5) break;
      }
      p1_step<15>(acc, c);
    }
    auto fetch = [&](int p) {
      asm volatile("ld.global.cg.v4.b32 {%0,%1,%2,%3}, [%4];" : "=r"(pk[4 * p]), "=r"(pk[4 * p + 1]), "=r"(pk[4 * p + 2]), "=r"(pk[4 * p + 3]) : "l"(gs->dpart + bid * 2048 + p * 256 + threadIdx.x) : "memory");
    };
    mbar_spin(sb + B_DEP + 40, 0, c.zero);
    fetch(0); fetch(1); fetch(2);
    p1_step<8>(acc, c);
    fetch(3); fetch(4); fetch(5);
    desc_add(c.a, 2 * rank); desc_add(c.b, 128 * rank);
    mbar_spin(sb + B_F1 + 8, 0, c.zero);
    wg_fence();
    wgmma256<1>(acc, c.a, c.b, rank ? 510 : 2, c.b1);
    wgmma256<1>(acc, c.a, c.b, rank ? 2 : 510, c.b1);
    wgmma256<1>(acc, c.a, c.b, 512 - 2 * rank, 1792 - 128 * rank);
    wg_commit();
    wg_wait<1>(); release(c, B_E1);
    fetch(6); fetch(7);
    {
      float accs[64];
      const uint32_t peer = mapa(sb, rank ^ 1);
      auto send_piece = [&](int p) {
        asm volatile("st.async.weak.shared::cluster.mbarrier::complete_tx::bytes.v4.b32 [%0], {%1,%2,%3,%4}, [%5];" ::"r"(peer + OFF_LAND + p * 4096 + threadIdx.x * 16),
                     "r"(pack2(acc[64 + 8 * p], acc[65 + 8 * p])), "r"(pack2(acc[66 + 8 * p], acc[67 + 8 * p])), "r"(pack2(acc[68 + 8 * p], acc[69 + 8 * p])), "r"(pack2(acc[70 + 8 * p], acc[71 + 8 * p])),
                     "r"(peer + B_EX + 16 * wg + 8 * (p >> 2)) : "memory");
      };
      auto silu_piece = [&](int p) {
        const uint4 r = lds128(sb + OFF_LAND + p * 4096 + threadIdx.x * 16);
        const uint32_t rr[4] = {add2(r.x, pk[4 * p]), add2(r.y, pk[4 * p + 1]), add2(r.z, pk[4 * p + 2]), add2(r.w, pk[4 * p + 3])};
#pragma unroll
        for (int i = 0; i < 4; i++) {
          const float a = acc[8 * p + 2 * i] + lo_f(rr[i]), b = acc[8 * p + 2 * i + 1] + hi_f(rr[i]);
          pk[4 * p + i] = pack2(silu_half(a), silu_half(b));
        }
        pin<4>(pk + 4 * p);
      };
      const uint32_t xa = sb + OFF_X + (warp * 16 + (lane & 7)) * 128 + (((lane >> 3) ^ (lane & 7)) << 4);
      auto x_addr = [&](int i) { return (xa ^ ((i & 1) << 6)) + ((i >> 1) & 1) * 1024 + (i >> 2) * 16384; };
      auto x_piece = [&](int i) { const uint4 v = ldsm(x_addr(i)); pk[32 + 4 * i] = v.x; pk[33 + 4 * i] = v.y; pk[34 + 4 * i] = v.z; pk[35 + 4 * i] = v.w; };
      p2_step<0>(accs, c);
      p2_step<1>(accs, c);
      mbar_spin(sb + B_E1 + 8, 0, c.zero);
      send_piece(0); send_piece(1);
      p2_step<2>(accs, c); sched_fence(c.zero); send_piece(2); send_piece(3);
      p2_step<3>(accs, c); sched_fence(c.zero); send_piece(4); send_piece(5);
      p2_step<4>(accs, c); mbar_spin(sb + B_XT, 0, c.zero); send_piece(6); send_piece(7);
      p2_step<5>(accs, c); mbar_spin(sb + B_EX + 16 * wg, 0, c.zero); silu_piece(0); x_piece(0);
      p2_step<6>(accs, c); sched_fence(c.zero); silu_piece(1); x_piece(1);
      p2_step<7>(accs, c); sched_fence(c.zero); silu_piece(2); x_piece(2);
      p2_step<8>(accs, c); sched_fence(c.zero); silu_piece(3); x_piece(3);
      p2_step<9>(accs, c); mbar_spin(sb + B_EX + 16 * wg + 8, 0, c.zero); silu_piece(4); x_piece(4);
      p2_step<10>(accs, c); sched_fence(c.zero); silu_piece(5); x_piece(5);
      p2_step<11>(accs, c); sched_fence(c.zero); silu_piece(6); x_piece(6); x_piece(7);
      auto out_half = [&](const float* a, int h) {
#pragma unroll
        for (int i = 4 * h; i < 4 * h + 4; i++) {
          uint32_t v[4];
#pragma unroll
          for (int k = 0; k < 4; k++) { const int o = 2 * (4 * (i & 1) + k) + ((i >> 1) & 1); v[k] = fma2(pack2(a[2 * o], a[2 * o + 1]), pk[16 * h + o], pk[32 + 4 * i + k]); }
          asm volatile("stmatrix.sync.aligned.m8n8.x4.shared.b16 [%0], {%1,%2,%3,%4};" ::"r"(x_addr(i)), "r"(v[0]), "r"(v[1]), "r"(v[2]), "r"(v[3]) : "memory");
          if (i & 1) {
            asm volatile("fence.proxy.async.shared::cta;" ::: "memory");
            __syncwarp();
            if (elect_one()) tma3d_store(&mp.out, sb + OFF_X + h * 16384 + warp * 2048 + (i & 2) * 512, j2 * 128 + h * 64, m2 * 64 + w * 16 + (i & 2) * 4, wg);
          }
        }
      };
      if (wg == 1) silu_piece(7);
      p2_step<12>(accs, c); p2_step<13>(accs, c); p2_step<14>(accs, c); p2_step<15>(accs, c);
      if (c.do_rel) mbar_arrive(sb + B_DONE);
      if (wg == 0) silu_piece(7);
      wg_wait<0>();
      out_half(accs, 0); out_half(accs + 32, 1);
      if (elect_one()) { asm volatile("cp.async.bulk.commit_group;\ncp.async.bulk.wait_group.read 0;" ::: "memory"); }
      if ((threadIdx.x & 127) == 0) { TS(33 + wg * 16); if (wg) { TG(59); unsigned id; asm volatile("mov.u32 %0, %%smid;" : "=r"(id)); TSV(60, id); } }
    }
  }
}

typedef CUresult (*EncodeFn)(CUtensorMap*, CUtensorMapDataType, cuuint32_t, void*, const cuuint64_t*, const cuuint64_t*, const cuuint32_t*, const cuuint32_t*,
                             CUtensorMapInterleave, CUtensorMapSwizzle, CUtensorMapL2promotion, CUtensorMapFloatOOBfill);

void encode(EncodeFn fn, CUtensorMap* tm, const void* p, int rank, const cuuint64_t* dims, const cuuint64_t* strides, const cuuint32_t* box) {
  const cuuint32_t es[5] = {1, 1, 1, 1, 1};
  fn(tm, CU_TENSOR_MAP_DATA_TYPE_BFLOAT16, rank, const_cast<void*>(p), dims, strides, box, es, CU_TENSOR_MAP_INTERLEAVE_NONE, CU_TENSOR_MAP_SWIZZLE_128B,
     CU_TENSOR_MAP_L2_PROMOTION_L2_128B, CU_TENSOR_MAP_FLOAT_OOB_FILL_NONE);
}

}

extern "C" void kernel_launch(void* const* d_in, const int* in_sizes, int n_in, void* d_out, int out_size) {
  (void)in_sizes; (void)n_in; (void)out_size;
  static EncodeFn fn = nullptr;
  static Scratch* gs = nullptr;
  static int nsm = 0;
  if (!fn) {
    void* p = nullptr;
    cudaDriverEntryPointQueryResult qr;
    cudaGetDriverEntryPoint("cuTensorMapEncodeTiled", &p, cudaEnableDefault, &qr);
    fn = (EncodeFn)p;
    cudaGetSymbolAddress((void**)&gs, g_scratch);
    int dev = 0;
    cudaGetDevice(&dev);
    cudaDeviceGetAttribute(&nsm, cudaDevAttrMultiProcessorCount, dev);
    cudaFuncSetAttribute(fused_kernel, cudaFuncAttributeMaxDynamicSharedMemorySize, SMEM_BYTES);
  }
  const void *x = d_in[0], *wqkv = d_in[1], *wo = d_in[2], *wg = d_in[4], *wu = d_in[5], *wd = d_in[6];
  Maps mp;
  {
    const cuuint64_t dims[3] = {DM, SEQ / 2, 2}, st[2] = {DM * 4, DM * 2};
    const cuuint32_t box_in[3] = {64, 64, 2}, box_out[3] = {64, 8, 1};
    encode(fn, &mp.x, x, 3, dims, st, box_in);
    encode(fn, &mp.out, d_out, 3, dims, st, box_out);
  }
  {
    const cuuint64_t dims[2] = {DM, SEQ}, st[1] = {DM * 2};
    const cuuint32_t box[2] = {64, 128};
    encode(fn, &mp.xn, gs->xn, 2, dims, st, box);
  }
  {
    const cuuint32_t box[2] = {64, 64};
    const cuuint64_t dq[2] = {3 * DM, DM}, sq[1] = {3 * DM * 2}, df[2] = {DFF, DM}, sf[1] = {DFF * 2}, dw[2] = {DM, DM}, sw[1] = {DM * 2};
    encode(fn, &mp.wqkv, wqkv, 2, dq, sq, box);
    encode(fn, &mp.wg, wg, 2, df, sf, box);
    encode(fn, &mp.wu, wu, 2, df, sf, box);
    encode(fn, &mp.wo, wo, 2, dw, sw, box);
  }
  {
    const cuuint32_t box[5] = {64, 2, 4, 4, 2};
    const cuuint64_t st[4] = {DM * 2, 8 * DM * 2, 2 * DM * 2, 32 * DM * 2};
    const cuuint64_t dd[5] = {DM, 2, 4, 4, DFF / 32};
    encode(fn, &mp.wd, wd, 5, dd, st, box);
  }
  fused_kernel<<<NCTA, 384, SMEM_BYTES>>>((const uint4*)x, (const uint4*)wg, (const uint4*)wu, gs, nsm == NCTA, mp);
}
```

```cpp
#include <cuda_runtime.h>
#include <cuda_bf16.h>
#include <cuda.h>
#include <stdint.h>

#define CS_KB 8
#define LN_KB 4

namespace {

constexpr int SEQ = 2048, DM = 1024, DFF = 3584;
constexpr int NMAIN = 128, NCTA = 132;
constexpr uint64_t EVICT_FIRST = 0x12F0000000000000ull, EVICT_NORMAL = 0x1000000000000000ull;

constexpr uint32_t SM_BASE = 0x400;
constexpr uint32_t P1_BYTES = 49152, P2_BYTES = 32768;
constexpr uint32_t OFF_A = 131072;
__host__ __device__ constexpr uint32_t p2_a(int s) { return s == 0 ? OFF_A + 32768 : s == 1 ? OFF_A + 49152 : s == 2 ? 114688 : s == 3 ? 16384 : 49152; }
__host__ __device__ constexpr uint32_t p2_b(int s) { return s < 3 ? 65536 + s * 16384 : (s - 3) * 32768; }
constexpr uint32_t OFF_LAND = OFF_A;
constexpr uint32_t OFF_X = 196608;
constexpr uint32_t OFF_CS = OFF_X + 14336;
constexpr uint32_t OFF_BAR = 229376;
constexpr uint32_t B_F1 = OFF_BAR, B_E1 = B_F1 + 32, B_E2 = B_E1 + 32, B_DONE = B_E2 + 40, B_F2 = B_DONE + 8, B_DEP = B_F2 + 40, B_CS = B_DEP + 48,
                   B_XT = B_CS + 16, B_EP = B_XT + 8, B_EX = B_EP + 8, B_AUX = B_EX + 32, B_HALO = B_AUX + 8, OFF_EPOCH = B_HALO + 16;
constexpr uint32_t SMEM_BYTES = 232448;
constexpr uint32_t AT_V = 0, AT_K = 8192, AT_REM = 11264, AT_WG = 15360;

constexpr int FL_XN = 0, FL_H = 16, FL_P = 80, FL_HALO = 96, FL_N = FL_HALO + 256;
struct __align__(1024) Scratch {
  uint4 h[16 * 56 * 1024];
  uint4 o[16 * 16 * 1024];
  uint4 xn[SEQ * DM / 8];
  uint4 dpart[128 * 8 * 256];
  uint4 halo[2 * 128 * 2 * 128];
  ulonglong2 cspart[8 * 16 * 128];
  unsigned long long stats[SEQ];
  unsigned flags[FL_N * 32];
  unsigned epoch[NCTA * 2];
};
__device__ Scratch g_scratch;
#define TG(i) do {} while (0)
#define TSV(i, v) do {} while (0)
#define TS(i) do {} while (0)

__device__ __forceinline__ unsigned role_id(bool by_sm) {
  unsigned sm;
  asm volatile("mov.u32 %0, %%smid;" : "=r"(sm));
  const unsigned t = sm >> 1;
  const unsigned c = t < 60 ? (t < 32 ? t : t + 1 + ((t - 32) * 37 >> 8)) : (t < 62 ? t + 4 : 8 * t - 464);
  return by_sm ? 2 * c + (blockIdx.x & 1) : blockIdx.x;
}

struct Maps { CUtensorMap x, wg, wu, xn, wqkv, wd, wo, out; };

__device__ __forceinline__ void mbar_init(uint32_t bar, uint32_t cnt) { asm volatile("mbarrier.init.shared::cta.b64 [%0], %1;" ::"r"(bar), "r"(cnt)); }
__device__ __forceinline__ void mbar_expect_tx(uint32_t bar, uint32_t bytes) { asm volatile("mbarrier.arrive.expect_tx.shared::cta.b64 _, [%0], %1;" ::"r"(bar), "r"(bytes) : "memory"); }
__device__ __forceinline__ void mbar_arrive(uint32_t bar) { asm volatile("mbarrier.arrive.shared::cta.b64 _, [%0];" ::"r"(bar) : "memory"); }
__device__ __forceinline__ void mbar_arrive_cl(uint32_t bar) { asm volatile("mbarrier.arrive.shared::cluster.b64 _, [%0];" ::"r"(bar) : "memory"); }
__device__ __forceinline__ uint32_t mapa(uint32_t a, uint32_t cta) { uint32_t r; asm("mapa.shared::cluster.u32 %0, %1, %2;" : "=r"(r) : "r"(a), "r"(cta)); return r; }
__device__ __forceinline__ void mbar_wait(uint32_t bar, uint32_t parity) {
  asm volatile("{\n.reg .pred p;\n.reg .u32 n;\nmov.u32 n, 0;\nLAB_WAIT:\nmbarrier.try_wait.parity.shared::cta.b64 p, [%0], %1;\n@p bra LAB_DONE;\n"
               "add.u32 n, n, 1;\nsetp.gt.u32 p, n, 4000000;\n@p trap;\nbra LAB_WAIT;\nLAB_DONE:\n}" ::"r"(bar), "r"(parity) : "memory");
}
__device__ __forceinline__ void mbar_spin(uint32_t bar, uint32_t parity, uint32_t zero) {
  asm volatile("{\n.reg .pred p, z;\nsetp.ne.u32 z, %2, 0;\nLAB_WAIT:\nmbarrier.try_wait.parity.shared::cta.b64 p, [%0], %1;\n@p bra LAB_DONE;\n@z trap;\nbra LAB_WAIT;\nLAB_DONE:\n}" ::"r"(bar), "r"(parity), "r"(zero) : "memory");
}
__device__ __forceinline__ void flag_wait(const unsigned* f, unsigned target) {
  asm volatile("{\n.reg .pred p;\n.reg .u32 n, v;\nmov.u32 n, 0;\nLAB_WAIT:\nld.relaxed.gpu.global.u32 v, [%0];\nsub.u32 v, v, %1;\nsetp.ge.s32 p, v, 0;\n@p bra LAB_DONE;\n"
               "nanosleep.u32 200;\nadd.u32 n, n, 1;\nsetp.gt.u32 p, n, 4000000;\n@p trap;\nbra LAB_WAIT;\nLAB_DONE:\nfence.acquire.gpu;\n}" ::"l"(f), "r"(target) : "memory");
}
__device__ __forceinline__ void flag_add(unsigned* f) { asm volatile("red.release.gpu.global.add.u32 [%0], 1;" ::"l"(f) : "memory"); }
__device__ __forceinline__ void fence_async() { asm volatile("fence.proxy.async.global;" ::: "memory"); }
__device__ __forceinline__ bool elect_one() { uint32_t p; asm volatile("{\n.reg .pred P;\nelect.sync _|P, 0xffffffff;\nselp.u32 %0, 1, 0, P;\n}" : "=r"(p)); return p; }
__device__ __forceinline__ void bar_sync(int id, int n) { asm volatile("bar.sync %0, %1;" ::"r"(id), "r"(n) : "memory"); }
__device__ __forceinline__ void bar_arrive(int id, int n) { asm volatile("bar.arrive %0, %1;" ::"r"(id), "r"(n) : "memory"); }

__device__ __forceinline__ void tma2d(uint32_t dst, const CUtensorMap* tm, uint32_t bar, int c0, int c1, uint64_t hint) {
  asm volatile("cp.async.bulk.tensor.2d.shared::cluster.global.mbarrier::complete_tx::bytes.L2::cache_hint [%0], [%1, {%3, %4}], [%2], %5;" ::"r"(dst), "l"(tm), "r"(bar), "r"(c0), "r"(c1), "l"(hint) : "memory");
}
__device__ __forceinline__ void tma2d_mc(uint32_t dst, const CUtensorMap* tm, uint32_t bar, int c0, int c1, uint64_t hint) {
  asm volatile("cp.async.bulk.tensor.2d.shared::cluster.global.mbarrier::complete_tx::bytes.multicast::cluster.L2::cache_hint [%0], [%1, {%3, %4}], [%2], %5, %6;" ::"r"(dst), "l"(tm), "r"(bar), "r"(c0), "r"(c1), "h"((uint16_t)3), "l"(hint) : "memory");
}
__device__ __forceinline__ void tma3d(uint32_t dst, const CUtensorMap* tm, uint32_t bar, int c0, int c1, int c2, uint64_t hint) {
  asm volatile("cp.async.bulk.tensor.3d.shared::cluster.global.mbarrier::complete_tx::bytes.L2::cache_hint [%0], [%1, {%3, %4, %5}], [%2], %6;" ::"r"(dst), "l"(tm), "r"(bar), "r"(c0), "r"(c1), "r"(c2), "l"(hint) : "memory");
}
__device__ __forceinline__ void tma5d(uint32_t dst, const CUtensorMap* tm, uint32_t bar, int c0, int c4, uint64_t hint) {
  asm volatile("cp.async.bulk.tensor.5d.shared::cluster.global.mbarrier::complete_tx::bytes.L2::cache_hint [%0], [%1, {%3, %5, %5, %5, %4}], [%2], %6;" ::"r"(dst), "l"(tm), "r"(bar), "r"(c0), "r"(c4), "r"(0), "l"(hint) : "memory");
}
__device__ __forceinline__ void tma3d_store(const CUtensorMap* tm, uint32_t src, int c0, int c1, int c2) {
  asm volatile("cp.async.bulk.tensor.3d.global.shared::cta.bulk_group.L2::cache_hint [%0, {%2, %3, %4}], [%1], %5;" ::"l"(tm), "r"(src), "r"(c0), "r"(c1), "r"(c2), "l"(EVICT_FIRST) : "memory");
}
__device__ __forceinline__ void bulk_load(uint32_t dst, const void* src, uint32_t bytes, uint32_t bar, uint64_t hint) {
  asm volatile("cp.async.bulk.shared::cluster.global.mbarrier::complete_tx::bytes.L2::cache_hint [%0], [%1], %2, [%3], %4;" ::"r"(dst), "l"(src), "r"(bytes), "r"(bar), "l"(hint) : "memory");
}
__device__ __forceinline__ void bulk_load_mc(uint32_t dst, const void* src, uint32_t bytes, uint32_t bar, uint64_t hint) {
  asm volatile("cp.async.bulk.shared::cluster.global.mbarrier::complete_tx::bytes.multicast::cluster.L2::cache_hint [%0], [%1], %2, [%3], %4, %5;" ::"r"(dst), "l"(src), "r"(bytes), "r"(bar), "h"((uint16_t)3), "l"(hint) : "memory");
}
__device__ __forceinline__ uint4 lds128(uint32_t a) { uint4 v; asm volatile("ld.shared.v4.b32 {%0,%1,%2,%3}, [%4];" : "=r"(v.x), "=r"(v.y), "=r"(v.z), "=r"(v.w) : "r"(a) : "memory"); return v; }
__device__ __forceinline__ void sts128(uint32_t a, uint4 v) { asm volatile("st.shared.v4.b32 [%0], {%1,%2,%3,%4};" ::"r"(a), "r"(v.x), "r"(v.y), "r"(v.z), "r"(v.w) : "memory"); }
__device__ __forceinline__ void stg128(void* p, uint32_t a, uint32_t b, uint32_t c, uint32_t d) { asm volatile("st.global.v4.b32 [%0], {%1,%2,%3,%4};" ::"l"(p), "r"(a), "r"(b), "r"(c), "r"(d) : "memory"); }

__device__ __forceinline__ uint32_t pack2(float lo, float hi) { uint32_t r; asm("cvt.rn.bf16x2.f32 %0, %1, %2;" : "=r"(r) : "f"(hi), "f"(lo)); return r; }
__device__ __forceinline__ float lo_f(uint32_t v) { return __uint_as_float(v << 16); }
__device__ __forceinline__ float hi_f(uint32_t v) { return __uint_as_float(v & 0xffff0000u); }
__device__ __forceinline__ float bf16r(float v) { return lo_f(pack2(v, 0.f)); }
__device__ __forceinline__ uint32_t mul2(uint32_t a, uint32_t b) { uint32_t r; asm("mul.rn.bf16x2 %0, %1, %2;" : "=r"(r) : "r"(a), "r"(b)); return r; }
__device__ __forceinline__ uint32_t add2(uint32_t a, uint32_t b) { uint32_t r; asm("add.rn.bf16x2 %0, %1, %2;" : "=r"(r) : "r"(a), "r"(b)); return r; }
__device__ __forceinline__ uint32_t sub2(uint32_t a, uint32_t b) { uint32_t r; asm("sub.rn.bf16x2 %0, %1, %2;" : "=r"(r) : "r"(a), "r"(b)); return r; }
__device__ __forceinline__ uint32_t fma2(uint32_t a, uint32_t b, uint32_t c) { uint32_t r; asm("fma.rn.bf16x2 %0, %1, %2, %3;" : "=r"(r) : "r"(a), "r"(b), "r"(c)); return r; }
__device__ __forceinline__ uint32_t max2(uint32_t a, uint32_t b) { uint32_t r; asm("max.bf16x2 %0, %1, %2;" : "=r"(r) : "r"(a), "r"(b)); return r; }
__device__ __forceinline__ float ex2f(float x) { float y; asm("ex2.approx.ftz.f32 %0, %1;" : "=f"(y) : "f"(x)); return y; }
__device__ __forceinline__ float rcpf(float x) { float y; asm("rcp.approx.ftz.f32 %0, %1;" : "=f"(y) : "f"(x)); return y; }
constexpr float GELU_C1 = 0.7978845608028654f, GELU_C3 = 0.035677408136300125f;
__device__ __forceinline__ float gelu_k(float g, float c1, float c3, float k) {
  float t;
  asm("tanh.approx.f32 %0, %1;" : "=f"(t) : "f"(g * fmaf(g * g, c3, c1)));
  g *= k;
  return fmaf(g, t, g);
}
__device__ __forceinline__ float silu_half(float z) { float t; asm("tanh.approx.f32 %0, %1;" : "=f"(t) : "f"(z)); return fmaf(z, t, z); }

__device__ __forceinline__ void wg_fence() { asm volatile("wgmma.fence.sync.aligned;" ::: "memory"); }
__device__ __forceinline__ void wg_commit() { asm volatile("wgmma.commit_group.sync.aligned;" ::: "memory"); }
template <int N> __device__ __forceinline__ void wg_wait() { asm volatile("wgmma.wait_group.sync.aligned %0;" ::"n"(N) : "memory"); }
#define A8(o) "+f"(d[(o)]), "+f"(d[(o) + 1]), "+f"(d[(o) + 2]), "+f"(d[(o) + 3]), "+f"(d[(o) + 4]), "+f"(d[(o) + 5]), "+f"(d[(o) + 6]), "+f"(d[(o) + 7])
#define A64(o) A8(o), A8((o) + 8), A8((o) + 16), A8((o) + 24), A8((o) + 32), A8((o) + 40), A8((o) + 48), A8((o) + 56)
#define REGS0_63 "%0,%1,%2,%3,%4,%5,%6,%7,%8,%9,%10,%11,%12,%13,%14,%15,%16,%17,%18,%19,%20,%21,%22,%23,%24,%25,%26,%27,%28,%29,%30,%31," \
                 "%32,%33,%34,%35,%36,%37,%38,%39,%40,%41,%42,%43,%44,%45,%46,%47,%48,%49,%50,%51,%52,%53,%54,%55,%56,%57,%58,%59,%60,%61,%62,%63"
#define REGS64_127 "%64,%65,%66,%67,%68,%69,%70,%71,%72,%73,%74,%75,%76,%77,%78,%79,%80,%81,%82,%83,%84,%85,%86,%87,%88,%89,%90,%91,%92,%93,%94,%95," \
                   "%96,%97,%98,%99,%100,%101,%102,%103,%104,%105,%106,%107,%108,%109,%110,%111,%112,%113,%114,%115,%116,%117,%118,%119,%120,%121,%122,%123,%124,%125,%126,%127"
__device__ __forceinline__ void desc_add(uint64_t& x, int v) { asm volatile("{\n.reg .b32 lo, hi;\nmov.b64 {lo, hi}, %0;\nadd.s32 lo, lo, %1;\nmov.b64 %0, {lo, hi};\n}" : "+l"(x) : "r"(v)); }
template <int ACCUM> __device__ __forceinline__ void wgmma256(float (&d)[128], uint64_t& a, uint64_t& b, int da, int db) {
  asm volatile("{\n.reg .pred p;\nsetp.ne.b32 p, %130, 0;\n"
               "wgmma.mma_async.sync.aligned.m64n256k16.f32.bf16.bf16 {" REGS0_63 "," REGS64_127 "}, %128, %129, p, 1, 1, 0, 1;\n}"
               : A64(0), A64(64) : "l"(a), "l"(b), "n"(ACCUM));
  desc_add(a, da); desc_add(b, db);
}
__device__ __forceinline__ void wgmma256_rs(float (&d)[128], uint32_t a0, uint32_t a1, uint32_t z0, uint32_t z1, uint32_t b_lo) {
  asm volatile("{\n.reg .b64 db;\nmov.b64 db, {%132, 0x00000008};\n"
               "wgmma.mma_async.sync.aligned.m64n256k16.f32.bf16.bf16 {" REGS0_63 "," REGS64_127 "}, {%128,%129,%130,%131}, db, 1, 1, 1, 0;\n}"
               : A64(0), A64(64) : "r"(a0), "r"(a1), "r"(z0), "r"(z1), "r"(b_lo));
}
template <int ACCUM> __device__ __forceinline__ void wgmma128(float (&d)[64], uint64_t& a, uint64_t& b, int da, int db) {
  asm volatile("{\n.reg .pred p;\nsetp.ne.b32 p, %66, 0;\n"
               "wgmma.mma_async.sync.aligned.m64n128k16.f32.bf16.bf16 {" REGS0_63 "}, %64, %65, p, 1, 1, 0, 1;\n}"
               : A64(0) : "l"(a), "l"(b), "n"(ACCUM));
  desc_add(a, da); desc_add(b, db);
}
template <int ACCUM> __device__ __forceinline__ void hmma(float (&c)[4], uint32_t a0, uint32_t a1, uint32_t a2, uint32_t a3, uint32_t b0, uint32_t b1) {
  if (ACCUM)
    asm volatile("mma.sync.aligned.m16n8k16.row.col.f32.bf16.bf16.f32 {%0,%1,%2,%3}, {%4,%5,%6,%7}, {%8,%9}, {%0,%1,%2,%3};"
                 : "+f"(c[0]), "+f"(c[1]), "+f"(c[2]), "+f"(c[3]) : "r"(a0), "r"(a1), "r"(a2), "r"(a3), "r"(b0), "r"(b1));
  else
    asm volatile("mma.sync.aligned.m16n8k16.row.col.f32.bf16.bf16.f32 {%0,%1,%2,%3}, {%4,%5,%6,%7}, {%8,%9}, {%10,%10,%10,%10};"
                 : "=f"(c[0]), "=f"(c[1]), "=f"(c[2]), "=f"(c[3]) : "r"(a0), "r"(a1), "r"(a2), "r"(a3), "r"(b0), "r"(b1), "f"(0.f));
}
__device__ __forceinline__ uint32_t movm(uint32_t a) { uint32_t d; asm volatile("movmatrix.sync.aligned.m8n8.trans.b16 %0, %1;" : "=r"(d) : "r"(a)); return d; }
__device__ __forceinline__ int lane_here() { int v; asm volatile("mov.u32 %0, %%laneid;" : "=r"(v)); return v; }
template <int N> __device__ __forceinline__ void pin(uint32_t* r) {
#pragma unroll
  for (int i = 0; i < N; i++) asm volatile("" : "+r"(r[i]));
}
template <int N> __device__ __forceinline__ void pin(float* r) {
#pragma unroll
  for (int i = 0; i < N; i++) asm volatile("" : "+f"(r[i]));
}
__device__ __forceinline__ void sched_fence(uint32_t zero) {
  asm volatile("{\n.reg .pred p;\nsetp.eq.u32 p, %0, 0;\nLAB_F:\n@p bra.uni LAB_D;\nnanosleep.u32 0;\nbra.uni LAB_F;\nLAB_D:\n}" ::"r"(zero) : "memory");
}
__device__ __forceinline__ uint4 ldsm(uint32_t a) { uint4 v; asm volatile("ldmatrix.sync.aligned.m8n8.x4.shared.b16 {%0,%1,%2,%3}, [%4];" : "=r"(v.x), "=r"(v.y), "=r"(v.z), "=r"(v.w) : "r"(a) : "memory"); return v; }
__device__ __forceinline__ uint4 ldsm_t(uint32_t a) { uint4 v; asm volatile("ldmatrix.sync.aligned.m8n8.x4.trans.shared.b16 {%0,%1,%2,%3}, [%4];" : "=r"(v.x), "=r"(v.y), "=r"(v.z), "=r"(v.w) : "r"(a) : "memory"); return v; }

constexpr int BAR_LAG = 1, BAR_MMA = 2, BAR_EV = 3;

struct Cons {
  uint32_t sb;
  mutable uint64_t a, b;
  int k1, k2, k4, k4w, b1;
  uint32_t rel;
  bool do_rel;
  int wg;
  uint32_t zero;
};
#define REL_TS(n) TS(64 + (n))
constexpr uint32_t DB_LO = (SM_BASE >> 4) | ((8192 >> 4) << 16);

template <int ST, int ACCUM, bool WAIT = true> __device__ __forceinline__ void p1_issue(float (&acc)[128], const Cons& c, uint32_t parity) {
  if (WAIT) mbar_spin(c.sb + B_F1 + 8 * ST, parity, c.zero);
  wg_fence();
  wgmma256<ACCUM>(acc, c.a, c.b, c.k1, c.b1);
  wgmma256<1>(acc, c.a, c.b, c.k2, c.b1);
  wgmma256<1>(acc, c.a, c.b, c.k1, c.b1);
  wgmma256<1>(acc, c.a, c.b, ST == 3 ? c.k4w : c.k4, ST == 3 ? -6144 - 384 : 2048 - 384);
  wg_commit();
}
__device__ __forceinline__ void release(const Cons& c, uint32_t bar) { if (c.do_rel) mbar_arrive_cl(c.rel + bar); }
template <int KB, bool WAIT = true> __device__ __forceinline__ void p1_step(float (&acc)[128], const Cons& c) {
  if (KB == 15) { if (c.wg == 1) { wg_wait<0>(); release(c, B_E1 + 16); bar_sync(BAR_LAG, 256); } }
  p1_issue<KB & 3, KB != 0, WAIT>(acc, c, (KB >> 2) & 1);
  if (KB == 15) { if (c.wg == 0) bar_arrive(BAR_LAG, 256); }
  if (KB > 0) { wg_wait<1>(); if (KB != 15 || c.wg == 0) release(c, B_E1 + 8 * ((KB - 1) & 3)); }
  if (KB == 15) { wg_wait<0>(); release(c, B_E1 + 24); }
}
template <class F> __device__ __forceinline__ void p1_loop(float (&acc)[128], const Cons& c, int from, int to, F&& shadow) {
#pragma unroll 1
  for (int kb = from; kb < to; kb++) {
    const bool wrap = (kb & 3) == 3;
    mbar_spin(c.sb + B_F1 + 8 * (kb & 3), (kb >> 2) & 1, c.zero);
    wg_fence();
    wgmma256<1>(acc, c.a, c.b, c.k1, c.b1);
    wgmma256<1>(acc, c.a, c.b, c.k2, c.b1);
    wgmma256<1>(acc, c.a, c.b, c.k1, c.b1);
    wgmma256<1>(acc, c.a, c.b, wrap ? c.k4w : c.k4, wrap ? -6144 - 384 : 2048 - 384);
    wg_commit();
    wg_wait<1>();
    release(c, B_E1 + 8 * ((kb - 1) & 3));
    shadow(kb);
  }
}
template <int T> __device__ __forceinline__ void p2_step(float (&acc)[64], const Cons& c) {
  if (T == 12) { if (c.wg == 1) bar_sync(BAR_LAG, 256); }
  mbar_spin(c.sb + B_F2 + 8 * (T % 5), (T / 5) & 1, c.zero);
  wg_fence();
  wgmma128<T != 0>(acc, c.a, c.b, c.k1, c.b1);
  wgmma128<1>(acc, c.a, c.b, c.k2, c.b1);
  wgmma128<1>(acc, c.a, c.b, c.k1, c.b1);
  wgmma128<1>(acc, c.a, c.b, ((int)p2_a((T + 1) % 5) - (int)p2_a(T % 5)) / 16 - 514, ((int)p2_b((T + 1) % 5) - (int)p2_b(T % 5)) / 16 - 384);
  wg_commit();
  if (T == 15) { if (c.wg == 0) bar_arrive(BAR_LAG, 256); }
  if (T <= 11) { wg_wait<1>(); release(c, T ? B_E2 + 8 * ((T + 4) % 5) : B_E1 + 8); }
}

template <int P> __device__ __forceinline__ void geglu_piece(uint32_t (&pk)[64], uint8_t* dst, const float (&gc)[6]) {
  constexpr int cg = P >> 1, r = P & 1;
  uint32_t v[4];
#pragma unroll
  for (int i = 0; i < 4; i++) {
    const uint32_t g = pk[2 * (4 * cg + i) + r];
    v[i] = mul2(pack2(gelu_k(lo_f(g), gc[r], gc[2 + r], gc[4 + r]), gelu_k(hi_f(g), gc[r], gc[2 + r], gc[4 + r])), pk[32 + 2 * (4 * cg + i) + r]);
  }
  stg128(dst + cg * 8192 + r * 512, v[0], v[1], v[2], v[3]);
#pragma unroll
  for (int i = 0; i < 4; i++) { const int o = 2 * (4 * cg + i) + r; pk[o] = pk[16 + o]; pk[32 + o] = pk[48 + o]; }
}
__device__ __forceinline__ void geglu_tile(float (&acc)[128], uint32_t (&pk)[64], const Cons& c, int to, uint8_t* dst, int ev, const float (&rs)[2]) {
  const int lane = lane_here();
  dst += (lane ^ (lane >> 3)) << 4;
  float gc[6];
#pragma unroll
  for (int r = 0; r < 2; r++) { gc[r] = GELU_C1 * rs[r]; gc[2 + r] = GELU_C3 * (rs[r] * rs[r]) * rs[r]; gc[4 + r] = 0.25f * (rs[r] * rs[r]); }
  pin<6>(gc);
  p1_loop(acc, c, 1, to, [&](int kb) {
    if (kb <= 8) {
      if (kb & 1) { if (kb & 2) geglu_piece<2>(pk, dst, gc); else geglu_piece<0>(pk, dst, gc); }
      else if (kb & 2) geglu_piece<1>(pk, dst, gc);
      else {
        geglu_piece<3>(pk, dst, gc);
        if (kb == 8) bar_arrive(ev, 288);
        dst += 16384;
      }
    }
  });
}

__device__ __forceinline__ void attn_tile(float (&acc)[128], uint32_t (&pk)[64], const Cons& c, int round, int warp, int m, unsigned bid, Scratch* gs, uint8_t* hdst, uint8_t* odst) {
  const int w = warp & 3;
  const uint32_t at = c.sb + OFF_X + c.wg * AT_WG;
  int lane = lane_here();
  hdst += (lane ^ (lane >> 3)) << 4;
  auto scatter = [&]() {
    const int lane = lane_here();
    const uint32_t swz = (lane ^ (lane >> 3)) << 4;
#pragma unroll
    for (int i = 0; i < 4; i++) {
      const int h = i & 1, r = i >> 1;
      sts128(at + AT_V + (2 * w + r) * 1024 + h * 512 + swz, make_uint4(pk[32 + 8 * h + r], pk[34 + 8 * h + r], pk[36 + 8 * h + r], pk[38 + 8 * h + r]));
    }
    if (w < 3) {
#pragma unroll
      for (int i = 0; i < 8; i++) asm volatile("st.shared.b32 [%0], %1;" ::"r"(at + AT_K + w * 1024 + i * 128 + lane * 4), "r"(pk[17 + 2 * i]) : "memory");
    } else {
      uint8_t* g = (uint8_t*)gs->halo + ((round * 128 + bid) * 2 + c.wg) * 2048;
#pragma unroll
      for (int i = 0; i < 8; i++) asm volatile("st.global.b32 [%0], %1;" ::"l"(g + i * 128 + lane * 4), "r"(pk[17 + 2 * i]) : "memory");
#pragma unroll
      for (int h = 0; h < 2; h++) stg128(g + 1024 + h * 512 + swz, pk[33 + 8 * h], pk[35 + 8 * h], pk[37 + 8 * h], pk[39 + 8 * h]);
      bar_arrive(BAR_EV + 2 + round, 96);
    }
    __syncwarp();
    if (lane == 0) mbar_arrive(c.sb + B_HALO + 8 * round);
    if (round) {
#pragma unroll
      for (int p = 0; p < 4; p++) {
        const int o = 32 + 8 * (p >> 1) + (p & 1);
        asm volatile("ld.global.cg.v4.b32 {%0,%1,%2,%3}, [%4];" : "=r"(pk[o]), "=r"(pk[o + 2]), "=r"(pk[o + 4]), "=r"(pk[o + 6]) : "l"(hdst + (p >> 1) * 8192 + (p & 1) * 512) : "memory");
      }
    }
  };
  auto gu_piece = [&](int p) {
    uint32_t v[4];
#pragma unroll
    for (int i = 0; i < 4; i++) {
      const int o = 2 * i + p;
      pin<1>(pk + 48 + o);
      const uint32_t g = pk[48 + o];
      v[i] = mul2(round ? pk[32 + o] : 0x3e803e80u, round ? g : pack2(gelu_k(lo_f(g), GELU_C1, GELU_C3, 1.0f), gelu_k(hi_f(g), GELU_C1, GELU_C3, 1.0f)));
    }
    stg128(hdst + p * 512, v[0], v[1], v[2], v[3]);
#pragma unroll
    for (int i = 0; i < 4; i++) { pk[32 + 2 * i + p] = pk[40 + 2 * i + p]; pk[48 + 2 * i + p] = pk[56 + 2 * i + p]; }
  };
  p1_step<1>(acc, c);
  scatter();
  p1_loop(acc, c, 2, 9, [&](int kb) {
    if (kb >= 3 && kb <= 6) {
      if (kb & 1) gu_piece(0);
      else {
        gu_piece(1);
        hdst += 8192;
      }
    }
  });
  const bool first = m == 0 && w == 0;
  uint32_t kl[16];
  mbar_spin(c.sb + B_HALO + 8 * round, 0, c.zero);
  lane = lane_here();
  {
    const uint32_t ka = at + lane * 4 + (w ? AT_K + (w - 1) * 1024 : (first ? AT_K : AT_REM + round * 2048));
#pragma unroll
    for (int i = 0; i < 8; i++) {
      asm volatile("ld.shared.b32 %0, [%1];" : "=r"(kl[2 * i]) : "r"(ka + i * 128) : "memory");
      kl[2 * i + 1] = pk[16 + 2 * i] | c.zero;
    }
  }
  float st[4][4];
  pin<16>(kl);
  bar_sync(BAR_MMA, 256);
  mbar_spin(c.sb + B_F1 + 8 * 1, 0, c.zero);
#pragma unroll
  for (int ks = 0; ks < 2; ks++) {
#pragma unroll
    for (int h = 0; h < 2; h++) {
      const int o = 8 * h + 4 * ks;
      if (ks == 0) { hmma<0>(st[2 * h], kl[o], kl[o + 1], kl[o + 2], kl[o + 3], pk[o], pk[o + 2]); hmma<0>(st[2 * h + 1], pk[16 + o], pk[17 + o], pk[18 + o], pk[19 + o], pk[o + 1], pk[o + 3]); }
      else { hmma<1>(st[2 * h], kl[o], kl[o + 1], kl[o + 2], kl[o + 3], pk[o], pk[o + 2]); hmma<1>(st[2 * h + 1], pk[16 + o], pk[17 + o], pk[18 + o], pk[19 + o], pk[o + 1], pk[o + 3]); }
    }
  }
  sched_fence(c.zero);
  bar_sync(BAR_MMA, 256);
  p1_step<9, false>(acc, c);
  sched_fence(c.zero);
  pin<16>(&st[0][0]);
  lane = lane_here();
  const int rho = lane >> 2, q = lane & 3;
  const bool le0 = 2 * q <= rho, le1 = 2 * q + 1 <= rho;
  uint32_t la[2], lb[2], mx[2];
#pragma unroll
  for (int h = 0; h < 2; h++) {
    uint32_t l[2];
#pragma unroll
    for (int r = 0; r < 2; r++) {
      const float (&t)[4] = st[2 * h + r];
      l[r] = movm(pack2(rho <= 2 * q ? t[2] : t[0], rho <= 2 * q + 1 ? t[3] : t[1]));
      l[r] = fma2(l[r], 0x3e353e35u, mul2(l[r], 0x379e379eu));
    }
    la[h] = __byte_perm(l[0], l[1], 0x5410); lb[h] = __byte_perm(l[0], l[1], 0x7632);
    if (first && !le0) la[h] = (la[h] & 0xffff0000u) | 0xce6eu;
    if (first && !le1) lb[h] = (lb[h] & 0xffff0000u) | 0xce6eu;
    mx[h] = max2(la[h], lb[h]);
  }
#pragma unroll
  for (int o = 1; o <= 2; o++) { mx[0] = max2(mx[0], __shfl_xor_sync(~0u, mx[0], o)); mx[1] = max2(mx[1], __shfl_xor_sync(~0u, mx[1], o)); }
  const float L2E = 1.4426950408889634f;
  float pr[2][4], z[4];
#pragma unroll
  for (int h = 0; h < 2; h++) {
    pr[h][0] = ex2f((lo_f(la[h]) - lo_f(mx[h])) * L2E); pr[h][1] = ex2f((lo_f(lb[h]) - lo_f(mx[h])) * L2E);
    pr[h][2] = ex2f((hi_f(la[h]) - hi_f(mx[h])) * L2E); pr[h][3] = ex2f((hi_f(lb[h]) - hi_f(mx[h])) * L2E);
    z[2 * h] = pr[h][0] + pr[h][1]; z[2 * h + 1] = pr[h][2] + pr[h][3];
  }
  p1_step<10>(acc, c);
#pragma unroll
  for (int o = 1; o <= 2; o++) {
#pragma unroll
    for (int i = 0; i < 4; i++) z[i] += __shfl_xor_sync(~0u, z[i], o);
  }
  const uint32_t LE = (le0 ? 0xffffu : 0u) | (le1 ? 0xffff0000u : 0u);
  uint32_t P[4][2];
  uint4 vt[4][2];
  {
    const uint32_t row = (lane & 7) * 64 + ((((lane >> 3) & 1) ^ ((lane & 7) >> 1)) << 4);
    const uint32_t v1 = at + AT_V + (2 * w + (lane >> 4)) * 1024 + row;
    const uint32_t v0 = (w || lane >= 16) ? v1 - 1024 : (first ? v1 : at + AT_REM + round * 2048 + 1024 + row);
#pragma unroll
    for (int i = 0; i < 4; i++) {
      const float rz = rcpf(z[i]);
      const uint32_t p = pack2(pr[i >> 1][2 * (i & 1)] * rz, pr[i >> 1][2 * (i & 1) + 1] * rz);
      P[i][0] = p & ~LE; P[i][1] = p & LE;
      const uint32_t a = ((i & 1) ? v1 : v0) + (i >> 1) * 512;
      vt[i][0] = ldsm_t(a); vt[i][1] = ldsm_t(a ^ 32);
    }
  }
  float ot[4][2][4];
  pin<8>(&P[0][0]);
  bar_sync(BAR_MMA, 256);
  mbar_spin(c.sb + B_F1 + 8 * 3, 0, c.zero);
#pragma unroll
  for (int i = 0; i < 8; i++) { const uint4& v = vt[i >> 1][i & 1]; hmma<0>(ot[i >> 1][i & 1], v.x, v.y, v.z, v.w, P[i >> 1][0], P[i >> 1][1]); }
  sched_fence(c.zero);
  bar_sync(BAR_MMA, 256);
  p1_step<11, false>(acc, c);
  sched_fence(c.zero);
  pin<32>(&ot[0][0][0]);
  lane = lane_here();
  odst += (lane ^ (lane >> 3)) << 4;
  auto o_piece = [&](int i) {
    stg128(odst + (i >> 1) * 8192 + (i & 1) * 512, movm(pack2(ot[i][0][0], ot[i][0][1])), movm(pack2(ot[i][0][2], ot[i][0][3])), movm(pack2(ot[i][1][0], ot[i][1][1])), movm(pack2(ot[i][1][2], ot[i][1][3])));
  };
  o_piece(0); o_piece(1);
  p1_step<12>(acc, c);
  o_piece(2); o_piece(3);
  if (round) bar_arrive(BAR_EV + 4, 288);
  p1_loop(acc, c, 13, 15, [](int) {});
}

__device__ __forceinline__ void ln_moments(const uint32_t* raw, float& c0, float& s, float& v) {
  c0 = lo_f(__shfl_sync(~0u, raw[0], 0));
  float ss[4] = {0.f, 0.f, 0.f, 0.f}, vv[4] = {0.f, 0.f, 0.f, 0.f};
#pragma unroll
  for (int i = 0; i < 16; i++) {
    const float a = lo_f(raw[i]) - c0, b = hi_f(raw[i]) - c0;
    ss[(2 * i) & 3] += a; ss[(2 * i + 1) & 3] += b;
    vv[(2 * i) & 3] = fmaf(a, a, vv[(2 * i) & 3]); vv[(2 * i + 1) & 3] = fmaf(b, b, vv[(2 * i + 1) & 3]);
  }
  s = (ss[0] + ss[1]) + (ss[2] + ss[3]); v = (vv[0] + vv[1]) + (vv[2] + vv[3]);
}
__device__ __forceinline__ void ln_reduce(float& s, float& v) {
#pragma unroll
  for (int o = 16; o; o >>= 1) { s += __shfl_xor_sync(~0u, s, o); v += __shfl_xor_sync(~0u, v, o); }
}
__device__ __forceinline__ uint32_t ln_finish(float c0, float s, float v) {
  s *= 1.0f / DM;
  float sd;
  asm("sqrt.approx.ftz.f32 %0, %1;" : "=f"(sd) : "f"(bf16r(bf16r(fmaxf(fmaf(v, 1.0f / DM, -s * s), 0.f)) + 1e-5f)));
  return pack2(c0 + s, sd);
}
__device__ __forceinline__ void ln_store(const uint32_t* raw, uint32_t st, uint4* dst) {
  const uint32_t m2 = __byte_perm(st, st, 0x1010);
  const float rinv = rcpf(hi_f(st));
  const uint32_t rh = pack2(rinv, rinv), rl = pack2(rinv - hi_f(rh), rinv - hi_f(rh));
#pragma unroll
  for (int c = 0; c < 4; c++) {
    uint32_t v[4];
#pragma unroll
    for (int i = 0; i < 4; i++) { const uint32_t t = sub2(raw[4 * c + i], m2); v[i] = fma2(t, rh, mul2(t, rl)); }
    stg128(dst + 32 * c, v[0], v[1], v[2], v[3]);
  }
}
__device__ __forceinline__ void col_sums(uint32_t tile, ulonglong2* part, uint32_t tag) {
  const int lane = threadIdx.x & 31;
  float cs[8] = {0, 0, 0, 0, 0, 0, 0, 0};
  uint32_t base = tile + ((lane >> 3) & 1) * 8192 + (lane >> 4) * 4096 + ((lane & 7) << 4);
#pragma unroll 1
  for (int k0 = 0; k0 < 8; k0++, base = (base ^ ((k0 ^ (k0 - 1)) << 4)) + 128) {
    uint4 v[4];
#pragma unroll
    for (int k = 0; k < 4; k++) v[k] = lds128(base + k * 1024);
#pragma unroll
    for (int k = 0; k < 4; k++) {
      cs[0] += lo_f(v[k].x); cs[1] += hi_f(v[k].x); cs[2] += lo_f(v[k].y); cs[3] += hi_f(v[k].y);
      cs[4] += lo_f(v[k].z); cs[5] += hi_f(v[k].z); cs[6] += lo_f(v[k].w); cs[7] += hi_f(v[k].w);
    }
  }
  const bool up = lane >= 16;
#pragma unroll
  for (int i = 0; i < 2; i++) {
    const float a = (up ? cs[4 + 2 * i] : cs[2 * i]) + __shfl_xor_sync(~0u, up ? cs[2 * i] : cs[4 + 2 * i], 16);
    const float b = (up ? cs[5 + 2 * i] : cs[1 + 2 * i]) + __shfl_xor_sync(~0u, up ? cs[1 + 2 * i] : cs[5 + 2 * i], 16);
    asm volatile("{\n.reg .b64 a, b;\nmov.b64 a, {%1, %3};\nmov.b64 b, {%2, %3};\nst.relaxed.gpu.global.v2.b64 [%0], {a, b};\n}"
                 ::"l"(part + 32 * (i + (up ? 2 : 0)) + (lane & 15)), "r"(__float_as_uint(a)), "r"(__float_as_uint(b)), "r"(tag) : "memory");
  }
  asm volatile("fence.proxy.async.shared::cta;" ::: "memory");
}

__global__ void __cluster_dims__(2, 1, 1) __launch_bounds__(384, 1)
fused_kernel(const uint4* __restrict__ x, const uint4* __restrict__ wgate, const uint4* __restrict__ wup, Scratch* gs, int by_sm, const __grid_constant__ Maps mp) {
  extern __shared__ __align__(1024) uint8_t smem_raw[];
  const uint32_t sb = (uint32_t)__cvta_generic_to_shared(smem_raw);
  const unsigned bid = role_id(by_sm);
  if (threadIdx.x == 352) TS(63);
  if (threadIdx.x < 256 && bid < NMAIN) {
    const uint32_t r = threadIdx.x >> 3, ch = threadIdx.x & 7;
    const uint32_t d = sb + r * 128 + ((ch ^ (r & 7)) << 4);
    const uint8_t* xa = (const uint8_t*)x + ((bid & 15) * 262144 + r * 4096 + ch * 16);
    const uint32_t wo = r * (DFF * 2) + (bid >> 4) * 256 + ch * 16;
    const uint8_t *wa = (const uint8_t*)wgate + wo, *wb = (const uint8_t*)wup + wo;
#pragma unroll
    for (int i = 0; i < 12; i++) {
      const int h = i >= 8;
      const uint8_t* src = (i >> 2) == 1 ? xa + (i & 1) * 131072 + ((i >> 1) & 1) * 2048 : ((i & 2) ? wb : wa) + h * 32 * (DFF * 2) + (i & 1) * 128;
      asm volatile("cp.async.cg.shared.global [%0], [%1], 16;" ::"r"(d + ((i >> 2) == 1 ? OFF_A + (i & 3) * 4096 : (i & 3) * 8192 + h * 4096)), "l"(src) : "memory");
    }
    if (threadIdx.x == 0) TS(23);
  }
  const int warp = __shfl_sync(~0u, threadIdx.x >> 5, 0), lane = threadIdx.x & 31;
  const int m = bid & 15, j = bid >> 4, rank = bid & 1;
  const int m2 = bid >> 3, j2 = bid & 7;
  const uint32_t zero = warp >> 8;
  const bool helper = bid >= NMAIN;
  if (warp >= 8) {
    asm volatile("setmaxnreg.dec.sync.aligned.u32 40;");
    if (warp == 8) {
      if (elect_one()) {
        asm volatile("prefetch.tensormap [%0];\nprefetch.tensormap [%1];\nprefetch.tensormap [%2];" ::"l"(&mp.x), "l"(&mp.wg), "l"(&mp.wu) : "memory");
        for (int s = 0; s < 4; s++) mbar_init(sb + B_F1 + 8 * s, 1);
        if (!helper) mbar_arrive(sb + B_F1);
        asm volatile("fence.mbarrier_init.release.cluster;" ::: "memory");
      }
      __syncwarp();
    } else if (warp == 9) {
      if (elect_one()) {
        unsigned nsmid;
        asm("mov.u32 %0, %%nsmid;" : "=r"(nsmid));
        if ((sb & 0xffffff) != SM_BASE || (by_sm && nsmid != NCTA)) asm volatile("trap;");
        for (uint32_t b = B_E1; b < B_F2; b += 8) mbar_init(sb + b, 4);
        for (uint32_t b = B_F2; b < B_AUX; b += 8) mbar_init(sb + b, 1);
        for (uint32_t b = B_EX; b < B_AUX; b += 8) mbar_expect_tx(sb + b, 8192);
        mbar_init(sb + B_AUX, 8); mbar_init(sb + B_HALO, 9); mbar_init(sb + B_HALO + 8, 9);
        asm volatile("st.shared.b32 [%0], %1;" ::"r"(sb + OFF_EPOCH + 4), "r"(bid) : "memory");
        asm volatile("fence.mbarrier_init.release.cluster;" ::: "memory");
      }
      __syncwarp();
    }
    asm volatile("barrier.cluster.arrive.relaxed.aligned;" ::: "memory");
    if (warp == 8 && !helper) {
      if (elect_one()) {
        TS(0); TG(51);
#pragma unroll 1
        for (int kb = 1; kb < 4; kb++) {
          const uint32_t sa = sb + OFF_A + kb * 16384, sw = sb + kb * 32768, fb = sb + B_F1 + 8 * kb;
          mbar_expect_tx(fb, P1_BYTES);
          tma3d(sa, &mp.x, fb, kb * 64, m * 64, 0, EVICT_NORMAL);
          tma2d(sw, &mp.wg, fb, j * 128, kb * 64, EVICT_NORMAL); tma2d(sw + 16384, &mp.wu, fb, j * 128, kb * 64, EVICT_NORMAL);
          tma2d(sw + 8192, &mp.wg, fb, j * 128 + 64, kb * 64, EVICT_NORMAL); tma2d(sw + 24576, &mp.wu, fb, j * 128 + 64, kb * 64, EVICT_NORMAL);
        }
        TS(7);
      }
      __syncwarp();
    }
    asm volatile("barrier.cluster.wait.aligned;" ::: "memory");
    if (helper) {
      if (warp == 8) {
        if (elect_one()) {
          unsigned* ep = &gs->epoch[bid * 2];
          const unsigned e = *ep + 1;
          *ep = e;
#pragma unroll 1
          for (int i = 0; i < 20; i++) {
            const uint32_t fb = sb + (i < 16 ? B_F1 + 8 * (i >> 2) : B_XT);
            if (!(i & 3)) mbar_expect_tx(fb, i < 16 ? P1_BYTES : 32768);
            tma5d(sb + (i < 16 ? i : i + 8) * 8192, &mp.wd, fb, (bid - NMAIN) * 256 + (i & 3) * 64, (i >> 2) * 2, EVICT_FIRST);
          }
          mbar_spin(sb + B_XT, 0, zero);
#pragma unroll 1
          for (int t = 0; t < 16; t++) {
            flag_wait(&gs->flags[(FL_H + t * 4) * 32], e * 8u);
            fence_async();
            if (t == 0) TS(0);
#pragma unroll 1
            for (int n = 0; n < 5; n++) {
              const int i = n ? n - 1 : 4;
              const uint32_t fb = sb + (i < 4 ? B_F1 + 8 * i : B_F2);
              if (t) mbar_spin(sb + B_E1 + 8 * i, ~t & 1, zero);
              if (t || i == 4) mbar_expect_tx(fb, i < 4 ? 16384 : 8192);
              const uint4* src = gs->h + (t * 56 + i) * 1024;
              bulk_load(sb + (i < 4 ? OFF_A + i * 16384 : OFF_X + 4096), src, i < 4 ? 16384 : 4096, fb, EVICT_NORMAL);
              if (i == 4) bulk_load(sb + OFF_X + 12288, src + 256, 4096, fb, EVICT_NORMAL);
            }
          }
        }
      } else if (warp == 9) {
#pragma unroll 1
        for (int t = 0; t < 16; t++) {
          bar_sync(BAR_EV + (t & 1), 288);
          if (lane == 0) { flag_add(&gs->flags[(FL_P + t) * 32]); TS(64 + t); }
          __syncwarp();
        }
      }
    } else if (warp == 8) {
      if (elect_one()) {
        uint32_t par = 0;

        auto x_load = [&]() {
          mbar_expect_tx(sb + B_XT, 32768);
          tma3d(sb + OFF_X, &mp.x, sb + B_XT, j2 * 128, m2 * 64, 0, EVICT_FIRST); tma3d(sb + OFF_X + 16384, &mp.x, sb + B_XT, j2 * 128 + 64, m2 * 64, 0, EVICT_FIRST);
        };
        auto w_tile = [&](int R, const CUtensorMap*& mb0, const CUtensorMap*& mb1, int& n0, int& n1) {
          if (R == 1 || R == 2) {
            mb0 = &mp.wqkv; n0 = 64 * (j + 8 * (R - 1)) + rank * 2048;
            mb1 = rank ? (R == 1 ? &mp.wg : &mp.wu) : &mp.wqkv; n1 = rank ? 1024 + 64 * j : n0 + 1024;
          } else {
            mb0 = mb1 = rank ? &mp.wu : &mp.wg;
            n0 = 128 * j + (R ? 1024 * R - 1536 : 0); n1 = n0 + 64;
          }
        };
        for (int R = 0; R < 5; R++) {
          const CUtensorMap *mb0, *mb1;
          int n0, n1;
          w_tile(R, mb0, mb1, n0, n1);
#pragma unroll 1
          for (int kb = R ? 0 : 4; kb < 16; kb++) {
            if (R == 0 && kb == CS_KB) {
#pragma unroll 1
              for (int h = 0; h < 2; h++) {
                const uint32_t cb = sb + B_CS + 8 * h, d = sb + OFF_X + 16384 * h;
                mbar_expect_tx(cb, 16384);
                tma2d(d, h ? &mp.wu : &mp.wg, cb, n0, m * 64, EVICT_NORMAL); tma2d(d + 8192, h ? &mp.wu : &mp.wg, cb, n1, m * 64, EVICT_NORMAL);
              }
            }
            const int st = kb & 3;
            const uint32_t sa = sb + OFF_A + st * 16384, sw = sb + st * 32768, fb = sb + B_F1 + 8 * st;
            mbar_spin(sb + B_E1 + 8 * st, par, zero);
            if (R * 16 + kb >= 4) REL_TS(R * 16 + kb - 4);
            mbar_expect_tx(fb, P1_BYTES);
            tma2d_mc(sw + rank * 16384, mb0, fb, n0, kb * 64, EVICT_FIRST);
            tma2d_mc(sw + 8192 + rank * 16384, mb1, fb, n1, kb * 64, EVICT_FIRST);
            if (R == 0) {
              tma3d(sa, &mp.x, fb, kb * 64, m * 64, 0, EVICT_NORMAL);
            } else {
              if (R == 1 && kb == 0) { mbar_spin(sb + B_DEP, 0, zero); TS(1); }
              tma2d(sa, &mp.xn, fb, kb * 64, m * 128, R == 4 ? EVICT_FIRST : EVICT_NORMAL);
            }
            if (R == 4 && kb == 4 + j2) x_load();
            if (st == 3) par ^= 1;
          }
        }
#pragma unroll 1
        for (int i = 0; i < 26; i++) {
          const int st = i & 3, kh = i < 25 ? 9 + 4 * i + 2 * rank : 109 + rank;
          const uint32_t sa = sb + OFF_A + st * 16384, sw = sb + st * 32768, fb = sb + B_F1 + 8 * st;
          mbar_spin(sb + B_E1 + 8 * st, par, zero);
          REL_TS(76 + i);
          mbar_expect_tx(fb, P1_BYTES);
          tma5d(sw, &mp.wd, fb, j2 * 128, kh, EVICT_FIRST); tma5d(sw + 8192, &mp.wd, fb, j2 * 128 + 64, kh, EVICT_FIRST);
          tma5d(sw + 16384, &mp.wd, fb, (j2 ^ 1) * 128, kh, EVICT_FIRST); tma5d(sw + 24576, &mp.wd, fb, (j2 ^ 1) * 128 + 64, kh, EVICT_FIRST);
          if (i == 0 || i == 5 || i == 9 || i == 17) mbar_spin(sb + B_DEP + 8 * (1 + ((i + 7) >> 3)), 0, zero);
          bulk_load(sa, gs->h + (m2 * 112 + kh) * 512, 16384, fb, EVICT_FIRST);
          if (st == 3) par ^= 1;
        }
        int st = 0; uint32_t par2 = 1;
#pragma unroll 1
        for (int t = 0; t < 16; t++) {
          constexpr auto tab = [](auto f) { uint32_t v = 0; for (int s = 0; s < 5; s++) v |= f(s) / 16384 << (4 * s); return v; };
          const uint32_t sa = sb + (tab(p2_a) >> (4 * st) & 15) * 16384, sw = sb + (tab(p2_b) >> (4 * st) & 15) * 16384, fb = sb + B_F2 + 8 * st;
          mbar_spin(sb + (t < 5 ? B_E1 + 8 * (0x10332 >> (4 * t) & 3) : B_E2 + 8 * st), t < 5 ? t < 3 : par2, zero);
          REL_TS(102 + t);
          mbar_expect_tx(fb, P2_BYTES);
          bulk_load_mc(sa + rank * 8192, gs->o + (m2 * 16 + t) * 1024 + rank * 512, 8192, fb, EVICT_FIRST);
          tma2d(sw, &mp.wo, fb, j2 * 128, t * 64, EVICT_FIRST); tma2d(sw + 8192, &mp.wo, fb, j2 * 128 + 64, t * 64, EVICT_FIRST);
          if (++st == 5) { st = 0; par2 ^= 1; }
        }
      }
    } else if (warp == 9) {
#pragma unroll 1
      for (int e = 0; e < 7; e++) {
        const bool halo = e == 2 || e == 3;
        bar_sync(BAR_EV + e, halo ? 96 : 288);
        if (lane == 0) {
          const int f = e == 0 ? FL_XN + m : (halo ? FL_HALO + (e - 2) * 128 + bid : FL_H + m * 4 + (e == 1 ? 0 : e - 3));
          TS(10 + 2 * e); TG(52 + e);
          flag_add(&gs->flags[f * 32]);
          if (e < 6) TS(11 + 2 * e);
        }
        __syncwarp();
      }
      unsigned other;
      asm volatile("ld.shared::cluster.b32 %0, [%1];" : "=r"(other) : "r"(mapa(sb + OFF_EPOCH + 4, rank ^ 1)) : "memory");
      if (other != (bid ^ 1)) asm volatile("trap;");
      mbar_wait(sb + B_DONE, 0);
    } else {
      unsigned e = 0;
      if (lane == 0) {
        unsigned* ep = &gs->epoch[bid * 2 + warp - 10];
        e = *ep + 1; *ep = e;
        if (warp == 10) { asm volatile("st.shared.b32 [%0], %1;" ::"r"(sb + OFF_EPOCH), "r"(e) : "memory"); mbar_arrive(sb + B_EP); }
      }
      e = __shfl_sync(~0u, e, 0);
      mbar_spin(sb + B_CS + 8 * (warp - 10), 0, zero);
      if (lane == 0 && warp == 11) TS(6);
      col_sums(sb + OFF_X + (warp - 10) * 16384, gs->cspart + (j * 16 + m) * 128 + (warp - 10) * 16, e);
      if (lane == 0 && warp == 11) TS(9);
      if (warp == 10) {
        if (lane == 0) {
#pragma unroll 1
          for (int g = 0; g < 6; g++) {
            flag_wait(&gs->flags[(g == 5 ? FL_P + m2 : (g ? FL_H + m2 * 4 + g - 1 : FL_XN + m)) * 32], e * (g == 5 ? 4u : 8u));
            fence_async();
            mbar_arrive(sb + B_DEP + 8 * g);
            if (g == 0) TS(8);
          }
        }
      } else
      if (elect_one()) {
#pragma unroll 1
        for (int i = 3; i < 8; i++) asm volatile("prefetch.tensormap [%0];" ::"l"(&mp.x + i) : "memory");
#pragma unroll 1
        for (int r = 0; r < 2; r++) {
          const uint32_t hb = sb + B_HALO + 8 * r;
          if (r) mbar_spin(sb + B_HALO, 0, zero);
          if (m) {
            flag_wait(&gs->flags[(FL_HALO + r * 128 + bid - 1) * 32], e);
            fence_async();
            mbar_expect_tx(hb, 4096);
            for (int g = 0; g < 2; g++) bulk_load(sb + OFF_X + g * AT_WG + AT_REM + r * 2048, gs->halo + ((r * 128 + bid - 1) * 2 + g) * 128, 2048, hb, EVICT_FIRST);
          } else {
            mbar_arrive(hb);
          }
          TS(34 + r);
        }
      }
    }
  } else {
    asm volatile("barrier.cluster.arrive.relaxed.aligned;" ::: "memory");
    asm volatile("setmaxnreg.inc.sync.aligned.u32 232;");
    const int wg = warp >> 2, w = warp & 3;
    Cons c;
    c.sb = sb; c.wg = wg; c.zero = zero;
    c.a = 0x4000004000010000ull + ((SM_BASE + OFF_A + wg * 8192) >> 4); c.k1 = 2 + c.zero; c.k2 = 2; c.k4 = 1024 - 6; c.k4w = -3072 - 6; c.b1 = 128 + c.zero;
    c.b = 0x4000004000000000ull + DB_LO + c.zero;
    c.rel = mapa(sb, threadIdx.x & 1);
    c.do_rel = (threadIdx.x & 127) < 2;
    float acc[128];
    uint32_t pk[64];
    float rs[2];
    const int q = lane & 3;

    if (helper) {
      asm volatile("barrier.cluster.wait.aligned;" ::: "memory");
      c.a = 0x8000002000010000ull + ((SM_BASE + OFF_A + wg * 4096) >> 4); c.k2 = 510; c.k4 = 1024 - 514; c.k4w = -3072 - 514;
      c.rel = sb;
      uint4* dst = gs->dpart + (bid - NMAIN) * 4096 + threadIdx.x;
      auto put = [&](int p) {
#pragma unroll
        for (int i = 4 * p; i < 4 * p + 4; i++) stg128(dst + i * 256, pk[4 * i], pk[4 * i + 1], pk[4 * i + 2], pk[4 * i + 3]);
      };
#pragma unroll 1
      for (int t = 0; t < 16; t++) {
        {
          uint64_t a = c.a, b = c.b;
          desc_add(a, (OFF_X + 4096 - OFF_A + wg * 4096) >> 4); desc_add(b, OFF_X >> 4);
          mbar_spin(sb + B_F2, t & 1, c.zero);
          wg_fence();
          wgmma256<0>(acc, a, b, 2, 128); wgmma256<1>(acc, a, b, 0, 0);
          wg_commit();
        }
        p1_issue<0, 1>(acc, c, t & 1); wg_wait<1>(); release(c, B_E2);
        if (t) put(0);
        p1_issue<1, 1>(acc, c, t & 1); wg_wait<1>(); release(c, B_E1);
        if (t) put(1);
        p1_issue<2, 1>(acc, c, t & 1); wg_wait<1>(); release(c, B_E1 + 8);
        if (t) put(2);
        if (wg == 1) { wg_wait<0>(); release(c, B_E1 + 16); bar_sync(BAR_LAG, 256); }
        p1_issue<3, 1>(acc, c, t & 1);
        if (wg == 0) bar_arrive(BAR_LAG, 256);
        if (t) { put(3); bar_arrive(BAR_EV + (~t & 1), 288); dst += 8 * 2048; }
        wg_wait<1>(); if (wg == 0) release(c, B_E1 + 16);
        wg_wait<0>(); release(c, B_E1 + 24);
#pragma unroll
        for (int i = 0; i < 64; i++) pk[i] = pack2(acc[2 * i], acc[2 * i + 1]);
      }
      put(0); put(1); put(2); put(3);
      bar_arrive(BAR_EV + 1, 288);
      return;
    }
    {
      const int prow = 16 * j + 2 * warp;
      const uint4* xr = x + (size_t)(128 * m + 2 * (prow & 63) + (prow >> 6)) * 128 + lane;
      uint4* xo = gs->xn + (size_t)(128 * m + prow) * 128 + lane;
      float c0[2], mo[4];
      uint32_t st[2];
      uint32_t e;
      asm volatile("" : "+l"(xr), "+l"(xo));
      wg_fence(); wgmma256<0>(acc, c.a, c.b, 0, 0); wg_commit(); wg_wait<0>();
      asm volatile("barrier.cluster.wait.aligned;" ::: "memory");
      asm volatile("cp.async.wait_all;\nfence.proxy.async.shared::cta;" ::: "memory");
      bar_sync(BAR_MMA, 256);
      if (threadIdx.x == 0) TS(39);
      p1_step<0, false>(acc, c);
      unsigned long long part[18];
      auto gather = [&](int from, int to) {
        const int lane = lane_here();
        const unsigned long long* cp = (const unsigned long long*)gs->cspart + j * 4096 + warp * 32 + lane;
        const unsigned long long* sp = gs->stats + 128 * m + warp * 16 + (lane >> 2);
#pragma unroll
        for (int i = from; i < to; i++) asm volatile("ld.relaxed.gpu.global.b64 %0, [%1];" : "=l"(part[i]) : "l"(i < 16 ? cp + i * 256 : sp + (i - 16) * 8) : "memory");
      };
      auto row_load = [&](int r) {
#pragma unroll
        for (int i = 4 * r; i < 4 * r + 4; i++)
          asm volatile("ld.global.nc.L1::no_allocate.v4.b32 {%0,%1,%2,%3}, [%4];" : "=r"(pk[4 * i]), "=r"(pk[4 * i + 1]), "=r"(pk[4 * i + 2]), "=r"(pk[4 * i + 3]) : "l"(xr + r * 256 + (i & 3) * 32));
      };
      p1_step<1>(acc, c); row_load(0);
      p1_step<2>(acc, c); row_load(1);
      p1_loop(acc, c, 3, LN_KB + 1, [](int) {});
      pin<16>(pk); ln_moments(pk, c0[0], mo[0], mo[1]); pin<2>(mo);
      p1_step<LN_KB + 1>(acc, c);
      sched_fence(c.zero);
      pin<16>(pk + 16); ln_moments(pk + 16, c0[1], mo[2], mo[3]); ln_reduce(mo[0], mo[1]); pin<4>(mo);
      p1_step<LN_KB + 2>(acc, c);
      mbar_spin(sb + B_EP, 0, c.zero);
      asm volatile("ld.shared.b32 %0, [%1];" : "=r"(e) : "r"(sb + OFF_EPOCH) : "memory");
      pin<2>(mo); st[0] = ln_finish(c0[0], mo[0], mo[1]); ln_reduce(mo[2], mo[3]); pin<1>(st); pin<2>(mo + 2);
      p1_step<LN_KB + 3>(acc, c);
      sched_fence(c.zero);
      pin<1>(st); pin<2>(mo + 2);
      st[1] = ln_finish(c0[1], mo[2], mo[3]);
      ln_store(pk, st[0], xo);
      if (lane == 0)
        asm volatile("{\n.reg .b64 a, b;\nmov.b64 a, {%1, %3};\nmov.b64 b, {%2, %3};\nst.relaxed.gpu.global.v2.b64 [%0], {a, b};\n}" ::"l"(gs->stats + 128 * m + prow), "r"(st[0]), "r"(st[1]), "r"(e) : "memory");
      p1_step<LN_KB + 4>(acc, c);
      sched_fence(c.zero);
      pin<1>(st + 1);
      ln_store(pk + 16, st[1], xo + 128);
      bar_arrive(BAR_EV, 288);
      p1_loop(acc, c, LN_KB + 5, 13, [](int) {});
      gather(0, 9);
      p1_step<13>(acc, c);
      gather(9, 18);
      p1_step<14>(acc, c);
      auto validate = [&]() {
        float csum;
        for (int tries = 0;; tries++) {
          uint32_t bad = 0;
          csum = 0.f;
#pragma unroll
          for (int i = 0; i < 18; i++) { bad |= (uint32_t)(part[i] >> 32) ^ e; if (i < 16) csum += __uint_as_float((uint32_t)part[i]); }
          if (!__any_sync(~0u, bad != 0) || tries > (1 << 20)) break;
          gather(0, 18);
        }
        const float hi = bf16r(csum), mid = bf16r(csum - hi);
        sts128(sb + OFF_CS + ((threadIdx.x & 62) * 4 + (threadIdx.x >> 6) * 2 + (threadIdx.x & 1)) * 16, make_uint4(pack2(hi, mid), pack2(csum - hi - mid, 0.f), 0, 0));
        asm volatile("fence.proxy.async.shared::cta;" ::: "memory");
        __syncwarp();
        if (lane == 0) mbar_arrive(sb + B_AUX);
      };
#pragma unroll 1
      for (int ph = 1; ph >= 0; ph--) {
        if (wg == ph) validate();
        if (ph) {
          if (wg == 1) { wg_wait<0>(); release(c, B_E1 + 16); bar_sync(BAR_LAG, 256); }
          p1_issue<3, 1>(acc, c, 1);
        }
      }
      const uint32_t keep = q == 0 ? 0xffffffffu : (q == 1 ? 0xffffu : 0u);
      const uint32_t a0 = (__byte_perm((uint32_t)part[16], 0, 0x1010) ^ 0x80008000u) & keep, a1 = (__byte_perm((uint32_t)part[17], 0, 0x1010) ^ 0x80008000u) & keep;
      mbar_spin(sb + B_AUX, 0, c.zero);
      wg_fence();
      wgmma256_rs(acc, a0, a1, 0, 0, (SM_BASE + OFF_CS) >> 4);
      wg_commit();
      if (wg == 0) bar_arrive(BAR_LAG, 256);
      rs[0] = rcpf(hi_f((uint32_t)part[16])); rs[1] = rcpf(hi_f((uint32_t)part[17]));
      wg_wait<2>(); if (wg == 0) release(c, B_E1 + 16);
      wg_wait<0>(); release(c, B_E1 + 24);
    }
#pragma unroll 1
    for (int R = 1;; R++) {
#pragma unroll
      for (int i = 0; i < 64; i++) pk[i] = pack2(acc[2 * i], acc[2 * i + 1]);
      uint8_t* hb = (uint8_t*)gs->h + (size_t)m * 56 * 16384 + warp * 1024;
      if (R == 5) { c.a = 0x8000002000010000ull + ((SM_BASE + OFF_A + wg * 4096) >> 4); c.k2 = 510; c.k4 = 1024 - 514; c.k4w = -3072 - 514; }
      p1_step<0>(acc, c);
      if (R == 2 || R == 3) {
        attn_tile(acc, pk, c, R - 2, warp, m, bid, gs, hb + (16 + j) * 16384, (uint8_t*)gs->o + (m * 16 + j + 8 * (R - 2)) * 16384 + warp * 1024);
      } else {
        geglu_tile(acc, pk, c, R == 5 ? 24 : 15, hb + (2 * j + (R == 1 ? 0 : 16 * R - 40)) * 16384, BAR_EV + (R == 1 ? 1 : R + 1), rs);
        rs[0] = rs[1] = 1.0f;
        if (R == 5) break;
      }
      p1_step<15>(acc, c);
    }
    auto fetch = [&](int p) {
      asm volatile("ld.global.cg.v4.b32 {%0,%1,%2,%3}, [%4];" : "=r"(pk[4 * p]), "=r"(pk[4 * p + 1]), "=r"(pk[4 * p + 2]), "=r"(pk[4 * p + 3]) : "l"(gs->dpart + bid * 2048 + p * 256 + threadIdx.x) : "memory");
    };
    mbar_spin(sb + B_DEP + 40, 0, c.zero);
    fetch(0); fetch(1); fetch(2);
    p1_step<8>(acc, c);
    fetch(3); fetch(4); fetch(5);
    desc_add(c.a, 2 * rank); desc_add(c.b, 128 * rank);
    mbar_spin(sb + B_F1 + 8, 0, c.zero);
    wg_fence();
    wgmma256<1>(acc, c.a, c.b, rank ? 510 : 2, c.b1);
    wgmma256<1>(acc, c.a, c.b, rank ? 2 : 510, c.b1);
    wgmma256<1>(acc, c.a, c.b, 512 - 2 * rank, 1792 - 128 * rank);
    wg_commit();
    wg_wait<1>(); release(c, B_E1);
    fetch(6); fetch(7);
    {
      float accs[64];
      const uint32_t peer = mapa(sb, rank ^ 1);
      auto send_piece = [&](int p) {
        asm volatile("st.async.weak.shared::cluster.mbarrier::complete_tx::bytes.v4.b32 [%0], {%1,%2,%3,%4}, [%5];" ::"r"(peer + OFF_LAND + p * 4096 + threadIdx.x * 16),
                     "r"(pack2(acc[64 + 8 * p], acc[65 + 8 * p])), "r"(pack2(acc[66 + 8 * p], acc[67 + 8 * p])), "r"(pack2(acc[68 + 8 * p], acc[69 + 8 * p])), "r"(pack2(acc[70 + 8 * p], acc[71 + 8 * p])),
                     "r"(peer + B_EX + 16 * wg + 8 * (p >> 2)) : "memory");
      };
      auto silu_piece = [&](int p) {
        const uint4 r = lds128(sb + OFF_LAND + p * 4096 + threadIdx.x * 16);
        const uint32_t rr[4] = {add2(r.x, pk[4 * p]), add2(r.y, pk[4 * p + 1]), add2(r.z, pk[4 * p + 2]), add2(r.w, pk[4 * p + 3])};
#pragma unroll
        for (int i = 0; i < 4; i++) {
          const float a = acc[8 * p + 2 * i] + lo_f(rr[i]), b = acc[8 * p + 2 * i + 1] + hi_f(rr[i]);
          pk[4 * p + i] = pack2(silu_half(a), silu_half(b));
        }
        pin<4>(pk + 4 * p);
      };
      const uint32_t xa = sb + OFF_X + (warp * 16 + (lane & 7)) * 128 + (((lane >> 3) ^ (lane & 7)) << 4);
      auto x_addr = [&](int i) { return (xa ^ ((i & 1) << 6)) + ((i >> 1) & 1) * 1024 + (i >> 2) * 16384; };
      auto x_piece = [&](int i) { const uint4 v = ldsm(x_addr(i)); pk[32 + 4 * i] = v.x; pk[33 + 4 * i] = v.y; pk[34 + 4 * i] = v.z; pk[35 + 4 * i] = v.w; };
      p2_step<0>(accs, c);
      p2_step<1>(accs, c);
      mbar_spin(sb + B_E1 + 8, 0, c.zero);
      send_piece(0); send_piece(1);
      p2_step<2>(accs, c); sched_fence(c.zero); send_piece(2); send_piece(3);
      p2_step<3>(accs, c); sched_fence(c.zero); send_piece(4); send_piece(5);
      p2_step<4>(accs, c); mbar_spin(sb + B_XT, 0, c.zero); send_piece(6); send_piece(7);
      p2_step<5>(accs, c); mbar_spin(sb + B_EX + 16 * wg, 0, c.zero); silu_piece(0); x_piece(0);
      p2_step<6>(accs, c); sched_fence(c.zero); silu_piece(1); x_piece(1);
      p2_step<7>(accs, c); sched_fence(c.zero); silu_piece(2); x_piece(2);
      p2_step<8>(accs, c); sched_fence(c.zero); silu_piece(3); x_piece(3);
      p2_step<9>(accs, c); mbar_spin(sb + B_EX + 16 * wg + 8, 0, c.zero); silu_piece(4); x_piece(4);
      p2_step<10>(accs, c); sched_fence(c.zero); silu_piece(5); x_piece(5);
      p2_step<11>(accs, c); sched_fence(c.zero); silu_piece(6); x_piece(6); x_piece(7);
      auto out_half = [&](const float* a, int h) {
#pragma unroll
        for (int i = 4 * h; i < 4 * h + 4; i++) {
          uint32_t v[4];
#pragma unroll
          for (int k = 0; k < 4; k++) { const int o = 2 * (4 * (i & 1) + k) + ((i >> 1) & 1); v[k] = fma2(pack2(a[2 * o], a[2 * o + 1]), pk[16 * h + o], pk[32 + 4 * i + k]); }
          asm volatile("stmatrix.sync.aligned.m8n8.x4.shared.b16 [%0], {%1,%2,%3,%4};" ::"r"(x_addr(i)), "r"(v[0]), "r"(v[1]), "r"(v[2]), "r"(v[3]) : "memory");
          if (i & 1) {
            asm volatile("fence.proxy.async.shared::cta;" ::: "memory");
            __syncwarp();
            if (elect_one()) tma3d_store(&mp.out, sb + OFF_X + h * 16384 + warp * 2048 + (i & 2) * 512, j2 * 128 + h * 64, m2 * 64 + w * 16 + (i & 2) * 4, wg);
          }
        }
      };
      if (wg == 1) silu_piece(7);
      p2_step<12>(accs, c); p2_step<13>(accs, c); p2_step<14>(accs, c); p2_step<15>(accs, c);
      if (c.do_rel) mbar_arrive(sb + B_DONE);
      if (wg == 0) silu_piece(7);
      wg_wait<0>();
      out_half(accs, 0); out_half(accs + 32, 1);
      if (elect_one()) { asm volatile("cp.async.bulk.commit_group;\ncp.async.bulk.wait_group.read 0;" ::: "memory"); }
    }
  }
}

typedef CUresult (*EncodeFn)(CUtensorMap*, CUtensorMapDataType, cuuint32_t, void*, const cuuint64_t*, const cuuint64_t*, const cuuint32_t*, const cuuint32_t*,
                             CUtensorMapInterleave, CUtensorMapSwizzle, CUtensorMapL2promotion, CUtensorMapFloatOOBfill);

void encode(EncodeFn fn, CUtensorMap* tm, const void* p, int rank, const cuuint64_t* dims, const cuuint64_t* strides, const cuuint32_t* box) {
  const cuuint32_t es[5] = {1, 1, 1, 1, 1};
  fn(tm, CU_TENSOR_MAP_DATA_TYPE_BFLOAT16, rank, const_cast<void*>(p), dims, strides, box, es, CU_TENSOR_MAP_INTERLEAVE_NONE, CU_TENSOR_MAP_SWIZZLE_128B,
     CU_TENSOR_MAP_L2_PROMOTION_L2_128B, CU_TENSOR_MAP_FLOAT_OOB_FILL_NONE);
}

}

extern "C" void kernel_launch(void* const* d_in, const int* in_sizes, int n_in, void* d_out, int out_size) {
  (void)in_sizes; (void)n_in; (void)out_size;
  static EncodeFn fn = nullptr;
  static Scratch* gs = nullptr;
  static int nsm = 0;
  if (!fn) {
    void* p = nullptr;
    cudaDriverEntryPointQueryResult qr;
    cudaGetDriverEntryPoint("cuTensorMapEncodeTiled", &p, cudaEnableDefault, &qr);
    fn = (EncodeFn)p;
    cudaGetSymbolAddress((void**)&gs, g_scratch);
    int dev = 0;
    cudaGetDevice(&dev);
    cudaDeviceGetAttribute(&nsm, cudaDevAttrMultiProcessorCount, dev);
    cudaFuncSetAttribute(fused_kernel, cudaFuncAttributeMaxDynamicSharedMemorySize, SMEM_BYTES);
  }
  const void *x = d_in[0], *wqkv = d_in[1], *wo = d_in[2], *wg = d_in[4], *wu = d_in[5], *wd = d_in[6];
  Maps mp;
  {
    const cuuint64_t dims[3] = {DM, SEQ / 2, 2}, st[2] = {DM * 4, DM * 2};
    const cuuint32_t box_in[3] = {64, 64, 2}, box_out[3] = {64, 8, 1};
    encode(fn, &mp.x, x, 3, dims, st, box_in);
    encode(fn, &mp.out, d_out, 3, dims, st, box_out);
  }
  {
    const cuuint64_t dims[2] = {DM, SEQ}, st[1] = {DM * 2};
    const cuuint32_t box[2] = {64, 128};
    encode(fn, &mp.xn, gs->xn, 2, dims, st, box);
  }
  {
    const cuuint32_t box[2] = {64, 64};
    const cuuint64_t dq[2] = {3 * DM, DM}, sq[1] = {3 * DM * 2}, df[2] = {DFF, DM}, sf[1] = {DFF * 2}, dw[2] = {DM, DM}, sw[1] = {DM * 2};
    encode(fn, &mp.wqkv, wqkv, 2, dq, sq, box);
    encode(fn, &mp.wg, wg, 2, df, sf, box);
    encode(fn, &mp.wu, wu, 2, df, sf, box);
    encode(fn, &mp.wo, wo, 2, dw, sw, box);
  }
  {
    const cuuint32_t box[5] = {64, 2, 4, 4, 2};
    const cuuint64_t st[4] = {DM * 2, 8 * DM * 2, 2 * DM * 2, 32 * DM * 2};
    const cuuint64_t dd[5] = {DM, 2, 4, 4, DFF / 32};
    encode(fn, &mp.wd, wd, 5, dd, st, box);
  }
  fused_kernel<<<NCTA, 384, SMEM_BYTES>>>((const uint4*)x, (const uint4*)wg, (const uint4*)wu, gs, nsm == NCTA, mp);
}
```

```cpp
#include <cuda_runtime.h>
#include <cuda_bf16.h>
#include <cuda.h>
#include <stdint.h>

#define CS_KB 8
#define LN_KB 4

namespace {

constexpr int SEQ = 2048, DM = 1024, DFF = 3584;
constexpr int NMAIN = 128, NCTA = 132;
constexpr uint64_t EVICT_FIRST = 0x12F0000000000000ull, EVICT_NORMAL = 0x1000000000000000ull;

constexpr uint32_t SM_BASE = 0x400;
constexpr uint32_t P1_BYTES = 49152, P2_BYTES = 32768;
constexpr uint32_t OFF_A = 131072;
__host__ __device__ constexpr uint32_t p2_a(int s) { return s == 0 ? OFF_A + 32768 : s == 1 ? OFF_A + 49152 : s == 2 ? 114688 : s == 3 ? 16384 : 49152; }
__host__ __device__ constexpr uint32_t p2_b(int s) { return s < 3 ? 65536 + s * 16384 : (s - 3) * 32768; }
constexpr uint32_t OFF_LAND = OFF_A;
constexpr uint32_t OFF_X = 196608;
constexpr uint32_t OFF_CS = OFF_X + 14336;
constexpr uint32_t OFF_BAR = 229376;
constexpr uint32_t B_F1 = OFF_BAR, B_E1 = B_F1 + 32, B_E2 = B_E1 + 32, B_DONE = B_E2 + 40, B_F2 = B_DONE + 8, B_DEP = B_F2 + 40, B_CS = B_DEP + 48,
                   B_XT = B_CS + 16, B_EP = B_XT + 8, B_EX = B_EP + 8, B_AUX = B_EX + 32, B_HALO = B_AUX + 8, OFF_EPOCH = B_HALO + 16;
constexpr uint32_t SMEM_BYTES = 232448;
constexpr uint32_t AT_V = 0, AT_K = 8192, AT_REM = 11264, AT_WG = 15360;

constexpr int FL_XN = 0, FL_H = 16, FL_P = 80, FL_HALO = 96, FL_N = FL_HALO + 256;
struct __align__(1024) Scratch {
  uint4 h[16 * 56 * 1024];
  uint4 o[16 * 16 * 1024];
  uint4 xn[SEQ * DM / 8];
  uint4 dpart[128 * 8 * 256];
  uint4 halo[2 * 128 * 2 * 128];
  ulonglong2 cspart[8 * 16 * 128];
  unsigned long long stats[SEQ];
  unsigned flags[FL_N * 32];
  unsigned epoch[NCTA * 2];
};
__device__ Scratch g_scratch;
#define TG(i) do {} while (0)
#define TSV(i, v) do {} while (0)
#define TS(i) do {} while (0)

__device__ __forceinline__ unsigned role_id(bool by_sm) {
  unsigned sm;
  asm volatile("mov.u32 %0, %%smid;" : "=r"(sm));
  const unsigned t = sm >> 1;
  const unsigned c = t < 60 ? (t < 32 ? t : t + 1 + ((t - 32) * 37 >> 8)) : (t < 62 ? t + 4 : 8 * t - 464);
  return by_sm ? 2 * c + (blockIdx.x & 1) : blockIdx.x;
}

struct Maps { CUtensorMap x, wg, wu, wqkv, wd, wo, out; };

__device__ __forceinline__ void mbar_init(uint32_t bar, uint32_t cnt) { asm volatile("mbarrier.init.shared::cta.b64 [%0], %1;" ::"r"(bar), "r"(cnt)); }
__device__ __forceinline__ void mbar_expect_tx(uint32_t bar, uint32_t bytes) { asm volatile("mbarrier.arrive.expect_tx.shared::cta.b64 _, [%0], %1;" ::"r"(bar), "r"(bytes) : "memory"); }
__device__ __forceinline__ void mbar_arrive(uint32_t bar) { asm volatile("mbarrier.arrive.shared::cta.b64 _, [%0];" ::"r"(bar) : "memory"); }
__device__ __forceinline__ void mbar_arrive_cl(uint32_t bar) { asm volatile("mbarrier.arrive.shared::cluster.b64 _, [%0];" ::"r"(bar) : "memory"); }
__device__ __forceinline__ uint32_t mapa(uint32_t a, uint32_t cta) { uint32_t r; asm("mapa.shared::cluster.u32 %0, %1, %2;" : "=r"(r) : "r"(a), "r"(cta)); return r; }
__device__ __forceinline__ void mbar_wait(uint32_t bar, uint32_t parity) {
  asm volatile("{\n.reg .pred p;\n.reg .u32 n;\nmov.u32 n, 0;\nLAB_WAIT:\nmbarrier.try_wait.parity.shared::cta.b64 p, [%0], %1;\n@p bra LAB_DONE;\n"
               "add.u32 n, n, 1;\nsetp.gt.u32 p, n, 4000000;\n@p trap;\nbra LAB_WAIT;\nLAB_DONE:\n}" ::"r"(bar), "r"(parity) : "memory");
}
__device__ __forceinline__ void mbar_spin(uint32_t bar, uint32_t parity, uint32_t zero) {
  asm volatile("{\n.reg .pred p, z;\nsetp.ne.u32 z, %2, 0;\nLAB_WAIT:\nmbarrier.try_wait.parity.shared::cta.b64 p, [%0], %1;\n@p bra LAB_DONE;\n@z trap;\nbra LAB_WAIT;\nLAB_DONE:\n}" ::"r"(bar), "r"(parity), "r"(zero) : "memory");
}
__device__ __forceinline__ void flag_wait(const unsigned* f, unsigned target) {
  asm volatile("{\n.reg .pred p;\n.reg .u32 n, v;\nmov.u32 n, 0;\nLAB_WAIT:\nld.relaxed.gpu.global.u32 v, [%0];\nsub.u32 v, v, %1;\nsetp.ge.s32 p, v, 0;\n@p bra LAB_DONE;\n"
               "nanosleep.u32 200;\nadd.u32 n, n, 1;\nsetp.gt.u32 p, n, 4000000;\n@p trap;\nbra LAB_WAIT;\nLAB_DONE:\nfence.acquire.gpu;\n}" ::"l"(f), "r"(target) : "memory");
}
__device__ __forceinline__ void flag_add(unsigned* f) { asm volatile("red.release.gpu.global.add.u32 [%0], 1;" ::"l"(f) : "memory"); }
__device__ __forceinline__ void fence_async() { asm volatile("fence.proxy.async.global;" ::: "memory"); }
__device__ __forceinline__ bool elect_one() { uint32_t p; asm volatile("{\n.reg .pred P;\nelect.sync _|P, 0xffffffff;\nselp.u32 %0, 1, 0, P;\n}" : "=r"(p)); return p; }
__device__ __forceinline__ void bar_sync(int id, int n) { asm volatile("bar.sync %0, %1;" ::"r"(id), "r"(n) : "memory"); }
__device__ __forceinline__ void bar_arrive(int id, int n) { asm volatile("bar.arrive %0, %1;" ::"r"(id), "r"(n) : "memory"); }

__device__ __forceinline__ void tma2d(uint32_t dst, const CUtensorMap* tm, uint32_t bar, int c0, int c1, uint64_t hint) {
  asm volatile("cp.async.bulk.tensor.2d.shared::cluster.global.mbarrier::complete_tx::bytes.L2::cache_hint [%0], [%1, {%3, %4}], [%2], %5;" ::"r"(dst), "l"(tm), "r"(bar), "r"(c0), "r"(c1), "l"(hint) : "memory");
}
__device__ __forceinline__ void tma2d_mc(uint32_t dst, const CUtensorMap* tm, uint32_t bar, int c0, int c1, uint64_t hint) {
  asm volatile("cp.async.bulk.tensor.2d.shared::cluster.global.mbarrier::complete_tx::bytes.multicast::cluster.L2::cache_hint [%0], [%1, {%3, %4}], [%2], %5, %6;" ::"r"(dst), "l"(tm), "r"(bar), "r"(c0), "r"(c1), "h"((uint16_t)3), "l"(hint) : "memory");
}
__device__ __forceinline__ void tma3d(uint32_t dst, const CUtensorMap* tm, uint32_t bar, int c0, int c1, int c2, uint64_t hint) {
  asm volatile("cp.async.bulk.tensor.3d.shared::cluster.global.mbarrier::complete_tx::bytes.L2::cache_hint [%0], [%1, {%3, %4, %5}], [%2], %6;" ::"r"(dst), "l"(tm), "r"(bar), "r"(c0), "r"(c1), "r"(c2), "l"(hint) : "memory");
}
__device__ __forceinline__ void tma5d(uint32_t dst, const CUtensorMap* tm, uint32_t bar, int c0, int c4, uint64_t hint) {
  asm volatile("cp.async.bulk.tensor.5d.shared::cluster.global.mbarrier::complete_tx::bytes.L2::cache_hint [%0], [%1, {%3, %5, %5, %5, %4}], [%2], %6;" ::"r"(dst), "l"(tm), "r"(bar), "r"(c0), "r"(c4), "r"(0), "l"(hint) : "memory");
}
__device__ __forceinline__ void tma3d_store(const CUtensorMap* tm, uint32_t src, int c0, int c1, int c2) {
  asm volatile("cp.async.bulk.tensor.3d.global.shared::cta.bulk_group.L2::cache_hint [%0, {%2, %3, %4}], [%1], %5;" ::"l"(tm), "r"(src), "r"(c0), "r"(c1), "r"(c2), "l"(EVICT_FIRST) : "memory");
}
__device__ __forceinline__ void bulk_load(uint32_t dst, const void* src, uint32_t bytes, uint32_t bar, uint64_t hint) {
  asm volatile("cp.async.bulk.shared::cluster.global.mbarrier::complete_tx::bytes.L2::cache_hint [%0], [%1], %2, [%3], %4;" ::"r"(dst), "l"(src), "r"(bytes), "r"(bar), "l"(hint) : "memory");
}
__device__ __forceinline__ void bulk_load_mc(uint32_t dst, const void* src, uint32_t bytes, uint32_t bar, uint64_t hint) {
  asm volatile("cp.async.bulk.shared::cluster.global.mbarrier::complete_tx::bytes.multicast::cluster.L2::cache_hint [%0], [%1], %2, [%3], %4, %5;" ::"r"(dst), "l"(src), "r"(bytes), "r"(bar), "h"((uint16_t)3), "l"(hint) : "memory");
}
__device__ __forceinline__ uint4 lds128(uint32_t a) { uint4 v; asm volatile("ld.shared.v4.b32 {%0,%1,%2,%3}, [%4];" : "=r"(v.x), "=r"(v.y), "=r"(v.z), "=r"(v.w) : "r"(a) : "memory"); return v; }
__device__ __forceinline__ void sts128(uint32_t a, uint4 v) { asm volatile("st.shared.v4.b32 [%0], {%1,%2,%3,%4};" ::"r"(a), "r"(v.x), "r"(v.y), "r"(v.z), "r"(v.w) : "memory"); }
__device__ __forceinline__ void stg128(void* p, uint32_t a, uint32_t b, uint32_t c, uint32_t d) { asm volatile("st.global.v4.b32 [%0], {%1,%2,%3,%4};" ::"l"(p), "r"(a), "r"(b), "r"(c), "r"(d) : "memory"); }

__device__ __forceinline__ uint32_t pack2(float lo, float hi) { uint32_t r; asm("cvt.rn.bf16x2.f32 %0, %1, %2;" : "=r"(r) : "f"(hi), "f"(lo)); return r; }
__device__ __forceinline__ float lo_f(uint32_t v) { return __uint_as_float(v << 16); }
__device__ __forceinline__ float hi_f(uint32_t v) { return __uint_as_float(v & 0xffff0000u); }
__device__ __forceinline__ float bf16r(float v) { return lo_f(pack2(v, 0.f)); }
__device__ __forceinline__ uint32_t mul2(uint32_t a, uint32_t b) { uint32_t r; asm("mul.rn.bf16x2 %0, %1, %2;" : "=r"(r) : "r"(a), "r"(b)); return r; }
__device__ __forceinline__ uint32_t add2(uint32_t a, uint32_t b) { uint32_t r; asm("add.rn.bf16x2 %0, %1, %2;" : "=r"(r) : "r"(a), "r"(b)); return r; }
__device__ __forceinline__ uint32_t sub2(uint32_t a, uint32_t b) { uint32_t r; asm("sub.rn.bf16x2 %0, %1, %2;" : "=r"(r) : "r"(a), "r"(b)); return r; }
__device__ __forceinline__ uint32_t fma2(uint32_t a, uint32_t b, uint32_t c) { uint32_t r; asm("fma.rn.bf16x2 %0, %1, %2, %3;" : "=r"(r) : "r"(a), "r"(b), "r"(c)); return r; }
__device__ __forceinline__ uint32_t max2(uint32_t a, uint32_t b) { uint32_t r; asm("max.bf16x2 %0, %1, %2;" : "=r"(r) : "r"(a), "r"(b)); return r; }
__device__ __forceinline__ float ex2f(float x) { float y; asm("ex2.approx.ftz.f32 %0, %1;" : "=f"(y) : "f"(x)); return y; }
__device__ __forceinline__ float rcpf(float x) { float y; asm("rcp.approx.ftz.f32 %0, %1;" : "=f"(y) : "f"(x)); return y; }
constexpr float GELU_C1 = 0.7978845608028654f, GELU_C3 = 0.035677408136300125f;
__device__ __forceinline__ float gelu_k(float g, float c1, float c3, float k) {
  float t;
  asm("tanh.approx.f32 %0, %1;" : "=f"(t) : "f"(g * fmaf(g * g, c3, c1)));
  g *= k;
  return fmaf(g, t, g);
}
__device__ __forceinline__ float silu_half(float z) { float t; asm("tanh.approx.f32 %0, %1;" : "=f"(t) : "f"(z)); return fmaf(z, t, z); }

__device__ __forceinline__ void wg_fence() { asm volatile("wgmma.fence.sync.aligned;" ::: "memory"); }
__device__ __forceinline__ void wg_commit() { asm volatile("wgmma.commit_group.sync.aligned;" ::: "memory"); }
template <int N> __device__ __forceinline__ void wg_wait() { asm volatile("wgmma.wait_group.sync.aligned %0;" ::"n"(N) : "memory"); }
#define A8(o) "+f"(d[(o)]), "+f"(d[(o) + 1]), "+f"(d[(o) + 2]), "+f"(d[(o) + 3]), "+f"(d[(o) + 4]), "+f"(d[(o) + 5]), "+f"(d[(o) + 6]), "+f"(d[(o) + 7])
#define A64(o) A8(o), A8((o) + 8), A8((o) + 16), A8((o) + 24), A8((o) + 32), A8((o) + 40), A8((o) + 48), A8((o) + 56)
#define REGS0_63 "%0,%1,%2,%3,%4,%5,%6,%7,%8,%9,%10,%11,%12,%13,%14,%15,%16,%17,%18,%19,%20,%21,%22,%23,%24,%25,%26,%27,%28,%29,%30,%31," \
                 "%32,%33,%34,%35,%36,%37,%38,%39,%40,%41,%42,%43,%44,%45,%46,%47,%48,%49,%50,%51,%52,%53,%54,%55,%56,%57,%58,%59,%60,%61,%62,%63"
#define REGS64_127 "%64,%65,%66,%67,%68,%69,%70,%71,%72,%73,%74,%75,%76,%77,%78,%79,%80,%81,%82,%83,%84,%85,%86,%87,%88,%89,%90,%91,%92,%93,%94,%95," \
                   "%96,%97,%98,%99,%100,%101,%102,%103,%104,%105,%106,%107,%108,%109,%110,%111,%112,%113,%114,%115,%116,%117,%118,%119,%120,%121,%122,%123,%124,%125,%126,%127"
__device__ __forceinline__ void desc_add(uint64_t& x, int v) { asm volatile("{\n.reg .b32 lo, hi;\nmov.b64 {lo, hi}, %0;\nadd.s32 lo, lo, %1;\nmov.b64 %0, {lo, hi};\n}" : "+l"(x) : "r"(v)); }
template <int ACCUM> __device__ __forceinline__ void wgmma256(float (&d)[128], uint64_t& a, uint64_t& b, int da, int db) {
  asm volatile("{\n.reg .pred p;\nsetp.ne.b32 p, %130, 0;\n"
               "wgmma.mma_async.sync.aligned.m64n256k16.f32.bf16.bf16 {" REGS0_63 "," REGS64_127 "}, %128, %129, p, 1, 1, 0, 1;\n}"
               : A64(0), A64(64) : "l"(a), "l"(b), "n"(ACCUM));
  desc_add(a, da); desc_add(b, db);
}
__device__ __forceinline__ void wgmma256_rs(float (&d)[128], uint32_t a0, uint32_t a1, uint32_t z0, uint32_t z1, uint32_t b_lo) {
  asm volatile("{\n.reg .b64 db;\nmov.b64 db, {%132, 0x00000008};\n"
               "wgmma.mma_async.sync.aligned.m64n256k16.f32.bf16.bf16 {" REGS0_63 "," REGS64_127 "}, {%128,%129,%130,%131}, db, 1, 1, 1, 0;\n}"
               : A64(0), A64(64) : "r"(a0), "r"(a1), "r"(z0), "r"(z1), "r"(b_lo));
}
template <int ACCUM> __device__ __forceinline__ void wgmma128(float (&d)[64], uint64_t& a, uint64_t& b, int da, int db) {
  asm volatile("{\n.reg .pred p;\nsetp.ne.b32 p, %66, 0;\n"
               "wgmma.mma_async.sync.aligned.m64n128k16.f32.bf16.bf16 {" REGS0_63 "}, %64, %65, p, 1, 1, 0, 1;\n}"
               : A64(0) : "l"(a), "l"(b), "n"(ACCUM));
  desc_add(a, da); desc_add(b, db);
}
template <int ACCUM> __device__ __forceinline__ void hmma(float (&c)[4], uint32_t a0, uint32_t a1, uint32_t a2, uint32_t a3, uint32_t b0, uint32_t b1) {
  if (ACCUM)
    asm volatile("mma.sync.aligned.m16n8k16.row.col.f32.bf16.bf16.f32 {%0,%1,%2,%3}, {%4,%5,%6,%7}, {%8,%9}, {%0,%1,%2,%3};"
                 : "+f"(c[0]), "+f"(c[1]), "+f"(c[2]), "+f"(c[3]) : "r"(a0), "r"(a1), "r"(a2), "r"(a3), "r"(b0), "r"(b1));
  else
    asm volatile("mma.sync.aligned.m16n8k16.row.col.f32.bf16.bf16.f32 {%0,%1,%2,%3}, {%4,%5,%6,%7}, {%8,%9}, {%10,%10,%10,%10};"
                 : "=f"(c[0]), "=f"(c[1]), "=f"(c[2]), "=f"(c[3]) : "r"(a0), "r"(a1), "r"(a2), "r"(a3), "r"(b0), "r"(b1), "f"(0.f));
}
__device__ __forceinline__ uint32_t movm(uint32_t a) { uint32_t d; asm volatile("movmatrix.sync.aligned.m8n8.trans.b16 %0, %1;" : "=r"(d) : "r"(a)); return d; }
__device__ __forceinline__ int lane_here() { int v; asm volatile("mov.u32 %0, %%laneid;" : "=r"(v)); return v; }
template <int N> __device__ __forceinline__ void pin(uint32_t* r) {
#pragma unroll
  for (int i = 0; i < N; i++) asm volatile("" : "+r"(r[i]));
}
template <int N> __device__ __forceinline__ void pin(float* r) {
#pragma unroll
  for (int i = 0; i < N; i++) asm volatile("" : "+f"(r[i]));
}
__device__ __forceinline__ void sched_fence(uint32_t zero) {
  asm volatile("{\n.reg .pred p;\nsetp.eq.u32 p, %0, 0;\nLAB_F:\n@p bra.uni LAB_D;\nnanosleep.u32 0;\nbra.uni LAB_F;\nLAB_D:\n}" ::"r"(zero) : "memory");
}
__device__ __forceinline__ uint4 ldsm(uint32_t a) { uint4 v; asm volatile("ldmatrix.sync.aligned.m8n8.x4.shared.b16 {%0,%1,%2,%3}, [%4];" : "=r"(v.x), "=r"(v.y), "=r"(v.z), "=r"(v.w) : "r"(a) : "memory"); return v; }
__device__ __forceinline__ uint4 ldsm_t(uint32_t a) { uint4 v; asm volatile("ldmatrix.sync.aligned.m8n8.x4.trans.shared.b16 {%0,%1,%2,%3}, [%4];" : "=r"(v.x), "=r"(v.y), "=r"(v.z), "=r"(v.w) : "r"(a) : "memory"); return v; }

constexpr int BAR_LAG = 1, BAR_MMA = 2, BAR_EV = 3;

struct Cons {
  uint32_t sb;
  mutable uint64_t a, b;
  int k1, k2, k4, k4w, b1;
  uint32_t rel;
  bool do_rel;
  int wg;
  uint32_t zero;
};
#define REL_TS(n) TS(64 + (n))
constexpr uint32_t DB_LO = (SM_BASE >> 4) | ((8192 >> 4) << 16);

template <int ST, int ACCUM, bool WAIT = true> __device__ __forceinline__ void p1_issue(float (&acc)[128], const Cons& c, uint32_t parity) {
  if (WAIT) mbar_spin(c.sb + B_F1 + 8 * ST, parity, c.zero);
  wg_fence();
  wgmma256<ACCUM>(acc, c.a, c.b, c.k1, c.b1);
  wgmma256<1>(acc, c.a, c.b, c.k2, c.b1);
  wgmma256<1>(acc, c.a, c.b, c.k1, c.b1);
  wgmma256<1>(acc, c.a, c.b, ST == 3 ? c.k4w : c.k4, ST == 3 ? -6144 - 384 : 2048 - 384);
  wg_commit();
}
__device__ __forceinline__ void release(const Cons& c, uint32_t bar) { if (c.do_rel) mbar_arrive_cl(c.rel + bar); }
template <int KB, bool WAIT = true> __device__ __forceinline__ void p1_step(float (&acc)[128], const Cons& c) {
  if (KB == 15) { if (c.wg == 1) { wg_wait<0>(); release(c, B_E1 + 16); bar_sync(BAR_LAG, 256); } }
  p1_issue<KB & 3, KB != 0, WAIT>(acc, c, (KB >> 2) & 1);
  if (KB == 15) { if (c.wg == 0) bar_arrive(BAR_LAG, 256); }
  if (KB > 0) { wg_wait<1>(); if (KB != 15 || c.wg == 0) release(c, B_E1 + 8 * ((KB - 1) & 3)); }
  if (KB == 15) { wg_wait<0>(); release(c, B_E1 + 24); }
}
template <class F> __device__ __forceinline__ void p1_loop(float (&acc)[128], const Cons& c, int from, int to, F&& shadow) {
#pragma unroll 1
  for (int kb = from; kb < to; kb++) {
    const bool wrap = (kb & 3) == 3;
    mbar_spin(c.sb + B_F1 + 8 * (kb & 3), (kb >> 2) & 1, c.zero);
    wg_fence();
    wgmma256<1>(acc, c.a, c.b, c.k1, c.b1);
    wgmma256<1>(acc, c.a, c.b, c.k2, c.b1);
    wgmma256<1>(acc, c.a, c.b, c.k1, c.b1);
    wgmma256<1>(acc, c.a, c.b, wrap ? c.k4w : c.k4, wrap ? -6144 - 384 : 2048 - 384);
    wg_commit();
    wg_wait<1>();
    release(c, B_E1 + 8 * ((kb - 1) & 3));
    shadow(kb);
  }
}
template <int T> __device__ __forceinline__ void p2_step(float (&acc)[64], const Cons& c) {
  if (T == 12) { if (c.wg == 1) bar_sync(BAR_LAG, 256); }
  mbar_spin(c.sb + B_F2 + 8 * (T % 5), (T / 5) & 1, c.zero);
  wg_fence();
  wgmma128<T != 0>(acc, c.a, c.b, c.k1, c.b1);
  wgmma128<1>(acc, c.a, c.b, c.k2, c.b1);
  wgmma128<1>(acc, c.a, c.b, c.k1, c.b1);
  wgmma128<1>(acc, c.a, c.b, ((int)p2_a((T + 1) % 5) - (int)p2_a(T % 5)) / 16 - 514, ((int)p2_b((T + 1) % 5) - (int)p2_b(T % 5)) / 16 - 384);
  wg_commit();
  if (T == 15) { if (c.wg == 0) bar_arrive(BAR_LAG, 256); }
  if (T <= 11) { wg_wait<1>(); release(c, T ? B_E2 + 8 * ((T + 4) % 5) : B_E1 + 8); }
}

template <int P> __device__ __forceinline__ void geglu_piece(uint32_t (&pk)[64], uint8_t* dst, const float (&gc)[6]) {
  constexpr int cg = P >> 1, r = P & 1;
  uint32_t v[4];
#pragma unroll
  for (int i = 0; i < 4; i++) {
    const uint32_t g = pk[2 * (4 * cg + i) + r];
    v[i] = mul2(pack2(gelu_k(lo_f(g), gc[r], gc[2 + r], gc[4 + r]), gelu_k(hi_f(g), gc[r], gc[2 + r], gc[4 + r])), pk[32 + 2 * (4 * cg + i) + r]);
  }
  stg128(dst + cg * 8192 + r * 512, v[0], v[1], v[2], v[3]);
#pragma unroll
  for (int i = 0; i < 4; i++) { const int o = 2 * (4 * cg + i) + r; pk[o] = pk[16 + o]; pk[32 + o] = pk[48 + o]; }
}
__device__ __forceinline__ void geglu_tile(float (&acc)[128], uint32_t (&pk)[64], const Cons& c, int to, uint8_t* dst, int ev, const float (&rs)[2]) {
  const int lane = lane_here();
  dst += (lane ^ (lane >> 3)) << 4;
  float gc[6];
#pragma unroll
  for (int r = 0; r < 2; r++) { gc[r] = GELU_C1 * rs[r]; gc[2 + r] = GELU_C3 * (rs[r] * rs[r]) * rs[r]; gc[4 + r] = 0.25f * (rs[r] * rs[r]); }
  pin<6>(gc);
  p1_loop(acc, c, 1, to, [&](int kb) {
    if (kb <= 8) {
      if (kb & 1) { if (kb & 2) geglu_piece<2>(pk, dst, gc); else geglu_piece<0>(pk, dst, gc); }
      else if (kb & 2) geglu_piece<1>(pk, dst, gc);
      else {
        geglu_piece<3>(pk, dst, gc);
        if (kb == 8) bar_arrive(ev, 288);
        dst += 16384;
      }
    }
  });
}

__device__ __forceinline__ void attn_tile(float (&acc)[128], uint32_t (&pk)[64], const Cons& c, int round, int warp, int m, unsigned bid, Scratch* gs, uint8_t* hdst, uint8_t* odst) {
  const int w = warp & 3;
  const uint32_t at = c.sb + OFF_X + c.wg * AT_WG;
  int lane = lane_here();
  hdst += (lane ^ (lane >> 3)) << 4;
  auto scatter = [&]() {
    const int lane = lane_here();
    const uint32_t swz = (lane ^ (lane >> 3)) << 4;
#pragma unroll
    for (int i = 0; i < 4; i++) {
      const int h = i & 1, r = i >> 1;
      sts128(at + AT_V + (2 * w + r) * 1024 + h * 512 + swz, make_uint4(pk[32 + 8 * h + r], pk[34 + 8 * h + r], pk[36 + 8 * h + r], pk[38 + 8 * h + r]));
    }
    if (w < 3) {
#pragma unroll
      for (int i = 0; i < 8; i++) asm volatile("st.shared.b32 [%0], %1;" ::"r"(at + AT_K + w * 1024 + i * 128 + lane * 4), "r"(pk[17 + 2 * i]) : "memory");
    } else {
      uint8_t* g = (uint8_t*)gs->halo + ((round * 128 + bid) * 2 + c.wg) * 2048;
#pragma unroll
      for (int i = 0; i < 8; i++) asm volatile("st.global.b32 [%0], %1;" ::"l"(g + i * 128 + lane * 4), "r"(pk[17 + 2 * i]) : "memory");
#pragma unroll
      for (int h = 0; h < 2; h++) stg128(g + 1024 + h * 512 + swz, pk[33 + 8 * h], pk[35 + 8 * h], pk[37 + 8 * h], pk[39 + 8 * h]);
      bar_arrive(BAR_EV + 2 + round, 96);
    }
    __syncwarp();
    if (lane == 0) mbar_arrive(c.sb + B_HALO + 8 * round);
    if (round) {
#pragma unroll
      for (int p = 0; p < 4; p++) {
        const int o = 32 + 8 * (p >> 1) + (p & 1);
        asm volatile("ld.global.cg.v4.b32 {%0,%1,%2,%3}, [%4];" : "=r"(pk[o]), "=r"(pk[o + 2]), "=r"(pk[o + 4]), "=r"(pk[o + 6]) : "l"(hdst + (p >> 1) * 8192 + (p & 1) * 512) : "memory");
      }
    }
  };
  auto gu_piece = [&](int p) {
    uint32_t v[4];
#pragma unroll
    for (int i = 0; i < 4; i++) {
      const int o = 2 * i + p;
      pin<1>(pk + 48 + o);
      const uint32_t g = pk[48 + o];
      v[i] = mul2(round ? pk[32 + o] : 0x3e803e80u, round ? g : pack2(gelu_k(lo_f(g), GELU_C1, GELU_C3, 1.0f), gelu_k(hi_f(g), GELU_C1, GELU_C3, 1.0f)));
    }
    stg128(hdst + p * 512, v[0], v[1], v[2], v[3]);
#pragma unroll
    for (int i = 0; i < 4; i++) { pk[32 + 2 * i + p] = pk[40 + 2 * i + p]; pk[48 + 2 * i + p] = pk[56 + 2 * i + p]; }
  };
  p1_step<1>(acc, c);
  scatter();
  p1_loop(acc, c, 2, 9, [&](int kb) {
    if (kb >= 3 && kb <= 6) {
      if (kb & 1) gu_piece(0);
      else {
        gu_piece(1);
        hdst += 8192;
      }
    }
  });
  const bool first = m == 0 && w == 0;
  uint32_t kl[16];
  mbar_spin(c.sb + B_HALO + 8 * round, 0, c.zero);
  lane = lane_here();
  {
    const uint32_t ka = at + lane * 4 + (w ? AT_K + (w - 1) * 1024 : (first ? AT_K : AT_REM + round * 2048));
#pragma unroll
    for (int i = 0; i < 8; i++) {
      asm volatile("ld.shared.b32 %0, [%1];" : "=r"(kl[2 * i]) : "r"(ka + i * 128) : "memory");
      kl[2 * i + 1] = pk[16 + 2 * i] | c.zero;
    }
  }
  float st[4][4];
  pin<16>(kl);
  bar_sync(BAR_MMA, 256);
  mbar_spin(c.sb + B_F1 + 8 * 1, 0, c.zero);
#pragma unroll
  for (int ks = 0; ks < 2; ks++) {
#pragma unroll
    for (int h = 0; h < 2; h++) {
      const int o = 8 * h + 4 * ks;
      if (ks == 0) { hmma<0>(st[2 * h], kl[o], kl[o + 1], kl[o + 2], kl[o + 3], pk[o], pk[o + 2]); hmma<0>(st[2 * h + 1], pk[16 + o], pk[17 + o], pk[18 + o], pk[19 + o], pk[o + 1], pk[o + 3]); }
      else { hmma<1>(st[2 * h], kl[o], kl[o + 1], kl[o + 2], kl[o + 3], pk[o], pk[o + 2]); hmma<1>(st[2 * h + 1], pk[16 + o], pk[17 + o], pk[18 + o], pk[19 + o], pk[o + 1], pk[o + 3]); }
    }
  }
  sched_fence(c.zero);
  bar_sync(BAR_MMA, 256);
  p1_step<9, false>(acc, c);
  sched_fence(c.zero);
  pin<16>(&st[0][0]);
  lane = lane_here();
  const int rho = lane >> 2, q = lane & 3;
  const bool le0 = 2 * q <= rho, le1 = 2 * q + 1 <= rho;
  uint32_t la[2], lb[2], mx[2];
#pragma unroll
  for (int h = 0; h < 2; h++) {
    uint32_t l[2];
#pragma unroll
    for (int r = 0; r < 2; r++) {
      const float (&t)[4] = st[2 * h + r];
      l[r] = movm(pack2(rho <= 2 * q ? t[2] : t[0], rho <= 2 * q + 1 ? t[3] : t[1]));
      l[r] = fma2(l[r], 0x3e353e35u, mul2(l[r], 0x379e379eu));
    }
    la[h] = __byte_perm(l[0], l[1], 0x5410); lb[h] = __byte_perm(l[0], l[1], 0x7632);
    if (first && !le0) la[h] = (la[h] & 0xffff0000u) | 0xce6eu;
    if (first && !le1) lb[h] = (lb[h] & 0xffff0000u) | 0xce6eu;
    mx[h] = max2(la[h], lb[h]);
  }
#pragma unroll
  for (int o = 1; o <= 2; o++) { mx[0] = max2(mx[0], __shfl_xor_sync(~0u, mx[0], o)); mx[1] = max2(mx[1], __shfl_xor_sync(~0u, mx[1], o)); }
  const float L2E = 1.4426950408889634f;
  float pr[2][4], z[4];
#pragma unroll
  for (int h = 0; h < 2; h++) {
    pr[h][0] = ex2f((lo_f(la[h]) - lo_f(mx[h])) * L2E); pr[h][1] = ex2f((lo_f(lb[h]) - lo_f(mx[h])) * L2E);
    pr[h][2] = ex2f((hi_f(la[h]) - hi_f(mx[h])) * L2E); pr[h][3] = ex2f((hi_f(lb[h]) - hi_f(mx[h])) * L2E);
    z[2 * h] = pr[h][0] + pr[h][1]; z[2 * h + 1] = pr[h][2] + pr[h][3];
  }
  p1_step<10>(acc, c);
#pragma unroll
  for (int o = 1; o <= 2; o++) {
#pragma unroll
    for (int i = 0; i < 4; i++) z[i] += __shfl_xor_sync(~0u, z[i], o);
  }
  const uint32_t LE = (le0 ? 0xffffu : 0u) | (le1 ? 0xffff0000u : 0u);
  uint32_t P[4][2];
  uint4 vt[4][2];
  {
    const uint32_t row = (lane & 7) * 64 + ((((lane >> 3) & 1) ^ ((lane & 7) >> 1)) << 4);
    const uint32_t v1 = at + AT_V + (2 * w + (lane >> 4)) * 1024 + row;
    const uint32_t v0 = (w || lane >= 16) ? v1 - 1024 : (first ? v1 : at + AT_REM + round * 2048 + 1024 + row);
#pragma unroll
    for (int i = 0; i < 4; i++) {
      const float rz = rcpf(z[i]);
      const uint32_t p = pack2(pr[i >> 1][2 * (i & 1)] * rz, pr[i >> 1][2 * (i & 1) + 1] * rz);
      P[i][0] = p & ~LE; P[i][1] = p & LE;
      const uint32_t a = ((i & 1) ? v1 : v0) + (i >> 1) * 512;
      vt[i][0] = ldsm_t(a); vt[i][1] = ldsm_t(a ^ 32);
    }
  }
  float ot[4][2][4];
  pin<8>(&P[0][0]);
  bar_sync(BAR_MMA, 256);
  mbar_spin(c.sb + B_F1 + 8 * 3, 0, c.zero);
#pragma unroll
  for (int i = 0; i < 8; i++) { const uint4& v = vt[i >> 1][i & 1]; hmma<0>(ot[i >> 1][i & 1], v.x, v.y, v.z, v.w, P[i >> 1][0], P[i >> 1][1]); }
  sched_fence(c.zero);
  bar_sync(BAR_MMA, 256);
  p1_step<11, false>(acc, c);
  sched_fence(c.zero);
  pin<32>(&ot[0][0][0]);
  lane = lane_here();
  odst += (lane ^ (lane >> 3)) << 4;
  auto o_piece = [&](int i) {
    stg128(odst + (i >> 1) * 8192 + (i & 1) * 512, movm(pack2(ot[i][0][0], ot[i][0][1])), movm(pack2(ot[i][0][2], ot[i][0][3])), movm(pack2(ot[i][1][0], ot[i][1][1])), movm(pack2(ot[i][1][2], ot[i][1][3])));
  };
  o_piece(0); o_piece(1);
  p1_step<12>(acc, c);
  o_piece(2); o_piece(3);
  if (round) bar_arrive(BAR_EV + 4, 288);
  p1_loop(acc, c, 13, 15, [](int) {});
}

__device__ __forceinline__ void ln_moments(const uint32_t* raw, float& c0, float& s, float& v) {
  c0 = lo_f(__shfl_sync(~0u, raw[0], 0));
  float ss[4] = {0.f, 0.f, 0.f, 0.f}, vv[4] = {0.f, 0.f, 0.f, 0.f};
#pragma unroll
  for (int i = 0; i < 16; i++) {
    const float a = lo_f(raw[i]) - c0, b = hi_f(raw[i]) - c0;
    ss[(2 * i) & 3] += a; ss[(2 * i + 1) & 3] += b;
    vv[(2 * i) & 3] = fmaf(a, a, vv[(2 * i) & 3]); vv[(2 * i + 1) & 3] = fmaf(b, b, vv[(2 * i + 1) & 3]);
  }
  s = (ss[0] + ss[1]) + (ss[2] + ss[3]); v = (vv[0] + vv[1]) + (vv[2] + vv[3]);
}
__device__ __forceinline__ void ln_reduce(float& s, float& v) {
#pragma unroll
  for (int o = 16; o; o >>= 1) { s += __shfl_xor_sync(~0u, s, o); v += __shfl_xor_sync(~0u, v, o); }
}
__device__ __forceinline__ uint32_t ln_finish(float c0, float s, float v) {
  s *= 1.0f / DM;
  float sd;
  asm("sqrt.approx.ftz.f32 %0, %1;" : "=f"(sd) : "f"(bf16r(bf16r(fmaxf(fmaf(v, 1.0f / DM, -s * s), 0.f)) + 1e-5f)));
  return pack2(c0 + s, sd);
}
__device__ __forceinline__ void ln_store(const uint32_t* raw, uint32_t st, uint4* dst) {
  const uint32_t m2 = __byte_perm(st, st, 0x1010);
  const float rinv = rcpf(hi_f(st));
  const uint32_t rh = pack2(rinv, rinv), rl = pack2(rinv - hi_f(rh), rinv - hi_f(rh));
#pragma unroll
  for (int c = 0; c < 4; c++) {
    uint32_t v[4];
#pragma unroll
    for (int i = 0; i < 4; i++) { const uint32_t t = sub2(raw[4 * c + i], m2); v[i] = fma2(t, rh, mul2(t, rl)); }
    stg128(dst + 4096 * c, v[0], v[1], v[2], v[3]);
  }
}
__device__ __forceinline__ void col_sums(uint32_t tile, ulonglong2* part, uint32_t tag) {
  const int lane = threadIdx.x & 31;
  float cs[8] = {0, 0, 0, 0, 0, 0, 0, 0};
  uint32_t base = tile + ((lane >> 3) & 1) * 8192 + (lane >> 4) * 4096 + ((lane & 7) << 4);
#pragma unroll 1
  for (int k0 = 0; k0 < 8; k0++, base = (base ^ ((k0 ^ (k0 - 1)) << 4)) + 128) {
    uint4 v[4];
#pragma unroll
    for (int k = 0; k < 4; k++) v[k] = lds128(base + k * 1024);
#pragma unroll
    for (int k = 0; k < 4; k++) {
      cs[0] += lo_f(v[k].x); cs[1] += hi_f(v[k].x); cs[2] += lo_f(v[k].y); cs[3] += hi_f(v[k].y);
      cs[4] += lo_f(v[k].z); cs[5] += hi_f(v[k].z); cs[6] += lo_f(v[k].w); cs[7] += hi_f(v[k].w);
    }
  }
  const bool up = lane >= 16;
#pragma unroll
  for (int i = 0; i < 2; i++) {
    const float a = (up ? cs[4 + 2 * i] : cs[2 * i]) + __shfl_xor_sync(~0u, up ? cs[2 * i] : cs[4 + 2 * i], 16);
    const float b = (up ? cs[5 + 2 * i] : cs[1 + 2 * i]) + __shfl_xor_sync(~0u, up ? cs[1 + 2 * i] : cs[5 + 2 * i], 16);
    asm volatile("{\n.reg .b64 a, b;\nmov.b64 a, {%1, %3};\nmov.b64 b, {%2, %3};\nst.relaxed.gpu.global.v2.b64 [%0], {a, b};\n}"
                 ::"l"(part + 32 * (i + (up ? 2 : 0)) + (lane & 15)), "r"(__float_as_uint(a)), "r"(__float_as_uint(b)), "r"(tag) : "memory");
  }
  asm volatile("fence.proxy.async.shared::cta;" ::: "memory");
}

__global__ void __cluster_dims__(2, 1, 1) __launch_bounds__(384, 1)
fused_kernel(const uint4* __restrict__ x, const uint4* __restrict__ wgate, const uint4* __restrict__ wup, Scratch* gs, int by_sm, const __grid_constant__ Maps mp) {
  extern __shared__ __align__(1024) uint8_t smem_raw[];
  const uint32_t sb = (uint32_t)__cvta_generic_to_shared(smem_raw);
  const unsigned bid = role_id(by_sm);
  if (threadIdx.x == 352) TS(63);
  if (threadIdx.x < 256 && bid < NMAIN) {
    const uint32_t r = threadIdx.x >> 3, ch = threadIdx.x & 7;
    const uint32_t d = sb + r * 128 + ((ch ^ (r & 7)) << 4);
    const uint8_t* xa = (const uint8_t*)x + ((bid & 15) * 262144 + r * 4096 + ch * 16);
    const uint32_t wo = r * (DFF * 2) + (bid >> 4) * 256 + ch * 16;
    const uint8_t *wa = (const uint8_t*)wgate + wo, *wb = (const uint8_t*)wup + wo;
#pragma unroll
    for (int i = 0; i < 12; i++) {
      const int h = i >= 8;
      const uint8_t* src = (i >> 2) == 1 ? xa + (i & 1) * 131072 + ((i >> 1) & 1) * 2048 : ((i & 2) ? wb : wa) + h * 32 * (DFF * 2) + (i & 1) * 128;
      asm volatile("cp.async.cg.shared.global [%0], [%1], 16;" ::"r"(d + ((i >> 2) == 1 ? OFF_A + (i & 3) * 4096 : (i & 3) * 8192 + h * 4096)), "l"(src) : "memory");
    }
    if (threadIdx.x == 0) TS(23);
  }
  const int warp = __shfl_sync(~0u, threadIdx.x >> 5, 0), lane = threadIdx.x & 31;
  const int m = bid & 15, j = bid >> 4, rank = bid & 1;
  const int m2 = bid >> 3, j2 = bid & 7;
  const uint32_t zero = warp >> 8;
  const bool helper = bid >= NMAIN;
  if (warp >= 8) {
    asm volatile("setmaxnreg.dec.sync.aligned.u32 40;");
    if (warp == 8) {
      if (elect_one()) {
        asm volatile("prefetch.tensormap [%0];\nprefetch.tensormap [%1];\nprefetch.tensormap [%2];" ::"l"(&mp.x), "l"(&mp.wg), "l"(&mp.wu) : "memory");
        for (int s = 0; s < 4; s++) mbar_init(sb + B_F1 + 8 * s, 1);
        if (!helper) mbar_arrive(sb + B_F1);
        asm volatile("fence.mbarrier_init.release.cluster;" ::: "memory");
      }
      __syncwarp();
    } else if (warp == 9) {
      if (elect_one()) {
        unsigned nsmid;
        asm("mov.u32 %0, %%nsmid;" : "=r"(nsmid));
        if ((sb & 0xffffff) != SM_BASE || (by_sm && nsmid != NCTA)) asm volatile("trap;");
        for (uint32_t b = B_E1; b < B_F2; b += 8) mbar_init(sb + b, 4);
        for (uint32_t b = B_F2; b < B_AUX; b += 8) mbar_init(sb + b, 1);
        for (uint32_t b = B_EX; b < B_AUX; b += 8) mbar_expect_tx(sb + b, 8192);
        mbar_init(sb + B_AUX, 8); mbar_init(sb + B_HALO, 9); mbar_init(sb + B_HALO + 8, 9);
        asm volatile("st.shared.b32 [%0], %1;" ::"r"(sb + OFF_EPOCH + 4), "r"(bid) : "memory");
        asm volatile("fence.mbarrier_init.release.cluster;" ::: "memory");
      }
      __syncwarp();
    }
    asm volatile("barrier.cluster.arrive.relaxed.aligned;" ::: "memory");
    if (warp == 8 && !helper) {
      if (elect_one()) {
        TS(0); TG(51);
#pragma unroll 1
        for (int kb = 1; kb < 4; kb++) {
          const uint32_t sa = sb + OFF_A + kb * 16384, sw = sb + kb * 32768, fb = sb + B_F1 + 8 * kb;
          mbar_expect_tx(fb, P1_BYTES);
          tma3d(sa, &mp.x, fb, kb * 64, m * 64, 0, EVICT_NORMAL);
          tma2d(sw, &mp.wg, fb, j * 128, kb * 64, EVICT_NORMAL); tma2d(sw + 16384, &mp.wu, fb, j * 128, kb * 64, EVICT_NORMAL);
          tma2d(sw + 8192, &mp.wg, fb, j * 128 + 64, kb * 64, EVICT_NORMAL); tma2d(sw + 24576, &mp.wu, fb, j * 128 + 64, kb * 64, EVICT_NORMAL);
        }
        TS(7);
      }
      __syncwarp();
    }
    asm volatile("barrier.cluster.wait.aligned;" ::: "memory");
    if (helper) {
      if (warp == 8) {
        if (elect_one()) {
          unsigned* ep = &gs->epoch[bid * 2];
          const unsigned e = *ep + 1;
          *ep = e;
#pragma unroll 1
          for (int i = 0; i < 20; i++) {
            const uint32_t fb = sb + (i < 16 ? B_F1 + 8 * (i >> 2) : B_XT);
            if (!(i & 3)) mbar_expect_tx(fb, i < 16 ? P1_BYTES : 32768);
            tma5d(sb + (i < 16 ? i : i + 8) * 8192, &mp.wd, fb, (bid - NMAIN) * 256 + (i & 3) * 64, (i >> 2) * 2, EVICT_FIRST);
          }
          mbar_spin(sb + B_XT, 0, zero);
#pragma unroll 1
          for (int t = 0; t < 16; t++) {
            flag_wait(&gs->flags[(FL_H + t * 4) * 32], e * 8u);
            fence_async();
            if (t == 0) TS(0);
#pragma unroll 1
            for (int n = 0; n < 5; n++) {
              const int i = n ? n - 1 : 4;
              const uint32_t fb = sb + (i < 4 ? B_F1 + 8 * i : B_F2);
              if (t) mbar_spin(sb + B_E1 + 8 * i, ~t & 1, zero);
              if (t || i == 4) mbar_expect_tx(fb, i < 4 ? 16384 : 8192);
              const uint4* src = gs->h + (t * 56 + i) * 1024;
              bulk_load(sb + (i < 4 ? OFF_A + i * 16384 : OFF_X + 4096), src, i < 4 ? 16384 : 4096, fb, EVICT_NORMAL);
              if (i == 4) bulk_load(sb + OFF_X + 12288, src + 256, 4096, fb, EVICT_NORMAL);
            }
          }
        }
      } else if (warp == 9) {
#pragma unroll 1
        for (int t = 0; t < 16; t++) {
          bar_sync(BAR_EV + (t & 1), 288);
          if (lane == 0) { flag_add(&gs->flags[(FL_P + t) * 32]); TS(64 + t); }
          __syncwarp();
        }
      }
    } else if (warp == 8) {
      if (elect_one()) {
        uint32_t par = 0;

        auto x_load = [&]() {
          mbar_expect_tx(sb + B_XT, 32768);
          tma3d(sb + OFF_X, &mp.x, sb + B_XT, j2 * 128, m2 * 64, 0, EVICT_FIRST); tma3d(sb + OFF_X + 16384, &mp.x, sb + B_XT, j2 * 128 + 64, m2 * 64, 0, EVICT_FIRST);
        };
        auto w_tile = [&](int R, const CUtensorMap*& mb0, const CUtensorMap*& mb1, int& n0, int& n1) {
          if (R == 1 || R == 2) {
            mb0 = &mp.wqkv; n0 = 64 * (j + 8 * (R - 1)) + rank * 2048;
            mb1 = rank ? (R == 1 ? &mp.wg : &mp.wu) : &mp.wqkv; n1 = rank ? 1024 + 64 * j : n0 + 1024;
          } else {
            mb0 = mb1 = rank ? &mp.wu : &mp.wg;
            n0 = 128 * j + (R ? 1024 * R - 1536 : 0); n1 = n0 + 64;
          }
        };
        for (int R = 0; R < 5; R++) {
          const CUtensorMap *mb0, *mb1;
          int n0, n1;
          w_tile(R, mb0, mb1, n0, n1);
#pragma unroll 1
          for (int kb = R ? 0 : 4; kb < 16; kb++) {
            if (R == 0 && kb == CS_KB) {
#pragma unroll 1
              for (int h = 0; h < 2; h++) {
                const uint32_t cb = sb + B_CS + 8 * h, d = sb + OFF_X + 16384 * h;
                mbar_expect_tx(cb, 16384);
                tma2d(d, h ? &mp.wu : &mp.wg, cb, n0, m * 64, EVICT_NORMAL); tma2d(d + 8192, h ? &mp.wu : &mp.wg, cb, n1, m * 64, EVICT_NORMAL);
              }
            }
            const int st = kb & 3;
            const uint32_t sa = sb + OFF_A + st * 16384, sw = sb + st * 32768, fb = sb + B_F1 + 8 * st;
            mbar_spin(sb + B_E1 + 8 * st, par, zero);
            if (R * 16 + kb >= 4) REL_TS(R * 16 + kb - 4);
            mbar_expect_tx(fb, P1_BYTES);
            tma2d_mc(sw + rank * 16384, mb0, fb, n0, kb * 64, EVICT_FIRST);
            tma2d_mc(sw + 8192 + rank * 16384, mb1, fb, n1, kb * 64, EVICT_FIRST);
            if (R == 0) {
              tma3d(sa, &mp.x, fb, kb * 64, m * 64, 0, EVICT_NORMAL);
            } else {
              if (R == 1 && kb == 0) { mbar_spin(sb + B_DEP, 0, zero); TS(1); }
              bulk_load(sa, gs->xn + (m * 16 + kb) * 1024, 16384, fb, R == 4 ? EVICT_FIRST : EVICT_NORMAL);
            }
            if (R == 4 && kb == 4 + j2) x_load();
            if (st == 3) par ^= 1;
          }
        }
#pragma unroll 1
        for (int i = 0; i < 26; i++) {
          const int st = i & 3, kh = i < 25 ? 9 + 4 * i + 2 * rank : 109 + rank;
          const uint32_t sa = sb + OFF_A + st * 16384, sw = sb + st * 32768, fb = sb + B_F1 + 8 * st;
          mbar_spin(sb + B_E1 + 8 * st, par, zero);
          REL_TS(76 + i);
          mbar_expect_tx(fb, P1_BYTES);
          tma5d(sw, &mp.wd, fb, j2 * 128, kh, EVICT_FIRST); tma5d(sw + 8192, &mp.wd, fb, j2 * 128 + 64, kh, EVICT_FIRST);
          tma5d(sw + 16384, &mp.wd, fb, (j2 ^ 1) * 128, kh, EVICT_FIRST); tma5d(sw + 24576, &mp.wd, fb, (j2 ^ 1) * 128 + 64, kh, EVICT_FIRST);
          if (i == 0 || i == 5 || i == 9 || i == 17) mbar_spin(sb + B_DEP + 8 * (1 + ((i + 7) >> 3)), 0, zero);
          bulk_load(sa, gs->h + (m2 * 112 + kh) * 512, 16384, fb, EVICT_FIRST);
          if (st == 3) par ^= 1;
        }
        int st = 0; uint32_t par2 = 1;
#pragma unroll 1
        for (int t = 0; t < 16; t++) {
          constexpr auto tab = [](auto f) { uint32_t v = 0; for (int s = 0; s < 5; s++) v |= f(s) / 16384 << (4 * s); return v; };
          const uint32_t sa = sb + (tab(p2_a) >> (4 * st) & 15) * 16384, sw = sb + (tab(p2_b) >> (4 * st) & 15) * 16384, fb = sb + B_F2 + 8 * st;
          mbar_spin(sb + (t < 5 ? B_E1 + 8 * (0x10332 >> (4 * t) & 3) : B_E2 + 8 * st), t < 5 ? t < 3 : par2, zero);
          REL_TS(102 + t);
          mbar_expect_tx(fb, P2_BYTES);
          bulk_load_mc(sa + rank * 8192, gs->o + (m2 * 16 + t) * 1024 + rank * 512, 8192, fb, EVICT_FIRST);
          tma2d(sw, &mp.wo, fb, j2 * 128, t * 64, EVICT_FIRST); tma2d(sw + 8192, &mp.wo, fb, j2 * 128 + 64, t * 64, EVICT_FIRST);
          if (++st == 5) { st = 0; par2 ^= 1; }
        }
      }
    } else if (warp == 9) {
#pragma unroll 1
      for (int e = 0; e < 7; e++) {
        const bool halo = e == 2 || e == 3;
        bar_sync(BAR_EV + e, halo ? 96 : 288);
        if (lane == 0) {
          const int f = e == 0 ? FL_XN + m : (halo ? FL_HALO + (e - 2) * 128 + bid : FL_H + m * 4 + (e == 1 ? 0 : e - 3));
          TS(10 + 2 * e); TG(52 + e);
          flag_add(&gs->flags[f * 32]);
          if (e < 6) TS(11 + 2 * e);
        }
        __syncwarp();
      }
      unsigned other;
      asm volatile("ld.shared::cluster.b32 %0, [%1];" : "=r"(other) : "r"(mapa(sb + OFF_EPOCH + 4, rank ^ 1)) : "memory");
      if (other != (bid ^ 1)) asm volatile("trap;");
      mbar_wait(sb + B_DONE, 0);
    } else {
      unsigned e = 0;
      if (lane == 0) {
        unsigned* ep = &gs->epoch[bid * 2 + warp - 10];
        e = *ep + 1; *ep = e;
        if (warp == 10) { asm volatile("st.shared.b32 [%0], %1;" ::"r"(sb + OFF_EPOCH), "r"(e) : "memory"); mbar_arrive(sb + B_EP); }
      }
      e = __shfl_sync(~0u, e, 0);
      mbar_spin(sb + B_CS + 8 * (warp - 10), 0, zero);
      if (lane == 0 && warp == 11) TS(6);
      col_sums(sb + OFF_X + (warp - 10) * 16384, gs->cspart + (j * 16 + m) * 128 + (warp - 10) * 16, e);
      if (lane == 0 && warp == 11) TS(9);
      if (warp == 10) {
        if (lane == 0) {
#pragma unroll 1
          for (int g = 0; g < 6; g++) {
            flag_wait(&gs->flags[(g == 5 ? FL_P + m2 : (g ? FL_H + m2 * 4 + g - 1 : FL_XN + m)) * 32], e * (g == 5 ? 4u : 8u));
            fence_async();
            mbar_arrive(sb + B_DEP + 8 * g);
            if (g == 0) TS(8);
          }
        }
      } else
      if (elect_one()) {
#pragma unroll 1
        for (int i = 3; i < 7; i++) asm volatile("prefetch.tensormap [%0];" ::"l"(&mp.x + i) : "memory");
#pragma unroll 1
        for (int r = 0; r < 2; r++) {
          const uint32_t hb = sb + B_HALO + 8 * r;
          if (r) mbar_spin(sb + B_HALO, 0, zero);
          if (m) {
            flag_wait(&gs->flags[(FL_HALO + r * 128 + bid - 1) * 32], e);
            fence_async();
            mbar_expect_tx(hb, 4096);
            for (int g = 0; g < 2; g++) bulk_load(sb + OFF_X + g * AT_WG + AT_REM + r * 2048, gs->halo + ((r * 128 + bid - 1) * 2 + g) * 128, 2048, hb, EVICT_FIRST);
          } else {
            mbar_arrive(hb);
          }
          TS(34 + r);
        }
      }
    }
  } else {
    asm volatile("barrier.cluster.arrive.relaxed.aligned;" ::: "memory");
    asm volatile("setmaxnreg.inc.sync.aligned.u32 232;");
    const int wg = warp >> 2, w = warp & 3;
    Cons c;
    c.sb = sb; c.wg = wg; c.zero = zero;
    c.a = 0x4000004000010000ull + ((SM_BASE + OFF_A + wg * 8192) >> 4); c.k1 = 2 + c.zero; c.k2 = 2; c.k4 = 1024 - 6; c.k4w = -3072 - 6; c.b1 = 128 + c.zero;
    c.b = 0x4000004000000000ull + DB_LO + c.zero;
    c.rel = mapa(sb, threadIdx.x & 1);
    c.do_rel = (threadIdx.x & 127) < 2;
    float acc[128];
    uint32_t pk[64];
    float rs[2];
    const int q = lane & 3;

    if (helper) {
      asm volatile("barrier.cluster.wait.aligned;" ::: "memory");
      c.a = 0x8000002000010000ull + ((SM_BASE + OFF_A + wg * 4096) >> 4); c.k2 = 510; c.k4 = 1024 - 514; c.k4w = -3072 - 514;
      c.rel = sb;
      uint4* dst = gs->dpart + (bid - NMAIN) * 4096 + threadIdx.x;
      auto put = [&](int p) {
#pragma unroll
        for (int i = 4 * p; i < 4 * p + 4; i++) stg128(dst + i * 256, pk[4 * i], pk[4 * i + 1], pk[4 * i + 2], pk[4 * i + 3]);
      };
#pragma unroll 1
      for (int t = 0; t < 16; t++) {
        {
          uint64_t a = c.a, b = c.b;
          desc_add(a, (OFF_X + 4096 - OFF_A + wg * 4096) >> 4); desc_add(b, OFF_X >> 4);
          mbar_spin(sb + B_F2, t & 1, c.zero);
          wg_fence();
          wgmma256<0>(acc, a, b, 2, 128); wgmma256<1>(acc, a, b, 0, 0);
          wg_commit();
        }
        p1_issue<0, 1>(acc, c, t & 1); wg_wait<1>(); release(c, B_E2);
        if (t) put(0);
        p1_issue<1, 1>(acc, c, t & 1); wg_wait<1>(); release(c, B_E1);
        if (t) put(1);
        p1_issue<2, 1>(acc, c, t & 1); wg_wait<1>(); release(c, B_E1 + 8);
        if (t) put(2);
        if (wg == 1) { wg_wait<0>(); release(c, B_E1 + 16); bar_sync(BAR_LAG, 256); }
        p1_issue<3, 1>(acc, c, t & 1);
        if (wg == 0) bar_arrive(BAR_LAG, 256);
        if (t) { put(3); bar_arrive(BAR_EV + (~t & 1), 288); dst += 8 * 2048; }
        wg_wait<1>(); if (wg == 0) release(c, B_E1 + 16);
        wg_wait<0>(); release(c, B_E1 + 24);
#pragma unroll
        for (int i = 0; i < 64; i++) pk[i] = pack2(acc[2 * i], acc[2 * i + 1]);
      }
      put(0); put(1); put(2); put(3);
      bar_arrive(BAR_EV + 1, 288);
      return;
    }
    {
      const int prow = 16 * j + 2 * warp;
      const uint4* xr = x + (size_t)(128 * m + 2 * (prow & 63) + (prow >> 6)) * 128 + lane;
      uint4* xo = gs->xn + (m * 16 + (lane >> 3)) * 1024 + prow * 8 + ((lane ^ prow) & 7);
      float c0[2], mo[4];
      uint32_t st[2];
      uint32_t e;
      asm volatile("" : "+l"(xr), "+l"(xo));
      wg_fence(); wgmma256<0>(acc, c.a, c.b, 0, 0); wg_commit(); wg_wait<0>();
      asm volatile("barrier.cluster.wait.aligned;" ::: "memory");
      asm volatile("cp.async.wait_all;\nfence.proxy.async.shared::cta;" ::: "memory");
      bar_sync(BAR_MMA, 256);
      if (threadIdx.x == 0) TS(39);
      p1_step<0, false>(acc, c);
      unsigned long long part[18];
      auto gather = [&](int from, int to) {
        const int lane = lane_here();
        const unsigned long long* cp = (const unsigned long long*)gs->cspart + j * 4096 + warp * 32 + lane;
        const unsigned long long* sp = gs->stats + 128 * m + warp * 16 + (lane >> 2);
#pragma unroll
        for (int i = from; i < to; i++) asm volatile("ld.relaxed.gpu.global.b64 %0, [%1];" : "=l"(part[i]) : "l"(i < 16 ? cp + i * 256 : sp + (i - 16) * 8) : "memory");
      };
      auto row_load = [&](int r) {
#pragma unroll
        for (int i = 4 * r; i < 4 * r + 4; i++)
          asm volatile("ld.global.nc.L1::no_allocate.v4.b32 {%0,%1,%2,%3}, [%4];" : "=r"(pk[4 * i]), "=r"(pk[4 * i + 1]), "=r"(pk[4 * i + 2]), "=r"(pk[4 * i + 3]) : "l"(xr + r * 256 + (i & 3) * 32));
      };
      p1_step<1>(acc, c); row_load(0);
      p1_step<2>(acc, c); row_load(1);
      p1_loop(acc, c, 3, LN_KB + 1, [](int) {});
      pin<16>(pk); ln_moments(pk, c0[0], mo[0], mo[1]); pin<2>(mo);
      p1_step<LN_KB + 1>(acc, c);
      sched_fence(c.zero);
      pin<16>(pk + 16); ln_moments(pk + 16, c0[1], mo[2], mo[3]); ln_reduce(mo[0], mo[1]); pin<4>(mo);
      p1_step<LN_KB + 2>(acc, c);
      mbar_spin(sb + B_EP, 0, c.zero);
      asm volatile("ld.shared.b32 %0, [%1];" : "=r"(e) : "r"(sb + OFF_EPOCH) : "memory");
      pin<2>(mo); st[0] = ln_finish(c0[0], mo[0], mo[1]); ln_reduce(mo[2], mo[3]); pin<1>(st); pin<2>(mo + 2);
      p1_step<LN_KB + 3>(acc, c);
      sched_fence(c.zero);
      pin<1>(st); pin<2>(mo + 2);
      st[1] = ln_finish(c0[1], mo[2], mo[3]);
      ln_store(pk, st[0], xo);
      if (lane == 0)
        asm volatile("{\n.reg .b64 a, b;\nmov.b64 a, {%1, %3};\nmov.b64 b, {%2, %3};\nst.relaxed.gpu.global.v2.b64 [%0], {a, b};\n}" ::"l"(gs->stats + 128 * m + prow), "r"(st[0]), "r"(st[1]), "r"(e) : "memory");
      p1_step<LN_KB + 4>(acc, c);
      sched_fence(c.zero);
      pin<1>(st + 1);
      ln_store(pk + 16, st[1], (uint4*)((uintptr_t)xo ^ 16) + 8);
      bar_arrive(BAR_EV, 288);
      p1_loop(acc, c, LN_KB + 5, 13, [](int) {});
      gather(0, 9);
      p1_step<13>(acc, c);
      gather(9, 18);
      p1_step<14>(acc, c);
      auto validate = [&]() {
        float csum;
        for (int tries = 0;; tries++) {
          uint32_t bad = 0;
          csum = 0.f;
#pragma unroll
          for (int i = 0; i < 18; i++) { bad |= (uint32_t)(part[i] >> 32) ^ e; if (i < 16) csum += __uint_as_float((uint32_t)part[i]); }
          if (!__any_sync(~0u, bad != 0) || tries > (1 << 20)) break;
          gather(0, 18);
        }
        const float hi = bf16r(csum), mid = bf16r(csum - hi);
        sts128(sb + OFF_CS + ((threadIdx.x & 62) * 4 + (threadIdx.x >> 6) * 2 + (threadIdx.x & 1)) * 16, make_uint4(pack2(hi, mid), pack2(csum - hi - mid, 0.f), 0, 0));
        asm volatile("fence.proxy.async.shared::cta;" ::: "memory");
        __syncwarp();
        if (lane == 0) mbar_arrive(sb + B_AUX);
      };
#pragma unroll 1
      for (int ph = 1; ph >= 0; ph--) {
        if (wg == ph) validate();
        if (ph) {
          if (wg == 1) { wg_wait<0>(); release(c, B_E1 + 16); bar_sync(BAR_LAG, 256); }
          p1_issue<3, 1>(acc, c, 1);
        }
      }
      const uint32_t keep = q == 0 ? 0xffffffffu : (q == 1 ? 0xffffu : 0u);
      const uint32_t a0 = (__byte_perm((uint32_t)part[16], 0, 0x1010) ^ 0x80008000u) & keep, a1 = (__byte_perm((uint32_t)part[17], 0, 0x1010) ^ 0x80008000u) & keep;
      mbar_spin(sb + B_AUX, 0, c.zero);
      wg_fence();
      wgmma256_rs(acc, a0, a1, 0, 0, (SM_BASE + OFF_CS) >> 4);
      wg_commit();
      if (wg == 0) bar_arrive(BAR_LAG, 256);
      rs[0] = rcpf(hi_f((uint32_t)part[16])); rs[1] = rcpf(hi_f((uint32_t)part[17]));
      wg_wait<2>(); if (wg == 0) release(c, B_E1 + 16);
      wg_wait<0>(); release(c, B_E1 + 24);
    }
#pragma unroll 1
    for (int R = 1;; R++) {
#pragma unroll
      for (int i = 0; i < 64; i++) pk[i] = pack2(acc[2 * i], acc[2 * i + 1]);
      uint8_t* hb = (uint8_t*)gs->h + (size_t)m * 56 * 16384 + warp * 1024;
      if (R == 5) { c.a = 0x8000002000010000ull + ((SM_BASE + OFF_A + wg * 4096) >> 4); c.k2 = 510; c.k4 = 1024 - 514; c.k4w = -3072 - 514; }
      p1_step<0>(acc, c);
      if (R == 2 || R == 3) {
        attn_tile(acc, pk, c, R - 2, warp, m, bid, gs, hb + (16 + j) * 16384, (uint8_t*)gs->o + (m * 16 + j + 8 * (R - 2)) * 16384 + warp * 1024);
      } else {
        geglu_tile(acc, pk, c, R == 5 ? 24 : 15, hb + (2 * j + (R == 1 ? 0 : 16 * R - 40)) * 16384, BAR_EV + (R == 1 ? 1 : R + 1), rs);
        rs[0] = rs[1] = 1.0f;
        if (R == 5) break;
      }
      p1_step<15>(acc, c);
    }
    auto fetch = [&](int p) {
      asm volatile("ld.global.cg.v4.b32 {%0,%1,%2,%3}, [%4];" : "=r"(pk[4 * p]), "=r"(pk[4 * p + 1]), "=r"(pk[4 * p + 2]), "=r"(pk[4 * p + 3]) : "l"(gs->dpart + bid * 2048 + p * 256 + threadIdx.x) : "memory");
    };
    mbar_spin(sb + B_DEP + 40, 0, c.zero);
    fetch(0); fetch(1); fetch(2);
    p1_step<8>(acc, c);
    fetch(3); fetch(4); fetch(5);
    desc_add(c.a, 2 * rank); desc_add(c.b, 128 * rank);
    mbar_spin(sb + B_F1 + 8, 0, c.zero);
    wg_fence();
    wgmma256<1>(acc, c.a, c.b, rank ? 510 : 2, c.b1);
    wgmma256<1>(acc, c.a, c.b, rank ? 2 : 510, c.b1);
    wgmma256<1>(acc, c.a, c.b, 512 - 2 * rank, 1792 - 128 * rank);
    wg_commit();
    wg_wait<1>(); release(c, B_E1);
    fetch(6); fetch(7);
    {
      float accs[64];
      const uint32_t peer = mapa(sb, rank ^ 1);
      auto send_piece = [&](int p) {
        asm volatile("st.async.weak.shared::cluster.mbarrier::complete_tx::bytes.v4.b32 [%0], {%1,%2,%3,%4}, [%5];" ::"r"(peer + OFF_LAND + p * 4096 + threadIdx.x * 16),
                     "r"(pack2(acc[64 + 8 * p], acc[65 + 8 * p])), "r"(pack2(acc[66 + 8 * p], acc[67 + 8 * p])), "r"(pack2(acc[68 + 8 * p], acc[69 + 8 * p])), "r"(pack2(acc[70 + 8 * p], acc[71 + 8 * p])),
                     "r"(peer + B_EX + 16 * wg + 8 * (p >> 2)) : "memory");
      };
      auto silu_piece = [&](int p) {
        const uint4 r = lds128(sb + OFF_LAND + p * 4096 + threadIdx.x * 16);
        const uint32_t rr[4] = {add2(r.x, pk[4 * p]), add2(r.y, pk[4 * p + 1]), add2(r.z, pk[4 * p + 2]), add2(r.w, pk[4 * p + 3])};
#pragma unroll
        for (int i = 0; i < 4; i++) {
          const float a = acc[8 * p + 2 * i] + lo_f(rr[i]), b = acc[8 * p + 2 * i + 1] + hi_f(rr[i]);
          pk[4 * p + i] = pack2(silu_half(a), silu_half(b));
        }
        pin<4>(pk + 4 * p);
      };
      const uint32_t xa = sb + OFF_X + (warp * 16 + (lane & 7)) * 128 + (((lane >> 3) ^ (lane & 7)) << 4);
      auto x_addr = [&](int i) { return (xa ^ ((i & 1) << 6)) + ((i >> 1) & 1) * 1024 + (i >> 2) * 16384; };
      auto x_piece = [&](int i) { const uint4 v = ldsm(x_addr(i)); pk[32 + 4 * i] = v.x; pk[33 + 4 * i] = v.y; pk[34 + 4 * i] = v.z; pk[35 + 4 * i] = v.w; };
      p2_step<0>(accs, c);
      p2_step<1>(accs, c);
      mbar_spin(sb + B_E1 + 8, 0, c.zero);
      send_piece(0); send_piece(1);
      p2_step<2>(accs, c); sched_fence(c.zero); send_piece(2); send_piece(3);
      p2_step<3>(accs, c); sched_fence(c.zero); send_piece(4); send_piece(5);
      p2_step<4>(accs, c); mbar_spin(sb + B_XT, 0, c.zero); send_piece(6); send_piece(7);
      p2_step<5>(accs, c); mbar_spin(sb + B_EX + 16 * wg, 0, c.zero); silu_piece(0); x_piece(0);
      p2_step<6>(accs, c); sched_fence(c.zero); silu_piece(1); x_piece(1);
      p2_step<7>(accs, c); sched_fence(c.zero); silu_piece(2); x_piece(2);
      p2_step<8>(accs, c); sched_fence(c.zero); silu_piece(3); x_piece(3);
      p2_step<9>(accs, c); mbar_spin(sb + B_EX + 16 * wg + 8, 0, c.zero); silu_piece(4); x_piece(4);
      p2_step<10>(accs, c); sched_fence(c.zero); silu_piece(5); x_piece(5);
      p2_step<11>(accs, c); sched_fence(c.zero); silu_piece(6); x_piece(6); x_piece(7);
      auto out_half = [&](const float* a, int h) {
#pragma unroll
        for (int i = 4 * h; i < 4 * h + 4; i++) {
          uint32_t v[4];
#pragma unroll
          for (int k = 0; k < 4; k++) { const int o = 2 * (4 * (i & 1) + k) + ((i >> 1) & 1); v[k] = fma2(pack2(a[2 * o], a[2 * o + 1]), pk[16 * h + o], pk[32 + 4 * i + k]); }
          asm volatile("stmatrix.sync.aligned.m8n8.x4.shared.b16 [%0], {%1,%2,%3,%4};" ::"r"(x_addr(i)), "r"(v[0]), "r"(v[1]), "r"(v[2]), "r"(v[3]) : "memory");
          if (i & 1) {
            asm volatile("fence.proxy.async.shared::cta;" ::: "memory");
            __syncwarp();
            if (elect_one()) tma3d_store(&mp.out, sb + OFF_X + h * 16384 + warp * 2048 + (i & 2) * 512, j2 * 128 + h * 64, m2 * 64 + w * 16 + (i & 2) * 4, wg);
          }
        }
      };
      if (wg == 1) silu_piece(7);
      p2_step<12>(accs, c); p2_step<13>(accs, c); p2_step<14>(accs, c); p2_step<15>(accs, c);
      if (c.do_rel) mbar_arrive(sb + B_DONE);
      if (wg == 0) silu_piece(7);
      wg_wait<0>();
      out_half(accs, 0); out_half(accs + 32, 1);
      if (elect_one()) { asm volatile("cp.async.bulk.commit_group;\ncp.async.bulk.wait_group.read 0;" ::: "memory"); }
    }
  }
}

typedef CUresult (*EncodeFn)(CUtensorMap*, CUtensorMapDataType, cuuint32_t, void*, const cuuint64_t*, const cuuint64_t*, const cuuint32_t*, const cuuint32_t*,
                             CUtensorMapInterleave, CUtensorMapSwizzle, CUtensorMapL2promotion, CUtensorMapFloatOOBfill);

void encode(EncodeFn fn, CUtensorMap* tm, const void* p, int rank, const cuuint64_t* dims, const cuuint64_t* strides, const cuuint32_t* box) {
  const cuuint32_t es[5] = {1, 1, 1, 1, 1};
  fn(tm, CU_TENSOR_MAP_DATA_TYPE_BFLOAT16, rank, const_cast<void*>(p), dims, strides, box, es, CU_TENSOR_MAP_INTERLEAVE_NONE, CU_TENSOR_MAP_SWIZZLE_128B,
     CU_TENSOR_MAP_L2_PROMOTION_L2_128B, CU_TENSOR_MAP_FLOAT_OOB_FILL_NONE);
}

}

extern "C" void kernel_launch(void* const* d_in, const int* in_sizes, int n_in, void* d_out, int out_size) {
  (void)in_sizes; (void)n_in; (void)out_size;
  static EncodeFn fn = nullptr;
  static Scratch* gs = nullptr;
  static int nsm = 0;
  if (!fn) {
    void* p = nullptr;
    cudaDriverEntryPointQueryResult qr;
    cudaGetDriverEntryPoint("cuTensorMapEncodeTiled", &p, cudaEnableDefault, &qr);
    fn = (EncodeFn)p;
    cudaGetSymbolAddress((void**)&gs, g_scratch);
    int dev = 0;
    cudaGetDevice(&dev);
    cudaDeviceGetAttribute(&nsm, cudaDevAttrMultiProcessorCount, dev);
    cudaFuncSetAttribute(fused_kernel, cudaFuncAttributeMaxDynamicSharedMemorySize, SMEM_BYTES);
  }
  const void *x = d_in[0], *wqkv = d_in[1], *wo = d_in[2], *wg = d_in[4], *wu = d_in[5], *wd = d_in[6];
  Maps mp;
  {
    const cuuint64_t dims[3] = {DM, SEQ / 2, 2}, st[2] = {DM * 4, DM * 2};
    const cuuint32_t box_in[3] = {64, 64, 2}, box_out[3] = {64, 8, 1};
    encode(fn, &mp.x, x, 3, dims, st, box_in);
    encode(fn, &mp.out, d_out, 3, dims, st, box_out);
  }
  {
    const cuuint32_t box[2] = {64, 64};
    const cuuint64_t dq[2] = {3 * DM, DM}, sq[1] = {3 * DM * 2}, df[2] = {DFF, DM}, sf[1] = {DFF * 2}, dw[2] = {DM, DM}, sw[1] = {DM * 2};
    encode(fn, &mp.wqkv, wqkv, 2, dq, sq, box);
    encode(fn, &mp.wg, wg, 2, df, sf, box);
    encode(fn, &mp.wu, wu, 2, df, sf, box);
    encode(fn, &mp.wo, wo, 2, dw, sw, box);
  }
  {
    const cuuint32_t box[5] = {64, 2, 4, 4, 2};
    const cuuint64_t st[4] = {DM * 2, 8 * DM * 2, 2 * DM * 2, 32 * DM * 2};
    const cuuint64_t dd[5] = {DM, 2, 4, 4, DFF / 32};
    encode(fn, &mp.wd, wd, 5, dd, st, box);
  }
  fused_kernel<<<NCTA, 384, SMEM_BYTES>>>((const uint4*)x, (const uint4*)wg, (const uint4*)wu, gs, nsm == NCTA, mp);
}
```
